```python
import torch

def _softmax(x, axis=-1):
    return torch.softmax(x, dim=axis)
def _gelu(x):
    return torch.nn.functional.gelu(x, approximate="tanh")
def _silu(x):
    return torch.nn.functional.silu(x)
def _sigmoid(x):
    return torch.sigmoid(x)
def _layernorm(x, axis=-1, eps=1e-5):
    m = x.mean(dim=axis, keepdim=True)
    v = x.var(dim=axis, keepdim=True, unbiased=False)
    return (x - m) / torch.sqrt(v + eps)
def _scatter_add(tgt, idx, src, axis=0):
    return tgt.clone().index_add_(axis, idx, src)
def _segment_sum(src, seg, n):
    out = torch.zeros((n,) + src.shape[1:], dtype=src.dtype)
    return out.index_add_(0, seg, src)
def _pad(x, pw):
    flat = tuple(v for pair in reversed(pw) for v in pair)
    return torch.nn.functional.pad(x, flat)

kernel_name = 'gated_mix__mha_block__mixer_s_mlp__prompt'

def setup_inputs():

    _w = (lambda a: (lambda t: t.to(torch.bfloat16) if t.is_floating_point() else t)(torch.as_tensor(a)))
    def _A_setup():
        B, S, D, H = 1, 2048, 1024, 32
        return {
            "x": _w((lambda *s: torch.randn(*s, dtype=torch.bfloat16) * 0.1)(B, S, D)),
            "wqkv": _w((lambda *s: torch.randn(*s, dtype=torch.bfloat16) * 0.4)(D, 3 * D)),
            "wo": _w((lambda *s: torch.randn(*s, dtype=torch.bfloat16) * 0.4)(D, D)),
        }
    _A_in = _A_setup()

    def _B_setup():
        B, S, D, F = 1, 2048, 1024, 3584
        return {
            "x":  _w((lambda *s: torch.randn(*s, dtype=torch.bfloat16) * 0.1)(B, S, D)),
            "w1": _w((lambda *s: torch.randn(*s, dtype=torch.bfloat16) * 3.2)(D, D) * (D ** -0.5)),
            "w2": _w((lambda *s: torch.randn(*s, dtype=torch.bfloat16) * 3.2)(D, D) * (D ** -0.5)),
            "w3": _w((lambda *s: torch.randn(*s, dtype=torch.bfloat16) * 3.2)(D, F) * (D ** -0.5)),
            "w4": _w((lambda *s: torch.randn(*s, dtype=torch.bfloat16) * 3.2)(F, D) * (F ** -0.5)),
        }
    _B_in = _B_setup()

    return {
        "A_x": _A_in["x"],
        "A_wqkv": _A_in["wqkv"],
        "A_wo": _A_in["wo"],
        "B_x": _B_in["x"],
        "B_w1": _B_in["w1"],
        "B_w2": _B_in["w2"],
        "B_w3": _B_in["w3"],
        "B_w4": _B_in["w4"],
        "gate_w": _w((lambda *s: torch.randn(*s, dtype=torch.bfloat16) * 0.4)(1024) * 16.0),
    }

def reference(A_x, A_wqkv, A_wo, B_x, B_w1, B_w2, B_w3, B_w4, gate_w):
    def _A_ref(x, wqkv, wo):
        B, S, D = x.shape
        H = 32
        Dh = D // H
        qkv = (lambda x, *d: x.permute(*d))((x @ wqkv).reshape(B, S, 3, H, Dh), 2, 0, 3, 1, 4)
        q, k, v = qkv[0], qkv[1], qkv[2]
        scores = torch.einsum("bhqd,bhkd->bhqk", q, k) * (Dh ** -0.5)
        p = _softmax(scores, axis=-1)
        o = torch.einsum("bhqk,bhkd->bhqd", p, v)
        return (lambda x, *d: x.permute(*d))(o, 0, 2, 1, 3).reshape(B, S, D) @ wo

    def _B_ref(x, w1, w2, w3, w4):
        B, S, D = x.shape
        h = _gelu(_layernorm(x, axis=-1) @ w1)
        c = D // 4
        g0 = _pad(h[:, :, 0*c:1*c], ((0, 0), (1, 0), (0, 0)))[:, :S, :]
        g1 = _pad(h[:, :, 1*c:2*c], ((0, 0), (0, 1), (0, 0)))[:, 1:, :]
        g2 = _pad(h[:, :, 2*c:3*c], ((0, 0), (2, 0), (0, 0)))[:, :S, :]
        g3 = _pad(h[:, :, 3*c:   ], ((0, 0), (0, 2), (0, 0)))[:, 2:, :]
        hs = torch.concatenate([g0, g1, g2, g3], axis=-1) @ w2
        x1 = x + hs
        h2 = _gelu(_layernorm(x1, axis=-1) @ w3) @ w4
        return x1 + h2

    x = A_x
    g = _sigmoid((x * gate_w).sum(-1, keepdims=True))
    a = _A_ref(x, A_wqkv, A_wo)
    b = _B_ref(x, B_w1, B_w2, B_w3, B_w4)
    return g * a + (1 - g) * b
```

```cpp
#include <cuda_runtime.h>
#include <cuda_bf16.h>
#include <cuda.h>
#include <stdint.h>

typedef __nv_bfloat16 bf16;

constexpr int S_LEN = 2048;
constexpr int DM = 1024;
constexpr int FF = 3584;
constexpr int NH = 32;
constexpr int DH = 32;
constexpr int A5W = DM + FF;

__device__ __align__(1024) bf16 g_qkv[S_LEN * 3 * DM];
__device__ __align__(1024) bf16 g_h[S_LEN * DM];
__device__ __align__(1024) bf16 g_x1[S_LEN * DM];
__device__ __align__(1024) bf16 g_a5[S_LEN * A5W];
__device__ __align__(16) float g_mean1[S_LEN];
__device__ __align__(16) float g_rstd1[S_LEN];
__device__ __align__(16) float g_gate[S_LEN];
__device__ __align__(16) float g_omg[S_LEN];
__device__ __align__(16) float g_cs1[DM];
__device__ __align__(16) float g_cs3[FF];
__device__ __align__(16) float2 g_stat2[S_LEN * 8];

__device__ __forceinline__ uint32_t smem_u32(const void* p) { return (uint32_t)__cvta_generic_to_shared(p); }

__device__ __forceinline__ void mbar_init(uint32_t bar, uint32_t count) {
    asm volatile("mbarrier.init.shared::cta.b64 [%0], %1;" ::"r"(bar), "r"(count));
}
__device__ __forceinline__ void mbar_expect_tx(uint32_t bar, uint32_t bytes) {
    asm volatile("mbarrier.arrive.expect_tx.shared::cta.b64 _, [%0], %1;" ::"r"(bar), "r"(bytes) : "memory");
}
__device__ __forceinline__ void mbar_arrive(uint32_t bar) {
    asm volatile("mbarrier.arrive.shared::cta.b64 _, [%0];" ::"r"(bar) : "memory");
}
__device__ __forceinline__ bool mbar_try_wait(uint32_t bar, uint32_t parity) {
    uint32_t ok;
    asm volatile(
        "{\n.reg .pred p;\n"
        "mbarrier.try_wait.parity.shared::cta.b64 p, [%1], %2;\n"
        "selp.u32 %0, 1, 0, p;\n}\n"
        : "=r"(ok)
        : "r"(bar), "r"(parity)
        : "memory");
    return ok != 0;
}
__device__ __forceinline__ void mbar_wait(uint32_t bar, uint32_t parity) {
    uint32_t spins = 0;
    while (!mbar_try_wait(bar, parity)) {
        if (++spins > (1u << 24)) __trap();
    }
}
__device__ __forceinline__ void tma_load_2d(uint32_t dst, const CUtensorMap* map, int c0, int c1, uint32_t bar) {
    asm volatile(
        "cp.async.bulk.tensor.2d.shared::cluster.global.mbarrier::complete_tx::bytes [%0], [%1, {%3, %4}], [%2];"
        ::"r"(dst), "l"(map), "r"(bar), "r"(c0), "r"(c1)
        : "memory");
}
__device__ __forceinline__ void tma_store_2d(const CUtensorMap* map, uint32_t src, int c0, int c1) {
    asm volatile("cp.async.bulk.tensor.2d.global.shared::cta.bulk_group [%0, {%2, %3}], [%1];"
                 ::"l"(map), "r"(src), "r"(c0), "r"(c1)
                 : "memory");
}
__device__ __forceinline__ void bulk_commit() { asm volatile("cp.async.bulk.commit_group;" ::: "memory"); }
__device__ __forceinline__ void bulk_wait_read0() { asm volatile("cp.async.bulk.wait_group.read 0;" ::: "memory"); }
__device__ __forceinline__ void bulk_wait0() { asm volatile("cp.async.bulk.wait_group 0;" ::: "memory"); }
__device__ __forceinline__ void fence_proxy_async() { asm volatile("fence.proxy.async.shared::cta;" ::: "memory"); }
__device__ __forceinline__ void named_bar_sync(int id, int n) { asm volatile("bar.sync %0, %1;" ::"r"(id), "r"(n) : "memory"); }
__device__ __forceinline__ void wgmma_fence() { asm volatile("wgmma.fence.sync.aligned;" ::: "memory"); }
__device__ __forceinline__ void wgmma_commit() { asm volatile("wgmma.commit_group.sync.aligned;" ::: "memory"); }
template <int N>
__device__ __forceinline__ void wgmma_wait() { asm volatile("wgmma.wait_group.sync.aligned %0;" ::"n"(N) : "memory"); }
__device__ __forceinline__ void prefetch_tmap(const CUtensorMap* m) {
    asm volatile("prefetch.tensormap [%0];" ::"l"(m) : "memory");
}
template <int R>
__device__ __forceinline__ void reg_alloc() { asm volatile("setmaxnreg.inc.sync.aligned.u32 %0;" ::"n"(R)); }
template <int R>
__device__ __forceinline__ void reg_dealloc() { asm volatile("setmaxnreg.dec.sync.aligned.u32 %0;" ::"n"(R)); }
__device__ __forceinline__ void stmatrix_x4(uint32_t addr, uint32_t r0, uint32_t r1, uint32_t r2, uint32_t r3) {
    asm volatile("stmatrix.sync.aligned.m8n8.x4.shared.b16 [%0], {%1, %2, %3, %4};"
                 ::"r"(addr), "r"(r0), "r"(r1), "r"(r2), "r"(r3)
                 : "memory");
}
__device__ __forceinline__ uint32_t pack_bf16(float lo, float hi) {
    uint32_t r;
    asm("cvt.rn.bf16x2.f32 %0, %1, %2;" : "=r"(r) : "f"(hi), "f"(lo));
    return r;
}
__device__ __forceinline__ float bf16_round(float v) { return __bfloat162float(__float2bfloat16_rn(v)); }
__device__ __forceinline__ float ex2(float x) {
    float y;
    asm("ex2.approx.ftz.f32 %0, %1;" : "=f"(y) : "f"(x));
    return y;
}
__device__ __forceinline__ float tanh_fast(float x) {
    float y;
    asm("tanh.approx.f32 %0, %1;" : "=f"(y) : "f"(x));
    return y;
}
__device__ __forceinline__ float gelu_tanh(float v) {
    float u = 0.7978845608028654f * (v + 0.044715f * v * v * v);
    float hv = 0.5f * v;
    return fmaf(hv, tanh_fast(u), hv);
}
__device__ __forceinline__ uint64_t make_desc(uint32_t addr, uint32_t lbo_bytes, uint32_t sbo_bytes, uint32_t swz) {
    uint64_t d = 0;
    d |= (uint64_t)((addr & 0x3FFFF) >> 4);
    d |= (uint64_t)((lbo_bytes >> 4) & 0x3FFF) << 16;
    d |= (uint64_t)((sbo_bytes >> 4) & 0x3FFF) << 32;
    d |= (uint64_t)swz << 62;
    return d;
}


__device__ __forceinline__ void wgmma_ss_n128_tb1(float (&d)[64], uint64_t da, uint64_t db, int scale_d) {
    asm volatile("{\n.reg .pred p;\nsetp.ne.b32 p, %66, 0;\n"
        "wgmma.mma_async.sync.aligned.m64n128k16.f32.bf16.bf16 {%0, %1, %2, %3, %4, %5, %6, %7, %8, %9, %10, %11, %12, %13, %14, %15, %16, %17, %18, %19, %20, %21, %22, %23, %24, %25, %26, %27, %28, %29, %30, %31, %32, %33, %34, %35, %36, %37, %38, %39, %40, %41, %42, %43, %44, %45, %46, %47, %48, %49, %50, %51, %52, %53, %54, %55, %56, %57, %58, %59, %60, %61, %62, %63}, %64, %65, p, 1, 1, 0, 1;\n}\n"
        : "+f"(d[0]), "+f"(d[1]), "+f"(d[2]), "+f"(d[3]), "+f"(d[4]), "+f"(d[5]), "+f"(d[6]), "+f"(d[7]), "+f"(d[8]), "+f"(d[9]), "+f"(d[10]), "+f"(d[11]), "+f"(d[12]), "+f"(d[13]), "+f"(d[14]), "+f"(d[15]), "+f"(d[16]), "+f"(d[17]), "+f"(d[18]), "+f"(d[19]), "+f"(d[20]), "+f"(d[21]), "+f"(d[22]), "+f"(d[23]), "+f"(d[24]), "+f"(d[25]), "+f"(d[26]), "+f"(d[27]), "+f"(d[28]), "+f"(d[29]), "+f"(d[30]), "+f"(d[31]), "+f"(d[32]), "+f"(d[33]), "+f"(d[34]), "+f"(d[35]), "+f"(d[36]), "+f"(d[37]), "+f"(d[38]), "+f"(d[39]), "+f"(d[40]), "+f"(d[41]), "+f"(d[42]), "+f"(d[43]), "+f"(d[44]), "+f"(d[45]), "+f"(d[46]), "+f"(d[47]), "+f"(d[48]), "+f"(d[49]), "+f"(d[50]), "+f"(d[51]), "+f"(d[52]), "+f"(d[53]), "+f"(d[54]), "+f"(d[55]), "+f"(d[56]), "+f"(d[57]), "+f"(d[58]), "+f"(d[59]), "+f"(d[60]), "+f"(d[61]), "+f"(d[62]), "+f"(d[63])
        : "l"(da), "l"(db), "r"(scale_d));
}

__device__ __forceinline__ void wgmma_ss_n192_tb1(float (&d)[96], uint64_t da, uint64_t db, int scale_d) {
    asm volatile("{\n.reg .pred p;\nsetp.ne.b32 p, %98, 0;\n"
        "wgmma.mma_async.sync.aligned.m64n192k16.f32.bf16.bf16 {%0, %1, %2, %3, %4, %5, %6, %7, %8, %9, %10, %11, %12, %13, %14, %15, %16, %17, %18, %19, %20, %21, %22, %23, %24, %25, %26, %27, %28, %29, %30, %31, %32, %33, %34, %35, %36, %37, %38, %39, %40, %41, %42, %43, %44, %45, %46, %47, %48, %49, %50, %51, %52, %53, %54, %55, %56, %57, %58, %59, %60, %61, %62, %63, %64, %65, %66, %67, %68, %69, %70, %71, %72, %73, %74, %75, %76, %77, %78, %79, %80, %81, %82, %83, %84, %85, %86, %87, %88, %89, %90, %91, %92, %93, %94, %95}, %96, %97, p, 1, 1, 0, 1;\n}\n"
        : "+f"(d[0]), "+f"(d[1]), "+f"(d[2]), "+f"(d[3]), "+f"(d[4]), "+f"(d[5]), "+f"(d[6]), "+f"(d[7]), "+f"(d[8]), "+f"(d[9]), "+f"(d[10]), "+f"(d[11]), "+f"(d[12]), "+f"(d[13]), "+f"(d[14]), "+f"(d[15]), "+f"(d[16]), "+f"(d[17]), "+f"(d[18]), "+f"(d[19]), "+f"(d[20]), "+f"(d[21]), "+f"(d[22]), "+f"(d[23]), "+f"(d[24]), "+f"(d[25]), "+f"(d[26]), "+f"(d[27]), "+f"(d[28]), "+f"(d[29]), "+f"(d[30]), "+f"(d[31]), "+f"(d[32]), "+f"(d[33]), "+f"(d[34]), "+f"(d[35]), "+f"(d[36]), "+f"(d[37]), "+f"(d[38]), "+f"(d[39]), "+f"(d[40]), "+f"(d[41]), "+f"(d[42]), "+f"(d[43]), "+f"(d[44]), "+f"(d[45]), "+f"(d[46]), "+f"(d[47]), "+f"(d[48]), "+f"(d[49]), "+f"(d[50]), "+f"(d[51]), "+f"(d[52]), "+f"(d[53]), "+f"(d[54]), "+f"(d[55]), "+f"(d[56]), "+f"(d[57]), "+f"(d[58]), "+f"(d[59]), "+f"(d[60]), "+f"(d[61]), "+f"(d[62]), "+f"(d[63]), "+f"(d[64]), "+f"(d[65]), "+f"(d[66]), "+f"(d[67]), "+f"(d[68]), "+f"(d[69]), "+f"(d[70]), "+f"(d[71]), "+f"(d[72]), "+f"(d[73]), "+f"(d[74]), "+f"(d[75]), "+f"(d[76]), "+f"(d[77]), "+f"(d[78]), "+f"(d[79]), "+f"(d[80]), "+f"(d[81]), "+f"(d[82]), "+f"(d[83]), "+f"(d[84]), "+f"(d[85]), "+f"(d[86]), "+f"(d[87]), "+f"(d[88]), "+f"(d[89]), "+f"(d[90]), "+f"(d[91]), "+f"(d[92]), "+f"(d[93]), "+f"(d[94]), "+f"(d[95])
        : "l"(da), "l"(db), "r"(scale_d));
}

__device__ __forceinline__ void wgmma_ss_n224_tb1(float (&d)[112], uint64_t da, uint64_t db, int scale_d) {
    asm volatile("{\n.reg .pred p;\nsetp.ne.b32 p, %114, 0;\n"
        "wgmma.mma_async.sync.aligned.m64n224k16.f32.bf16.bf16 {%0, %1, %2, %3, %4, %5, %6, %7, %8, %9, %10, %11, %12, %13, %14, %15, %16, %17, %18, %19, %20, %21, %22, %23, %24, %25, %26, %27, %28, %29, %30, %31, %32, %33, %34, %35, %36, %37, %38, %39, %40, %41, %42, %43, %44, %45, %46, %47, %48, %49, %50, %51, %52, %53, %54, %55, %56, %57, %58, %59, %60, %61, %62, %63, %64, %65, %66, %67, %68, %69, %70, %71, %72, %73, %74, %75, %76, %77, %78, %79, %80, %81, %82, %83, %84, %85, %86, %87, %88, %89, %90, %91, %92, %93, %94, %95, %96, %97, %98, %99, %100, %101, %102, %103, %104, %105, %106, %107, %108, %109, %110, %111}, %112, %113, p, 1, 1, 0, 1;\n}\n"
        : "+f"(d[0]), "+f"(d[1]), "+f"(d[2]), "+f"(d[3]), "+f"(d[4]), "+f"(d[5]), "+f"(d[6]), "+f"(d[7]), "+f"(d[8]), "+f"(d[9]), "+f"(d[10]), "+f"(d[11]), "+f"(d[12]), "+f"(d[13]), "+f"(d[14]), "+f"(d[15]), "+f"(d[16]), "+f"(d[17]), "+f"(d[18]), "+f"(d[19]), "+f"(d[20]), "+f"(d[21]), "+f"(d[22]), "+f"(d[23]), "+f"(d[24]), "+f"(d[25]), "+f"(d[26]), "+f"(d[27]), "+f"(d[28]), "+f"(d[29]), "+f"(d[30]), "+f"(d[31]), "+f"(d[32]), "+f"(d[33]), "+f"(d[34]), "+f"(d[35]), "+f"(d[36]), "+f"(d[37]), "+f"(d[38]), "+f"(d[39]), "+f"(d[40]), "+f"(d[41]), "+f"(d[42]), "+f"(d[43]), "+f"(d[44]), "+f"(d[45]), "+f"(d[46]), "+f"(d[47]), "+f"(d[48]), "+f"(d[49]), "+f"(d[50]), "+f"(d[51]), "+f"(d[52]), "+f"(d[53]), "+f"(d[54]), "+f"(d[55]), "+f"(d[56]), "+f"(d[57]), "+f"(d[58]), "+f"(d[59]), "+f"(d[60]), "+f"(d[61]), "+f"(d[62]), "+f"(d[63]), "+f"(d[64]), "+f"(d[65]), "+f"(d[66]), "+f"(d[67]), "+f"(d[68]), "+f"(d[69]), "+f"(d[70]), "+f"(d[71]), "+f"(d[72]), "+f"(d[73]), "+f"(d[74]), "+f"(d[75]), "+f"(d[76]), "+f"(d[77]), "+f"(d[78]), "+f"(d[79]), "+f"(d[80]), "+f"(d[81]), "+f"(d[82]), "+f"(d[83]), "+f"(d[84]), "+f"(d[85]), "+f"(d[86]), "+f"(d[87]), "+f"(d[88]), "+f"(d[89]), "+f"(d[90]), "+f"(d[91]), "+f"(d[92]), "+f"(d[93]), "+f"(d[94]), "+f"(d[95]), "+f"(d[96]), "+f"(d[97]), "+f"(d[98]), "+f"(d[99]), "+f"(d[100]), "+f"(d[101]), "+f"(d[102]), "+f"(d[103]), "+f"(d[104]), "+f"(d[105]), "+f"(d[106]), "+f"(d[107]), "+f"(d[108]), "+f"(d[109]), "+f"(d[110]), "+f"(d[111])
        : "l"(da), "l"(db), "r"(scale_d));
}

__device__ __forceinline__ void wgmma_ss_n256_tb1(float (&d)[128], uint64_t da, uint64_t db, int scale_d) {
    asm volatile("{\n.reg .pred p;\nsetp.ne.b32 p, %130, 0;\n"
        "wgmma.mma_async.sync.aligned.m64n256k16.f32.bf16.bf16 {%0, %1, %2, %3, %4, %5, %6, %7, %8, %9, %10, %11, %12, %13, %14, %15, %16, %17, %18, %19, %20, %21, %22, %23, %24, %25, %26, %27, %28, %29, %30, %31, %32, %33, %34, %35, %36, %37, %38, %39, %40, %41, %42, %43, %44, %45, %46, %47, %48, %49, %50, %51, %52, %53, %54, %55, %56, %57, %58, %59, %60, %61, %62, %63, %64, %65, %66, %67, %68, %69, %70, %71, %72, %73, %74, %75, %76, %77, %78, %79, %80, %81, %82, %83, %84, %85, %86, %87, %88, %89, %90, %91, %92, %93, %94, %95, %96, %97, %98, %99, %100, %101, %102, %103, %104, %105, %106, %107, %108, %109, %110, %111, %112, %113, %114, %115, %116, %117, %118, %119, %120, %121, %122, %123, %124, %125, %126, %127}, %128, %129, p, 1, 1, 0, 1;\n}\n"
        : "+f"(d[0]), "+f"(d[1]), "+f"(d[2]), "+f"(d[3]), "+f"(d[4]), "+f"(d[5]), "+f"(d[6]), "+f"(d[7]), "+f"(d[8]), "+f"(d[9]), "+f"(d[10]), "+f"(d[11]), "+f"(d[12]), "+f"(d[13]), "+f"(d[14]), "+f"(d[15]), "+f"(d[16]), "+f"(d[17]), "+f"(d[18]), "+f"(d[19]), "+f"(d[20]), "+f"(d[21]), "+f"(d[22]), "+f"(d[23]), "+f"(d[24]), "+f"(d[25]), "+f"(d[26]), "+f"(d[27]), "+f"(d[28]), "+f"(d[29]), "+f"(d[30]), "+f"(d[31]), "+f"(d[32]), "+f"(d[33]), "+f"(d[34]), "+f"(d[35]), "+f"(d[36]), "+f"(d[37]), "+f"(d[38]), "+f"(d[39]), "+f"(d[40]), "+f"(d[41]), "+f"(d[42]), "+f"(d[43]), "+f"(d[44]), "+f"(d[45]), "+f"(d[46]), "+f"(d[47]), "+f"(d[48]), "+f"(d[49]), "+f"(d[50]), "+f"(d[51]), "+f"(d[52]), "+f"(d[53]), "+f"(d[54]), "+f"(d[55]), "+f"(d[56]), "+f"(d[57]), "+f"(d[58]), "+f"(d[59]), "+f"(d[60]), "+f"(d[61]), "+f"(d[62]), "+f"(d[63]), "+f"(d[64]), "+f"(d[65]), "+f"(d[66]), "+f"(d[67]), "+f"(d[68]), "+f"(d[69]), "+f"(d[70]), "+f"(d[71]), "+f"(d[72]), "+f"(d[73]), "+f"(d[74]), "+f"(d[75]), "+f"(d[76]), "+f"(d[77]), "+f"(d[78]), "+f"(d[79]), "+f"(d[80]), "+f"(d[81]), "+f"(d[82]), "+f"(d[83]), "+f"(d[84]), "+f"(d[85]), "+f"(d[86]), "+f"(d[87]), "+f"(d[88]), "+f"(d[89]), "+f"(d[90]), "+f"(d[91]), "+f"(d[92]), "+f"(d[93]), "+f"(d[94]), "+f"(d[95]), "+f"(d[96]), "+f"(d[97]), "+f"(d[98]), "+f"(d[99]), "+f"(d[100]), "+f"(d[101]), "+f"(d[102]), "+f"(d[103]), "+f"(d[104]), "+f"(d[105]), "+f"(d[106]), "+f"(d[107]), "+f"(d[108]), "+f"(d[109]), "+f"(d[110]), "+f"(d[111]), "+f"(d[112]), "+f"(d[113]), "+f"(d[114]), "+f"(d[115]), "+f"(d[116]), "+f"(d[117]), "+f"(d[118]), "+f"(d[119]), "+f"(d[120]), "+f"(d[121]), "+f"(d[122]), "+f"(d[123]), "+f"(d[124]), "+f"(d[125]), "+f"(d[126]), "+f"(d[127])
        : "l"(da), "l"(db), "r"(scale_d));
}

__device__ __forceinline__ void wgmma_rs_n128_tb0(float (&d)[64], uint32_t a0, uint32_t a1, uint32_t a2, uint32_t a3, uint64_t db, int scale_d) {
    asm volatile("{\n.reg .pred p;\nsetp.ne.b32 p, %69, 0;\n"
        "wgmma.mma_async.sync.aligned.m64n128k16.f32.bf16.bf16 {%0, %1, %2, %3, %4, %5, %6, %7, %8, %9, %10, %11, %12, %13, %14, %15, %16, %17, %18, %19, %20, %21, %22, %23, %24, %25, %26, %27, %28, %29, %30, %31, %32, %33, %34, %35, %36, %37, %38, %39, %40, %41, %42, %43, %44, %45, %46, %47, %48, %49, %50, %51, %52, %53, %54, %55, %56, %57, %58, %59, %60, %61, %62, %63}, {%64, %65, %66, %67}, %68, p, 1, 1, 0;\n}\n"
        : "+f"(d[0]), "+f"(d[1]), "+f"(d[2]), "+f"(d[3]), "+f"(d[4]), "+f"(d[5]), "+f"(d[6]), "+f"(d[7]), "+f"(d[8]), "+f"(d[9]), "+f"(d[10]), "+f"(d[11]), "+f"(d[12]), "+f"(d[13]), "+f"(d[14]), "+f"(d[15]), "+f"(d[16]), "+f"(d[17]), "+f"(d[18]), "+f"(d[19]), "+f"(d[20]), "+f"(d[21]), "+f"(d[22]), "+f"(d[23]), "+f"(d[24]), "+f"(d[25]), "+f"(d[26]), "+f"(d[27]), "+f"(d[28]), "+f"(d[29]), "+f"(d[30]), "+f"(d[31]), "+f"(d[32]), "+f"(d[33]), "+f"(d[34]), "+f"(d[35]), "+f"(d[36]), "+f"(d[37]), "+f"(d[38]), "+f"(d[39]), "+f"(d[40]), "+f"(d[41]), "+f"(d[42]), "+f"(d[43]), "+f"(d[44]), "+f"(d[45]), "+f"(d[46]), "+f"(d[47]), "+f"(d[48]), "+f"(d[49]), "+f"(d[50]), "+f"(d[51]), "+f"(d[52]), "+f"(d[53]), "+f"(d[54]), "+f"(d[55]), "+f"(d[56]), "+f"(d[57]), "+f"(d[58]), "+f"(d[59]), "+f"(d[60]), "+f"(d[61]), "+f"(d[62]), "+f"(d[63])
        : "r"(a0), "r"(a1), "r"(a2), "r"(a3), "l"(db), "r"(scale_d));
}

__device__ __forceinline__ void wgmma_rs_n64_tb0(float (&d)[32], uint32_t a0, uint32_t a1, uint32_t a2, uint32_t a3, uint64_t db, int scale_d) {
    asm volatile("{\n.reg .pred p;\nsetp.ne.b32 p, %37, 0;\n"
        "wgmma.mma_async.sync.aligned.m64n64k16.f32.bf16.bf16 {%0, %1, %2, %3, %4, %5, %6, %7, %8, %9, %10, %11, %12, %13, %14, %15, %16, %17, %18, %19, %20, %21, %22, %23, %24, %25, %26, %27, %28, %29, %30, %31}, {%32, %33, %34, %35}, %36, p, 1, 1, 0;\n}\n"
        : "+f"(d[0]), "+f"(d[1]), "+f"(d[2]), "+f"(d[3]), "+f"(d[4]), "+f"(d[5]), "+f"(d[6]), "+f"(d[7]), "+f"(d[8]), "+f"(d[9]), "+f"(d[10]), "+f"(d[11]), "+f"(d[12]), "+f"(d[13]), "+f"(d[14]), "+f"(d[15]), "+f"(d[16]), "+f"(d[17]), "+f"(d[18]), "+f"(d[19]), "+f"(d[20]), "+f"(d[21]), "+f"(d[22]), "+f"(d[23]), "+f"(d[24]), "+f"(d[25]), "+f"(d[26]), "+f"(d[27]), "+f"(d[28]), "+f"(d[29]), "+f"(d[30]), "+f"(d[31])
        : "r"(a0), "r"(a1), "r"(a2), "r"(a3), "l"(db), "r"(scale_d));
}

__device__ __forceinline__ void wgmma_rs_n32_tb1(float (&d)[16], uint32_t a0, uint32_t a1, uint32_t a2, uint32_t a3, uint64_t db, int scale_d) {
    asm volatile("{\n.reg .pred p;\nsetp.ne.b32 p, %21, 0;\n"
        "wgmma.mma_async.sync.aligned.m64n32k16.f32.bf16.bf16 {%0, %1, %2, %3, %4, %5, %6, %7, %8, %9, %10, %11, %12, %13, %14, %15}, {%16, %17, %18, %19}, %20, p, 1, 1, 1;\n}\n"
        : "+f"(d[0]), "+f"(d[1]), "+f"(d[2]), "+f"(d[3]), "+f"(d[4]), "+f"(d[5]), "+f"(d[6]), "+f"(d[7]), "+f"(d[8]), "+f"(d[9]), "+f"(d[10]), "+f"(d[11]), "+f"(d[12]), "+f"(d[13]), "+f"(d[14]), "+f"(d[15])
        : "r"(a0), "r"(a1), "r"(a2), "r"(a3), "l"(db), "r"(scale_d));
}

__device__ __forceinline__ void wgmma_rs_n40_tb1(float (&d)[20], uint32_t a0, uint32_t a1, uint32_t a2, uint32_t a3, uint64_t db, int scale_d) {
    asm volatile("{\n.reg .pred p;\nsetp.ne.b32 p, %25, 0;\n"
        "wgmma.mma_async.sync.aligned.m64n40k16.f32.bf16.bf16 {%0, %1, %2, %3, %4, %5, %6, %7, %8, %9, %10, %11, %12, %13, %14, %15, %16, %17, %18, %19}, {%20, %21, %22, %23}, %24, p, 1, 1, 1;\n}\n"
        : "+f"(d[0]), "+f"(d[1]), "+f"(d[2]), "+f"(d[3]), "+f"(d[4]), "+f"(d[5]), "+f"(d[6]), "+f"(d[7]), "+f"(d[8]), "+f"(d[9]), "+f"(d[10]), "+f"(d[11]), "+f"(d[12]), "+f"(d[13]), "+f"(d[14]), "+f"(d[15]), "+f"(d[16]), "+f"(d[17]), "+f"(d[18]), "+f"(d[19])
        : "r"(a0), "r"(a1), "r"(a2), "r"(a3), "l"(db), "r"(scale_d));
}


template <int BN>
__device__ __forceinline__ void wgmma_tile(float (&d)[BN / 2], uint64_t da, uint64_t db, int sd) {
    if constexpr (BN == 128) wgmma_ss_n128_tb1(d, da, db, sd);
    else if constexpr (BN == 192) wgmma_ss_n192_tb1(d, da, db, sd);
    else if constexpr (BN == 224) wgmma_ss_n224_tb1(d, da, db, sd);
    else wgmma_ss_n256_tb1(d, da, db, sd);
}

__global__ void __launch_bounds__(256) prep_kernel(const bf16* __restrict__ x, const bf16* __restrict__ gate_w,
                                                   const bf16* __restrict__ w1, const bf16* __restrict__ w3) {
    const int tid = threadIdx.x;
    if (blockIdx.x < 256) {
        const int row = blockIdx.x * 8 + (tid >> 5);
        const int lane = tid & 31;
        const uint4* xr = reinterpret_cast<const uint4*>(x + (size_t)row * DM);
        const uint4* gw = reinterpret_cast<const uint4*>(gate_w);
        float v[32];
        float gsum = 0.f, sum = 0.f;
#pragma unroll
        for (int i = 0; i < 4; i++) {
            uint4 a = xr[lane + 32 * i];
            uint4 b = gw[lane + 32 * i];
            const uint32_t aa[4] = {a.x, a.y, a.z, a.w};
            const uint32_t bb[4] = {b.x, b.y, b.z, b.w};
#pragma unroll
            for (int j = 0; j < 4; j++) {
                float x0 = __uint_as_float(aa[j] << 16), x1 = __uint_as_float(aa[j] & 0xFFFF0000u);
                float g0 = __uint_as_float(bb[j] << 16), g1 = __uint_as_float(bb[j] & 0xFFFF0000u);
                v[i * 8 + j * 2] = x0;
                v[i * 8 + j * 2 + 1] = x1;
                sum += x0 + x1;
                gsum += bf16_round(x0 * g0) + bf16_round(x1 * g1);
            }
        }
#pragma unroll
        for (int o = 16; o > 0; o >>= 1) {
            sum += __shfl_xor_sync(0xffffffffu, sum, o);
            gsum += __shfl_xor_sync(0xffffffffu, gsum, o);
        }
        const float mean = sum * (1.0f / DM);
        float m2 = 0.f;
#pragma unroll
        for (int i = 0; i < 32; i++) {
            float d = v[i] - mean;
            m2 += d * d;
        }
#pragma unroll
        for (int o = 16; o > 0; o >>= 1) m2 += __shfl_xor_sync(0xffffffffu, m2, o);
        if (lane == 0) {
            g_mean1[row] = mean;
            g_rstd1[row] = rsqrtf(m2 * (1.0f / DM) + 1e-5f);
            float logit = bf16_round(gsum);
            float g = bf16_round(1.0f / (1.0f + __expf(-logit)));
            g_gate[row] = g;
            g_omg[row] = bf16_round(1.0f - g);
        }
    } else {
        __shared__ float red[32][65];
        const int strip = blockIdx.x - 256;
        const bf16* w;
        float* out;
        int ld, col0;
        if (strip < 16) { w = w1; ld = DM; col0 = strip * 64; out = g_cs1; }
        else { w = w3; ld = FF; col0 = (strip - 16) * 64; out = g_cs3; }
        const int cg = tid & 7;
        const int rg = tid >> 3;
        float acc[8];
#pragma unroll
        for (int j = 0; j < 8; j++) acc[j] = 0.f;
#pragma unroll 8
        for (int r = 0; r < 32; r++) {
            uint4 a = *reinterpret_cast<const uint4*>(w + (size_t)(r * 32 + rg) * ld + col0 + cg * 8);
            const uint32_t aa[4] = {a.x, a.y, a.z, a.w};
#pragma unroll
            for (int j = 0; j < 4; j++) {
                acc[2 * j] += __uint_as_float(aa[j] << 16);
                acc[2 * j + 1] += __uint_as_float(aa[j] & 0xFFFF0000u);
            }
        }
#pragma unroll
        for (int j = 0; j < 8; j++) red[rg][cg * 8 + j] = acc[j];
        __syncthreads();
        if (tid < 64) {
            float s = 0.f;
#pragma unroll
            for (int r = 0; r < 32; r++) s += red[r][tid];
            out[col0 + tid] = s;
        }
    }
}

template <int BN, int STAGES>
struct GemmSmem {
    static constexpr int A_BYTES = 128 * 64 * 2;
    static constexpr int B_BOXES = (BN + 63) / 64;
    static constexpr int B_BYTES = B_BOXES * 64 * 64 * 2;
    static constexpr int STAGE_BYTES = A_BYTES + B_BYTES;
    static constexpr int STG_OFF = STAGES * STAGE_BYTES;
    static constexpr int BAR_OFF = STG_OFF + 2 * 16384;
    static constexpr int TOTAL = BAR_OFF + 256 + 1024;
};

template <int MODE, int BN, int STAGES>
__global__ void __launch_bounds__(384, 1)
gemm_kernel(const __grid_constant__ CUtensorMap mA, const __grid_constant__ CUtensorMap mB0,
            const __grid_constant__ CUtensorMap mB1, const __grid_constant__ CUtensorMap mC0,
            const __grid_constant__ CUtensorMap mC1, const bf16* __restrict__ xin, int n_tiles_n, int kblocks) {
    using L = GemmSmem<BN, STAGES>;
    extern __shared__ uint8_t smem_raw[];
    const uint32_t sbase = (smem_u32(smem_raw) + 1023u) & ~1023u;
    const uint32_t bar_full = sbase + L::BAR_OFF;
    const uint32_t bar_empty = bar_full + 8 * STAGES;
    const int wg = threadIdx.x >> 7;
    const int ntiles = 16 * n_tiles_n;

    if (threadIdx.x == 0) {
        for (int s = 0; s < STAGES; s++) {
            mbar_init(bar_full + 8 * s, 1);
            mbar_init(bar_empty + 8 * s, 2);
        }
        asm volatile("fence.mbarrier_init.release.cluster;" ::: "memory");
    }
    __syncthreads();

    if (wg == 0) {
        reg_dealloc<40>();
        if (threadIdx.x == 0) {
            prefetch_tmap(&mA);
            prefetch_tmap(&mB0);
            prefetch_tmap(&mB1);
            int stage = 0;
            uint32_t phase = 1;
            for (int tile = blockIdx.x; tile < ntiles; tile += gridDim.x) {
                const int m0 = (tile & 15) * 128;
                const int n0 = (tile >> 4) * BN;
                for (int kb = 0; kb < kblocks; kb++) {
                    mbar_wait(bar_empty + 8 * stage, phase);
                    const uint32_t sa = sbase + stage * L::STAGE_BYTES;
                    const uint32_t sb = sa + L::A_BYTES;
                    const uint32_t fb = bar_full + 8 * stage;
                    mbar_expect_tx(fb, L::STAGE_BYTES);
                    int arow = m0;
                    if (MODE == 2) {
                        const int grp = kb >> 2;
                        arow += (grp == 0) ? -1 : (grp == 1) ? 1 : (grp == 2) ? -2 : 2;
                    }
                    tma_load_2d(sa, &mA, kb * 64, arow, fb);
                    const CUtensorMap* mb = &mB0;
                    int bc = n0, br = kb * 64;
                    if (MODE == 1 && n0 >= 3 * DM) { mb = &mB1; bc = n0 - 3 * DM; }
                    if (MODE == 5 && kb >= 16) { mb = &mB1; br = (kb - 16) * 64; }
#pragma unroll
                    for (int b = 0; b < L::B_BOXES; b++) tma_load_2d(sb + b * 8192, mb, bc + b * 64, br, fb);
                    if (++stage == STAGES) { stage = 0; phase ^= 1; }
                }
            }
        }
    } else {
        reg_alloc<232>();
        const int c = wg - 1;
        const int warp = (threadIdx.x >> 5) & 3;
        const int lane = threadIdx.x & 31;
        const int tid_wg = threadIdx.x & 127;
        const uint32_t stg = sbase + L::STG_OFF + c * 16384;
        int stage = 0;
        uint32_t phase = 0;
        float acc[BN / 2];
        for (int tile = blockIdx.x; tile < ntiles; tile += gridDim.x) {
            const int m0 = (tile & 15) * 128;
            const int n0 = (tile >> 4) * BN;
            int prev_stage = 0;
            for (int kb = 0; kb < kblocks; kb++) {
                mbar_wait(bar_full + 8 * stage, phase);
                const uint32_t sa = sbase + stage * L::STAGE_BYTES + c * 8192;
                const uint32_t sb = sbase + stage * L::STAGE_BYTES + L::A_BYTES;
                const uint64_t da = make_desc(sa, 16, 1024, 1);
                const uint64_t db = make_desc(sb, 8192, 1024, 1);
                wgmma_fence();
#pragma unroll
                for (int k = 0; k < 4; k++) wgmma_tile<BN>(acc, da + k * 2, db + k * 128, (kb | k) != 0);
                wgmma_commit();
                if (kb > 0) {
                    wgmma_wait<1>();
                    if (tid_wg == 0) mbar_arrive(bar_empty + 8 * prev_stage);
                }
                prev_stage = stage;
                if (++stage == STAGES) { stage = 0; phase ^= 1; }
            }
            wgmma_wait<0>();
            if (tid_wg == 0) mbar_arrive(bar_empty + 8 * prev_stage);

            const int r0 = m0 + c * 64 + warp * 16 + (lane >> 2);
            const int r1 = r0 + 8;
            const int cq = (lane & 3) * 2;
            const CUtensorMap* mc = &mC0;
            int out_c0 = n0;
            if (MODE == 1) {
                if (n0 >= 3 * DM) {
                    mc = &mC1;
                    out_c0 = n0 - 3 * DM;
                    const float mu0 = g_mean1[r0], mu1 = g_mean1[r1];
                    const float rs0 = g_rstd1[r0], rs1 = g_rstd1[r1];
#pragma unroll
                    for (int j = 0; j < BN / 8; j++) {
                        const float2 cs = *reinterpret_cast<const float2*>(&g_cs1[out_c0 + 8 * j + cq]);
                        acc[4 * j + 0] = gelu_tanh(rs0 * fmaf(-mu0, cs.x, acc[4 * j + 0]));
                        acc[4 * j + 1] = gelu_tanh(rs0 * fmaf(-mu0, cs.y, acc[4 * j + 1]));
                        acc[4 * j + 2] = gelu_tanh(rs1 * fmaf(-mu1, cs.x, acc[4 * j + 2]));
                        acc[4 * j + 3] = gelu_tanh(rs1 * fmaf(-mu1, cs.y, acc[4 * j + 3]));
                    }
                }
            } else if (MODE == 2) {
                float s0 = 0.f, s1 = 0.f;
#pragma unroll
                for (int j = 0; j < BN / 8; j++) {
                    const uint32_t xa = *reinterpret_cast<const uint32_t*>(xin + (size_t)r0 * DM + n0 + 8 * j + cq);
                    const uint32_t xb = *reinterpret_cast<const uint32_t*>(xin + (size_t)r1 * DM + n0 + 8 * j + cq);
                    acc[4 * j + 0] = bf16_round(bf16_round(acc[4 * j + 0]) + __uint_as_float(xa << 16));
                    acc[4 * j + 1] = bf16_round(bf16_round(acc[4 * j + 1]) + __uint_as_float(xa & 0xFFFF0000u));
                    acc[4 * j + 2] = bf16_round(bf16_round(acc[4 * j + 2]) + __uint_as_float(xb << 16));
                    acc[4 * j + 3] = bf16_round(bf16_round(acc[4 * j + 3]) + __uint_as_float(xb & 0xFFFF0000u));
                    s0 += acc[4 * j + 0] + acc[4 * j + 1];
                    s1 += acc[4 * j + 2] + acc[4 * j + 3];
                }
                s0 += __shfl_xor_sync(0xffffffffu, s0, 1);
                s0 += __shfl_xor_sync(0xffffffffu, s0, 2);
                s1 += __shfl_xor_sync(0xffffffffu, s1, 1);
                s1 += __shfl_xor_sync(0xffffffffu, s1, 2);
                const float mu0 = s0 * (1.0f / BN), mu1 = s1 * (1.0f / BN);
                float q0 = 0.f, q1 = 0.f;
#pragma unroll
                for (int j = 0; j < BN / 8; j++) {
                    float d;
                    d = acc[4 * j + 0] - mu0; q0 += d * d;
                    d = acc[4 * j + 1] - mu0; q0 += d * d;
                    d = acc[4 * j + 2] - mu1; q1 += d * d;
                    d = acc[4 * j + 3] - mu1; q1 += d * d;
                }
                q0 += __shfl_xor_sync(0xffffffffu, q0, 1);
                q0 += __shfl_xor_sync(0xffffffffu, q0, 2);
                q1 += __shfl_xor_sync(0xffffffffu, q1, 1);
                q1 += __shfl_xor_sync(0xffffffffu, q1, 2);
                if ((lane & 3) == 0) {
                    static_assert(MODE != 2 || BN == 128, "stats layout assumes BN=128");
                    g_stat2[r0 * 8 + (n0 >> 7)] = make_float2(s0, q0);
                    g_stat2[r1 * 8 + (n0 >> 7)] = make_float2(s1, q1);
                }
            } else if (MODE == 3) {
                out_c0 = n0 + DM;
                float mu[2], rs[2];
#pragma unroll
                for (int h = 0; h < 2; h++) {
                    const float4* sp = reinterpret_cast<const float4*>(&g_stat2[(h ? r1 : r0) * 8]);
                    float4 p[4];
                    float s = 0.f;
#pragma unroll
                    for (int i = 0; i < 4; i++) { p[i] = sp[i]; s += p[i].x + p[i].z; }
                    const float mean = s * (1.0f / DM);
                    float m2 = 0.f;
#pragma unroll
                    for (int i = 0; i < 4; i++) {
                        float d0 = p[i].x * (1.0f / 128) - mean, d1 = p[i].z * (1.0f / 128) - mean;
                        m2 += p[i].y + p[i].w + 128.0f * (d0 * d0 + d1 * d1);
                    }
                    mu[h] = mean;
                    rs[h] = rsqrtf(m2 * (1.0f / DM) + 1e-5f);
                }
                const float og0 = g_omg[r0], og1 = g_omg[r1];
#pragma unroll
                for (int j = 0; j < BN / 8; j++) {
                    const float2 cs = *reinterpret_cast<const float2*>(&g_cs3[n0 + 8 * j + cq]);
                    acc[4 * j + 0] = og0 * gelu_tanh(rs[0] * fmaf(-mu[0], cs.x, acc[4 * j + 0]));
                    acc[4 * j + 1] = og0 * gelu_tanh(rs[0] * fmaf(-mu[0], cs.y, acc[4 * j + 1]));
                    acc[4 * j + 2] = og1 * gelu_tanh(rs[1] * fmaf(-mu[1], cs.x, acc[4 * j + 2]));
                    acc[4 * j + 3] = og1 * gelu_tanh(rs[1] * fmaf(-mu[1], cs.y, acc[4 * j + 3]));
                }
            } else {
                const float og0 = g_omg[r0], og1 = g_omg[r1];
#pragma unroll
                for (int j = 0; j < BN / 8; j++) {
                    const uint32_t xa = *reinterpret_cast<const uint32_t*>(xin + (size_t)r0 * DM + n0 + 8 * j + cq);
                    const uint32_t xb = *reinterpret_cast<const uint32_t*>(xin + (size_t)r1 * DM + n0 + 8 * j + cq);
                    acc[4 * j + 0] = fmaf(og0, __uint_as_float(xa << 16), acc[4 * j + 0]);
                    acc[4 * j + 1] = fmaf(og0, __uint_as_float(xa & 0xFFFF0000u), acc[4 * j + 1]);
                    acc[4 * j + 2] = fmaf(og1, __uint_as_float(xb << 16), acc[4 * j + 2]);
                    acc[4 * j + 3] = fmaf(og1, __uint_as_float(xb & 0xFFFF0000u), acc[4 * j + 3]);
                }
            }
            const int srow = warp * 16 + (lane & 7) + ((lane >> 3) & 1) * 8;
#pragma unroll
            for (int rnd = 0; rnd < (BN + 127) / 128; rnd++) {
                if (tid_wg == 0) bulk_wait_read0();
                named_bar_sync(1 + c, 128);
#pragma unroll
                for (int jj = 0; jj < 8; jj++) {
                    const int j = rnd * 16 + jj * 2;
                    if (j * 8 < BN) {
                        const int jb = jj * 2 + (lane >> 4);
                        const uint32_t addr = stg + (jb >> 3) * 8192 + srow * 128 + (((jb & 7) ^ (srow & 7)) << 4);
                        stmatrix_x4(addr, pack_bf16(acc[4 * j + 0], acc[4 * j + 1]), pack_bf16(acc[4 * j + 2], acc[4 * j + 3]),
                                    pack_bf16(acc[4 * j + 4], acc[4 * j + 5]), pack_bf16(acc[4 * j + 6], acc[4 * j + 7]));
                    }
                }
                fence_proxy_async();
                named_bar_sync(1 + c, 128);
                if (tid_wg == 0) {
                    tma_store_2d(mc, stg, out_c0 + rnd * 128, m0 + c * 64);
                    if (rnd * 128 + 64 < BN) tma_store_2d(mc, stg + 8192, out_c0 + rnd * 128 + 64, m0 + c * 64);
                    bulk_commit();
                }
            }
        }
        if (tid_wg == 0) bulk_wait0();
    }
}

constexpr int ATT_STAGES = 4;
constexpr int ATT_DIST = 2;
constexpr int ATT_SMEM = ATT_STAGES * 16384 + 256 + 1024;

__global__ void __launch_bounds__(256, 2)
attn_kernel(const __grid_constant__ CUtensorMap mKV) {
    extern __shared__ uint8_t smem_raw[];
    const uint32_t sbase = (smem_u32(smem_raw) + 1023u) & ~1023u;
    const uint32_t bar_kfull = sbase + ATT_STAGES * 16384;
    const uint32_t bar_vfull = bar_kfull + 8 * ATT_STAGES;
    const uint32_t bar_empty = bar_vfull + 8 * ATT_STAGES;
    const int head = blockIdx.x >> 4;
    const int q0 = (blockIdx.x & 15) * 128;
    const int warp_id = threadIdx.x >> 5;
    const int lane = threadIdx.x & 31;
    constexpr int NBLK = S_LEN / 128;

    if (threadIdx.x == 0) {
        for (int s = 0; s < ATT_STAGES; s++) {
            mbar_init(bar_kfull + 8 * s, 1);
            mbar_init(bar_vfull + 8 * s, 1);
            mbar_init(bar_empty + 8 * s, 2);
        }
        asm volatile("fence.mbarrier_init.release.cluster;" ::: "memory");
        prefetch_tmap(&mKV);
#pragma unroll
        for (int j = 0; j < ATT_DIST; j++) {
            const uint32_t sk = sbase + j * 16384;
            mbar_expect_tx(bar_kfull + 8 * j, 8192);
            tma_load_2d(sk, &mKV, DM + head * DH, j * 128, bar_kfull + 8 * j);
            mbar_expect_tx(bar_vfull + 8 * j, 8192);
            tma_load_2d(sk + 8192, &mKV, 2 * DM + head * DH, j * 128, bar_vfull + 8 * j);
        }
    }
    __syncthreads();

    const int tid_wg = threadIdx.x & 127;
    const int row0 = q0 + warp_id * 16 + (lane >> 2);
    const int cq = (lane & 3) * 2;
    uint32_t qf[8];
    {
        const bf16* qp0 = g_qkv + (size_t)row0 * (3 * DM) + head * DH + cq;
        const bf16* qp1 = qp0 + 8 * (3 * DM);
#pragma unroll
        for (int t = 0; t < 2; t++) {
            qf[4 * t + 0] = *reinterpret_cast<const uint32_t*>(qp0 + 16 * t);
            qf[4 * t + 1] = *reinterpret_cast<const uint32_t*>(qp1 + 16 * t);
            qf[4 * t + 2] = *reinterpret_cast<const uint32_t*>(qp0 + 16 * t + 8);
            qf[4 * t + 3] = *reinterpret_cast<const uint32_t*>(qp1 + 16 * t + 8);
        }
    }
    const float cs = 0.17677669529663687f * 1.4426950408889634f;
    float o[16];
#pragma unroll
    for (int i = 0; i < 16; i++) o[i] = 0.f;
    float m0 = -INFINITY, m1 = -INFINITY, l0 = 0.f, l1 = 0.f;
    int stage = 0;
    uint32_t phase = 0;
    for (int j = 0; j < NBLK; j++) {
        if (threadIdx.x == 0 && j + ATT_DIST < NBLK) {
            const int jn = j + ATT_DIST;
            const int sn = jn % ATT_STAGES;
            if (jn >= ATT_STAGES) mbar_wait(bar_empty + 8 * sn, ((jn / ATT_STAGES) - 1) & 1);
            const uint32_t skn = sbase + sn * 16384;
            mbar_expect_tx(bar_kfull + 8 * sn, 8192);
            tma_load_2d(skn, &mKV, DM + head * DH, jn * 128, bar_kfull + 8 * sn);
            mbar_expect_tx(bar_vfull + 8 * sn, 8192);
            tma_load_2d(skn + 8192, &mKV, 2 * DM + head * DH, jn * 128, bar_vfull + 8 * sn);
        }
        __syncwarp();
        const uint32_t sk = sbase + stage * 16384;
        float s[64];
        mbar_wait(bar_kfull + 8 * stage, phase);
        const uint64_t dk = make_desc(sk, 16, 512, 2);
        wgmma_fence();
        wgmma_rs_n128_tb0(s, qf[0], qf[1], qf[2], qf[3], dk, 0);
        wgmma_rs_n128_tb0(s, qf[4], qf[5], qf[6], qf[7], dk + 2, 1);
        wgmma_commit();
        wgmma_wait<0>();
        float mx0 = s[0], mx1 = s[2];
#pragma unroll
        for (int i = 0; i < 16; i++) {
            mx0 = fmaxf(mx0, fmaxf(s[4 * i], s[4 * i + 1]));
            mx1 = fmaxf(mx1, fmaxf(s[4 * i + 2], s[4 * i + 3]));
        }
        mx0 = fmaxf(mx0, __shfl_xor_sync(0xffffffffu, mx0, 1));
        mx0 = fmaxf(mx0, __shfl_xor_sync(0xffffffffu, mx0, 2));
        mx1 = fmaxf(mx1, __shfl_xor_sync(0xffffffffu, mx1, 1));
        mx1 = fmaxf(mx1, __shfl_xor_sync(0xffffffffu, mx1, 2));
        const float mn0 = fmaxf(m0, mx0), mn1 = fmaxf(m1, mx1);
        const float a0 = ex2((m0 - mn0) * cs), a1 = ex2((m1 - mn1) * cs);
        m0 = mn0; m1 = mn1;
        const float b0 = mn0 * cs, b1 = mn1 * cs;
        float t0 = 0.f, t1 = 0.f;
        uint32_t p[32];
#pragma unroll
        for (int i = 0; i < 16; i++) {
            const float e0 = ex2(fmaf(s[4 * i + 0], cs, -b0));
            const float e1 = ex2(fmaf(s[4 * i + 1], cs, -b0));
            const float e2 = ex2(fmaf(s[4 * i + 2], cs, -b1));
            const float e3 = ex2(fmaf(s[4 * i + 3], cs, -b1));
            t0 += e0 + e1;
            t1 += e2 + e3;
            p[2 * i] = pack_bf16(e0, e1);
            p[2 * i + 1] = pack_bf16(e2, e3);
        }
        l0 = fmaf(l0, a0, t0);
        l1 = fmaf(l1, a1, t1);
#pragma unroll
        for (int i = 0; i < 4; i++) {
            o[4 * i + 0] *= a0; o[4 * i + 1] *= a0;
            o[4 * i + 2] *= a1; o[4 * i + 3] *= a1;
        }
        mbar_wait(bar_vfull + 8 * stage, phase);
        const uint64_t dv = make_desc(sk + 8192, 16, 512, 2);
        wgmma_fence();
#pragma unroll
        for (int t = 0; t < 8; t++)
            wgmma_rs_n32_tb1(o, p[4 * t], p[4 * t + 1], p[4 * t + 2], p[4 * t + 3], dv + t * 64, 1);
        wgmma_commit();
        wgmma_wait<0>();
        if (tid_wg == 0) mbar_arrive(bar_empty + 8 * stage);
        if (++stage == ATT_STAGES) { stage = 0; phase ^= 1; }
    }
    l0 += __shfl_xor_sync(0xffffffffu, l0, 1);
    l0 += __shfl_xor_sync(0xffffffffu, l0, 2);
    l1 += __shfl_xor_sync(0xffffffffu, l1, 1);
    l1 += __shfl_xor_sync(0xffffffffu, l1, 2);
    const float f0 = g_gate[row0] / l0, f1 = g_gate[row0 + 8] / l1;
    bf16* op0 = g_a5 + (size_t)row0 * A5W + head * DH + cq;
    bf16* op1 = op0 + 8 * A5W;
#pragma unroll
    for (int i = 0; i < 4; i++) {
        *reinterpret_cast<uint32_t*>(op0 + 8 * i) = pack_bf16(o[4 * i] * f0, o[4 * i + 1] * f0);
        *reinterpret_cast<uint32_t*>(op1 + 8 * i) = pack_bf16(o[4 * i + 2] * f1, o[4 * i + 3] * f1);
    }
}

typedef CUresult (*EncodeFn)(CUtensorMap*, CUtensorMapDataType, cuuint32_t, void*, const cuuint64_t*, const cuuint64_t*,
                             const cuuint32_t*, const cuuint32_t*, CUtensorMapInterleave, CUtensorMapSwizzle,
                             CUtensorMapL2promotion, CUtensorMapFloatOOBfill);

static CUtensorMap make_map(EncodeFn fn, const void* ptr, int rows, int cols, int box_cols, int box_rows,
                            CUtensorMapSwizzle swz) {
    CUtensorMap m;
    cuuint64_t dims[2] = {(cuuint64_t)cols, (cuuint64_t)rows};
    cuuint64_t strides[1] = {(cuuint64_t)cols * 2};
    cuuint32_t box[2] = {(cuuint32_t)box_cols, (cuuint32_t)box_rows};
    cuuint32_t es[2] = {1, 1};
    fn(&m, CU_TENSOR_MAP_DATA_TYPE_BFLOAT16, 2, const_cast<void*>(ptr), dims, strides, box, es,
       CU_TENSOR_MAP_INTERLEAVE_NONE, swz, CU_TENSOR_MAP_L2_PROMOTION_L2_256B, CU_TENSOR_MAP_FLOAT_OOB_FILL_NONE);
    return m;
}

extern "C" void kernel_launch(void* const* d_in, const int* in_sizes, int n_in, void* d_out, int out_size) {
    const bf16* x = (const bf16*)d_in[0];
    const bf16* wqkv = (const bf16*)d_in[1];
    const bf16* wo = (const bf16*)d_in[2];
    const bf16* w1 = (const bf16*)d_in[4];
    const bf16* w2 = (const bf16*)d_in[5];
    const bf16* w3 = (const bf16*)d_in[6];
    const bf16* w4 = (const bf16*)d_in[7];
    const bf16* gate_w = (const bf16*)d_in[8];

    static EncodeFn enc = nullptr;
    static void *p_qkv, *p_h, *p_x1, *p_a5;
    if (!enc) {
        void* fn = nullptr;
        cudaDriverEntryPointQueryResult qres;
        cudaGetDriverEntryPoint("cuTensorMapEncodeTiled", &fn, cudaEnableDefault, &qres);
        enc = (EncodeFn)fn;
        cudaGetSymbolAddress(&p_qkv, g_qkv);
        cudaGetSymbolAddress(&p_h, g_h);
        cudaGetSymbolAddress(&p_x1, g_x1);
        cudaGetSymbolAddress(&p_a5, g_a5);
        cudaFuncSetAttribute(gemm_kernel<1, 256, 4>, cudaFuncAttributeMaxDynamicSharedMemorySize, GemmSmem<256, 4>::TOTAL);
        cudaFuncSetAttribute(gemm_kernel<2, 128, 5>, cudaFuncAttributeMaxDynamicSharedMemorySize, GemmSmem<128, 5>::TOTAL);
        cudaFuncSetAttribute(gemm_kernel<3, 256, 4>, cudaFuncAttributeMaxDynamicSharedMemorySize, GemmSmem<256, 4>::TOTAL);
        cudaFuncSetAttribute(gemm_kernel<5, 128, 5>, cudaFuncAttributeMaxDynamicSharedMemorySize, GemmSmem<128, 5>::TOTAL);
        cudaFuncSetAttribute(attn_kernel, cudaFuncAttributeMaxDynamicSharedMemorySize, ATT_SMEM);
    }
    const CUtensorMapSwizzle SW128 = CU_TENSOR_MAP_SWIZZLE_128B, SW64 = CU_TENSOR_MAP_SWIZZLE_64B;
    CUtensorMap mX = make_map(enc, x, S_LEN, DM, 64, 128, SW128);
    CUtensorMap mWqkv = make_map(enc, wqkv, DM, 3 * DM, 64, 64, SW128);
    CUtensorMap mW1 = make_map(enc, w1, DM, DM, 64, 64, SW128);
    CUtensorMap mW2 = make_map(enc, w2, DM, DM, 64, 64, SW128);
    CUtensorMap mW3 = make_map(enc, w3, DM, FF, 64, 64, SW128);
    CUtensorMap mW4 = make_map(enc, w4, FF, DM, 64, 64, SW128);
    CUtensorMap mWo = make_map(enc, wo, DM, DM, 64, 64, SW128);
    CUtensorMap mQKVst = make_map(enc, p_qkv, S_LEN, 3 * DM, 64, 64, SW128);
    CUtensorMap mKV = make_map(enc, p_qkv, S_LEN, 3 * DM, 32, 128, SW64);
    CUtensorMap mHst = make_map(enc, p_h, S_LEN, DM, 64, 64, SW128);
    CUtensorMap mHld = make_map(enc, p_h, S_LEN, DM, 64, 128, SW128);
    CUtensorMap mX1st = make_map(enc, p_x1, S_LEN, DM, 64, 64, SW128);
    CUtensorMap mX1ld = make_map(enc, p_x1, S_LEN, DM, 64, 128, SW128);
    CUtensorMap mA5st = make_map(enc, p_a5, S_LEN, A5W, 64, 64, SW128);
    CUtensorMap mA5ld = make_map(enc, p_a5, S_LEN, A5W, 64, 128, SW128);
    CUtensorMap mOut = make_map(enc, d_out, S_LEN, DM, 64, 64, SW128);

    cudaStream_t st = cudaStreamPerThread;
    prep_kernel<<<256 + 72, 256, 0, st>>>(x, gate_w, w1, w3);
    gemm_kernel<1, 256, 4><<<132, 384, GemmSmem<256, 4>::TOTAL, st>>>(mX, mWqkv, mW1, mQKVst, mHst, x, 16, 16);
    attn_kernel<<<NH * 16, 256, ATT_SMEM, st>>>(mKV);
    gemm_kernel<2, 128, 5><<<128, 384, GemmSmem<128, 5>::TOTAL, st>>>(mHld, mW2, mW2, mX1st, mX1st, x, 8, 16);
    gemm_kernel<3, 256, 4><<<132, 384, GemmSmem<256, 4>::TOTAL, st>>>(mX1ld, mW3, mW3, mA5st, mA5st, x, 14, 16);
    gemm_kernel<5, 128, 5><<<128, 384, GemmSmem<128, 5>::TOTAL, st>>>(mA5ld, mWo, mW4, mOut, mOut, (const bf16*)p_x1, 8, 72);
}
```

```cpp
#include <cuda_runtime.h>
#include <cuda_bf16.h>
#include <cuda.h>
#include <stdint.h>

typedef __nv_bfloat16 bf16;

constexpr int S_LEN = 2048;
constexpr int DM = 1024;
constexpr int FF = 3584;
constexpr int NH = 32;
constexpr int DH = 32;
constexpr int A5W = DM + FF;

__device__ __align__(1024) bf16 g_qkv[S_LEN * 3 * DM];
__device__ __align__(1024) bf16 g_h[S_LEN * DM];
__device__ __align__(1024) bf16 g_x1[S_LEN * DM];
__device__ __align__(1024) bf16 g_a5[S_LEN * A5W];
__device__ __align__(16) float g_mean1[S_LEN];
__device__ __align__(16) float g_rstd1[S_LEN];
__device__ __align__(16) float g_gate[S_LEN];
__device__ __align__(16) float g_omg[S_LEN];
__device__ __align__(16) float g_cs1[DM];
__device__ __align__(16) float g_cs3[FF];
__device__ __align__(16) float2 g_stat2[S_LEN * 8];

__device__ __forceinline__ uint32_t smem_u32(const void* p) { return (uint32_t)__cvta_generic_to_shared(p); }

__device__ __forceinline__ void mbar_init(uint32_t bar, uint32_t count) {
    asm volatile("mbarrier.init.shared::cta.b64 [%0], %1;" ::"r"(bar), "r"(count));
}
__device__ __forceinline__ void mbar_expect_tx(uint32_t bar, uint32_t bytes) {
    asm volatile("mbarrier.arrive.expect_tx.shared::cta.b64 _, [%0], %1;" ::"r"(bar), "r"(bytes) : "memory");
}
__device__ __forceinline__ void mbar_arrive(uint32_t bar) {
    asm volatile("mbarrier.arrive.shared::cta.b64 _, [%0];" ::"r"(bar) : "memory");
}
__device__ __forceinline__ bool mbar_try_wait(uint32_t bar, uint32_t parity) {
    uint32_t ok;
    asm volatile(
        "{\n.reg .pred p;\n"
        "mbarrier.try_wait.parity.shared::cta.b64 p, [%1], %2;\n"
        "selp.u32 %0, 1, 0, p;\n}\n"
        : "=r"(ok)
        : "r"(bar), "r"(parity)
        : "memory");
    return ok != 0;
}
__device__ __forceinline__ void mbar_wait(uint32_t bar, uint32_t parity) {
    uint32_t spins = 0;
    while (!mbar_try_wait(bar, parity)) {
        if (++spins > (1u << 24)) __trap();
    }
}
__device__ __forceinline__ void tma_load_2d(uint32_t dst, const CUtensorMap* map, int c0, int c1, uint32_t bar) {
    asm volatile(
        "cp.async.bulk.tensor.2d.shared::cluster.global.mbarrier::complete_tx::bytes [%0], [%1, {%3, %4}], [%2];"
        ::"r"(dst), "l"(map), "r"(bar), "r"(c0), "r"(c1)
        : "memory");
}
__device__ __forceinline__ void tma_store_2d(const CUtensorMap* map, uint32_t src, int c0, int c1) {
    asm volatile("cp.async.bulk.tensor.2d.global.shared::cta.bulk_group [%0, {%2, %3}], [%1];"
                 ::"l"(map), "r"(src), "r"(c0), "r"(c1)
                 : "memory");
}
__device__ __forceinline__ void bulk_commit() { asm volatile("cp.async.bulk.commit_group;" ::: "memory"); }
__device__ __forceinline__ void bulk_wait_read0() { asm volatile("cp.async.bulk.wait_group.read 0;" ::: "memory"); }
__device__ __forceinline__ void bulk_wait0() { asm volatile("cp.async.bulk.wait_group 0;" ::: "memory"); }
__device__ __forceinline__ void fence_proxy_async() { asm volatile("fence.proxy.async.shared::cta;" ::: "memory"); }
__device__ __forceinline__ void named_bar_sync(int id, int n) { asm volatile("bar.sync %0, %1;" ::"r"(id), "r"(n) : "memory"); }
__device__ __forceinline__ void named_bar_arrive(int id, int n) { asm volatile("bar.arrive %0, %1;" ::"r"(id), "r"(n) : "memory"); }
__device__ __forceinline__ void wgmma_fence() { asm volatile("wgmma.fence.sync.aligned;" ::: "memory"); }
__device__ __forceinline__ void wgmma_commit() { asm volatile("wgmma.commit_group.sync.aligned;" ::: "memory"); }
template <int N>
__device__ __forceinline__ void wgmma_wait() { asm volatile("wgmma.wait_group.sync.aligned %0;" ::"n"(N) : "memory"); }
__device__ __forceinline__ void prefetch_tmap(const CUtensorMap* m) {
    asm volatile("prefetch.tensormap [%0];" ::"l"(m) : "memory");
}
template <int R>
__device__ __forceinline__ void reg_alloc() { asm volatile("setmaxnreg.inc.sync.aligned.u32 %0;" ::"n"(R)); }
template <int R>
__device__ __forceinline__ void reg_dealloc() { asm volatile("setmaxnreg.dec.sync.aligned.u32 %0;" ::"n"(R)); }
__device__ __forceinline__ void stmatrix_x4(uint32_t addr, uint32_t r0, uint32_t r1, uint32_t r2, uint32_t r3) {
    asm volatile("stmatrix.sync.aligned.m8n8.x4.shared.b16 [%0], {%1, %2, %3, %4};"
                 ::"r"(addr), "r"(r0), "r"(r1), "r"(r2), "r"(r3)
                 : "memory");
}
__device__ __forceinline__ uint32_t pack_bf16(float lo, float hi) {
    uint32_t r;
    asm("cvt.rn.bf16x2.f32 %0, %1, %2;" : "=r"(r) : "f"(hi), "f"(lo));
    return r;
}
__device__ __forceinline__ float bf16_round(float v) { return __bfloat162float(__float2bfloat16_rn(v)); }
__device__ __forceinline__ float ex2(float x) {
    float y;
    asm("ex2.approx.ftz.f32 %0, %1;" : "=f"(y) : "f"(x));
    return y;
}
__device__ __forceinline__ float tanh_fast(float x) {
    float y;
    asm("tanh.approx.f32 %0, %1;" : "=f"(y) : "f"(x));
    return y;
}
__device__ __forceinline__ float gelu_tanh(float v) {
    float u = 0.7978845608028654f * (v + 0.044715f * v * v * v);
    float hv = 0.5f * v;
    return fmaf(hv, tanh_fast(u), hv);
}
__device__ __forceinline__ uint64_t make_desc(uint32_t addr, uint32_t lbo_bytes, uint32_t sbo_bytes, uint32_t swz) {
    uint64_t d = 0;
    d |= (uint64_t)((addr & 0x3FFFF) >> 4);
    d |= (uint64_t)((lbo_bytes >> 4) & 0x3FFF) << 16;
    d |= (uint64_t)((sbo_bytes >> 4) & 0x3FFF) << 32;
    d |= (uint64_t)swz << 62;
    return d;
}


__device__ __forceinline__ void wgmma_ss_n128_tb1(float (&d)[64], uint64_t da, uint64_t db, int scale_d) {
    asm volatile("{\n.reg .pred p;\nsetp.ne.b32 p, %66, 0;\n"
        "wgmma.mma_async.sync.aligned.m64n128k16.f32.bf16.bf16 {%0, %1, %2, %3, %4, %5, %6, %7, %8, %9, %10, %11, %12, %13, %14, %15, %16, %17, %18, %19, %20, %21, %22, %23, %24, %25, %26, %27, %28, %29, %30, %31, %32, %33, %34, %35, %36, %37, %38, %39, %40, %41, %42, %43, %44, %45, %46, %47, %48, %49, %50, %51, %52, %53, %54, %55, %56, %57, %58, %59, %60, %61, %62, %63}, %64, %65, p, 1, 1, 0, 1;\n}\n"
        : "+f"(d[0]), "+f"(d[1]), "+f"(d[2]), "+f"(d[3]), "+f"(d[4]), "+f"(d[5]), "+f"(d[6]), "+f"(d[7]), "+f"(d[8]), "+f"(d[9]), "+f"(d[10]), "+f"(d[11]), "+f"(d[12]), "+f"(d[13]), "+f"(d[14]), "+f"(d[15]), "+f"(d[16]), "+f"(d[17]), "+f"(d[18]), "+f"(d[19]), "+f"(d[20]), "+f"(d[21]), "+f"(d[22]), "+f"(d[23]), "+f"(d[24]), "+f"(d[25]), "+f"(d[26]), "+f"(d[27]), "+f"(d[28]), "+f"(d[29]), "+f"(d[30]), "+f"(d[31]), "+f"(d[32]), "+f"(d[33]), "+f"(d[34]), "+f"(d[35]), "+f"(d[36]), "+f"(d[37]), "+f"(d[38]), "+f"(d[39]), "+f"(d[40]), "+f"(d[41]), "+f"(d[42]), "+f"(d[43]), "+f"(d[44]), "+f"(d[45]), "+f"(d[46]), "+f"(d[47]), "+f"(d[48]), "+f"(d[49]), "+f"(d[50]), "+f"(d[51]), "+f"(d[52]), "+f"(d[53]), "+f"(d[54]), "+f"(d[55]), "+f"(d[56]), "+f"(d[57]), "+f"(d[58]), "+f"(d[59]), "+f"(d[60]), "+f"(d[61]), "+f"(d[62]), "+f"(d[63])
        : "l"(da), "l"(db), "r"(scale_d));
}

__device__ __forceinline__ void wgmma_ss_n192_tb1(float (&d)[96], uint64_t da, uint64_t db, int scale_d) {
    asm volatile("{\n.reg .pred p;\nsetp.ne.b32 p, %98, 0;\n"
        "wgmma.mma_async.sync.aligned.m64n192k16.f32.bf16.bf16 {%0, %1, %2, %3, %4, %5, %6, %7, %8, %9, %10, %11, %12, %13, %14, %15, %16, %17, %18, %19, %20, %21, %22, %23, %24, %25, %26, %27, %28, %29, %30, %31, %32, %33, %34, %35, %36, %37, %38, %39, %40, %41, %42, %43, %44, %45, %46, %47, %48, %49, %50, %51, %52, %53, %54, %55, %56, %57, %58, %59, %60, %61, %62, %63, %64, %65, %66, %67, %68, %69, %70, %71, %72, %73, %74, %75, %76, %77, %78, %79, %80, %81, %82, %83, %84, %85, %86, %87, %88, %89, %90, %91, %92, %93, %94, %95}, %96, %97, p, 1, 1, 0, 1;\n}\n"
        : "+f"(d[0]), "+f"(d[1]), "+f"(d[2]), "+f"(d[3]), "+f"(d[4]), "+f"(d[5]), "+f"(d[6]), "+f"(d[7]), "+f"(d[8]), "+f"(d[9]), "+f"(d[10]), "+f"(d[11]), "+f"(d[12]), "+f"(d[13]), "+f"(d[14]), "+f"(d[15]), "+f"(d[16]), "+f"(d[17]), "+f"(d[18]), "+f"(d[19]), "+f"(d[20]), "+f"(d[21]), "+f"(d[22]), "+f"(d[23]), "+f"(d[24]), "+f"(d[25]), "+f"(d[26]), "+f"(d[27]), "+f"(d[28]), "+f"(d[29]), "+f"(d[30]), "+f"(d[31]), "+f"(d[32]), "+f"(d[33]), "+f"(d[34]), "+f"(d[35]), "+f"(d[36]), "+f"(d[37]), "+f"(d[38]), "+f"(d[39]), "+f"(d[40]), "+f"(d[41]), "+f"(d[42]), "+f"(d[43]), "+f"(d[44]), "+f"(d[45]), "+f"(d[46]), "+f"(d[47]), "+f"(d[48]), "+f"(d[49]), "+f"(d[50]), "+f"(d[51]), "+f"(d[52]), "+f"(d[53]), "+f"(d[54]), "+f"(d[55]), "+f"(d[56]), "+f"(d[57]), "+f"(d[58]), "+f"(d[59]), "+f"(d[60]), "+f"(d[61]), "+f"(d[62]), "+f"(d[63]), "+f"(d[64]), "+f"(d[65]), "+f"(d[66]), "+f"(d[67]), "+f"(d[68]), "+f"(d[69]), "+f"(d[70]), "+f"(d[71]), "+f"(d[72]), "+f"(d[73]), "+f"(d[74]), "+f"(d[75]), "+f"(d[76]), "+f"(d[77]), "+f"(d[78]), "+f"(d[79]), "+f"(d[80]), "+f"(d[81]), "+f"(d[82]), "+f"(d[83]), "+f"(d[84]), "+f"(d[85]), "+f"(d[86]), "+f"(d[87]), "+f"(d[88]), "+f"(d[89]), "+f"(d[90]), "+f"(d[91]), "+f"(d[92]), "+f"(d[93]), "+f"(d[94]), "+f"(d[95])
        : "l"(da), "l"(db), "r"(scale_d));
}

__device__ __forceinline__ void wgmma_ss_n224_tb1(float (&d)[112], uint64_t da, uint64_t db, int scale_d) {
    asm volatile("{\n.reg .pred p;\nsetp.ne.b32 p, %114, 0;\n"
        "wgmma.mma_async.sync.aligned.m64n224k16.f32.bf16.bf16 {%0, %1, %2, %3, %4, %5, %6, %7, %8, %9, %10, %11, %12, %13, %14, %15, %16, %17, %18, %19, %20, %21, %22, %23, %24, %25, %26, %27, %28, %29, %30, %31, %32, %33, %34, %35, %36, %37, %38, %39, %40, %41, %42, %43, %44, %45, %46, %47, %48, %49, %50, %51, %52, %53, %54, %55, %56, %57, %58, %59, %60, %61, %62, %63, %64, %65, %66, %67, %68, %69, %70, %71, %72, %73, %74, %75, %76, %77, %78, %79, %80, %81, %82, %83, %84, %85, %86, %87, %88, %89, %90, %91, %92, %93, %94, %95, %96, %97, %98, %99, %100, %101, %102, %103, %104, %105, %106, %107, %108, %109, %110, %111}, %112, %113, p, 1, 1, 0, 1;\n}\n"
        : "+f"(d[0]), "+f"(d[1]), "+f"(d[2]), "+f"(d[3]), "+f"(d[4]), "+f"(d[5]), "+f"(d[6]), "+f"(d[7]), "+f"(d[8]), "+f"(d[9]), "+f"(d[10]), "+f"(d[11]), "+f"(d[12]), "+f"(d[13]), "+f"(d[14]), "+f"(d[15]), "+f"(d[16]), "+f"(d[17]), "+f"(d[18]), "+f"(d[19]), "+f"(d[20]), "+f"(d[21]), "+f"(d[22]), "+f"(d[23]), "+f"(d[24]), "+f"(d[25]), "+f"(d[26]), "+f"(d[27]), "+f"(d[28]), "+f"(d[29]), "+f"(d[30]), "+f"(d[31]), "+f"(d[32]), "+f"(d[33]), "+f"(d[34]), "+f"(d[35]), "+f"(d[36]), "+f"(d[37]), "+f"(d[38]), "+f"(d[39]), "+f"(d[40]), "+f"(d[41]), "+f"(d[42]), "+f"(d[43]), "+f"(d[44]), "+f"(d[45]), "+f"(d[46]), "+f"(d[47]), "+f"(d[48]), "+f"(d[49]), "+f"(d[50]), "+f"(d[51]), "+f"(d[52]), "+f"(d[53]), "+f"(d[54]), "+f"(d[55]), "+f"(d[56]), "+f"(d[57]), "+f"(d[58]), "+f"(d[59]), "+f"(d[60]), "+f"(d[61]), "+f"(d[62]), "+f"(d[63]), "+f"(d[64]), "+f"(d[65]), "+f"(d[66]), "+f"(d[67]), "+f"(d[68]), "+f"(d[69]), "+f"(d[70]), "+f"(d[71]), "+f"(d[72]), "+f"(d[73]), "+f"(d[74]), "+f"(d[75]), "+f"(d[76]), "+f"(d[77]), "+f"(d[78]), "+f"(d[79]), "+f"(d[80]), "+f"(d[81]), "+f"(d[82]), "+f"(d[83]), "+f"(d[84]), "+f"(d[85]), "+f"(d[86]), "+f"(d[87]), "+f"(d[88]), "+f"(d[89]), "+f"(d[90]), "+f"(d[91]), "+f"(d[92]), "+f"(d[93]), "+f"(d[94]), "+f"(d[95]), "+f"(d[96]), "+f"(d[97]), "+f"(d[98]), "+f"(d[99]), "+f"(d[100]), "+f"(d[101]), "+f"(d[102]), "+f"(d[103]), "+f"(d[104]), "+f"(d[105]), "+f"(d[106]), "+f"(d[107]), "+f"(d[108]), "+f"(d[109]), "+f"(d[110]), "+f"(d[111])
        : "l"(da), "l"(db), "r"(scale_d));
}

__device__ __forceinline__ void wgmma_ss_n256_tb1(float (&d)[128], uint64_t da, uint64_t db, int scale_d) {
    asm volatile("{\n.reg .pred p;\nsetp.ne.b32 p, %130, 0;\n"
        "wgmma.mma_async.sync.aligned.m64n256k16.f32.bf16.bf16 {%0, %1, %2, %3, %4, %5, %6, %7, %8, %9, %10, %11, %12, %13, %14, %15, %16, %17, %18, %19, %20, %21, %22, %23, %24, %25, %26, %27, %28, %29, %30, %31, %32, %33, %34, %35, %36, %37, %38, %39, %40, %41, %42, %43, %44, %45, %46, %47, %48, %49, %50, %51, %52, %53, %54, %55, %56, %57, %58, %59, %60, %61, %62, %63, %64, %65, %66, %67, %68, %69, %70, %71, %72, %73, %74, %75, %76, %77, %78, %79, %80, %81, %82, %83, %84, %85, %86, %87, %88, %89, %90, %91, %92, %93, %94, %95, %96, %97, %98, %99, %100, %101, %102, %103, %104, %105, %106, %107, %108, %109, %110, %111, %112, %113, %114, %115, %116, %117, %118, %119, %120, %121, %122, %123, %124, %125, %126, %127}, %128, %129, p, 1, 1, 0, 1;\n}\n"
        : "+f"(d[0]), "+f"(d[1]), "+f"(d[2]), "+f"(d[3]), "+f"(d[4]), "+f"(d[5]), "+f"(d[6]), "+f"(d[7]), "+f"(d[8]), "+f"(d[9]), "+f"(d[10]), "+f"(d[11]), "+f"(d[12]), "+f"(d[13]), "+f"(d[14]), "+f"(d[15]), "+f"(d[16]), "+f"(d[17]), "+f"(d[18]), "+f"(d[19]), "+f"(d[20]), "+f"(d[21]), "+f"(d[22]), "+f"(d[23]), "+f"(d[24]), "+f"(d[25]), "+f"(d[26]), "+f"(d[27]), "+f"(d[28]), "+f"(d[29]), "+f"(d[30]), "+f"(d[31]), "+f"(d[32]), "+f"(d[33]), "+f"(d[34]), "+f"(d[35]), "+f"(d[36]), "+f"(d[37]), "+f"(d[38]), "+f"(d[39]), "+f"(d[40]), "+f"(d[41]), "+f"(d[42]), "+f"(d[43]), "+f"(d[44]), "+f"(d[45]), "+f"(d[46]), "+f"(d[47]), "+f"(d[48]), "+f"(d[49]), "+f"(d[50]), "+f"(d[51]), "+f"(d[52]), "+f"(d[53]), "+f"(d[54]), "+f"(d[55]), "+f"(d[56]), "+f"(d[57]), "+f"(d[58]), "+f"(d[59]), "+f"(d[60]), "+f"(d[61]), "+f"(d[62]), "+f"(d[63]), "+f"(d[64]), "+f"(d[65]), "+f"(d[66]), "+f"(d[67]), "+f"(d[68]), "+f"(d[69]), "+f"(d[70]), "+f"(d[71]), "+f"(d[72]), "+f"(d[73]), "+f"(d[74]), "+f"(d[75]), "+f"(d[76]), "+f"(d[77]), "+f"(d[78]), "+f"(d[79]), "+f"(d[80]), "+f"(d[81]), "+f"(d[82]), "+f"(d[83]), "+f"(d[84]), "+f"(d[85]), "+f"(d[86]), "+f"(d[87]), "+f"(d[88]), "+f"(d[89]), "+f"(d[90]), "+f"(d[91]), "+f"(d[92]), "+f"(d[93]), "+f"(d[94]), "+f"(d[95]), "+f"(d[96]), "+f"(d[97]), "+f"(d[98]), "+f"(d[99]), "+f"(d[100]), "+f"(d[101]), "+f"(d[102]), "+f"(d[103]), "+f"(d[104]), "+f"(d[105]), "+f"(d[106]), "+f"(d[107]), "+f"(d[108]), "+f"(d[109]), "+f"(d[110]), "+f"(d[111]), "+f"(d[112]), "+f"(d[113]), "+f"(d[114]), "+f"(d[115]), "+f"(d[116]), "+f"(d[117]), "+f"(d[118]), "+f"(d[119]), "+f"(d[120]), "+f"(d[121]), "+f"(d[122]), "+f"(d[123]), "+f"(d[124]), "+f"(d[125]), "+f"(d[126]), "+f"(d[127])
        : "l"(da), "l"(db), "r"(scale_d));
}

__device__ __forceinline__ void wgmma_rs_n128_tb0(float (&d)[64], uint32_t a0, uint32_t a1, uint32_t a2, uint32_t a3, uint64_t db, int scale_d) {
    asm volatile("{\n.reg .pred p;\nsetp.ne.b32 p, %69, 0;\n"
        "wgmma.mma_async.sync.aligned.m64n128k16.f32.bf16.bf16 {%0, %1, %2, %3, %4, %5, %6, %7, %8, %9, %10, %11, %12, %13, %14, %15, %16, %17, %18, %19, %20, %21, %22, %23, %24, %25, %26, %27, %28, %29, %30, %31, %32, %33, %34, %35, %36, %37, %38, %39, %40, %41, %42, %43, %44, %45, %46, %47, %48, %49, %50, %51, %52, %53, %54, %55, %56, %57, %58, %59, %60, %61, %62, %63}, {%64, %65, %66, %67}, %68, p, 1, 1, 0;\n}\n"
        : "+f"(d[0]), "+f"(d[1]), "+f"(d[2]), "+f"(d[3]), "+f"(d[4]), "+f"(d[5]), "+f"(d[6]), "+f"(d[7]), "+f"(d[8]), "+f"(d[9]), "+f"(d[10]), "+f"(d[11]), "+f"(d[12]), "+f"(d[13]), "+f"(d[14]), "+f"(d[15]), "+f"(d[16]), "+f"(d[17]), "+f"(d[18]), "+f"(d[19]), "+f"(d[20]), "+f"(d[21]), "+f"(d[22]), "+f"(d[23]), "+f"(d[24]), "+f"(d[25]), "+f"(d[26]), "+f"(d[27]), "+f"(d[28]), "+f"(d[29]), "+f"(d[30]), "+f"(d[31]), "+f"(d[32]), "+f"(d[33]), "+f"(d[34]), "+f"(d[35]), "+f"(d[36]), "+f"(d[37]), "+f"(d[38]), "+f"(d[39]), "+f"(d[40]), "+f"(d[41]), "+f"(d[42]), "+f"(d[43]), "+f"(d[44]), "+f"(d[45]), "+f"(d[46]), "+f"(d[47]), "+f"(d[48]), "+f"(d[49]), "+f"(d[50]), "+f"(d[51]), "+f"(d[52]), "+f"(d[53]), "+f"(d[54]), "+f"(d[55]), "+f"(d[56]), "+f"(d[57]), "+f"(d[58]), "+f"(d[59]), "+f"(d[60]), "+f"(d[61]), "+f"(d[62]), "+f"(d[63])
        : "r"(a0), "r"(a1), "r"(a2), "r"(a3), "l"(db), "r"(scale_d));
}

__device__ __forceinline__ void wgmma_rs_n64_tb0(float (&d)[32], uint32_t a0, uint32_t a1, uint32_t a2, uint32_t a3, uint64_t db, int scale_d) {
    asm volatile("{\n.reg .pred p;\nsetp.ne.b32 p, %37, 0;\n"
        "wgmma.mma_async.sync.aligned.m64n64k16.f32.bf16.bf16 {%0, %1, %2, %3, %4, %5, %6, %7, %8, %9, %10, %11, %12, %13, %14, %15, %16, %17, %18, %19, %20, %21, %22, %23, %24, %25, %26, %27, %28, %29, %30, %31}, {%32, %33, %34, %35}, %36, p, 1, 1, 0;\n}\n"
        : "+f"(d[0]), "+f"(d[1]), "+f"(d[2]), "+f"(d[3]), "+f"(d[4]), "+f"(d[5]), "+f"(d[6]), "+f"(d[7]), "+f"(d[8]), "+f"(d[9]), "+f"(d[10]), "+f"(d[11]), "+f"(d[12]), "+f"(d[13]), "+f"(d[14]), "+f"(d[15]), "+f"(d[16]), "+f"(d[17]), "+f"(d[18]), "+f"(d[19]), "+f"(d[20]), "+f"(d[21]), "+f"(d[22]), "+f"(d[23]), "+f"(d[24]), "+f"(d[25]), "+f"(d[26]), "+f"(d[27]), "+f"(d[28]), "+f"(d[29]), "+f"(d[30]), "+f"(d[31])
        : "r"(a0), "r"(a1), "r"(a2), "r"(a3), "l"(db), "r"(scale_d));
}

__device__ __forceinline__ void wgmma_rs_n32_tb1(float (&d)[16], uint32_t a0, uint32_t a1, uint32_t a2, uint32_t a3, uint64_t db, int scale_d) {
    asm volatile("{\n.reg .pred p;\nsetp.ne.b32 p, %21, 0;\n"
        "wgmma.mma_async.sync.aligned.m64n32k16.f32.bf16.bf16 {%0, %1, %2, %3, %4, %5, %6, %7, %8, %9, %10, %11, %12, %13, %14, %15}, {%16, %17, %18, %19}, %20, p, 1, 1, 1;\n}\n"
        : "+f"(d[0]), "+f"(d[1]), "+f"(d[2]), "+f"(d[3]), "+f"(d[4]), "+f"(d[5]), "+f"(d[6]), "+f"(d[7]), "+f"(d[8]), "+f"(d[9]), "+f"(d[10]), "+f"(d[11]), "+f"(d[12]), "+f"(d[13]), "+f"(d[14]), "+f"(d[15])
        : "r"(a0), "r"(a1), "r"(a2), "r"(a3), "l"(db), "r"(scale_d));
}

__device__ __forceinline__ void wgmma_rs_n40_tb1(float (&d)[20], uint32_t a0, uint32_t a1, uint32_t a2, uint32_t a3, uint64_t db, int scale_d) {
    asm volatile("{\n.reg .pred p;\nsetp.ne.b32 p, %25, 0;\n"
        "wgmma.mma_async.sync.aligned.m64n40k16.f32.bf16.bf16 {%0, %1, %2, %3, %4, %5, %6, %7, %8, %9, %10, %11, %12, %13, %14, %15, %16, %17, %18, %19}, {%20, %21, %22, %23}, %24, p, 1, 1, 1;\n}\n"
        : "+f"(d[0]), "+f"(d[1]), "+f"(d[2]), "+f"(d[3]), "+f"(d[4]), "+f"(d[5]), "+f"(d[6]), "+f"(d[7]), "+f"(d[8]), "+f"(d[9]), "+f"(d[10]), "+f"(d[11]), "+f"(d[12]), "+f"(d[13]), "+f"(d[14]), "+f"(d[15]), "+f"(d[16]), "+f"(d[17]), "+f"(d[18]), "+f"(d[19])
        : "r"(a0), "r"(a1), "r"(a2), "r"(a3), "l"(db), "r"(scale_d));
}


template <int BN>
__device__ __forceinline__ void wgmma_tile(float (&d)[BN / 2], uint64_t da, uint64_t db, int sd) {
    if constexpr (BN == 128) wgmma_ss_n128_tb1(d, da, db, sd);
    else if constexpr (BN == 192) wgmma_ss_n192_tb1(d, da, db, sd);
    else if constexpr (BN == 224) wgmma_ss_n224_tb1(d, da, db, sd);
    else wgmma_ss_n256_tb1(d, da, db, sd);
}

__global__ void __launch_bounds__(256) prep_kernel(const bf16* __restrict__ x, const bf16* __restrict__ gate_w,
                                                   const bf16* __restrict__ w1, const bf16* __restrict__ w3) {
    const int tid = threadIdx.x;
    if (blockIdx.x < 256) {
        const int row = blockIdx.x * 8 + (tid >> 5);
        const int lane = tid & 31;
        const uint4* xr = reinterpret_cast<const uint4*>(x + (size_t)row * DM);
        const uint4* gw = reinterpret_cast<const uint4*>(gate_w);
        float v[32];
        float gsum = 0.f, sum = 0.f;
#pragma unroll
        for (int i = 0; i < 4; i++) {
            uint4 a = xr[lane + 32 * i];
            uint4 b = gw[lane + 32 * i];
            const uint32_t aa[4] = {a.x, a.y, a.z, a.w};
            const uint32_t bb[4] = {b.x, b.y, b.z, b.w};
#pragma unroll
            for (int j = 0; j < 4; j++) {
                float x0 = __uint_as_float(aa[j] << 16), x1 = __uint_as_float(aa[j] & 0xFFFF0000u);
                float g0 = __uint_as_float(bb[j] << 16), g1 = __uint_as_float(bb[j] & 0xFFFF0000u);
                v[i * 8 + j * 2] = x0;
                v[i * 8 + j * 2 + 1] = x1;
                sum += x0 + x1;
                gsum += bf16_round(x0 * g0) + bf16_round(x1 * g1);
            }
        }
#pragma unroll
        for (int o = 16; o > 0; o >>= 1) {
            sum += __shfl_xor_sync(0xffffffffu, sum, o);
            gsum += __shfl_xor_sync(0xffffffffu, gsum, o);
        }
        const float mean = sum * (1.0f / DM);
        float m2 = 0.f;
#pragma unroll
        for (int i = 0; i < 32; i++) {
            float d = v[i] - mean;
            m2 += d * d;
        }
#pragma unroll
        for (int o = 16; o > 0; o >>= 1) m2 += __shfl_xor_sync(0xffffffffu, m2, o);
        if (lane == 0) {
            g_mean1[row] = mean;
            g_rstd1[row] = rsqrtf(m2 * (1.0f / DM) + 1e-5f);
            float logit = bf16_round(gsum);
            float g = bf16_round(1.0f / (1.0f + __expf(-logit)));
            g_gate[row] = g;
            g_omg[row] = bf16_round(1.0f - g);
        }
    } else {
        __shared__ float red[32][65];
        const int strip = blockIdx.x - 256;
        const bf16* w;
        float* out;
        int ld, col0;
        if (strip < 16) { w = w1; ld = DM; col0 = strip * 64; out = g_cs1; }
        else { w = w3; ld = FF; col0 = (strip - 16) * 64; out = g_cs3; }
        const int cg = tid & 7;
        const int rg = tid >> 3;
        float acc[8];
#pragma unroll
        for (int j = 0; j < 8; j++) acc[j] = 0.f;
#pragma unroll 8
        for (int r = 0; r < 32; r++) {
            uint4 a = *reinterpret_cast<const uint4*>(w + (size_t)(r * 32 + rg) * ld + col0 + cg * 8);
            const uint32_t aa[4] = {a.x, a.y, a.z, a.w};
#pragma unroll
            for (int j = 0; j < 4; j++) {
                acc[2 * j] += __uint_as_float(aa[j] << 16);
                acc[2 * j + 1] += __uint_as_float(aa[j] & 0xFFFF0000u);
            }
        }
#pragma unroll
        for (int j = 0; j < 8; j++) red[rg][cg * 8 + j] = acc[j];
        __syncthreads();
        if (tid < 64) {
            float s = 0.f;
#pragma unroll
            for (int r = 0; r < 32; r++) s += red[r][tid];
            out[col0 + tid] = s;
        }
    }
}

template <int BN, int STAGES>
struct GemmSmem {
    static constexpr int A_BYTES = 128 * 64 * 2;
    static constexpr int B_BOXES = (BN + 63) / 64;
    static constexpr int B_BYTES = B_BOXES * 64 * 64 * 2;
    static constexpr int STAGE_BYTES = A_BYTES + B_BYTES;
    static constexpr int STG_OFF = STAGES * STAGE_BYTES;
    static constexpr int BAR_OFF = STG_OFF + 2 * 16384;
    static constexpr int TOTAL = BAR_OFF + 256 + 1024;
};

template <int MODE, int BN, int STAGES>
__global__ void __launch_bounds__(384, 1)
gemm_kernel(const __grid_constant__ CUtensorMap mA, const __grid_constant__ CUtensorMap mB0,
            const __grid_constant__ CUtensorMap mB1, const __grid_constant__ CUtensorMap mC0,
            const __grid_constant__ CUtensorMap mC1, const bf16* __restrict__ xin, int n_tiles_n, int kblocks) {
    using L = GemmSmem<BN, STAGES>;
    extern __shared__ uint8_t smem_raw[];
    const uint32_t sbase = (smem_u32(smem_raw) + 1023u) & ~1023u;
    const uint32_t bar_full = sbase + L::BAR_OFF;
    const uint32_t bar_empty = bar_full + 8 * STAGES;
    const int wg = threadIdx.x >> 7;
    const int ntiles = 16 * n_tiles_n;

    if (threadIdx.x == 0) {
        for (int s = 0; s < STAGES; s++) {
            mbar_init(bar_full + 8 * s, 1);
            mbar_init(bar_empty + 8 * s, 2);
        }
        asm volatile("fence.mbarrier_init.release.cluster;" ::: "memory");
    }
    __syncthreads();

    if (wg == 0) {
        reg_dealloc<40>();
        if (threadIdx.x == 0) {
            prefetch_tmap(&mA);
            prefetch_tmap(&mB0);
            prefetch_tmap(&mB1);
            int stage = 0;
            uint32_t phase = 1;
            for (int tile = blockIdx.x; tile < ntiles; tile += gridDim.x) {
                const int m0 = (tile & 15) * 128;
                const int n0 = (tile >> 4) * BN;
                for (int kb = 0; kb < kblocks; kb++) {
                    mbar_wait(bar_empty + 8 * stage, phase);
                    const uint32_t sa = sbase + stage * L::STAGE_BYTES;
                    const uint32_t sb = sa + L::A_BYTES;
                    const uint32_t fb = bar_full + 8 * stage;
                    mbar_expect_tx(fb, L::STAGE_BYTES);
                    int arow = m0;
                    if (MODE == 2) {
                        const int grp = kb >> 2;
                        arow += (grp == 0) ? -1 : (grp == 1) ? 1 : (grp == 2) ? -2 : 2;
                    }
                    tma_load_2d(sa, &mA, kb * 64, arow, fb);
                    const CUtensorMap* mb = &mB0;
                    int bc = n0, br = kb * 64;
                    if (MODE == 1 && n0 >= 3 * DM) { mb = &mB1; bc = n0 - 3 * DM; }
                    if (MODE == 5 && kb >= 16) { mb = &mB1; br = (kb - 16) * 64; }
#pragma unroll
                    for (int b = 0; b < L::B_BOXES; b++) tma_load_2d(sb + b * 8192, mb, bc + b * 64, br, fb);
                    if (++stage == STAGES) { stage = 0; phase ^= 1; }
                }
            }
        }
    } else {
        reg_alloc<232>();
        const int c = wg - 1;
        const int warp = (threadIdx.x >> 5) & 3;
        const int lane = threadIdx.x & 31;
        const int tid_wg = threadIdx.x & 127;
        const uint32_t stg = sbase + L::STG_OFF + c * 16384;
        int stage = 0;
        uint32_t phase = 0;
        float acc[BN / 2];
        for (int tile = blockIdx.x; tile < ntiles; tile += gridDim.x) {
            const int m0 = (tile & 15) * 128;
            const int n0 = (tile >> 4) * BN;
            int prev_stage = 0;
            for (int kb = 0; kb < kblocks; kb++) {
                mbar_wait(bar_full + 8 * stage, phase);
                const uint32_t sa = sbase + stage * L::STAGE_BYTES + c * 8192;
                const uint32_t sb = sbase + stage * L::STAGE_BYTES + L::A_BYTES;
                const uint64_t da = make_desc(sa, 16, 1024, 1);
                const uint64_t db = make_desc(sb, 8192, 1024, 1);
                wgmma_fence();
#pragma unroll
                for (int k = 0; k < 4; k++) wgmma_tile<BN>(acc, da + k * 2, db + k * 128, (kb | k) != 0);
                wgmma_commit();
                if (kb > 0) {
                    wgmma_wait<1>();
                    if (tid_wg == 0) mbar_arrive(bar_empty + 8 * prev_stage);
                }
                prev_stage = stage;
                if (++stage == STAGES) { stage = 0; phase ^= 1; }
            }
            wgmma_wait<0>();
            if (tid_wg == 0) mbar_arrive(bar_empty + 8 * prev_stage);

            const int r0 = m0 + c * 64 + warp * 16 + (lane >> 2);
            const int r1 = r0 + 8;
            const int cq = (lane & 3) * 2;
            const CUtensorMap* mc = &mC0;
            int out_c0 = n0;
            if (MODE == 1) {
                if (n0 >= 3 * DM) {
                    mc = &mC1;
                    out_c0 = n0 - 3 * DM;
                    const float mu0 = g_mean1[r0], mu1 = g_mean1[r1];
                    const float rs0 = g_rstd1[r0], rs1 = g_rstd1[r1];
#pragma unroll
                    for (int j = 0; j < BN / 8; j++) {
                        const float2 cs = *reinterpret_cast<const float2*>(&g_cs1[out_c0 + 8 * j + cq]);
                        acc[4 * j + 0] = gelu_tanh(rs0 * fmaf(-mu0, cs.x, acc[4 * j + 0]));
                        acc[4 * j + 1] = gelu_tanh(rs0 * fmaf(-mu0, cs.y, acc[4 * j + 1]));
                        acc[4 * j + 2] = gelu_tanh(rs1 * fmaf(-mu1, cs.x, acc[4 * j + 2]));
                        acc[4 * j + 3] = gelu_tanh(rs1 * fmaf(-mu1, cs.y, acc[4 * j + 3]));
                    }
                }
            } else if (MODE == 2) {
                float s0 = 0.f, s1 = 0.f;
#pragma unroll
                for (int j = 0; j < BN / 8; j++) {
                    const uint32_t xa = *reinterpret_cast<const uint32_t*>(xin + (size_t)r0 * DM + n0 + 8 * j + cq);
                    const uint32_t xb = *reinterpret_cast<const uint32_t*>(xin + (size_t)r1 * DM + n0 + 8 * j + cq);
                    acc[4 * j + 0] = bf16_round(bf16_round(acc[4 * j + 0]) + __uint_as_float(xa << 16));
                    acc[4 * j + 1] = bf16_round(bf16_round(acc[4 * j + 1]) + __uint_as_float(xa & 0xFFFF0000u));
                    acc[4 * j + 2] = bf16_round(bf16_round(acc[4 * j + 2]) + __uint_as_float(xb << 16));
                    acc[4 * j + 3] = bf16_round(bf16_round(acc[4 * j + 3]) + __uint_as_float(xb & 0xFFFF0000u));
                    s0 += acc[4 * j + 0] + acc[4 * j + 1];
                    s1 += acc[4 * j + 2] + acc[4 * j + 3];
                }
                s0 += __shfl_xor_sync(0xffffffffu, s0, 1);
                s0 += __shfl_xor_sync(0xffffffffu, s0, 2);
                s1 += __shfl_xor_sync(0xffffffffu, s1, 1);
                s1 += __shfl_xor_sync(0xffffffffu, s1, 2);
                const float mu0 = s0 * (1.0f / BN), mu1 = s1 * (1.0f / BN);
                float q0 = 0.f, q1 = 0.f;
#pragma unroll
                for (int j = 0; j < BN / 8; j++) {
                    float d;
                    d = acc[4 * j + 0] - mu0; q0 += d * d;
                    d = acc[4 * j + 1] - mu0; q0 += d * d;
                    d = acc[4 * j + 2] - mu1; q1 += d * d;
                    d = acc[4 * j + 3] - mu1; q1 += d * d;
                }
                q0 += __shfl_xor_sync(0xffffffffu, q0, 1);
                q0 += __shfl_xor_sync(0xffffffffu, q0, 2);
                q1 += __shfl_xor_sync(0xffffffffu, q1, 1);
                q1 += __shfl_xor_sync(0xffffffffu, q1, 2);
                if ((lane & 3) == 0) {
                    static_assert(MODE != 2 || BN == 128, "stats layout assumes BN=128");
                    g_stat2[r0 * 8 + (n0 >> 7)] = make_float2(s0, q0);
                    g_stat2[r1 * 8 + (n0 >> 7)] = make_float2(s1, q1);
                }
            } else if (MODE == 3) {
                out_c0 = n0 + DM;
                float mu[2], rs[2];
#pragma unroll
                for (int h = 0; h < 2; h++) {
                    const float4* sp = reinterpret_cast<const float4*>(&g_stat2[(h ? r1 : r0) * 8]);
                    float4 p[4];
                    float s = 0.f;
#pragma unroll
                    for (int i = 0; i < 4; i++) { p[i] = sp[i]; s += p[i].x + p[i].z; }
                    const float mean = s * (1.0f / DM);
                    float m2 = 0.f;
#pragma unroll
                    for (int i = 0; i < 4; i++) {
                        float d0 = p[i].x * (1.0f / 128) - mean, d1 = p[i].z * (1.0f / 128) - mean;
                        m2 += p[i].y + p[i].w + 128.0f * (d0 * d0 + d1 * d1);
                    }
                    mu[h] = mean;
                    rs[h] = rsqrtf(m2 * (1.0f / DM) + 1e-5f);
                }
                const float og0 = g_omg[r0], og1 = g_omg[r1];
#pragma unroll
                for (int j = 0; j < BN / 8; j++) {
                    const float2 cs = *reinterpret_cast<const float2*>(&g_cs3[n0 + 8 * j + cq]);
                    acc[4 * j + 0] = og0 * gelu_tanh(rs[0] * fmaf(-mu[0], cs.x, acc[4 * j + 0]));
                    acc[4 * j + 1] = og0 * gelu_tanh(rs[0] * fmaf(-mu[0], cs.y, acc[4 * j + 1]));
                    acc[4 * j + 2] = og1 * gelu_tanh(rs[1] * fmaf(-mu[1], cs.x, acc[4 * j + 2]));
                    acc[4 * j + 3] = og1 * gelu_tanh(rs[1] * fmaf(-mu[1], cs.y, acc[4 * j + 3]));
                }
            } else {
                const float og0 = g_omg[r0], og1 = g_omg[r1];
#pragma unroll
                for (int j = 0; j < BN / 8; j++) {
                    const uint32_t xa = *reinterpret_cast<const uint32_t*>(xin + (size_t)r0 * DM + n0 + 8 * j + cq);
                    const uint32_t xb = *reinterpret_cast<const uint32_t*>(xin + (size_t)r1 * DM + n0 + 8 * j + cq);
                    acc[4 * j + 0] = fmaf(og0, __uint_as_float(xa << 16), acc[4 * j + 0]);
                    acc[4 * j + 1] = fmaf(og0, __uint_as_float(xa & 0xFFFF0000u), acc[4 * j + 1]);
                    acc[4 * j + 2] = fmaf(og1, __uint_as_float(xb << 16), acc[4 * j + 2]);
                    acc[4 * j + 3] = fmaf(og1, __uint_as_float(xb & 0xFFFF0000u), acc[4 * j + 3]);
                }
            }
            const int srow = warp * 16 + (lane & 7) + ((lane >> 3) & 1) * 8;
#pragma unroll
            for (int rnd = 0; rnd < (BN + 127) / 128; rnd++) {
                if (tid_wg == 0) bulk_wait_read0();
                named_bar_sync(1 + c, 128);
#pragma unroll
                for (int jj = 0; jj < 8; jj++) {
                    const int j = rnd * 16 + jj * 2;
                    if (j * 8 < BN) {
                        const int jb = jj * 2 + (lane >> 4);
                        const uint32_t addr = stg + (jb >> 3) * 8192 + srow * 128 + (((jb & 7) ^ (srow & 7)) << 4);
                        stmatrix_x4(addr, pack_bf16(acc[4 * j + 0], acc[4 * j + 1]), pack_bf16(acc[4 * j + 2], acc[4 * j + 3]),
                                    pack_bf16(acc[4 * j + 4], acc[4 * j + 5]), pack_bf16(acc[4 * j + 6], acc[4 * j + 7]));
                    }
                }
                fence_proxy_async();
                named_bar_sync(1 + c, 128);
                if (tid_wg == 0) {
                    tma_store_2d(mc, stg, out_c0 + rnd * 128, m0 + c * 64);
                    if (rnd * 128 + 64 < BN) tma_store_2d(mc, stg + 8192, out_c0 + rnd * 128 + 64, m0 + c * 64);
                    bulk_commit();
                }
            }
        }
        if (tid_wg == 0) bulk_wait0();
    }
}

constexpr int ATT_STAGES = 4;
constexpr int ATT_DIST = 2;
constexpr int ATT_SMEM = ATT_STAGES * 16384 + 256 + 1024;

__global__ void __launch_bounds__(256, 2)
attn_kernel(const __grid_constant__ CUtensorMap mKV) {
    extern __shared__ uint8_t smem_raw[];
    const uint32_t sbase = (smem_u32(smem_raw) + 1023u) & ~1023u;
    const uint32_t bar_kfull = sbase + ATT_STAGES * 16384;
    const uint32_t bar_vfull = bar_kfull + 8 * ATT_STAGES;
    const uint32_t bar_empty = bar_vfull + 8 * ATT_STAGES;
    const int head = blockIdx.x >> 4;
    const int q0 = (blockIdx.x & 15) * 128;
    const int warp_id = threadIdx.x >> 5;
    const int lane = threadIdx.x & 31;
    constexpr int NBLK = S_LEN / 128;

    if (threadIdx.x == 0) {
        for (int s = 0; s < ATT_STAGES; s++) {
            mbar_init(bar_kfull + 8 * s, 1);
            mbar_init(bar_vfull + 8 * s, 1);
            mbar_init(bar_empty + 8 * s, 2);
        }
        asm volatile("fence.mbarrier_init.release.cluster;" ::: "memory");
        prefetch_tmap(&mKV);
#pragma unroll
        for (int j = 0; j < ATT_DIST; j++) {
            const uint32_t sk = sbase + j * 16384;
            mbar_expect_tx(bar_kfull + 8 * j, 8192);
            tma_load_2d(sk, &mKV, DM + head * DH, j * 128, bar_kfull + 8 * j);
            mbar_expect_tx(bar_vfull + 8 * j, 8192);
            tma_load_2d(sk + 8192, &mKV, 2 * DM + head * DH, j * 128, bar_vfull + 8 * j);
        }
    }
    __syncthreads();

    const int tid_wg = threadIdx.x & 127;
    const int row0 = q0 + warp_id * 16 + (lane >> 2);
    const int cq = (lane & 3) * 2;
    uint32_t qf[8];
    {
        const bf16* qp0 = g_qkv + (size_t)row0 * (3 * DM) + head * DH + cq;
        const bf16* qp1 = qp0 + 8 * (3 * DM);
#pragma unroll
        for (int t = 0; t < 2; t++) {
            qf[4 * t + 0] = *reinterpret_cast<const uint32_t*>(qp0 + 16 * t);
            qf[4 * t + 1] = *reinterpret_cast<const uint32_t*>(qp1 + 16 * t);
            qf[4 * t + 2] = *reinterpret_cast<const uint32_t*>(qp0 + 16 * t + 8);
            qf[4 * t + 3] = *reinterpret_cast<const uint32_t*>(qp1 + 16 * t + 8);
        }
    }
    const float cs = 0.17677669529663687f * 1.4426950408889634f;
    float o[16];
#pragma unroll
    for (int i = 0; i < 16; i++) o[i] = 0.f;
    float m0 = -INFINITY, m1 = -INFINITY, l0 = 0.f, l1 = 0.f;
    int stage = 0;
    uint32_t phase = 0;
    const int wgi = threadIdx.x >> 7;
    if (wgi == 1) named_bar_arrive(1, 256);
    for (int j = 0; j < NBLK; j++) {
        if (threadIdx.x == 0 && j + ATT_DIST < NBLK) {
            const int jn = j + ATT_DIST;
            const int sn = jn % ATT_STAGES;
            if (jn >= ATT_STAGES) mbar_wait(bar_empty + 8 * sn, ((jn / ATT_STAGES) - 1) & 1);
            const uint32_t skn = sbase + sn * 16384;
            mbar_expect_tx(bar_kfull + 8 * sn, 8192);
            tma_load_2d(skn, &mKV, DM + head * DH, jn * 128, bar_kfull + 8 * sn);
            mbar_expect_tx(bar_vfull + 8 * sn, 8192);
            tma_load_2d(skn + 8192, &mKV, 2 * DM + head * DH, jn * 128, bar_vfull + 8 * sn);
        }
        __syncwarp();
        const uint32_t sk = sbase + stage * 16384;
        float s[64];
        mbar_wait(bar_kfull + 8 * stage, phase);
        const uint64_t dk = make_desc(sk, 16, 512, 2);
        wgmma_fence();
        wgmma_rs_n128_tb0(s, qf[0], qf[1], qf[2], qf[3], dk, 0);
        wgmma_rs_n128_tb0(s, qf[4], qf[5], qf[6], qf[7], dk + 2, 1);
        wgmma_commit();
        wgmma_wait<0>();
        named_bar_sync(1 + wgi, 256);
        float mx0 = s[0], mx1 = s[2];
#pragma unroll
        for (int i = 0; i < 16; i++) {
            mx0 = fmaxf(mx0, fmaxf(s[4 * i], s[4 * i + 1]));
            mx1 = fmaxf(mx1, fmaxf(s[4 * i + 2], s[4 * i + 3]));
        }
        mx0 = fmaxf(mx0, __shfl_xor_sync(0xffffffffu, mx0, 1));
        mx0 = fmaxf(mx0, __shfl_xor_sync(0xffffffffu, mx0, 2));
        mx1 = fmaxf(mx1, __shfl_xor_sync(0xffffffffu, mx1, 1));
        mx1 = fmaxf(mx1, __shfl_xor_sync(0xffffffffu, mx1, 2));
        const float mn0 = fmaxf(m0, mx0), mn1 = fmaxf(m1, mx1);
        const float a0 = ex2((m0 - mn0) * cs), a1 = ex2((m1 - mn1) * cs);
        m0 = mn0; m1 = mn1;
        const float b0 = mn0 * cs, b1 = mn1 * cs;
        float t0 = 0.f, t1 = 0.f;
        uint32_t p[32];
#pragma unroll
        for (int i = 0; i < 16; i++) {
            const float e0 = ex2(fmaf(s[4 * i + 0], cs, -b0));
            const float e1 = ex2(fmaf(s[4 * i + 1], cs, -b0));
            const float e2 = ex2(fmaf(s[4 * i + 2], cs, -b1));
            const float e3 = ex2(fmaf(s[4 * i + 3], cs, -b1));
            t0 += e0 + e1;
            t1 += e2 + e3;
            p[2 * i] = pack_bf16(e0, e1);
            p[2 * i + 1] = pack_bf16(e2, e3);
        }
        if (!(wgi == 1 && j == NBLK - 1)) named_bar_arrive(2 - wgi, 256);
        l0 = fmaf(l0, a0, t0);
        l1 = fmaf(l1, a1, t1);
#pragma unroll
        for (int i = 0; i < 4; i++) {
            o[4 * i + 0] *= a0; o[4 * i + 1] *= a0;
            o[4 * i + 2] *= a1; o[4 * i + 3] *= a1;
        }
        mbar_wait(bar_vfull + 8 * stage, phase);
        const uint64_t dv = make_desc(sk + 8192, 16, 512, 2);
        wgmma_fence();
#pragma unroll
        for (int t = 0; t < 8; t++)
            wgmma_rs_n32_tb1(o, p[4 * t], p[4 * t + 1], p[4 * t + 2], p[4 * t + 3], dv + t * 64, 1);
        wgmma_commit();
        wgmma_wait<0>();
        if (tid_wg == 0) mbar_arrive(bar_empty + 8 * stage);
        if (++stage == ATT_STAGES) { stage = 0; phase ^= 1; }
    }
    l0 += __shfl_xor_sync(0xffffffffu, l0, 1);
    l0 += __shfl_xor_sync(0xffffffffu, l0, 2);
    l1 += __shfl_xor_sync(0xffffffffu, l1, 1);
    l1 += __shfl_xor_sync(0xffffffffu, l1, 2);
    const float f0 = g_gate[row0] / l0, f1 = g_gate[row0 + 8] / l1;
    bf16* op0 = g_a5 + (size_t)row0 * A5W + head * DH + cq;
    bf16* op1 = op0 + 8 * A5W;
#pragma unroll
    for (int i = 0; i < 4; i++) {
        *reinterpret_cast<uint32_t*>(op0 + 8 * i) = pack_bf16(o[4 * i] * f0, o[4 * i + 1] * f0);
        *reinterpret_cast<uint32_t*>(op1 + 8 * i) = pack_bf16(o[4 * i + 2] * f1, o[4 * i + 3] * f1);
    }
}

typedef CUresult (*EncodeFn)(CUtensorMap*, CUtensorMapDataType, cuuint32_t, void*, const cuuint64_t*, const cuuint64_t*,
                             const cuuint32_t*, const cuuint32_t*, CUtensorMapInterleave, CUtensorMapSwizzle,
                             CUtensorMapL2promotion, CUtensorMapFloatOOBfill);

static CUtensorMap make_map(EncodeFn fn, const void* ptr, int rows, int cols, int box_cols, int box_rows,
                            CUtensorMapSwizzle swz) {
    CUtensorMap m;
    cuuint64_t dims[2] = {(cuuint64_t)cols, (cuuint64_t)rows};
    cuuint64_t strides[1] = {(cuuint64_t)cols * 2};
    cuuint32_t box[2] = {(cuuint32_t)box_cols, (cuuint32_t)box_rows};
    cuuint32_t es[2] = {1, 1};
    fn(&m, CU_TENSOR_MAP_DATA_TYPE_BFLOAT16, 2, const_cast<void*>(ptr), dims, strides, box, es,
       CU_TENSOR_MAP_INTERLEAVE_NONE, swz, CU_TENSOR_MAP_L2_PROMOTION_L2_256B, CU_TENSOR_MAP_FLOAT_OOB_FILL_NONE);
    return m;
}

extern "C" void kernel_launch(void* const* d_in, const int* in_sizes, int n_in, void* d_out, int out_size) {
    const bf16* x = (const bf16*)d_in[0];
    const bf16* wqkv = (const bf16*)d_in[1];
    const bf16* wo = (const bf16*)d_in[2];
    const bf16* w1 = (const bf16*)d_in[4];
    const bf16* w2 = (const bf16*)d_in[5];
    const bf16* w3 = (const bf16*)d_in[6];
    const bf16* w4 = (const bf16*)d_in[7];
    const bf16* gate_w = (const bf16*)d_in[8];

    static EncodeFn enc = nullptr;
    static void *p_qkv, *p_h, *p_x1, *p_a5;
    if (!enc) {
        void* fn = nullptr;
        cudaDriverEntryPointQueryResult qres;
        cudaGetDriverEntryPoint("cuTensorMapEncodeTiled", &fn, cudaEnableDefault, &qres);
        enc = (EncodeFn)fn;
        cudaGetSymbolAddress(&p_qkv, g_qkv);
        cudaGetSymbolAddress(&p_h, g_h);
        cudaGetSymbolAddress(&p_x1, g_x1);
        cudaGetSymbolAddress(&p_a5, g_a5);
        cudaFuncSetAttribute(gemm_kernel<1, 256, 4>, cudaFuncAttributeMaxDynamicSharedMemorySize, GemmSmem<256, 4>::TOTAL);
        cudaFuncSetAttribute(gemm_kernel<2, 128, 5>, cudaFuncAttributeMaxDynamicSharedMemorySize, GemmSmem<128, 5>::TOTAL);
        cudaFuncSetAttribute(gemm_kernel<3, 256, 4>, cudaFuncAttributeMaxDynamicSharedMemorySize, GemmSmem<256, 4>::TOTAL);
        cudaFuncSetAttribute(gemm_kernel<5, 128, 5>, cudaFuncAttributeMaxDynamicSharedMemorySize, GemmSmem<128, 5>::TOTAL);
        cudaFuncSetAttribute(attn_kernel, cudaFuncAttributeMaxDynamicSharedMemorySize, ATT_SMEM);
    }
    const CUtensorMapSwizzle SW128 = CU_TENSOR_MAP_SWIZZLE_128B, SW64 = CU_TENSOR_MAP_SWIZZLE_64B;
    CUtensorMap mX = make_map(enc, x, S_LEN, DM, 64, 128, SW128);
    CUtensorMap mWqkv = make_map(enc, wqkv, DM, 3 * DM, 64, 64, SW128);
    CUtensorMap mW1 = make_map(enc, w1, DM, DM, 64, 64, SW128);
    CUtensorMap mW2 = make_map(enc, w2, DM, DM, 64, 64, SW128);
    CUtensorMap mW3 = make_map(enc, w3, DM, FF, 64, 64, SW128);
    CUtensorMap mW4 = make_map(enc, w4, FF, DM, 64, 64, SW128);
    CUtensorMap mWo = make_map(enc, wo, DM, DM, 64, 64, SW128);
    CUtensorMap mQKVst = make_map(enc, p_qkv, S_LEN, 3 * DM, 64, 64, SW128);
    CUtensorMap mKV = make_map(enc, p_qkv, S_LEN, 3 * DM, 32, 128, SW64);
    CUtensorMap mHst = make_map(enc, p_h, S_LEN, DM, 64, 64, SW128);
    CUtensorMap mHld = make_map(enc, p_h, S_LEN, DM, 64, 128, SW128);
    CUtensorMap mX1st = make_map(enc, p_x1, S_LEN, DM, 64, 64, SW128);
    CUtensorMap mX1ld = make_map(enc, p_x1, S_LEN, DM, 64, 128, SW128);
    CUtensorMap mA5st = make_map(enc, p_a5, S_LEN, A5W, 64, 64, SW128);
    CUtensorMap mA5ld = make_map(enc, p_a5, S_LEN, A5W, 64, 128, SW128);
    CUtensorMap mOut = make_map(enc, d_out, S_LEN, DM, 64, 64, SW128);

    cudaStream_t st = cudaStreamPerThread;
    prep_kernel<<<256 + 72, 256, 0, st>>>(x, gate_w, w1, w3);
    gemm_kernel<1, 256, 4><<<132, 384, GemmSmem<256, 4>::TOTAL, st>>>(mX, mWqkv, mW1, mQKVst, mHst, x, 16, 16);
    attn_kernel<<<NH * 16, 256, ATT_SMEM, st>>>(mKV);
    gemm_kernel<2, 128, 5><<<128, 384, GemmSmem<128, 5>::TOTAL, st>>>(mHld, mW2, mW2, mX1st, mX1st, x, 8, 16);
    gemm_kernel<3, 256, 4><<<132, 384, GemmSmem<256, 4>::TOTAL, st>>>(mX1ld, mW3, mW3, mA5st, mA5st, x, 14, 16);
    gemm_kernel<5, 128, 5><<<128, 384, GemmSmem<128, 5>::TOTAL, st>>>(mA5ld, mWo, mW4, mOut, mOut, (const bf16*)p_x1, 8, 72);
}
```

```cpp
#include <cuda_runtime.h>
#include <cuda_bf16.h>
#include <cuda.h>
#include <stdint.h>

typedef __nv_bfloat16 bf16;

constexpr int S_LEN = 2048;
constexpr int DM = 1024;
constexpr int FF = 3584;
constexpr int NH = 32;
constexpr int DH = 32;
constexpr int A5W = DM + FF;

__device__ __align__(1024) bf16 g_qkv[S_LEN * 3 * DM];
__device__ __align__(1024) bf16 g_h[S_LEN * DM];
__device__ __align__(1024) bf16 g_x1[S_LEN * DM];
__device__ __align__(1024) bf16 g_a5[S_LEN * A5W];
__device__ __align__(16) float g_mean1[S_LEN];
__device__ __align__(16) float g_rstd1[S_LEN];
__device__ __align__(16) float g_gate[S_LEN];
__device__ __align__(16) float g_omg[S_LEN];
__device__ __align__(16) float g_cs1[DM];
__device__ __align__(16) float g_cs3[FF];
__device__ __align__(16) float2 g_stat2[S_LEN * 8];

__device__ __forceinline__ uint32_t smem_u32(const void* p) { return (uint32_t)__cvta_generic_to_shared(p); }

__device__ __forceinline__ void mbar_init(uint32_t bar, uint32_t count) {
    asm volatile("mbarrier.init.shared::cta.b64 [%0], %1;" ::"r"(bar), "r"(count));
}
__device__ __forceinline__ void mbar_expect_tx(uint32_t bar, uint32_t bytes) {
    asm volatile("mbarrier.arrive.expect_tx.shared::cta.b64 _, [%0], %1;" ::"r"(bar), "r"(bytes) : "memory");
}
__device__ __forceinline__ void mbar_arrive(uint32_t bar) {
    asm volatile("mbarrier.arrive.shared::cta.b64 _, [%0];" ::"r"(bar) : "memory");
}
__device__ __forceinline__ bool mbar_try_wait(uint32_t bar, uint32_t parity) {
    uint32_t ok;
    asm volatile(
        "{\n.reg .pred p;\n"
        "mbarrier.try_wait.parity.shared::cta.b64 p, [%1], %2;\n"
        "selp.u32 %0, 1, 0, p;\n}\n"
        : "=r"(ok)
        : "r"(bar), "r"(parity)
        : "memory");
    return ok != 0;
}
__device__ __forceinline__ void mbar_wait(uint32_t bar, uint32_t parity) {
    uint32_t spins = 0;
    while (!mbar_try_wait(bar, parity)) {
        if (++spins > (1u << 24)) __trap();
    }
}
__device__ __forceinline__ void tma_load_2d(uint32_t dst, const CUtensorMap* map, int c0, int c1, uint32_t bar) {
    asm volatile(
        "cp.async.bulk.tensor.2d.shared::cluster.global.mbarrier::complete_tx::bytes [%0], [%1, {%3, %4}], [%2];"
        ::"r"(dst), "l"(map), "r"(bar), "r"(c0), "r"(c1)
        : "memory");
}
__device__ __forceinline__ void tma_store_2d(const CUtensorMap* map, uint32_t src, int c0, int c1) {
    asm volatile("cp.async.bulk.tensor.2d.global.shared::cta.bulk_group [%0, {%2, %3}], [%1];"
                 ::"l"(map), "r"(src), "r"(c0), "r"(c1)
                 : "memory");
}
__device__ __forceinline__ void bulk_commit() { asm volatile("cp.async.bulk.commit_group;" ::: "memory"); }
__device__ __forceinline__ void bulk_wait_read0() { asm volatile("cp.async.bulk.wait_group.read 0;" ::: "memory"); }
__device__ __forceinline__ void bulk_wait0() { asm volatile("cp.async.bulk.wait_group 0;" ::: "memory"); }
__device__ __forceinline__ void fence_proxy_async() { asm volatile("fence.proxy.async.shared::cta;" ::: "memory"); }
__device__ __forceinline__ void named_bar_sync(int id, int n) { asm volatile("bar.sync %0, %1;" ::"r"(id), "r"(n) : "memory"); }
__device__ __forceinline__ void named_bar_arrive(int id, int n) { asm volatile("bar.arrive %0, %1;" ::"r"(id), "r"(n) : "memory"); }
__device__ __forceinline__ void wgmma_fence() { asm volatile("wgmma.fence.sync.aligned;" ::: "memory"); }
__device__ __forceinline__ void wgmma_commit() { asm volatile("wgmma.commit_group.sync.aligned;" ::: "memory"); }
template <int N>
__device__ __forceinline__ void wgmma_wait() { asm volatile("wgmma.wait_group.sync.aligned %0;" ::"n"(N) : "memory"); }
__device__ __forceinline__ void prefetch_tmap(const CUtensorMap* m) {
    asm volatile("prefetch.tensormap [%0];" ::"l"(m) : "memory");
}
template <int R>
__device__ __forceinline__ void reg_alloc() { asm volatile("setmaxnreg.inc.sync.aligned.u32 %0;" ::"n"(R)); }
template <int R>
__device__ __forceinline__ void reg_dealloc() { asm volatile("setmaxnreg.dec.sync.aligned.u32 %0;" ::"n"(R)); }
__device__ __forceinline__ void stmatrix_x4(uint32_t addr, uint32_t r0, uint32_t r1, uint32_t r2, uint32_t r3) {
    asm volatile("stmatrix.sync.aligned.m8n8.x4.shared.b16 [%0], {%1, %2, %3, %4};"
                 ::"r"(addr), "r"(r0), "r"(r1), "r"(r2), "r"(r3)
                 : "memory");
}
__device__ __forceinline__ uint32_t pack_bf16(float lo, float hi) {
    uint32_t r;
    asm("cvt.rn.bf16x2.f32 %0, %1, %2;" : "=r"(r) : "f"(hi), "f"(lo));
    return r;
}
__device__ __forceinline__ float bf16_round(float v) { return __bfloat162float(__float2bfloat16_rn(v)); }
__device__ __forceinline__ float ex2(float x) {
    float y;
    asm("ex2.approx.ftz.f32 %0, %1;" : "=f"(y) : "f"(x));
    return y;
}
__device__ __forceinline__ float tanh_fast(float x) {
    float y;
    asm("tanh.approx.f32 %0, %1;" : "=f"(y) : "f"(x));
    return y;
}
__device__ __forceinline__ float gelu_tanh(float v) {
    float u = 0.7978845608028654f * (v + 0.044715f * v * v * v);
    float hv = 0.5f * v;
    return fmaf(hv, tanh_fast(u), hv);
}
__device__ __forceinline__ uint64_t make_desc(uint32_t addr, uint32_t lbo_bytes, uint32_t sbo_bytes, uint32_t swz) {
    uint64_t d = 0;
    d |= (uint64_t)((addr & 0x3FFFF) >> 4);
    d |= (uint64_t)((lbo_bytes >> 4) & 0x3FFF) << 16;
    d |= (uint64_t)((sbo_bytes >> 4) & 0x3FFF) << 32;
    d |= (uint64_t)swz << 62;
    return d;
}


__device__ __forceinline__ void wgmma_ss_n128_tb1(float (&d)[64], uint64_t da, uint64_t db, int scale_d) {
    asm volatile("{\n.reg .pred p;\nsetp.ne.b32 p, %66, 0;\n"
        "wgmma.mma_async.sync.aligned.m64n128k16.f32.bf16.bf16 {%0, %1, %2, %3, %4, %5, %6, %7, %8, %9, %10, %11, %12, %13, %14, %15, %16, %17, %18, %19, %20, %21, %22, %23, %24, %25, %26, %27, %28, %29, %30, %31, %32, %33, %34, %35, %36, %37, %38, %39, %40, %41, %42, %43, %44, %45, %46, %47, %48, %49, %50, %51, %52, %53, %54, %55, %56, %57, %58, %59, %60, %61, %62, %63}, %64, %65, p, 1, 1, 0, 1;\n}\n"
        : "+f"(d[0]), "+f"(d[1]), "+f"(d[2]), "+f"(d[3]), "+f"(d[4]), "+f"(d[5]), "+f"(d[6]), "+f"(d[7]), "+f"(d[8]), "+f"(d[9]), "+f"(d[10]), "+f"(d[11]), "+f"(d[12]), "+f"(d[13]), "+f"(d[14]), "+f"(d[15]), "+f"(d[16]), "+f"(d[17]), "+f"(d[18]), "+f"(d[19]), "+f"(d[20]), "+f"(d[21]), "+f"(d[22]), "+f"(d[23]), "+f"(d[24]), "+f"(d[25]), "+f"(d[26]), "+f"(d[27]), "+f"(d[28]), "+f"(d[29]), "+f"(d[30]), "+f"(d[31]), "+f"(d[32]), "+f"(d[33]), "+f"(d[34]), "+f"(d[35]), "+f"(d[36]), "+f"(d[37]), "+f"(d[38]), "+f"(d[39]), "+f"(d[40]), "+f"(d[41]), "+f"(d[42]), "+f"(d[43]), "+f"(d[44]), "+f"(d[45]), "+f"(d[46]), "+f"(d[47]), "+f"(d[48]), "+f"(d[49]), "+f"(d[50]), "+f"(d[51]), "+f"(d[52]), "+f"(d[53]), "+f"(d[54]), "+f"(d[55]), "+f"(d[56]), "+f"(d[57]), "+f"(d[58]), "+f"(d[59]), "+f"(d[60]), "+f"(d[61]), "+f"(d[62]), "+f"(d[63])
        : "l"(da), "l"(db), "r"(scale_d));
}

__device__ __forceinline__ void wgmma_ss_n192_tb1(float (&d)[96], uint64_t da, uint64_t db, int scale_d) {
    asm volatile("{\n.reg .pred p;\nsetp.ne.b32 p, %98, 0;\n"
        "wgmma.mma_async.sync.aligned.m64n192k16.f32.bf16.bf16 {%0, %1, %2, %3, %4, %5, %6, %7, %8, %9, %10, %11, %12, %13, %14, %15, %16, %17, %18, %19, %20, %21, %22, %23, %24, %25, %26, %27, %28, %29, %30, %31, %32, %33, %34, %35, %36, %37, %38, %39, %40, %41, %42, %43, %44, %45, %46, %47, %48, %49, %50, %51, %52, %53, %54, %55, %56, %57, %58, %59, %60, %61, %62, %63, %64, %65, %66, %67, %68, %69, %70, %71, %72, %73, %74, %75, %76, %77, %78, %79, %80, %81, %82, %83, %84, %85, %86, %87, %88, %89, %90, %91, %92, %93, %94, %95}, %96, %97, p, 1, 1, 0, 1;\n}\n"
        : "+f"(d[0]), "+f"(d[1]), "+f"(d[2]), "+f"(d[3]), "+f"(d[4]), "+f"(d[5]), "+f"(d[6]), "+f"(d[7]), "+f"(d[8]), "+f"(d[9]), "+f"(d[10]), "+f"(d[11]), "+f"(d[12]), "+f"(d[13]), "+f"(d[14]), "+f"(d[15]), "+f"(d[16]), "+f"(d[17]), "+f"(d[18]), "+f"(d[19]), "+f"(d[20]), "+f"(d[21]), "+f"(d[22]), "+f"(d[23]), "+f"(d[24]), "+f"(d[25]), "+f"(d[26]), "+f"(d[27]), "+f"(d[28]), "+f"(d[29]), "+f"(d[30]), "+f"(d[31]), "+f"(d[32]), "+f"(d[33]), "+f"(d[34]), "+f"(d[35]), "+f"(d[36]), "+f"(d[37]), "+f"(d[38]), "+f"(d[39]), "+f"(d[40]), "+f"(d[41]), "+f"(d[42]), "+f"(d[43]), "+f"(d[44]), "+f"(d[45]), "+f"(d[46]), "+f"(d[47]), "+f"(d[48]), "+f"(d[49]), "+f"(d[50]), "+f"(d[51]), "+f"(d[52]), "+f"(d[53]), "+f"(d[54]), "+f"(d[55]), "+f"(d[56]), "+f"(d[57]), "+f"(d[58]), "+f"(d[59]), "+f"(d[60]), "+f"(d[61]), "+f"(d[62]), "+f"(d[63]), "+f"(d[64]), "+f"(d[65]), "+f"(d[66]), "+f"(d[67]), "+f"(d[68]), "+f"(d[69]), "+f"(d[70]), "+f"(d[71]), "+f"(d[72]), "+f"(d[73]), "+f"(d[74]), "+f"(d[75]), "+f"(d[76]), "+f"(d[77]), "+f"(d[78]), "+f"(d[79]), "+f"(d[80]), "+f"(d[81]), "+f"(d[82]), "+f"(d[83]), "+f"(d[84]), "+f"(d[85]), "+f"(d[86]), "+f"(d[87]), "+f"(d[88]), "+f"(d[89]), "+f"(d[90]), "+f"(d[91]), "+f"(d[92]), "+f"(d[93]), "+f"(d[94]), "+f"(d[95])
        : "l"(da), "l"(db), "r"(scale_d));
}

__device__ __forceinline__ void wgmma_ss_n224_tb1(float (&d)[112], uint64_t da, uint64_t db, int scale_d) {
    asm volatile("{\n.reg .pred p;\nsetp.ne.b32 p, %114, 0;\n"
        "wgmma.mma_async.sync.aligned.m64n224k16.f32.bf16.bf16 {%0, %1, %2, %3, %4, %5, %6, %7, %8, %9, %10, %11, %12, %13, %14, %15, %16, %17, %18, %19, %20, %21, %22, %23, %24, %25, %26, %27, %28, %29, %30, %31, %32, %33, %34, %35, %36, %37, %38, %39, %40, %41, %42, %43, %44, %45, %46, %47, %48, %49, %50, %51, %52, %53, %54, %55, %56, %57, %58, %59, %60, %61, %62, %63, %64, %65, %66, %67, %68, %69, %70, %71, %72, %73, %74, %75, %76, %77, %78, %79, %80, %81, %82, %83, %84, %85, %86, %87, %88, %89, %90, %91, %92, %93, %94, %95, %96, %97, %98, %99, %100, %101, %102, %103, %104, %105, %106, %107, %108, %109, %110, %111}, %112, %113, p, 1, 1, 0, 1;\n}\n"
        : "+f"(d[0]), "+f"(d[1]), "+f"(d[2]), "+f"(d[3]), "+f"(d[4]), "+f"(d[5]), "+f"(d[6]), "+f"(d[7]), "+f"(d[8]), "+f"(d[9]), "+f"(d[10]), "+f"(d[11]), "+f"(d[12]), "+f"(d[13]), "+f"(d[14]), "+f"(d[15]), "+f"(d[16]), "+f"(d[17]), "+f"(d[18]), "+f"(d[19]), "+f"(d[20]), "+f"(d[21]), "+f"(d[22]), "+f"(d[23]), "+f"(d[24]), "+f"(d[25]), "+f"(d[26]), "+f"(d[27]), "+f"(d[28]), "+f"(d[29]), "+f"(d[30]), "+f"(d[31]), "+f"(d[32]), "+f"(d[33]), "+f"(d[34]), "+f"(d[35]), "+f"(d[36]), "+f"(d[37]), "+f"(d[38]), "+f"(d[39]), "+f"(d[40]), "+f"(d[41]), "+f"(d[42]), "+f"(d[43]), "+f"(d[44]), "+f"(d[45]), "+f"(d[46]), "+f"(d[47]), "+f"(d[48]), "+f"(d[49]), "+f"(d[50]), "+f"(d[51]), "+f"(d[52]), "+f"(d[53]), "+f"(d[54]), "+f"(d[55]), "+f"(d[56]), "+f"(d[57]), "+f"(d[58]), "+f"(d[59]), "+f"(d[60]), "+f"(d[61]), "+f"(d[62]), "+f"(d[63]), "+f"(d[64]), "+f"(d[65]), "+f"(d[66]), "+f"(d[67]), "+f"(d[68]), "+f"(d[69]), "+f"(d[70]), "+f"(d[71]), "+f"(d[72]), "+f"(d[73]), "+f"(d[74]), "+f"(d[75]), "+f"(d[76]), "+f"(d[77]), "+f"(d[78]), "+f"(d[79]), "+f"(d[80]), "+f"(d[81]), "+f"(d[82]), "+f"(d[83]), "+f"(d[84]), "+f"(d[85]), "+f"(d[86]), "+f"(d[87]), "+f"(d[88]), "+f"(d[89]), "+f"(d[90]), "+f"(d[91]), "+f"(d[92]), "+f"(d[93]), "+f"(d[94]), "+f"(d[95]), "+f"(d[96]), "+f"(d[97]), "+f"(d[98]), "+f"(d[99]), "+f"(d[100]), "+f"(d[101]), "+f"(d[102]), "+f"(d[103]), "+f"(d[104]), "+f"(d[105]), "+f"(d[106]), "+f"(d[107]), "+f"(d[108]), "+f"(d[109]), "+f"(d[110]), "+f"(d[111])
        : "l"(da), "l"(db), "r"(scale_d));
}

__device__ __forceinline__ void wgmma_ss_n256_tb1(float (&d)[128], uint64_t da, uint64_t db, int scale_d) {
    asm volatile("{\n.reg .pred p;\nsetp.ne.b32 p, %130, 0;\n"
        "wgmma.mma_async.sync.aligned.m64n256k16.f32.bf16.bf16 {%0, %1, %2, %3, %4, %5, %6, %7, %8, %9, %10, %11, %12, %13, %14, %15, %16, %17, %18, %19, %20, %21, %22, %23, %24, %25, %26, %27, %28, %29, %30, %31, %32, %33, %34, %35, %36, %37, %38, %39, %40, %41, %42, %43, %44, %45, %46, %47, %48, %49, %50, %51, %52, %53, %54, %55, %56, %57, %58, %59, %60, %61, %62, %63, %64, %65, %66, %67, %68, %69, %70, %71, %72, %73, %74, %75, %76, %77, %78, %79, %80, %81, %82, %83, %84, %85, %86, %87, %88, %89, %90, %91, %92, %93, %94, %95, %96, %97, %98, %99, %100, %101, %102, %103, %104, %105, %106, %107, %108, %109, %110, %111, %112, %113, %114, %115, %116, %117, %118, %119, %120, %121, %122, %123, %124, %125, %126, %127}, %128, %129, p, 1, 1, 0, 1;\n}\n"
        : "+f"(d[0]), "+f"(d[1]), "+f"(d[2]), "+f"(d[3]), "+f"(d[4]), "+f"(d[5]), "+f"(d[6]), "+f"(d[7]), "+f"(d[8]), "+f"(d[9]), "+f"(d[10]), "+f"(d[11]), "+f"(d[12]), "+f"(d[13]), "+f"(d[14]), "+f"(d[15]), "+f"(d[16]), "+f"(d[17]), "+f"(d[18]), "+f"(d[19]), "+f"(d[20]), "+f"(d[21]), "+f"(d[22]), "+f"(d[23]), "+f"(d[24]), "+f"(d[25]), "+f"(d[26]), "+f"(d[27]), "+f"(d[28]), "+f"(d[29]), "+f"(d[30]), "+f"(d[31]), "+f"(d[32]), "+f"(d[33]), "+f"(d[34]), "+f"(d[35]), "+f"(d[36]), "+f"(d[37]), "+f"(d[38]), "+f"(d[39]), "+f"(d[40]), "+f"(d[41]), "+f"(d[42]), "+f"(d[43]), "+f"(d[44]), "+f"(d[45]), "+f"(d[46]), "+f"(d[47]), "+f"(d[48]), "+f"(d[49]), "+f"(d[50]), "+f"(d[51]), "+f"(d[52]), "+f"(d[53]), "+f"(d[54]), "+f"(d[55]), "+f"(d[56]), "+f"(d[57]), "+f"(d[58]), "+f"(d[59]), "+f"(d[60]), "+f"(d[61]), "+f"(d[62]), "+f"(d[63]), "+f"(d[64]), "+f"(d[65]), "+f"(d[66]), "+f"(d[67]), "+f"(d[68]), "+f"(d[69]), "+f"(d[70]), "+f"(d[71]), "+f"(d[72]), "+f"(d[73]), "+f"(d[74]), "+f"(d[75]), "+f"(d[76]), "+f"(d[77]), "+f"(d[78]), "+f"(d[79]), "+f"(d[80]), "+f"(d[81]), "+f"(d[82]), "+f"(d[83]), "+f"(d[84]), "+f"(d[85]), "+f"(d[86]), "+f"(d[87]), "+f"(d[88]), "+f"(d[89]), "+f"(d[90]), "+f"(d[91]), "+f"(d[92]), "+f"(d[93]), "+f"(d[94]), "+f"(d[95]), "+f"(d[96]), "+f"(d[97]), "+f"(d[98]), "+f"(d[99]), "+f"(d[100]), "+f"(d[101]), "+f"(d[102]), "+f"(d[103]), "+f"(d[104]), "+f"(d[105]), "+f"(d[106]), "+f"(d[107]), "+f"(d[108]), "+f"(d[109]), "+f"(d[110]), "+f"(d[111]), "+f"(d[112]), "+f"(d[113]), "+f"(d[114]), "+f"(d[115]), "+f"(d[116]), "+f"(d[117]), "+f"(d[118]), "+f"(d[119]), "+f"(d[120]), "+f"(d[121]), "+f"(d[122]), "+f"(d[123]), "+f"(d[124]), "+f"(d[125]), "+f"(d[126]), "+f"(d[127])
        : "l"(da), "l"(db), "r"(scale_d));
}

__device__ __forceinline__ void wgmma_rs_n128_tb0(float (&d)[64], uint32_t a0, uint32_t a1, uint32_t a2, uint32_t a3, uint64_t db, int scale_d) {
    asm volatile("{\n.reg .pred p;\nsetp.ne.b32 p, %69, 0;\n"
        "wgmma.mma_async.sync.aligned.m64n128k16.f32.bf16.bf16 {%0, %1, %2, %3, %4, %5, %6, %7, %8, %9, %10, %11, %12, %13, %14, %15, %16, %17, %18, %19, %20, %21, %22, %23, %24, %25, %26, %27, %28, %29, %30, %31, %32, %33, %34, %35, %36, %37, %38, %39, %40, %41, %42, %43, %44, %45, %46, %47, %48, %49, %50, %51, %52, %53, %54, %55, %56, %57, %58, %59, %60, %61, %62, %63}, {%64, %65, %66, %67}, %68, p, 1, 1, 0;\n}\n"
        : "+f"(d[0]), "+f"(d[1]), "+f"(d[2]), "+f"(d[3]), "+f"(d[4]), "+f"(d[5]), "+f"(d[6]), "+f"(d[7]), "+f"(d[8]), "+f"(d[9]), "+f"(d[10]), "+f"(d[11]), "+f"(d[12]), "+f"(d[13]), "+f"(d[14]), "+f"(d[15]), "+f"(d[16]), "+f"(d[17]), "+f"(d[18]), "+f"(d[19]), "+f"(d[20]), "+f"(d[21]), "+f"(d[22]), "+f"(d[23]), "+f"(d[24]), "+f"(d[25]), "+f"(d[26]), "+f"(d[27]), "+f"(d[28]), "+f"(d[29]), "+f"(d[30]), "+f"(d[31]), "+f"(d[32]), "+f"(d[33]), "+f"(d[34]), "+f"(d[35]), "+f"(d[36]), "+f"(d[37]), "+f"(d[38]), "+f"(d[39]), "+f"(d[40]), "+f"(d[41]), "+f"(d[42]), "+f"(d[43]), "+f"(d[44]), "+f"(d[45]), "+f"(d[46]), "+f"(d[47]), "+f"(d[48]), "+f"(d[49]), "+f"(d[50]), "+f"(d[51]), "+f"(d[52]), "+f"(d[53]), "+f"(d[54]), "+f"(d[55]), "+f"(d[56]), "+f"(d[57]), "+f"(d[58]), "+f"(d[59]), "+f"(d[60]), "+f"(d[61]), "+f"(d[62]), "+f"(d[63])
        : "r"(a0), "r"(a1), "r"(a2), "r"(a3), "l"(db), "r"(scale_d));
}

__device__ __forceinline__ void wgmma_rs_n64_tb0(float (&d)[32], uint32_t a0, uint32_t a1, uint32_t a2, uint32_t a3, uint64_t db, int scale_d) {
    asm volatile("{\n.reg .pred p;\nsetp.ne.b32 p, %37, 0;\n"
        "wgmma.mma_async.sync.aligned.m64n64k16.f32.bf16.bf16 {%0, %1, %2, %3, %4, %5, %6, %7, %8, %9, %10, %11, %12, %13, %14, %15, %16, %17, %18, %19, %20, %21, %22, %23, %24, %25, %26, %27, %28, %29, %30, %31}, {%32, %33, %34, %35}, %36, p, 1, 1, 0;\n}\n"
        : "+f"(d[0]), "+f"(d[1]), "+f"(d[2]), "+f"(d[3]), "+f"(d[4]), "+f"(d[5]), "+f"(d[6]), "+f"(d[7]), "+f"(d[8]), "+f"(d[9]), "+f"(d[10]), "+f"(d[11]), "+f"(d[12]), "+f"(d[13]), "+f"(d[14]), "+f"(d[15]), "+f"(d[16]), "+f"(d[17]), "+f"(d[18]), "+f"(d[19]), "+f"(d[20]), "+f"(d[21]), "+f"(d[22]), "+f"(d[23]), "+f"(d[24]), "+f"(d[25]), "+f"(d[26]), "+f"(d[27]), "+f"(d[28]), "+f"(d[29]), "+f"(d[30]), "+f"(d[31])
        : "r"(a0), "r"(a1), "r"(a2), "r"(a3), "l"(db), "r"(scale_d));
}

__device__ __forceinline__ void wgmma_rs_n32_tb1(float (&d)[16], uint32_t a0, uint32_t a1, uint32_t a2, uint32_t a3, uint64_t db, int scale_d) {
    asm volatile("{\n.reg .pred p;\nsetp.ne.b32 p, %21, 0;\n"
        "wgmma.mma_async.sync.aligned.m64n32k16.f32.bf16.bf16 {%0, %1, %2, %3, %4, %5, %6, %7, %8, %9, %10, %11, %12, %13, %14, %15}, {%16, %17, %18, %19}, %20, p, 1, 1, 1;\n}\n"
        : "+f"(d[0]), "+f"(d[1]), "+f"(d[2]), "+f"(d[3]), "+f"(d[4]), "+f"(d[5]), "+f"(d[6]), "+f"(d[7]), "+f"(d[8]), "+f"(d[9]), "+f"(d[10]), "+f"(d[11]), "+f"(d[12]), "+f"(d[13]), "+f"(d[14]), "+f"(d[15])
        : "r"(a0), "r"(a1), "r"(a2), "r"(a3), "l"(db), "r"(scale_d));
}

__device__ __forceinline__ void wgmma_rs_n40_tb1(float (&d)[20], uint32_t a0, uint32_t a1, uint32_t a2, uint32_t a3, uint64_t db, int scale_d) {
    asm volatile("{\n.reg .pred p;\nsetp.ne.b32 p, %25, 0;\n"
        "wgmma.mma_async.sync.aligned.m64n40k16.f32.bf16.bf16 {%0, %1, %2, %3, %4, %5, %6, %7, %8, %9, %10, %11, %12, %13, %14, %15, %16, %17, %18, %19}, {%20, %21, %22, %23}, %24, p, 1, 1, 1;\n}\n"
        : "+f"(d[0]), "+f"(d[1]), "+f"(d[2]), "+f"(d[3]), "+f"(d[4]), "+f"(d[5]), "+f"(d[6]), "+f"(d[7]), "+f"(d[8]), "+f"(d[9]), "+f"(d[10]), "+f"(d[11]), "+f"(d[12]), "+f"(d[13]), "+f"(d[14]), "+f"(d[15]), "+f"(d[16]), "+f"(d[17]), "+f"(d[18]), "+f"(d[19])
        : "r"(a0), "r"(a1), "r"(a2), "r"(a3), "l"(db), "r"(scale_d));
}


template <int BN>
__device__ __forceinline__ void wgmma_tile(float (&d)[BN / 2], uint64_t da, uint64_t db, int sd) {
    if constexpr (BN == 128) wgmma_ss_n128_tb1(d, da, db, sd);
    else if constexpr (BN == 192) wgmma_ss_n192_tb1(d, da, db, sd);
    else if constexpr (BN == 224) wgmma_ss_n224_tb1(d, da, db, sd);
    else wgmma_ss_n256_tb1(d, da, db, sd);
}

__global__ void __launch_bounds__(256) prep_kernel(const bf16* __restrict__ x, const bf16* __restrict__ gate_w,
                                                   const bf16* __restrict__ w1, const bf16* __restrict__ w3) {
    const int tid = threadIdx.x;
    if (blockIdx.x < 256) {
        const int row = blockIdx.x * 8 + (tid >> 5);
        const int lane = tid & 31;
        const uint4* xr = reinterpret_cast<const uint4*>(x + (size_t)row * DM);
        const uint4* gw = reinterpret_cast<const uint4*>(gate_w);
        float v[32];
        float gsum = 0.f, sum = 0.f;
#pragma unroll
        for (int i = 0; i < 4; i++) {
            uint4 a = xr[lane + 32 * i];
            uint4 b = gw[lane + 32 * i];
            const uint32_t aa[4] = {a.x, a.y, a.z, a.w};
            const uint32_t bb[4] = {b.x, b.y, b.z, b.w};
#pragma unroll
            for (int j = 0; j < 4; j++) {
                float x0 = __uint_as_float(aa[j] << 16), x1 = __uint_as_float(aa[j] & 0xFFFF0000u);
                float g0 = __uint_as_float(bb[j] << 16), g1 = __uint_as_float(bb[j] & 0xFFFF0000u);
                v[i * 8 + j * 2] = x0;
                v[i * 8 + j * 2 + 1] = x1;
                sum += x0 + x1;
                gsum += bf16_round(x0 * g0) + bf16_round(x1 * g1);
            }
        }
#pragma unroll
        for (int o = 16; o > 0; o >>= 1) {
            sum += __shfl_xor_sync(0xffffffffu, sum, o);
            gsum += __shfl_xor_sync(0xffffffffu, gsum, o);
        }
        const float mean = sum * (1.0f / DM);
        float m2 = 0.f;
#pragma unroll
        for (int i = 0; i < 32; i++) {
            float d = v[i] - mean;
            m2 += d * d;
        }
#pragma unroll
        for (int o = 16; o > 0; o >>= 1) m2 += __shfl_xor_sync(0xffffffffu, m2, o);
        if (lane == 0) {
            g_mean1[row] = mean;
            g_rstd1[row] = rsqrtf(m2 * (1.0f / DM) + 1e-5f);
            float logit = bf16_round(gsum);
            float g = bf16_round(1.0f / (1.0f + __expf(-logit)));
            g_gate[row] = g;
            g_omg[row] = bf16_round(1.0f - g);
        }
    } else {
        __shared__ float red[32][65];
        const int strip = blockIdx.x - 256;
        const bf16* w;
        float* out;
        int ld, col0;
        if (strip < 16) { w = w1; ld = DM; col0 = strip * 64; out = g_cs1; }
        else { w = w3; ld = FF; col0 = (strip - 16) * 64; out = g_cs3; }
        const int cg = tid & 7;
        const int rg = tid >> 3;
        float acc[8];
#pragma unroll
        for (int j = 0; j < 8; j++) acc[j] = 0.f;
#pragma unroll 8
        for (int r = 0; r < 32; r++) {
            uint4 a = *reinterpret_cast<const uint4*>(w + (size_t)(r * 32 + rg) * ld + col0 + cg * 8);
            const uint32_t aa[4] = {a.x, a.y, a.z, a.w};
#pragma unroll
            for (int j = 0; j < 4; j++) {
                acc[2 * j] += __uint_as_float(aa[j] << 16);
                acc[2 * j + 1] += __uint_as_float(aa[j] & 0xFFFF0000u);
            }
        }
#pragma unroll
        for (int j = 0; j < 8; j++) red[rg][cg * 8 + j] = acc[j];
        __syncthreads();
        if (tid < 64) {
            float s = 0.f;
#pragma unroll
            for (int r = 0; r < 32; r++) s += red[r][tid];
            out[col0 + tid] = s;
        }
    }
}

template <int BN, int STAGES>
struct GemmSmem {
    static constexpr int A_BYTES = 128 * 64 * 2;
    static constexpr int B_BOXES = (BN + 63) / 64;
    static constexpr int B_BYTES = B_BOXES * 64 * 64 * 2;
    static constexpr int STAGE_BYTES = A_BYTES + B_BYTES;
    static constexpr int STG_OFF = STAGES * STAGE_BYTES;
    static constexpr int BAR_OFF = STG_OFF + 2 * 16384;
    static constexpr int TOTAL = BAR_OFF + 256 + 1024;
};

template <int MODE, int BN, int STAGES>
__global__ void __launch_bounds__(384, 1)
gemm_kernel(const __grid_constant__ CUtensorMap mA, const __grid_constant__ CUtensorMap mB0,
            const __grid_constant__ CUtensorMap mB1, const __grid_constant__ CUtensorMap mC0,
            const __grid_constant__ CUtensorMap mC1, const bf16* __restrict__ xin, int n_tiles_n, int kblocks) {
    using L = GemmSmem<BN, STAGES>;
    extern __shared__ uint8_t smem_raw[];
    const uint32_t sbase = (smem_u32(smem_raw) + 1023u) & ~1023u;
    const uint32_t bar_full = sbase + L::BAR_OFF;
    const uint32_t bar_empty = bar_full + 8 * STAGES;
    const int wg = threadIdx.x >> 7;
    const int ntiles = 16 * n_tiles_n;

    if (threadIdx.x == 0) {
        for (int s = 0; s < STAGES; s++) {
            mbar_init(bar_full + 8 * s, 1);
            mbar_init(bar_empty + 8 * s, 2);
        }
        asm volatile("fence.mbarrier_init.release.cluster;" ::: "memory");
    }
    __syncthreads();

    if (wg == 0) {
        reg_dealloc<40>();
        if (threadIdx.x == 0) {
            prefetch_tmap(&mA);
            prefetch_tmap(&mB0);
            prefetch_tmap(&mB1);
            int stage = 0;
            uint32_t phase = 1;
            for (int tile = blockIdx.x; tile < ntiles; tile += gridDim.x) {
                const int m0 = (tile & 15) * 128;
                const int n0 = (tile >> 4) * BN;
                for (int kb = 0; kb < kblocks; kb++) {
                    mbar_wait(bar_empty + 8 * stage, phase);
                    const uint32_t sa = sbase + stage * L::STAGE_BYTES;
                    const uint32_t sb = sa + L::A_BYTES;
                    const uint32_t fb = bar_full + 8 * stage;
                    mbar_expect_tx(fb, L::STAGE_BYTES);
                    int arow = m0;
                    if (MODE == 2) {
                        const int grp = kb >> 2;
                        arow += (grp == 0) ? -1 : (grp == 1) ? 1 : (grp == 2) ? -2 : 2;
                    }
                    tma_load_2d(sa, &mA, kb * 64, arow, fb);
                    const CUtensorMap* mb = &mB0;
                    int bc = n0, br = kb * 64;
                    if (MODE == 1 && n0 >= 3 * DM) { mb = &mB1; bc = n0 - 3 * DM; }
                    if (MODE == 5 && kb >= 16) { mb = &mB1; br = (kb - 16) * 64; }
#pragma unroll
                    for (int b = 0; b < L::B_BOXES; b++) tma_load_2d(sb + b * 8192, mb, bc + b * 64, br, fb);
                    if (++stage == STAGES) { stage = 0; phase ^= 1; }
                }
            }
        }
    } else {
        reg_alloc<232>();
        const int c = wg - 1;
        const int warp = (threadIdx.x >> 5) & 3;
        const int lane = threadIdx.x & 31;
        const int tid_wg = threadIdx.x & 127;
        const uint32_t stg = sbase + L::STG_OFF + c * 16384;
        int stage = 0;
        uint32_t phase = 0;
        float acc[BN / 2];
        for (int tile = blockIdx.x; tile < ntiles; tile += gridDim.x) {
            const int m0 = (tile & 15) * 128;
            const int n0 = (tile >> 4) * BN;
            int prev_stage = 0;
            for (int kb = 0; kb < kblocks; kb++) {
                mbar_wait(bar_full + 8 * stage, phase);
                const uint32_t sa = sbase + stage * L::STAGE_BYTES + c * 8192;
                const uint32_t sb = sbase + stage * L::STAGE_BYTES + L::A_BYTES;
                const uint64_t da = make_desc(sa, 16, 1024, 1);
                const uint64_t db = make_desc(sb, 8192, 1024, 1);
                wgmma_fence();
#pragma unroll
                for (int k = 0; k < 4; k++) wgmma_tile<BN>(acc, da + k * 2, db + k * 128, (kb | k) != 0);
                wgmma_commit();
                if (kb > 0) {
                    wgmma_wait<1>();
                    if (tid_wg == 0) mbar_arrive(bar_empty + 8 * prev_stage);
                }
                prev_stage = stage;
                if (++stage == STAGES) { stage = 0; phase ^= 1; }
            }
            wgmma_wait<0>();
            if (tid_wg == 0) mbar_arrive(bar_empty + 8 * prev_stage);

            const int r0 = m0 + c * 64 + warp * 16 + (lane >> 2);
            const int r1 = r0 + 8;
            const int cq = (lane & 3) * 2;
            const CUtensorMap* mc = &mC0;
            int out_c0 = n0;
            if (MODE == 1) {
                if (n0 >= 3 * DM) {
                    mc = &mC1;
                    out_c0 = n0 - 3 * DM;
                    const float mu0 = g_mean1[r0], mu1 = g_mean1[r1];
                    const float rs0 = g_rstd1[r0], rs1 = g_rstd1[r1];
#pragma unroll
                    for (int j = 0; j < BN / 8; j++) {
                        const float2 cs = *reinterpret_cast<const float2*>(&g_cs1[out_c0 + 8 * j + cq]);
                        acc[4 * j + 0] = gelu_tanh(rs0 * fmaf(-mu0, cs.x, acc[4 * j + 0]));
                        acc[4 * j + 1] = gelu_tanh(rs0 * fmaf(-mu0, cs.y, acc[4 * j + 1]));
                        acc[4 * j + 2] = gelu_tanh(rs1 * fmaf(-mu1, cs.x, acc[4 * j + 2]));
                        acc[4 * j + 3] = gelu_tanh(rs1 * fmaf(-mu1, cs.y, acc[4 * j + 3]));
                    }
                }
            } else if (MODE == 2) {
                float s0 = 0.f, s1 = 0.f;
#pragma unroll
                for (int j = 0; j < BN / 8; j++) {
                    const uint32_t xa = *reinterpret_cast<const uint32_t*>(xin + (size_t)r0 * DM + n0 + 8 * j + cq);
                    const uint32_t xb = *reinterpret_cast<const uint32_t*>(xin + (size_t)r1 * DM + n0 + 8 * j + cq);
                    acc[4 * j + 0] = bf16_round(bf16_round(acc[4 * j + 0]) + __uint_as_float(xa << 16));
                    acc[4 * j + 1] = bf16_round(bf16_round(acc[4 * j + 1]) + __uint_as_float(xa & 0xFFFF0000u));
                    acc[4 * j + 2] = bf16_round(bf16_round(acc[4 * j + 2]) + __uint_as_float(xb << 16));
                    acc[4 * j + 3] = bf16_round(bf16_round(acc[4 * j + 3]) + __uint_as_float(xb & 0xFFFF0000u));
                    s0 += acc[4 * j + 0] + acc[4 * j + 1];
                    s1 += acc[4 * j + 2] + acc[4 * j + 3];
                }
                s0 += __shfl_xor_sync(0xffffffffu, s0, 1);
                s0 += __shfl_xor_sync(0xffffffffu, s0, 2);
                s1 += __shfl_xor_sync(0xffffffffu, s1, 1);
                s1 += __shfl_xor_sync(0xffffffffu, s1, 2);
                const float mu0 = s0 * (1.0f / BN), mu1 = s1 * (1.0f / BN);
                float q0 = 0.f, q1 = 0.f;
#pragma unroll
                for (int j = 0; j < BN / 8; j++) {
                    float d;
                    d = acc[4 * j + 0] - mu0; q0 += d * d;
                    d = acc[4 * j + 1] - mu0; q0 += d * d;
                    d = acc[4 * j + 2] - mu1; q1 += d * d;
                    d = acc[4 * j + 3] - mu1; q1 += d * d;
                }
                q0 += __shfl_xor_sync(0xffffffffu, q0, 1);
                q0 += __shfl_xor_sync(0xffffffffu, q0, 2);
                q1 += __shfl_xor_sync(0xffffffffu, q1, 1);
                q1 += __shfl_xor_sync(0xffffffffu, q1, 2);
                if ((lane & 3) == 0) {
                    static_assert(MODE != 2 || BN == 128, "stats layout assumes BN=128");
                    g_stat2[r0 * 8 + (n0 >> 7)] = make_float2(s0, q0);
                    g_stat2[r1 * 8 + (n0 >> 7)] = make_float2(s1, q1);
                }
            } else if (MODE == 3) {
                out_c0 = n0 + DM;
                float mu[2], rs[2];
#pragma unroll
                for (int h = 0; h < 2; h++) {
                    const float4* sp = reinterpret_cast<const float4*>(&g_stat2[(h ? r1 : r0) * 8]);
                    float4 p[4];
                    float s = 0.f;
#pragma unroll
                    for (int i = 0; i < 4; i++) { p[i] = sp[i]; s += p[i].x + p[i].z; }
                    const float mean = s * (1.0f / DM);
                    float m2 = 0.f;
#pragma unroll
                    for (int i = 0; i < 4; i++) {
                        float d0 = p[i].x * (1.0f / 128) - mean, d1 = p[i].z * (1.0f / 128) - mean;
                        m2 += p[i].y + p[i].w + 128.0f * (d0 * d0 + d1 * d1);
                    }
                    mu[h] = mean;
                    rs[h] = rsqrtf(m2 * (1.0f / DM) + 1e-5f);
                }
                const float og0 = g_omg[r0], og1 = g_omg[r1];
#pragma unroll
                for (int j = 0; j < BN / 8; j++) {
                    const float2 cs = *reinterpret_cast<const float2*>(&g_cs3[n0 + 8 * j + cq]);
                    acc[4 * j + 0] = og0 * gelu_tanh(rs[0] * fmaf(-mu[0], cs.x, acc[4 * j + 0]));
                    acc[4 * j + 1] = og0 * gelu_tanh(rs[0] * fmaf(-mu[0], cs.y, acc[4 * j + 1]));
                    acc[4 * j + 2] = og1 * gelu_tanh(rs[1] * fmaf(-mu[1], cs.x, acc[4 * j + 2]));
                    acc[4 * j + 3] = og1 * gelu_tanh(rs[1] * fmaf(-mu[1], cs.y, acc[4 * j + 3]));
                }
            } else {
                const float og0 = g_omg[r0], og1 = g_omg[r1];
#pragma unroll
                for (int j = 0; j < BN / 8; j++) {
                    const uint32_t xa = *reinterpret_cast<const uint32_t*>(xin + (size_t)r0 * DM + n0 + 8 * j + cq);
                    const uint32_t xb = *reinterpret_cast<const uint32_t*>(xin + (size_t)r1 * DM + n0 + 8 * j + cq);
                    acc[4 * j + 0] = fmaf(og0, __uint_as_float(xa << 16), acc[4 * j + 0]);
                    acc[4 * j + 1] = fmaf(og0, __uint_as_float(xa & 0xFFFF0000u), acc[4 * j + 1]);
                    acc[4 * j + 2] = fmaf(og1, __uint_as_float(xb << 16), acc[4 * j + 2]);
                    acc[4 * j + 3] = fmaf(og1, __uint_as_float(xb & 0xFFFF0000u), acc[4 * j + 3]);
                }
            }
            const int srow = warp * 16 + (lane & 7) + ((lane >> 3) & 1) * 8;
#pragma unroll
            for (int rnd = 0; rnd < (BN + 127) / 128; rnd++) {
                if (tid_wg == 0) bulk_wait_read0();
                named_bar_sync(1 + c, 128);
#pragma unroll
                for (int jj = 0; jj < 8; jj++) {
                    const int j = rnd * 16 + jj * 2;
                    if (j * 8 < BN) {
                        const int jb = jj * 2 + (lane >> 4);
                        const uint32_t addr = stg + (jb >> 3) * 8192 + srow * 128 + (((jb & 7) ^ (srow & 7)) << 4);
                        stmatrix_x4(addr, pack_bf16(acc[4 * j + 0], acc[4 * j + 1]), pack_bf16(acc[4 * j + 2], acc[4 * j + 3]),
                                    pack_bf16(acc[4 * j + 4], acc[4 * j + 5]), pack_bf16(acc[4 * j + 6], acc[4 * j + 7]));
                    }
                }
                fence_proxy_async();
                named_bar_sync(1 + c, 128);
                if (tid_wg == 0) {
                    tma_store_2d(mc, stg, out_c0 + rnd * 128, m0 + c * 64);
                    if (rnd * 128 + 64 < BN) tma_store_2d(mc, stg + 8192, out_c0 + rnd * 128 + 64, m0 + c * 64);
                    bulk_commit();
                }
            }
        }
        if (tid_wg == 0) bulk_wait0();
    }
}

constexpr int ATT_STAGES = 4;
constexpr int ATT_DIST = 2;
constexpr int ATT_SMEM = ATT_STAGES * 16384 + 256 + 1024;

struct AttState {
    float o[16];
    float m0, m1, l0, l1;
};

__device__ __forceinline__ void attn_step(float (&sc)[32], float (&sn)[32], const uint32_t (&qf)[8], AttState& st,
                                          uint64_t dk_next, uint64_t dv_cur, uint32_t release_bar) {
    const float cs = 0.17677669529663687f * 1.4426950408889634f;
    wgmma_fence();
    wgmma_rs_n64_tb0(sn, qf[0], qf[1], qf[2], qf[3], dk_next, 0);
    wgmma_rs_n64_tb0(sn, qf[4], qf[5], qf[6], qf[7], dk_next + 2, 1);
    wgmma_commit();
    wgmma_wait<2>();
    float mx0 = fmaxf(sc[0], sc[1]), mx1 = fmaxf(sc[2], sc[3]);
#pragma unroll
    for (int i = 1; i < 8; i++) {
        mx0 = fmaxf(mx0, fmaxf(sc[4 * i], sc[4 * i + 1]));
        mx1 = fmaxf(mx1, fmaxf(sc[4 * i + 2], sc[4 * i + 3]));
    }
    mx0 = fmaxf(mx0, __shfl_xor_sync(0xffffffffu, mx0, 1));
    mx1 = fmaxf(mx1, __shfl_xor_sync(0xffffffffu, mx1, 1));
    mx0 = fmaxf(mx0, __shfl_xor_sync(0xffffffffu, mx0, 2));
    mx1 = fmaxf(mx1, __shfl_xor_sync(0xffffffffu, mx1, 2));
    const float mn0 = fmaxf(st.m0, mx0), mn1 = fmaxf(st.m1, mx1);
    const float a0 = ex2((st.m0 - mn0) * cs), a1 = ex2((st.m1 - mn1) * cs);
    st.m0 = mn0; st.m1 = mn1;
    const float b0 = mn0 * cs, b1 = mn1 * cs;
    float t0 = 0.f, t1 = 0.f;
#pragma unroll
    for (int i = 0; i < 8; i++) {
        sc[4 * i + 0] = ex2(fmaf(sc[4 * i + 0], cs, -b0));
        sc[4 * i + 1] = ex2(fmaf(sc[4 * i + 1], cs, -b0));
        sc[4 * i + 2] = ex2(fmaf(sc[4 * i + 2], cs, -b1));
        sc[4 * i + 3] = ex2(fmaf(sc[4 * i + 3], cs, -b1));
        t0 += sc[4 * i + 0] + sc[4 * i + 1];
        t1 += sc[4 * i + 2] + sc[4 * i + 3];
    }
    st.l0 = fmaf(st.l0, a0, t0);
    st.l1 = fmaf(st.l1, a1, t1);
    wgmma_wait<1>();
    if (release_bar != 0 && (threadIdx.x & 127) == 0) mbar_arrive(release_bar);
#pragma unroll
    for (int i = 0; i < 4; i++) {
        st.o[4 * i + 0] *= a0; st.o[4 * i + 1] *= a0;
        st.o[4 * i + 2] *= a1; st.o[4 * i + 3] *= a1;
    }
    uint32_t p[16];
#pragma unroll
    for (int i = 0; i < 8; i++) {
        p[2 * i] = pack_bf16(sc[4 * i + 0], sc[4 * i + 1]);
        p[2 * i + 1] = pack_bf16(sc[4 * i + 2], sc[4 * i + 3]);
    }
    wgmma_fence();
#pragma unroll
    for (int t = 0; t < 4; t++)
        wgmma_rs_n32_tb1(st.o, p[4 * t], p[4 * t + 1], p[4 * t + 2], p[4 * t + 3], dv_cur + t * 64, 1);
    wgmma_commit();
}

__global__ void __launch_bounds__(256, 2)
attn_kernel(const __grid_constant__ CUtensorMap mKV) {
    extern __shared__ uint8_t smem_raw[];
    const uint32_t sbase = (smem_u32(smem_raw) + 1023u) & ~1023u;
    const uint32_t bar_kfull = sbase + ATT_STAGES * 16384;
    const uint32_t bar_vfull = bar_kfull + 8 * ATT_STAGES;
    const uint32_t bar_empty = bar_vfull + 8 * ATT_STAGES;
    const int head = blockIdx.x >> 4;
    const int q0 = (blockIdx.x & 15) * 128;
    const int warp_id = threadIdx.x >> 5;
    const int lane = threadIdx.x & 31;
    constexpr int NBLK = S_LEN / 128;

    if (threadIdx.x == 0) {
        for (int s = 0; s < ATT_STAGES; s++) {
            mbar_init(bar_kfull + 8 * s, 1);
            mbar_init(bar_vfull + 8 * s, 1);
            mbar_init(bar_empty + 8 * s, 2);
        }
        asm volatile("fence.mbarrier_init.release.cluster;" ::: "memory");
        prefetch_tmap(&mKV);
#pragma unroll
        for (int j = 0; j < ATT_DIST; j++) {
            const uint32_t sk = sbase + j * 16384;
            mbar_expect_tx(bar_kfull + 8 * j, 8192);
            tma_load_2d(sk, &mKV, DM + head * DH, j * 128, bar_kfull + 8 * j);
            mbar_expect_tx(bar_vfull + 8 * j, 8192);
            tma_load_2d(sk + 8192, &mKV, 2 * DM + head * DH, j * 128, bar_vfull + 8 * j);
        }
    }
    __syncthreads();

    const int row0 = q0 + warp_id * 16 + (lane >> 2);
    const int cq = (lane & 3) * 2;
    uint32_t qf[8];
    {
        const bf16* qp0 = g_qkv + (size_t)row0 * (3 * DM) + head * DH + cq;
        const bf16* qp1 = qp0 + 8 * (3 * DM);
#pragma unroll
        for (int t = 0; t < 2; t++) {
            qf[4 * t + 0] = *reinterpret_cast<const uint32_t*>(qp0 + 16 * t);
            qf[4 * t + 1] = *reinterpret_cast<const uint32_t*>(qp1 + 16 * t);
            qf[4 * t + 2] = *reinterpret_cast<const uint32_t*>(qp0 + 16 * t + 8);
            qf[4 * t + 3] = *reinterpret_cast<const uint32_t*>(qp1 + 16 * t + 8);
        }
    }
    AttState st;
#pragma unroll
    for (int i = 0; i < 16; i++) st.o[i] = 0.f;
    st.m0 = -INFINITY; st.m1 = -INFINITY; st.l0 = 0.f; st.l1 = 0.f;
    float s0[32], s1[32];
    const uint64_t desc0 = make_desc(sbase, 16, 512, 2);
    mbar_wait(bar_kfull, 0);
    wgmma_fence();
    wgmma_rs_n64_tb0(s0, qf[0], qf[1], qf[2], qf[3], desc0, 0);
    wgmma_rs_n64_tb0(s0, qf[4], qf[5], qf[6], qf[7], desc0 + 2, 1);
    wgmma_commit();
    wgmma_commit();
    int stage = 0;
    uint32_t phase = 0;
#pragma unroll 1
    for (int j = 0; j < NBLK; j++) {
        if (threadIdx.x == 0 && j + ATT_DIST < NBLK) {
            const int jn = j + ATT_DIST;
            const int sn = jn % ATT_STAGES;
            if (jn >= ATT_STAGES) mbar_wait(bar_empty + 8 * sn, ((jn / ATT_STAGES) - 1) & 1);
            const uint32_t skn = sbase + sn * 16384;
            mbar_expect_tx(bar_kfull + 8 * sn, 8192);
            tma_load_2d(skn, &mKV, DM + head * DH, jn * 128, bar_kfull + 8 * sn);
            mbar_expect_tx(bar_vfull + 8 * sn, 8192);
            tma_load_2d(skn + 8192, &mKV, 2 * DM + head * DH, jn * 128, bar_vfull + 8 * sn);
        }
        __syncwarp();
        const uint64_t dk = desc0 + (uint64_t)(stage * 1024);
        const int pstage = (stage + ATT_STAGES - 1) % ATT_STAGES;
        mbar_wait(bar_vfull + 8 * stage, phase);
        attn_step(s0, s1, qf, st, dk + 256, dk + 512, j > 0 ? bar_empty + 8 * pstage : 0u);
        int nstage = stage + 1;
        uint32_t nphase = phase;
        if (nstage == ATT_STAGES) { nstage = 0; nphase ^= 1; }
        uint64_t dkn = dk;
        if (j + 1 < NBLK) {
            mbar_wait(bar_kfull + 8 * nstage, nphase);
            dkn = desc0 + (uint64_t)(nstage * 1024);
        }
        attn_step(s1, s0, qf, st, dkn, dk + 512 + 256, 0u);
        stage = nstage;
        phase = nphase;
    }
    wgmma_wait<0>();
    float l0 = st.l0, l1 = st.l1;
    l0 += __shfl_xor_sync(0xffffffffu, l0, 1);
    l0 += __shfl_xor_sync(0xffffffffu, l0, 2);
    l1 += __shfl_xor_sync(0xffffffffu, l1, 1);
    l1 += __shfl_xor_sync(0xffffffffu, l1, 2);
    const float f0 = g_gate[row0] / l0, f1 = g_gate[row0 + 8] / l1;
    bf16* op0 = g_a5 + (size_t)row0 * A5W + head * DH + cq;
    bf16* op1 = op0 + 8 * A5W;
#pragma unroll
    for (int i = 0; i < 4; i++) {
        *reinterpret_cast<uint32_t*>(op0 + 8 * i) = pack_bf16(st.o[4 * i] * f0, st.o[4 * i + 1] * f0);
        *reinterpret_cast<uint32_t*>(op1 + 8 * i) = pack_bf16(st.o[4 * i + 2] * f1, st.o[4 * i + 3] * f1);
    }
}

typedef CUresult (*EncodeFn)(CUtensorMap*, CUtensorMapDataType, cuuint32_t, void*, const cuuint64_t*, const cuuint64_t*,
                             const cuuint32_t*, const cuuint32_t*, CUtensorMapInterleave, CUtensorMapSwizzle,
                             CUtensorMapL2promotion, CUtensorMapFloatOOBfill);

static CUtensorMap make_map(EncodeFn fn, const void* ptr, int rows, int cols, int box_cols, int box_rows,
                            CUtensorMapSwizzle swz) {
    CUtensorMap m;
    cuuint64_t dims[2] = {(cuuint64_t)cols, (cuuint64_t)rows};
    cuuint64_t strides[1] = {(cuuint64_t)cols * 2};
    cuuint32_t box[2] = {(cuuint32_t)box_cols, (cuuint32_t)box_rows};
    cuuint32_t es[2] = {1, 1};
    fn(&m, CU_TENSOR_MAP_DATA_TYPE_BFLOAT16, 2, const_cast<void*>(ptr), dims, strides, box, es,
       CU_TENSOR_MAP_INTERLEAVE_NONE, swz, CU_TENSOR_MAP_L2_PROMOTION_L2_256B, CU_TENSOR_MAP_FLOAT_OOB_FILL_NONE);
    return m;
}

extern "C" void kernel_launch(void* const* d_in, const int* in_sizes, int n_in, void* d_out, int out_size) {
    const bf16* x = (const bf16*)d_in[0];
    const bf16* wqkv = (const bf16*)d_in[1];
    const bf16* wo = (const bf16*)d_in[2];
    const bf16* w1 = (const bf16*)d_in[4];
    const bf16* w2 = (const bf16*)d_in[5];
    const bf16* w3 = (const bf16*)d_in[6];
    const bf16* w4 = (const bf16*)d_in[7];
    const bf16* gate_w = (const bf16*)d_in[8];

    static EncodeFn enc = nullptr;
    static void *p_qkv, *p_h, *p_x1, *p_a5;
    if (!enc) {
        void* fn = nullptr;
        cudaDriverEntryPointQueryResult qres;
        cudaGetDriverEntryPoint("cuTensorMapEncodeTiled", &fn, cudaEnableDefault, &qres);
        enc = (EncodeFn)fn;
        cudaGetSymbolAddress(&p_qkv, g_qkv);
        cudaGetSymbolAddress(&p_h, g_h);
        cudaGetSymbolAddress(&p_x1, g_x1);
        cudaGetSymbolAddress(&p_a5, g_a5);
        cudaFuncSetAttribute(gemm_kernel<1, 256, 4>, cudaFuncAttributeMaxDynamicSharedMemorySize, GemmSmem<256, 4>::TOTAL);
        cudaFuncSetAttribute(gemm_kernel<2, 128, 5>, cudaFuncAttributeMaxDynamicSharedMemorySize, GemmSmem<128, 5>::TOTAL);
        cudaFuncSetAttribute(gemm_kernel<3, 256, 4>, cudaFuncAttributeMaxDynamicSharedMemorySize, GemmSmem<256, 4>::TOTAL);
        cudaFuncSetAttribute(gemm_kernel<5, 128, 5>, cudaFuncAttributeMaxDynamicSharedMemorySize, GemmSmem<128, 5>::TOTAL);
        cudaFuncSetAttribute(attn_kernel, cudaFuncAttributeMaxDynamicSharedMemorySize, ATT_SMEM);
    }
    const CUtensorMapSwizzle SW128 = CU_TENSOR_MAP_SWIZZLE_128B, SW64 = CU_TENSOR_MAP_SWIZZLE_64B;
    CUtensorMap mX = make_map(enc, x, S_LEN, DM, 64, 128, SW128);
    CUtensorMap mWqkv = make_map(enc, wqkv, DM, 3 * DM, 64, 64, SW128);
    CUtensorMap mW1 = make_map(enc, w1, DM, DM, 64, 64, SW128);
    CUtensorMap mW2 = make_map(enc, w2, DM, DM, 64, 64, SW128);
    CUtensorMap mW3 = make_map(enc, w3, DM, FF, 64, 64, SW128);
    CUtensorMap mW4 = make_map(enc, w4, FF, DM, 64, 64, SW128);
    CUtensorMap mWo = make_map(enc, wo, DM, DM, 64, 64, SW128);
    CUtensorMap mQKVst = make_map(enc, p_qkv, S_LEN, 3 * DM, 64, 64, SW128);
    CUtensorMap mKV = make_map(enc, p_qkv, S_LEN, 3 * DM, 32, 128, SW64);
    CUtensorMap mHst = make_map(enc, p_h, S_LEN, DM, 64, 64, SW128);
    CUtensorMap mHld = make_map(enc, p_h, S_LEN, DM, 64, 128, SW128);
    CUtensorMap mX1st = make_map(enc, p_x1, S_LEN, DM, 64, 64, SW128);
    CUtensorMap mX1ld = make_map(enc, p_x1, S_LEN, DM, 64, 128, SW128);
    CUtensorMap mA5st = make_map(enc, p_a5, S_LEN, A5W, 64, 64, SW128);
    CUtensorMap mA5ld = make_map(enc, p_a5, S_LEN, A5W, 64, 128, SW128);
    CUtensorMap mOut = make_map(enc, d_out, S_LEN, DM, 64, 64, SW128);

    cudaStream_t st = cudaStreamPerThread;
    prep_kernel<<<256 + 72, 256, 0, st>>>(x, gate_w, w1, w3);
    gemm_kernel<1, 256, 4><<<132, 384, GemmSmem<256, 4>::TOTAL, st>>>(mX, mWqkv, mW1, mQKVst, mHst, x, 16, 16);
    attn_kernel<<<NH * 16, 256, ATT_SMEM, st>>>(mKV);
    gemm_kernel<2, 128, 5><<<128, 384, GemmSmem<128, 5>::TOTAL, st>>>(mHld, mW2, mW2, mX1st, mX1st, x, 8, 16);
    gemm_kernel<3, 256, 4><<<132, 384, GemmSmem<256, 4>::TOTAL, st>>>(mX1ld, mW3, mW3, mA5st, mA5st, x, 14, 16);
    gemm_kernel<5, 128, 5><<<128, 384, GemmSmem<128, 5>::TOTAL, st>>>(mA5ld, mWo, mW4, mOut, mOut, (const bf16*)p_x1, 8, 72);
}
```

```cpp
#include <cuda_runtime.h>
#include <cuda_bf16.h>
#include <cuda.h>
#include <stdint.h>

typedef __nv_bfloat16 bf16;

constexpr int S_LEN = 2048;
constexpr int DM = 1024;
constexpr int FF = 3584;
constexpr int NH = 32;
constexpr int DH = 32;
constexpr int A5W = DM + FF;

__device__ __align__(1024) bf16 g_qkv[S_LEN * 3 * DM];
__device__ __align__(1024) bf16 g_h[S_LEN * DM];
__device__ __align__(1024) bf16 g_x1[S_LEN * DM];
__device__ __align__(1024) bf16 g_a5[S_LEN * A5W];
__device__ __align__(16) float g_mean1[S_LEN];
__device__ __align__(16) float g_rstd1[S_LEN];
__device__ __align__(16) float g_gate[S_LEN];
__device__ __align__(16) float g_omg[S_LEN];
__device__ __align__(16) float g_cs1[DM];
__device__ __align__(16) float g_cs3[FF];
__device__ __align__(16) float2 g_stat2[S_LEN * 8];

__device__ __forceinline__ uint32_t smem_u32(const void* p) { return (uint32_t)__cvta_generic_to_shared(p); }

__device__ __forceinline__ void mbar_init(uint32_t bar, uint32_t count) {
    asm volatile("mbarrier.init.shared::cta.b64 [%0], %1;" ::"r"(bar), "r"(count));
}
__device__ __forceinline__ void mbar_expect_tx(uint32_t bar, uint32_t bytes) {
    asm volatile("mbarrier.arrive.expect_tx.shared::cta.b64 _, [%0], %1;" ::"r"(bar), "r"(bytes) : "memory");
}
__device__ __forceinline__ void mbar_arrive(uint32_t bar) {
    asm volatile("mbarrier.arrive.shared::cta.b64 _, [%0];" ::"r"(bar) : "memory");
}
__device__ __forceinline__ bool mbar_try_wait(uint32_t bar, uint32_t parity) {
    uint32_t ok;
    asm volatile(
        "{\n.reg .pred p;\n"
        "mbarrier.try_wait.parity.shared::cta.b64 p, [%1], %2;\n"
        "selp.u32 %0, 1, 0, p;\n}\n"
        : "=r"(ok)
        : "r"(bar), "r"(parity)
        : "memory");
    return ok != 0;
}
__device__ __forceinline__ void mbar_wait(uint32_t bar, uint32_t parity) {
    uint32_t spins = 0;
    while (!mbar_try_wait(bar, parity)) {
        if (++spins > (1u << 24)) __trap();
    }
}
__device__ __forceinline__ void tma_load_2d(uint32_t dst, const CUtensorMap* map, int c0, int c1, uint32_t bar) {
    asm volatile(
        "cp.async.bulk.tensor.2d.shared::cluster.global.mbarrier::complete_tx::bytes [%0], [%1, {%3, %4}], [%2];"
        ::"r"(dst), "l"(map), "r"(bar), "r"(c0), "r"(c1)
        : "memory");
}
__device__ __forceinline__ void tma_store_2d(const CUtensorMap* map, uint32_t src, int c0, int c1) {
    asm volatile("cp.async.bulk.tensor.2d.global.shared::cta.bulk_group [%0, {%2, %3}], [%1];"
                 ::"l"(map), "r"(src), "r"(c0), "r"(c1)
                 : "memory");
}
__device__ __forceinline__ void bulk_commit() { asm volatile("cp.async.bulk.commit_group;" ::: "memory"); }
__device__ __forceinline__ void bulk_wait_read0() { asm volatile("cp.async.bulk.wait_group.read 0;" ::: "memory"); }
__device__ __forceinline__ void bulk_wait0() { asm volatile("cp.async.bulk.wait_group 0;" ::: "memory"); }
__device__ __forceinline__ void fence_proxy_async() { asm volatile("fence.proxy.async.shared::cta;" ::: "memory"); }
__device__ __forceinline__ void named_bar_sync(int id, int n) { asm volatile("bar.sync %0, %1;" ::"r"(id), "r"(n) : "memory"); }
__device__ __forceinline__ void named_bar_arrive(int id, int n) { asm volatile("bar.arrive %0, %1;" ::"r"(id), "r"(n) : "memory"); }
__device__ __forceinline__ void wgmma_fence() { asm volatile("wgmma.fence.sync.aligned;" ::: "memory"); }
__device__ __forceinline__ void wgmma_commit() { asm volatile("wgmma.commit_group.sync.aligned;" ::: "memory"); }
template <int N>
__device__ __forceinline__ void wgmma_wait() { asm volatile("wgmma.wait_group.sync.aligned %0;" ::"n"(N) : "memory"); }
__device__ __forceinline__ void prefetch_tmap(const CUtensorMap* m) {
    asm volatile("prefetch.tensormap [%0];" ::"l"(m) : "memory");
}
template <int R>
__device__ __forceinline__ void reg_alloc() { asm volatile("setmaxnreg.inc.sync.aligned.u32 %0;" ::"n"(R)); }
template <int R>
__device__ __forceinline__ void reg_dealloc() { asm volatile("setmaxnreg.dec.sync.aligned.u32 %0;" ::"n"(R)); }
__device__ __forceinline__ void stmatrix_x4(uint32_t addr, uint32_t r0, uint32_t r1, uint32_t r2, uint32_t r3) {
    asm volatile("stmatrix.sync.aligned.m8n8.x4.shared.b16 [%0], {%1, %2, %3, %4};"
                 ::"r"(addr), "r"(r0), "r"(r1), "r"(r2), "r"(r3)
                 : "memory");
}
__device__ __forceinline__ uint32_t pack_bf16(float lo, float hi) {
    uint32_t r;
    asm("cvt.rn.bf16x2.f32 %0, %1, %2;" : "=r"(r) : "f"(hi), "f"(lo));
    return r;
}
__device__ __forceinline__ float bf16_round(float v) { return __bfloat162float(__float2bfloat16_rn(v)); }
__device__ __forceinline__ float ex2(float x) {
    float y;
    asm("ex2.approx.ftz.f32 %0, %1;" : "=f"(y) : "f"(x));
    return y;
}
__device__ __forceinline__ float tanh_fast(float x) {
    float y;
    asm("tanh.approx.f32 %0, %1;" : "=f"(y) : "f"(x));
    return y;
}
__device__ __forceinline__ float gelu_tanh(float v) {
    float u = 0.7978845608028654f * (v + 0.044715f * v * v * v);
    float hv = 0.5f * v;
    return fmaf(hv, tanh_fast(u), hv);
}
__device__ __forceinline__ uint64_t make_desc(uint32_t addr, uint32_t lbo_bytes, uint32_t sbo_bytes, uint32_t swz) {
    uint64_t d = 0;
    d |= (uint64_t)((addr & 0x3FFFF) >> 4);
    d |= (uint64_t)((lbo_bytes >> 4) & 0x3FFF) << 16;
    d |= (uint64_t)((sbo_bytes >> 4) & 0x3FFF) << 32;
    d |= (uint64_t)swz << 62;
    return d;
}


__device__ __forceinline__ void wgmma_ss_n128_tb1(float (&d)[64], uint64_t da, uint64_t db, int scale_d) {
    asm volatile("{\n.reg .pred p;\nsetp.ne.b32 p, %66, 0;\n"
        "wgmma.mma_async.sync.aligned.m64n128k16.f32.bf16.bf16 {%0, %1, %2, %3, %4, %5, %6, %7, %8, %9, %10, %11, %12, %13, %14, %15, %16, %17, %18, %19, %20, %21, %22, %23, %24, %25, %26, %27, %28, %29, %30, %31, %32, %33, %34, %35, %36, %37, %38, %39, %40, %41, %42, %43, %44, %45, %46, %47, %48, %49, %50, %51, %52, %53, %54, %55, %56, %57, %58, %59, %60, %61, %62, %63}, %64, %65, p, 1, 1, 0, 1;\n}\n"
        : "+f"(d[0]), "+f"(d[1]), "+f"(d[2]), "+f"(d[3]), "+f"(d[4]), "+f"(d[5]), "+f"(d[6]), "+f"(d[7]), "+f"(d[8]), "+f"(d[9]), "+f"(d[10]), "+f"(d[11]), "+f"(d[12]), "+f"(d[13]), "+f"(d[14]), "+f"(d[15]), "+f"(d[16]), "+f"(d[17]), "+f"(d[18]), "+f"(d[19]), "+f"(d[20]), "+f"(d[21]), "+f"(d[22]), "+f"(d[23]), "+f"(d[24]), "+f"(d[25]), "+f"(d[26]), "+f"(d[27]), "+f"(d[28]), "+f"(d[29]), "+f"(d[30]), "+f"(d[31]), "+f"(d[32]), "+f"(d[33]), "+f"(d[34]), "+f"(d[35]), "+f"(d[36]), "+f"(d[37]), "+f"(d[38]), "+f"(d[39]), "+f"(d[40]), "+f"(d[41]), "+f"(d[42]), "+f"(d[43]), "+f"(d[44]), "+f"(d[45]), "+f"(d[46]), "+f"(d[47]), "+f"(d[48]), "+f"(d[49]), "+f"(d[50]), "+f"(d[51]), "+f"(d[52]), "+f"(d[53]), "+f"(d[54]), "+f"(d[55]), "+f"(d[56]), "+f"(d[57]), "+f"(d[58]), "+f"(d[59]), "+f"(d[60]), "+f"(d[61]), "+f"(d[62]), "+f"(d[63])
        : "l"(da), "l"(db), "r"(scale_d));
}

__device__ __forceinline__ void wgmma_ss_n192_tb1(float (&d)[96], uint64_t da, uint64_t db, int scale_d) {
    asm volatile("{\n.reg .pred p;\nsetp.ne.b32 p, %98, 0;\n"
        "wgmma.mma_async.sync.aligned.m64n192k16.f32.bf16.bf16 {%0, %1, %2, %3, %4, %5, %6, %7, %8, %9, %10, %11, %12, %13, %14, %15, %16, %17, %18, %19, %20, %21, %22, %23, %24, %25, %26, %27, %28, %29, %30, %31, %32, %33, %34, %35, %36, %37, %38, %39, %40, %41, %42, %43, %44, %45, %46, %47, %48, %49, %50, %51, %52, %53, %54, %55, %56, %57, %58, %59, %60, %61, %62, %63, %64, %65, %66, %67, %68, %69, %70, %71, %72, %73, %74, %75, %76, %77, %78, %79, %80, %81, %82, %83, %84, %85, %86, %87, %88, %89, %90, %91, %92, %93, %94, %95}, %96, %97, p, 1, 1, 0, 1;\n}\n"
        : "+f"(d[0]), "+f"(d[1]), "+f"(d[2]), "+f"(d[3]), "+f"(d[4]), "+f"(d[5]), "+f"(d[6]), "+f"(d[7]), "+f"(d[8]), "+f"(d[9]), "+f"(d[10]), "+f"(d[11]), "+f"(d[12]), "+f"(d[13]), "+f"(d[14]), "+f"(d[15]), "+f"(d[16]), "+f"(d[17]), "+f"(d[18]), "+f"(d[19]), "+f"(d[20]), "+f"(d[21]), "+f"(d[22]), "+f"(d[23]), "+f"(d[24]), "+f"(d[25]), "+f"(d[26]), "+f"(d[27]), "+f"(d[28]), "+f"(d[29]), "+f"(d[30]), "+f"(d[31]), "+f"(d[32]), "+f"(d[33]), "+f"(d[34]), "+f"(d[35]), "+f"(d[36]), "+f"(d[37]), "+f"(d[38]), "+f"(d[39]), "+f"(d[40]), "+f"(d[41]), "+f"(d[42]), "+f"(d[43]), "+f"(d[44]), "+f"(d[45]), "+f"(d[46]), "+f"(d[47]), "+f"(d[48]), "+f"(d[49]), "+f"(d[50]), "+f"(d[51]), "+f"(d[52]), "+f"(d[53]), "+f"(d[54]), "+f"(d[55]), "+f"(d[56]), "+f"(d[57]), "+f"(d[58]), "+f"(d[59]), "+f"(d[60]), "+f"(d[61]), "+f"(d[62]), "+f"(d[63]), "+f"(d[64]), "+f"(d[65]), "+f"(d[66]), "+f"(d[67]), "+f"(d[68]), "+f"(d[69]), "+f"(d[70]), "+f"(d[71]), "+f"(d[72]), "+f"(d[73]), "+f"(d[74]), "+f"(d[75]), "+f"(d[76]), "+f"(d[77]), "+f"(d[78]), "+f"(d[79]), "+f"(d[80]), "+f"(d[81]), "+f"(d[82]), "+f"(d[83]), "+f"(d[84]), "+f"(d[85]), "+f"(d[86]), "+f"(d[87]), "+f"(d[88]), "+f"(d[89]), "+f"(d[90]), "+f"(d[91]), "+f"(d[92]), "+f"(d[93]), "+f"(d[94]), "+f"(d[95])
        : "l"(da), "l"(db), "r"(scale_d));
}

__device__ __forceinline__ void wgmma_ss_n224_tb1(float (&d)[112], uint64_t da, uint64_t db, int scale_d) {
    asm volatile("{\n.reg .pred p;\nsetp.ne.b32 p, %114, 0;\n"
        "wgmma.mma_async.sync.aligned.m64n224k16.f32.bf16.bf16 {%0, %1, %2, %3, %4, %5, %6, %7, %8, %9, %10, %11, %12, %13, %14, %15, %16, %17, %18, %19, %20, %21, %22, %23, %24, %25, %26, %27, %28, %29, %30, %31, %32, %33, %34, %35, %36, %37, %38, %39, %40, %41, %42, %43, %44, %45, %46, %47, %48, %49, %50, %51, %52, %53, %54, %55, %56, %57, %58, %59, %60, %61, %62, %63, %64, %65, %66, %67, %68, %69, %70, %71, %72, %73, %74, %75, %76, %77, %78, %79, %80, %81, %82, %83, %84, %85, %86, %87, %88, %89, %90, %91, %92, %93, %94, %95, %96, %97, %98, %99, %100, %101, %102, %103, %104, %105, %106, %107, %108, %109, %110, %111}, %112, %113, p, 1, 1, 0, 1;\n}\n"
        : "+f"(d[0]), "+f"(d[1]), "+f"(d[2]), "+f"(d[3]), "+f"(d[4]), "+f"(d[5]), "+f"(d[6]), "+f"(d[7]), "+f"(d[8]), "+f"(d[9]), "+f"(d[10]), "+f"(d[11]), "+f"(d[12]), "+f"(d[13]), "+f"(d[14]), "+f"(d[15]), "+f"(d[16]), "+f"(d[17]), "+f"(d[18]), "+f"(d[19]), "+f"(d[20]), "+f"(d[21]), "+f"(d[22]), "+f"(d[23]), "+f"(d[24]), "+f"(d[25]), "+f"(d[26]), "+f"(d[27]), "+f"(d[28]), "+f"(d[29]), "+f"(d[30]), "+f"(d[31]), "+f"(d[32]), "+f"(d[33]), "+f"(d[34]), "+f"(d[35]), "+f"(d[36]), "+f"(d[37]), "+f"(d[38]), "+f"(d[39]), "+f"(d[40]), "+f"(d[41]), "+f"(d[42]), "+f"(d[43]), "+f"(d[44]), "+f"(d[45]), "+f"(d[46]), "+f"(d[47]), "+f"(d[48]), "+f"(d[49]), "+f"(d[50]), "+f"(d[51]), "+f"(d[52]), "+f"(d[53]), "+f"(d[54]), "+f"(d[55]), "+f"(d[56]), "+f"(d[57]), "+f"(d[58]), "+f"(d[59]), "+f"(d[60]), "+f"(d[61]), "+f"(d[62]), "+f"(d[63]), "+f"(d[64]), "+f"(d[65]), "+f"(d[66]), "+f"(d[67]), "+f"(d[68]), "+f"(d[69]), "+f"(d[70]), "+f"(d[71]), "+f"(d[72]), "+f"(d[73]), "+f"(d[74]), "+f"(d[75]), "+f"(d[76]), "+f"(d[77]), "+f"(d[78]), "+f"(d[79]), "+f"(d[80]), "+f"(d[81]), "+f"(d[82]), "+f"(d[83]), "+f"(d[84]), "+f"(d[85]), "+f"(d[86]), "+f"(d[87]), "+f"(d[88]), "+f"(d[89]), "+f"(d[90]), "+f"(d[91]), "+f"(d[92]), "+f"(d[93]), "+f"(d[94]), "+f"(d[95]), "+f"(d[96]), "+f"(d[97]), "+f"(d[98]), "+f"(d[99]), "+f"(d[100]), "+f"(d[101]), "+f"(d[102]), "+f"(d[103]), "+f"(d[104]), "+f"(d[105]), "+f"(d[106]), "+f"(d[107]), "+f"(d[108]), "+f"(d[109]), "+f"(d[110]), "+f"(d[111])
        : "l"(da), "l"(db), "r"(scale_d));
}

__device__ __forceinline__ void wgmma_ss_n256_tb1(float (&d)[128], uint64_t da, uint64_t db, int scale_d) {
    asm volatile("{\n.reg .pred p;\nsetp.ne.b32 p, %130, 0;\n"
        "wgmma.mma_async.sync.aligned.m64n256k16.f32.bf16.bf16 {%0, %1, %2, %3, %4, %5, %6, %7, %8, %9, %10, %11, %12, %13, %14, %15, %16, %17, %18, %19, %20, %21, %22, %23, %24, %25, %26, %27, %28, %29, %30, %31, %32, %33, %34, %35, %36, %37, %38, %39, %40, %41, %42, %43, %44, %45, %46, %47, %48, %49, %50, %51, %52, %53, %54, %55, %56, %57, %58, %59, %60, %61, %62, %63, %64, %65, %66, %67, %68, %69, %70, %71, %72, %73, %74, %75, %76, %77, %78, %79, %80, %81, %82, %83, %84, %85, %86, %87, %88, %89, %90, %91, %92, %93, %94, %95, %96, %97, %98, %99, %100, %101, %102, %103, %104, %105, %106, %107, %108, %109, %110, %111, %112, %113, %114, %115, %116, %117, %118, %119, %120, %121, %122, %123, %124, %125, %126, %127}, %128, %129, p, 1, 1, 0, 1;\n}\n"
        : "+f"(d[0]), "+f"(d[1]), "+f"(d[2]), "+f"(d[3]), "+f"(d[4]), "+f"(d[5]), "+f"(d[6]), "+f"(d[7]), "+f"(d[8]), "+f"(d[9]), "+f"(d[10]), "+f"(d[11]), "+f"(d[12]), "+f"(d[13]), "+f"(d[14]), "+f"(d[15]), "+f"(d[16]), "+f"(d[17]), "+f"(d[18]), "+f"(d[19]), "+f"(d[20]), "+f"(d[21]), "+f"(d[22]), "+f"(d[23]), "+f"(d[24]), "+f"(d[25]), "+f"(d[26]), "+f"(d[27]), "+f"(d[28]), "+f"(d[29]), "+f"(d[30]), "+f"(d[31]), "+f"(d[32]), "+f"(d[33]), "+f"(d[34]), "+f"(d[35]), "+f"(d[36]), "+f"(d[37]), "+f"(d[38]), "+f"(d[39]), "+f"(d[40]), "+f"(d[41]), "+f"(d[42]), "+f"(d[43]), "+f"(d[44]), "+f"(d[45]), "+f"(d[46]), "+f"(d[47]), "+f"(d[48]), "+f"(d[49]), "+f"(d[50]), "+f"(d[51]), "+f"(d[52]), "+f"(d[53]), "+f"(d[54]), "+f"(d[55]), "+f"(d[56]), "+f"(d[57]), "+f"(d[58]), "+f"(d[59]), "+f"(d[60]), "+f"(d[61]), "+f"(d[62]), "+f"(d[63]), "+f"(d[64]), "+f"(d[65]), "+f"(d[66]), "+f"(d[67]), "+f"(d[68]), "+f"(d[69]), "+f"(d[70]), "+f"(d[71]), "+f"(d[72]), "+f"(d[73]), "+f"(d[74]), "+f"(d[75]), "+f"(d[76]), "+f"(d[77]), "+f"(d[78]), "+f"(d[79]), "+f"(d[80]), "+f"(d[81]), "+f"(d[82]), "+f"(d[83]), "+f"(d[84]), "+f"(d[85]), "+f"(d[86]), "+f"(d[87]), "+f"(d[88]), "+f"(d[89]), "+f"(d[90]), "+f"(d[91]), "+f"(d[92]), "+f"(d[93]), "+f"(d[94]), "+f"(d[95]), "+f"(d[96]), "+f"(d[97]), "+f"(d[98]), "+f"(d[99]), "+f"(d[100]), "+f"(d[101]), "+f"(d[102]), "+f"(d[103]), "+f"(d[104]), "+f"(d[105]), "+f"(d[106]), "+f"(d[107]), "+f"(d[108]), "+f"(d[109]), "+f"(d[110]), "+f"(d[111]), "+f"(d[112]), "+f"(d[113]), "+f"(d[114]), "+f"(d[115]), "+f"(d[116]), "+f"(d[117]), "+f"(d[118]), "+f"(d[119]), "+f"(d[120]), "+f"(d[121]), "+f"(d[122]), "+f"(d[123]), "+f"(d[124]), "+f"(d[125]), "+f"(d[126]), "+f"(d[127])
        : "l"(da), "l"(db), "r"(scale_d));
}

__device__ __forceinline__ void wgmma_rs_n128_tb0(float (&d)[64], uint32_t a0, uint32_t a1, uint32_t a2, uint32_t a3, uint64_t db, int scale_d) {
    asm volatile("{\n.reg .pred p;\nsetp.ne.b32 p, %69, 0;\n"
        "wgmma.mma_async.sync.aligned.m64n128k16.f32.bf16.bf16 {%0, %1, %2, %3, %4, %5, %6, %7, %8, %9, %10, %11, %12, %13, %14, %15, %16, %17, %18, %19, %20, %21, %22, %23, %24, %25, %26, %27, %28, %29, %30, %31, %32, %33, %34, %35, %36, %37, %38, %39, %40, %41, %42, %43, %44, %45, %46, %47, %48, %49, %50, %51, %52, %53, %54, %55, %56, %57, %58, %59, %60, %61, %62, %63}, {%64, %65, %66, %67}, %68, p, 1, 1, 0;\n}\n"
        : "+f"(d[0]), "+f"(d[1]), "+f"(d[2]), "+f"(d[3]), "+f"(d[4]), "+f"(d[5]), "+f"(d[6]), "+f"(d[7]), "+f"(d[8]), "+f"(d[9]), "+f"(d[10]), "+f"(d[11]), "+f"(d[12]), "+f"(d[13]), "+f"(d[14]), "+f"(d[15]), "+f"(d[16]), "+f"(d[17]), "+f"(d[18]), "+f"(d[19]), "+f"(d[20]), "+f"(d[21]), "+f"(d[22]), "+f"(d[23]), "+f"(d[24]), "+f"(d[25]), "+f"(d[26]), "+f"(d[27]), "+f"(d[28]), "+f"(d[29]), "+f"(d[30]), "+f"(d[31]), "+f"(d[32]), "+f"(d[33]), "+f"(d[34]), "+f"(d[35]), "+f"(d[36]), "+f"(d[37]), "+f"(d[38]), "+f"(d[39]), "+f"(d[40]), "+f"(d[41]), "+f"(d[42]), "+f"(d[43]), "+f"(d[44]), "+f"(d[45]), "+f"(d[46]), "+f"(d[47]), "+f"(d[48]), "+f"(d[49]), "+f"(d[50]), "+f"(d[51]), "+f"(d[52]), "+f"(d[53]), "+f"(d[54]), "+f"(d[55]), "+f"(d[56]), "+f"(d[57]), "+f"(d[58]), "+f"(d[59]), "+f"(d[60]), "+f"(d[61]), "+f"(d[62]), "+f"(d[63])
        : "r"(a0), "r"(a1), "r"(a2), "r"(a3), "l"(db), "r"(scale_d));
}

__device__ __forceinline__ void wgmma_rs_n64_tb0(float (&d)[32], uint32_t a0, uint32_t a1, uint32_t a2, uint32_t a3, uint64_t db, int scale_d) {
    asm volatile("{\n.reg .pred p;\nsetp.ne.b32 p, %37, 0;\n"
        "wgmma.mma_async.sync.aligned.m64n64k16.f32.bf16.bf16 {%0, %1, %2, %3, %4, %5, %6, %7, %8, %9, %10, %11, %12, %13, %14, %15, %16, %17, %18, %19, %20, %21, %22, %23, %24, %25, %26, %27, %28, %29, %30, %31}, {%32, %33, %34, %35}, %36, p, 1, 1, 0;\n}\n"
        : "+f"(d[0]), "+f"(d[1]), "+f"(d[2]), "+f"(d[3]), "+f"(d[4]), "+f"(d[5]), "+f"(d[6]), "+f"(d[7]), "+f"(d[8]), "+f"(d[9]), "+f"(d[10]), "+f"(d[11]), "+f"(d[12]), "+f"(d[13]), "+f"(d[14]), "+f"(d[15]), "+f"(d[16]), "+f"(d[17]), "+f"(d[18]), "+f"(d[19]), "+f"(d[20]), "+f"(d[21]), "+f"(d[22]), "+f"(d[23]), "+f"(d[24]), "+f"(d[25]), "+f"(d[26]), "+f"(d[27]), "+f"(d[28]), "+f"(d[29]), "+f"(d[30]), "+f"(d[31])
        : "r"(a0), "r"(a1), "r"(a2), "r"(a3), "l"(db), "r"(scale_d));
}

__device__ __forceinline__ void wgmma_rs_n32_tb1(float (&d)[16], uint32_t a0, uint32_t a1, uint32_t a2, uint32_t a3, uint64_t db, int scale_d) {
    asm volatile("{\n.reg .pred p;\nsetp.ne.b32 p, %21, 0;\n"
        "wgmma.mma_async.sync.aligned.m64n32k16.f32.bf16.bf16 {%0, %1, %2, %3, %4, %5, %6, %7, %8, %9, %10, %11, %12, %13, %14, %15}, {%16, %17, %18, %19}, %20, p, 1, 1, 1;\n}\n"
        : "+f"(d[0]), "+f"(d[1]), "+f"(d[2]), "+f"(d[3]), "+f"(d[4]), "+f"(d[5]), "+f"(d[6]), "+f"(d[7]), "+f"(d[8]), "+f"(d[9]), "+f"(d[10]), "+f"(d[11]), "+f"(d[12]), "+f"(d[13]), "+f"(d[14]), "+f"(d[15])
        : "r"(a0), "r"(a1), "r"(a2), "r"(a3), "l"(db), "r"(scale_d));
}

__device__ __forceinline__ void wgmma_rs_n40_tb1(float (&d)[20], uint32_t a0, uint32_t a1, uint32_t a2, uint32_t a3, uint64_t db, int scale_d) {
    asm volatile("{\n.reg .pred p;\nsetp.ne.b32 p, %25, 0;\n"
        "wgmma.mma_async.sync.aligned.m64n40k16.f32.bf16.bf16 {%0, %1, %2, %3, %4, %5, %6, %7, %8, %9, %10, %11, %12, %13, %14, %15, %16, %17, %18, %19}, {%20, %21, %22, %23}, %24, p, 1, 1, 1;\n}\n"
        : "+f"(d[0]), "+f"(d[1]), "+f"(d[2]), "+f"(d[3]), "+f"(d[4]), "+f"(d[5]), "+f"(d[6]), "+f"(d[7]), "+f"(d[8]), "+f"(d[9]), "+f"(d[10]), "+f"(d[11]), "+f"(d[12]), "+f"(d[13]), "+f"(d[14]), "+f"(d[15]), "+f"(d[16]), "+f"(d[17]), "+f"(d[18]), "+f"(d[19])
        : "r"(a0), "r"(a1), "r"(a2), "r"(a3), "l"(db), "r"(scale_d));
}


template <int BN>
__device__ __forceinline__ void wgmma_tile(float (&d)[BN / 2], uint64_t da, uint64_t db, int sd) {
    if constexpr (BN == 128) wgmma_ss_n128_tb1(d, da, db, sd);
    else if constexpr (BN == 192) wgmma_ss_n192_tb1(d, da, db, sd);
    else if constexpr (BN == 224) wgmma_ss_n224_tb1(d, da, db, sd);
    else wgmma_ss_n256_tb1(d, da, db, sd);
}

__global__ void __launch_bounds__(256) prep_kernel(const bf16* __restrict__ x, const bf16* __restrict__ gate_w,
                                                   const bf16* __restrict__ w1, const bf16* __restrict__ w3) {
    const int tid = threadIdx.x;
    if (blockIdx.x < 256) {
        const int row = blockIdx.x * 8 + (tid >> 5);
        const int lane = tid & 31;
        const uint4* xr = reinterpret_cast<const uint4*>(x + (size_t)row * DM);
        const uint4* gw = reinterpret_cast<const uint4*>(gate_w);
        float v[32];
        float gsum = 0.f, sum = 0.f;
#pragma unroll
        for (int i = 0; i < 4; i++) {
            uint4 a = xr[lane + 32 * i];
            uint4 b = gw[lane + 32 * i];
            const uint32_t aa[4] = {a.x, a.y, a.z, a.w};
            const uint32_t bb[4] = {b.x, b.y, b.z, b.w};
#pragma unroll
            for (int j = 0; j < 4; j++) {
                float x0 = __uint_as_float(aa[j] << 16), x1 = __uint_as_float(aa[j] & 0xFFFF0000u);
                float g0 = __uint_as_float(bb[j] << 16), g1 = __uint_as_float(bb[j] & 0xFFFF0000u);
                v[i * 8 + j * 2] = x0;
                v[i * 8 + j * 2 + 1] = x1;
                sum += x0 + x1;
                gsum += bf16_round(x0 * g0) + bf16_round(x1 * g1);
            }
        }
#pragma unroll
        for (int o = 16; o > 0; o >>= 1) {
            sum += __shfl_xor_sync(0xffffffffu, sum, o);
            gsum += __shfl_xor_sync(0xffffffffu, gsum, o);
        }
        const float mean = sum * (1.0f / DM);
        float m2 = 0.f;
#pragma unroll
        for (int i = 0; i < 32; i++) {
            float d = v[i] - mean;
            m2 += d * d;
        }
#pragma unroll
        for (int o = 16; o > 0; o >>= 1) m2 += __shfl_xor_sync(0xffffffffu, m2, o);
        if (lane == 0) {
            g_mean1[row] = mean;
            g_rstd1[row] = rsqrtf(m2 * (1.0f / DM) + 1e-5f);
            float logit = bf16_round(gsum);
            float g = bf16_round(1.0f / (1.0f + __expf(-logit)));
            g_gate[row] = g;
            g_omg[row] = bf16_round(1.0f - g);
        }
    } else {
        __shared__ float red[32][65];
        const int strip = blockIdx.x - 256;
        const bf16* w;
        float* out;
        int ld, col0;
        if (strip < 16) { w = w1; ld = DM; col0 = strip * 64; out = g_cs1; }
        else { w = w3; ld = FF; col0 = (strip - 16) * 64; out = g_cs3; }
        const int cg = tid & 7;
        const int rg = tid >> 3;
        float acc[8];
#pragma unroll
        for (int j = 0; j < 8; j++) acc[j] = 0.f;
#pragma unroll 8
        for (int r = 0; r < 32; r++) {
            uint4 a = *reinterpret_cast<const uint4*>(w + (size_t)(r * 32 + rg) * ld + col0 + cg * 8);
            const uint32_t aa[4] = {a.x, a.y, a.z, a.w};
#pragma unroll
            for (int j = 0; j < 4; j++) {
                acc[2 * j] += __uint_as_float(aa[j] << 16);
                acc[2 * j + 1] += __uint_as_float(aa[j] & 0xFFFF0000u);
            }
        }
#pragma unroll
        for (int j = 0; j < 8; j++) red[rg][cg * 8 + j] = acc[j];
        __syncthreads();
        if (tid < 64) {
            float s = 0.f;
#pragma unroll
            for (int r = 0; r < 32; r++) s += red[r][tid];
            out[col0 + tid] = s;
        }
    }
}

template <int BN, int STAGES>
struct GemmSmem {
    static constexpr int A_BYTES = 128 * 64 * 2;
    static constexpr int B_BOXES = (BN + 63) / 64;
    static constexpr int B_BYTES = B_BOXES * 64 * 64 * 2;
    static constexpr int STAGE_BYTES = A_BYTES + B_BYTES;
    static constexpr int STG_OFF = STAGES * STAGE_BYTES;
    static constexpr int BAR_OFF = STG_OFF + 2 * 16384;
    static constexpr int TOTAL = BAR_OFF + 256 + 1024;
};

template <int MODE, int BN, int STAGES>
__global__ void __launch_bounds__(384, 1)
gemm_kernel(const __grid_constant__ CUtensorMap mA, const __grid_constant__ CUtensorMap mB0,
            const __grid_constant__ CUtensorMap mB1, const __grid_constant__ CUtensorMap mC0,
            const __grid_constant__ CUtensorMap mC1, const bf16* __restrict__ xin, int n_tiles_n, int kblocks) {
    using L = GemmSmem<BN, STAGES>;
    extern __shared__ uint8_t smem_raw[];
    const uint32_t sbase = (smem_u32(smem_raw) + 1023u) & ~1023u;
    const uint32_t bar_full = sbase + L::BAR_OFF;
    const uint32_t bar_empty = bar_full + 8 * STAGES;
    const int wg = threadIdx.x >> 7;
    const int ntiles = 16 * n_tiles_n;

    if (threadIdx.x == 0) {
        for (int s = 0; s < STAGES; s++) {
            mbar_init(bar_full + 8 * s, 1);
            mbar_init(bar_empty + 8 * s, 2);
        }
        asm volatile("fence.mbarrier_init.release.cluster;" ::: "memory");
    }
    __syncthreads();

    if (wg == 0) {
        reg_dealloc<40>();
        if (threadIdx.x == 0) {
            prefetch_tmap(&mA);
            prefetch_tmap(&mB0);
            prefetch_tmap(&mB1);
            int stage = 0;
            uint32_t phase = 1;
            for (int tile = blockIdx.x; tile < ntiles; tile += gridDim.x) {
                const int m0 = (tile & 15) * 128;
                const int n0 = (tile >> 4) * BN;
                for (int kb = 0; kb < kblocks; kb++) {
                    mbar_wait(bar_empty + 8 * stage, phase);
                    const uint32_t sa = sbase + stage * L::STAGE_BYTES;
                    const uint32_t sb = sa + L::A_BYTES;
                    const uint32_t fb = bar_full + 8 * stage;
                    mbar_expect_tx(fb, L::STAGE_BYTES);
                    int arow = m0;
                    if (MODE == 2) {
                        const int grp = kb >> 2;
                        arow += (grp == 0) ? -1 : (grp == 1) ? 1 : (grp == 2) ? -2 : 2;
                    }
                    tma_load_2d(sa, &mA, kb * 64, arow, fb);
                    const CUtensorMap* mb = &mB0;
                    int bc = n0, br = kb * 64;
                    if (MODE == 1 && n0 >= 3 * DM) { mb = &mB1; bc = n0 - 3 * DM; }
                    if (MODE == 5 && kb >= 16) { mb = &mB1; br = (kb - 16) * 64; }
#pragma unroll
                    for (int b = 0; b < L::B_BOXES; b++) tma_load_2d(sb + b * 8192, mb, bc + b * 64, br, fb);
                    if (++stage == STAGES) { stage = 0; phase ^= 1; }
                }
            }
        }
    } else {
        reg_alloc<232>();
        const int c = wg - 1;
        const int warp = (threadIdx.x >> 5) & 3;
        const int lane = threadIdx.x & 31;
        const int tid_wg = threadIdx.x & 127;
        const uint32_t stg = sbase + L::STG_OFF + c * 16384;
        int stage = 0;
        uint32_t phase = 0;
        float acc[BN / 2];
        for (int tile = blockIdx.x; tile < ntiles; tile += gridDim.x) {
            const int m0 = (tile & 15) * 128;
            const int n0 = (tile >> 4) * BN;
            int prev_stage = 0;
            for (int kb = 0; kb < kblocks; kb++) {
                mbar_wait(bar_full + 8 * stage, phase);
                const uint32_t sa = sbase + stage * L::STAGE_BYTES + c * 8192;
                const uint32_t sb = sbase + stage * L::STAGE_BYTES + L::A_BYTES;
                const uint64_t da = make_desc(sa, 16, 1024, 1);
                const uint64_t db = make_desc(sb, 8192, 1024, 1);
                wgmma_fence();
#pragma unroll
                for (int k = 0; k < 4; k++) wgmma_tile<BN>(acc, da + k * 2, db + k * 128, (kb | k) != 0);
                wgmma_commit();
                if (kb > 0) {
                    wgmma_wait<1>();
                    if (tid_wg == 0) mbar_arrive(bar_empty + 8 * prev_stage);
                }
                prev_stage = stage;
                if (++stage == STAGES) { stage = 0; phase ^= 1; }
            }
            wgmma_wait<0>();
            if (tid_wg == 0) mbar_arrive(bar_empty + 8 * prev_stage);

            const int r0 = m0 + c * 64 + warp * 16 + (lane >> 2);
            const int r1 = r0 + 8;
            const int cq = (lane & 3) * 2;
            const CUtensorMap* mc = &mC0;
            int out_c0 = n0;
            if (MODE == 1) {
                if (n0 >= 3 * DM) {
                    mc = &mC1;
                    out_c0 = n0 - 3 * DM;
                    const float mu0 = g_mean1[r0], mu1 = g_mean1[r1];
                    const float rs0 = g_rstd1[r0], rs1 = g_rstd1[r1];
#pragma unroll
                    for (int j = 0; j < BN / 8; j++) {
                        const float2 cs = *reinterpret_cast<const float2*>(&g_cs1[out_c0 + 8 * j + cq]);
                        acc[4 * j + 0] = gelu_tanh(rs0 * fmaf(-mu0, cs.x, acc[4 * j + 0]));
                        acc[4 * j + 1] = gelu_tanh(rs0 * fmaf(-mu0, cs.y, acc[4 * j + 1]));
                        acc[4 * j + 2] = gelu_tanh(rs1 * fmaf(-mu1, cs.x, acc[4 * j + 2]));
                        acc[4 * j + 3] = gelu_tanh(rs1 * fmaf(-mu1, cs.y, acc[4 * j + 3]));
                    }
                }
            } else if (MODE == 2) {
                float s0 = 0.f, s1 = 0.f;
#pragma unroll
                for (int j = 0; j < BN / 8; j++) {
                    const uint32_t xa = *reinterpret_cast<const uint32_t*>(xin + (size_t)r0 * DM + n0 + 8 * j + cq);
                    const uint32_t xb = *reinterpret_cast<const uint32_t*>(xin + (size_t)r1 * DM + n0 + 8 * j + cq);
                    acc[4 * j + 0] = bf16_round(bf16_round(acc[4 * j + 0]) + __uint_as_float(xa << 16));
                    acc[4 * j + 1] = bf16_round(bf16_round(acc[4 * j + 1]) + __uint_as_float(xa & 0xFFFF0000u));
                    acc[4 * j + 2] = bf16_round(bf16_round(acc[4 * j + 2]) + __uint_as_float(xb << 16));
                    acc[4 * j + 3] = bf16_round(bf16_round(acc[4 * j + 3]) + __uint_as_float(xb & 0xFFFF0000u));
                    s0 += acc[4 * j + 0] + acc[4 * j + 1];
                    s1 += acc[4 * j + 2] + acc[4 * j + 3];
                }
                s0 += __shfl_xor_sync(0xffffffffu, s0, 1);
                s0 += __shfl_xor_sync(0xffffffffu, s0, 2);
                s1 += __shfl_xor_sync(0xffffffffu, s1, 1);
                s1 += __shfl_xor_sync(0xffffffffu, s1, 2);
                const float mu0 = s0 * (1.0f / BN), mu1 = s1 * (1.0f / BN);
                float q0 = 0.f, q1 = 0.f;
#pragma unroll
                for (int j = 0; j < BN / 8; j++) {
                    float d;
                    d = acc[4 * j + 0] - mu0; q0 += d * d;
                    d = acc[4 * j + 1] - mu0; q0 += d * d;
                    d = acc[4 * j + 2] - mu1; q1 += d * d;
                    d = acc[4 * j + 3] - mu1; q1 += d * d;
                }
                q0 += __shfl_xor_sync(0xffffffffu, q0, 1);
                q0 += __shfl_xor_sync(0xffffffffu, q0, 2);
                q1 += __shfl_xor_sync(0xffffffffu, q1, 1);
                q1 += __shfl_xor_sync(0xffffffffu, q1, 2);
                if ((lane & 3) == 0) {
                    static_assert(MODE != 2 || BN == 128, "stats layout assumes BN=128");
                    g_stat2[r0 * 8 + (n0 >> 7)] = make_float2(s0, q0);
                    g_stat2[r1 * 8 + (n0 >> 7)] = make_float2(s1, q1);
                }
            } else if (MODE == 3) {
                out_c0 = n0 + DM;
                float mu[2], rs[2];
#pragma unroll
                for (int h = 0; h < 2; h++) {
                    const float4* sp = reinterpret_cast<const float4*>(&g_stat2[(h ? r1 : r0) * 8]);
                    float4 p[4];
                    float s = 0.f;
#pragma unroll
                    for (int i = 0; i < 4; i++) { p[i] = sp[i]; s += p[i].x + p[i].z; }
                    const float mean = s * (1.0f / DM);
                    float m2 = 0.f;
#pragma unroll
                    for (int i = 0; i < 4; i++) {
                        float d0 = p[i].x * (1.0f / 128) - mean, d1 = p[i].z * (1.0f / 128) - mean;
                        m2 += p[i].y + p[i].w + 128.0f * (d0 * d0 + d1 * d1);
                    }
                    mu[h] = mean;
                    rs[h] = rsqrtf(m2 * (1.0f / DM) + 1e-5f);
                }
                const float og0 = g_omg[r0], og1 = g_omg[r1];
#pragma unroll
                for (int j = 0; j < BN / 8; j++) {
                    const float2 cs = *reinterpret_cast<const float2*>(&g_cs3[n0 + 8 * j + cq]);
                    acc[4 * j + 0] = og0 * gelu_tanh(rs[0] * fmaf(-mu[0], cs.x, acc[4 * j + 0]));
                    acc[4 * j + 1] = og0 * gelu_tanh(rs[0] * fmaf(-mu[0], cs.y, acc[4 * j + 1]));
                    acc[4 * j + 2] = og1 * gelu_tanh(rs[1] * fmaf(-mu[1], cs.x, acc[4 * j + 2]));
                    acc[4 * j + 3] = og1 * gelu_tanh(rs[1] * fmaf(-mu[1], cs.y, acc[4 * j + 3]));
                }
            } else {
                const float og0 = g_omg[r0], og1 = g_omg[r1];
#pragma unroll
                for (int j = 0; j < BN / 8; j++) {
                    const uint32_t xa = *reinterpret_cast<const uint32_t*>(xin + (size_t)r0 * DM + n0 + 8 * j + cq);
                    const uint32_t xb = *reinterpret_cast<const uint32_t*>(xin + (size_t)r1 * DM + n0 + 8 * j + cq);
                    acc[4 * j + 0] = fmaf(og0, __uint_as_float(xa << 16), acc[4 * j + 0]);
                    acc[4 * j + 1] = fmaf(og0, __uint_as_float(xa & 0xFFFF0000u), acc[4 * j + 1]);
                    acc[4 * j + 2] = fmaf(og1, __uint_as_float(xb << 16), acc[4 * j + 2]);
                    acc[4 * j + 3] = fmaf(og1, __uint_as_float(xb & 0xFFFF0000u), acc[4 * j + 3]);
                }
            }
            const int srow = warp * 16 + (lane & 7) + ((lane >> 3) & 1) * 8;
#pragma unroll
            for (int rnd = 0; rnd < (BN + 127) / 128; rnd++) {
                if (tid_wg == 0) bulk_wait_read0();
                named_bar_sync(1 + c, 128);
#pragma unroll
                for (int jj = 0; jj < 8; jj++) {
                    const int j = rnd * 16 + jj * 2;
                    if (j * 8 < BN) {
                        const int jb = jj * 2 + (lane >> 4);
                        const uint32_t addr = stg + (jb >> 3) * 8192 + srow * 128 + (((jb & 7) ^ (srow & 7)) << 4);
                        stmatrix_x4(addr, pack_bf16(acc[4 * j + 0], acc[4 * j + 1]), pack_bf16(acc[4 * j + 2], acc[4 * j + 3]),
                                    pack_bf16(acc[4 * j + 4], acc[4 * j + 5]), pack_bf16(acc[4 * j + 6], acc[4 * j + 7]));
                    }
                }
                fence_proxy_async();
                named_bar_sync(1 + c, 128);
                if (tid_wg == 0) {
                    tma_store_2d(mc, stg, out_c0 + rnd * 128, m0 + c * 64);
                    if (rnd * 128 + 64 < BN) tma_store_2d(mc, stg + 8192, out_c0 + rnd * 128 + 64, m0 + c * 64);
                    bulk_commit();
                }
            }
        }
        if (tid_wg == 0) bulk_wait0();
    }
}

constexpr int ATT_STAGES = 4;
constexpr int ATT_DIST = 2;
constexpr int ATT_SMEM = ATT_STAGES * 16384 + 256 + 1024;

struct AttState {
    float o[16];
    float m0, m1, l0, l1;
};

__device__ __forceinline__ void attn_step(float (&sc)[32], float (&sn)[32], uint32_t (&p)[16], const uint32_t (&qf)[8],
                                          AttState& st, uint64_t dk_next, uint64_t dv_prev, uint32_t release_bar) {
    const float cs = 0.17677669529663687f * 1.4426950408889634f;
    wgmma_fence();
    wgmma_rs_n64_tb0(sn, qf[0], qf[1], qf[2], qf[3], dk_next, 0);
    wgmma_rs_n64_tb0(sn, qf[4], qf[5], qf[6], qf[7], dk_next + 2, 1);
#pragma unroll
    for (int t = 0; t < 4; t++)
        wgmma_rs_n32_tb1(st.o, p[4 * t], p[4 * t + 1], p[4 * t + 2], p[4 * t + 3], dv_prev + t * 64, 1);
    wgmma_commit();
    float mx0 = fmaxf(sc[0], sc[1]), mx1 = fmaxf(sc[2], sc[3]);
#pragma unroll
    for (int i = 1; i < 8; i++) {
        mx0 = fmaxf(mx0, fmaxf(sc[4 * i], sc[4 * i + 1]));
        mx1 = fmaxf(mx1, fmaxf(sc[4 * i + 2], sc[4 * i + 3]));
    }
    mx0 = fmaxf(mx0, __shfl_xor_sync(0xffffffffu, mx0, 1));
    mx1 = fmaxf(mx1, __shfl_xor_sync(0xffffffffu, mx1, 1));
    mx0 = fmaxf(mx0, __shfl_xor_sync(0xffffffffu, mx0, 2));
    mx1 = fmaxf(mx1, __shfl_xor_sync(0xffffffffu, mx1, 2));
    const float mn0 = fmaxf(st.m0, mx0), mn1 = fmaxf(st.m1, mx1);
    const float a0 = ex2((st.m0 - mn0) * cs), a1 = ex2((st.m1 - mn1) * cs);
    st.m0 = mn0; st.m1 = mn1;
    const float b0 = mn0 * cs, b1 = mn1 * cs;
    float t0 = 0.f, t1 = 0.f;
#pragma unroll
    for (int i = 0; i < 8; i++) {
        sc[4 * i + 0] = ex2(fmaf(sc[4 * i + 0], cs, -b0));
        sc[4 * i + 1] = ex2(fmaf(sc[4 * i + 1], cs, -b0));
        sc[4 * i + 2] = ex2(fmaf(sc[4 * i + 2], cs, -b1));
        sc[4 * i + 3] = ex2(fmaf(sc[4 * i + 3], cs, -b1));
        t0 += sc[4 * i + 0] + sc[4 * i + 1];
        t1 += sc[4 * i + 2] + sc[4 * i + 3];
    }
    st.l0 = fmaf(st.l0, a0, t0);
    st.l1 = fmaf(st.l1, a1, t1);
    wgmma_wait<0>();
    if (release_bar != 0 && (threadIdx.x & 127) == 0) mbar_arrive(release_bar);
#pragma unroll
    for (int i = 0; i < 4; i++) {
        st.o[4 * i + 0] *= a0; st.o[4 * i + 1] *= a0;
        st.o[4 * i + 2] *= a1; st.o[4 * i + 3] *= a1;
    }
#pragma unroll
    for (int i = 0; i < 8; i++) {
        p[2 * i] = pack_bf16(sc[4 * i + 0], sc[4 * i + 1]);
        p[2 * i + 1] = pack_bf16(sc[4 * i + 2], sc[4 * i + 3]);
    }
}

__global__ void __launch_bounds__(256, 2)
attn_kernel(const __grid_constant__ CUtensorMap mKV) {
    extern __shared__ uint8_t smem_raw[];
    const uint32_t sbase = (smem_u32(smem_raw) + 1023u) & ~1023u;
    const uint32_t bar_kfull = sbase + ATT_STAGES * 16384;
    const uint32_t bar_vfull = bar_kfull + 8 * ATT_STAGES;
    const uint32_t bar_empty = bar_vfull + 8 * ATT_STAGES;
    const int head = blockIdx.x >> 4;
    const int q0 = (blockIdx.x & 15) * 128;
    const int warp_id = threadIdx.x >> 5;
    const int lane = threadIdx.x & 31;
    constexpr int NBLK = S_LEN / 128;

    if (threadIdx.x == 0) {
        for (int s = 0; s < ATT_STAGES; s++) {
            mbar_init(bar_kfull + 8 * s, 1);
            mbar_init(bar_vfull + 8 * s, 1);
            mbar_init(bar_empty + 8 * s, 2);
        }
        asm volatile("fence.mbarrier_init.release.cluster;" ::: "memory");
        prefetch_tmap(&mKV);
#pragma unroll
        for (int j = 0; j < ATT_DIST; j++) {
            const uint32_t sk = sbase + j * 16384;
            mbar_expect_tx(bar_kfull + 8 * j, 8192);
            tma_load_2d(sk, &mKV, DM + head * DH, j * 128, bar_kfull + 8 * j);
            mbar_expect_tx(bar_vfull + 8 * j, 8192);
            tma_load_2d(sk + 8192, &mKV, 2 * DM + head * DH, j * 128, bar_vfull + 8 * j);
        }
    }
    __syncthreads();

    const int row0 = q0 + warp_id * 16 + (lane >> 2);
    const int cq = (lane & 3) * 2;
    uint32_t qf[8];
    {
        const bf16* qp0 = g_qkv + (size_t)row0 * (3 * DM) + head * DH + cq;
        const bf16* qp1 = qp0 + 8 * (3 * DM);
#pragma unroll
        for (int t = 0; t < 2; t++) {
            qf[4 * t + 0] = *reinterpret_cast<const uint32_t*>(qp0 + 16 * t);
            qf[4 * t + 1] = *reinterpret_cast<const uint32_t*>(qp1 + 16 * t);
            qf[4 * t + 2] = *reinterpret_cast<const uint32_t*>(qp0 + 16 * t + 8);
            qf[4 * t + 3] = *reinterpret_cast<const uint32_t*>(qp1 + 16 * t + 8);
        }
    }
    AttState st;
#pragma unroll
    for (int i = 0; i < 16; i++) st.o[i] = 0.f;
    st.m0 = -INFINITY; st.m1 = -INFINITY; st.l0 = 0.f; st.l1 = 0.f;
    float s0[32], s1[32];
    const uint64_t desc0 = make_desc(sbase, 16, 512, 2);
    uint32_t p[16];
#pragma unroll
    for (int i = 0; i < 16; i++) p[i] = 0u;
    mbar_wait(bar_kfull, 0);
    wgmma_fence();
    wgmma_rs_n64_tb0(s0, qf[0], qf[1], qf[2], qf[3], desc0, 0);
    wgmma_rs_n64_tb0(s0, qf[4], qf[5], qf[6], qf[7], desc0 + 2, 1);
    wgmma_commit();
    mbar_wait(bar_vfull, 0);
    wgmma_wait<0>();
    int stage = 0;
    uint32_t phase = 0;
    uint64_t dv_prev = desc0 + 512;
#pragma unroll 1
    for (int j = 0; j < NBLK; j++) {
        if (threadIdx.x == 0 && j + ATT_DIST < NBLK) {
            const int jn = j + ATT_DIST;
            const int sn = jn % ATT_STAGES;
            if (jn >= ATT_STAGES) mbar_wait(bar_empty + 8 * sn, ((jn / ATT_STAGES) - 1) & 1);
            const uint32_t skn = sbase + sn * 16384;
            mbar_expect_tx(bar_kfull + 8 * sn, 8192);
            tma_load_2d(skn, &mKV, DM + head * DH, jn * 128, bar_kfull + 8 * sn);
            mbar_expect_tx(bar_vfull + 8 * sn, 8192);
            tma_load_2d(skn + 8192, &mKV, 2 * DM + head * DH, jn * 128, bar_vfull + 8 * sn);
        }
        __syncwarp();
        const uint64_t dk = desc0 + (uint64_t)(stage * 1024);
        const int pstage = (stage + ATT_STAGES - 1) % ATT_STAGES;
        attn_step(s0, s1, p, qf, st, dk + 256, dv_prev, j > 0 ? bar_empty + 8 * pstage : 0u);
        int nstage = stage + 1;
        uint32_t nphase = phase;
        if (nstage == ATT_STAGES) { nstage = 0; nphase ^= 1; }
        uint64_t dkn = dk;
        if (j + 1 < NBLK) {
            mbar_wait(bar_kfull + 8 * nstage, nphase);
            dkn = desc0 + (uint64_t)(nstage * 1024);
        }
        mbar_wait(bar_vfull + 8 * stage, phase);
        attn_step(s1, s0, p, qf, st, dkn, dk + 512, 0u);
        dv_prev = dk + 512 + 256;
        stage = nstage;
        phase = nphase;
    }
    wgmma_fence();
#pragma unroll
    for (int t = 0; t < 4; t++)
        wgmma_rs_n32_tb1(st.o, p[4 * t], p[4 * t + 1], p[4 * t + 2], p[4 * t + 3], dv_prev + t * 64, 1);
    wgmma_commit();
    wgmma_wait<0>();
    float l0 = st.l0, l1 = st.l1;
    l0 += __shfl_xor_sync(0xffffffffu, l0, 1);
    l0 += __shfl_xor_sync(0xffffffffu, l0, 2);
    l1 += __shfl_xor_sync(0xffffffffu, l1, 1);
    l1 += __shfl_xor_sync(0xffffffffu, l1, 2);
    const float f0 = g_gate[row0] / l0, f1 = g_gate[row0 + 8] / l1;
    bf16* op0 = g_a5 + (size_t)row0 * A5W + head * DH + cq;
    bf16* op1 = op0 + 8 * A5W;
#pragma unroll
    for (int i = 0; i < 4; i++) {
        *reinterpret_cast<uint32_t*>(op0 + 8 * i) = pack_bf16(st.o[4 * i] * f0, st.o[4 * i + 1] * f0);
        *reinterpret_cast<uint32_t*>(op1 + 8 * i) = pack_bf16(st.o[4 * i + 2] * f1, st.o[4 * i + 3] * f1);
    }
}

typedef CUresult (*EncodeFn)(CUtensorMap*, CUtensorMapDataType, cuuint32_t, void*, const cuuint64_t*, const cuuint64_t*,
                             const cuuint32_t*, const cuuint32_t*, CUtensorMapInterleave, CUtensorMapSwizzle,
                             CUtensorMapL2promotion, CUtensorMapFloatOOBfill);

static CUtensorMap make_map(EncodeFn fn, const void* ptr, int rows, int cols, int box_cols, int box_rows,
                            CUtensorMapSwizzle swz) {
    CUtensorMap m;
    cuuint64_t dims[2] = {(cuuint64_t)cols, (cuuint64_t)rows};
    cuuint64_t strides[1] = {(cuuint64_t)cols * 2};
    cuuint32_t box[2] = {(cuuint32_t)box_cols, (cuuint32_t)box_rows};
    cuuint32_t es[2] = {1, 1};
    fn(&m, CU_TENSOR_MAP_DATA_TYPE_BFLOAT16, 2, const_cast<void*>(ptr), dims, strides, box, es,
       CU_TENSOR_MAP_INTERLEAVE_NONE, swz, CU_TENSOR_MAP_L2_PROMOTION_L2_256B, CU_TENSOR_MAP_FLOAT_OOB_FILL_NONE);
    return m;
}

extern "C" void kernel_launch(void* const* d_in, const int* in_sizes, int n_in, void* d_out, int out_size) {
    const bf16* x = (const bf16*)d_in[0];
    const bf16* wqkv = (const bf16*)d_in[1];
    const bf16* wo = (const bf16*)d_in[2];
    const bf16* w1 = (const bf16*)d_in[4];
    const bf16* w2 = (const bf16*)d_in[5];
    const bf16* w3 = (const bf16*)d_in[6];
    const bf16* w4 = (const bf16*)d_in[7];
    const bf16* gate_w = (const bf16*)d_in[8];

    static EncodeFn enc = nullptr;
    static void *p_qkv, *p_h, *p_x1, *p_a5;
    if (!enc) {
        void* fn = nullptr;
        cudaDriverEntryPointQueryResult qres;
        cudaGetDriverEntryPoint("cuTensorMapEncodeTiled", &fn, cudaEnableDefault, &qres);
        enc = (EncodeFn)fn;
        cudaGetSymbolAddress(&p_qkv, g_qkv);
        cudaGetSymbolAddress(&p_h, g_h);
        cudaGetSymbolAddress(&p_x1, g_x1);
        cudaGetSymbolAddress(&p_a5, g_a5);
        cudaFuncSetAttribute(gemm_kernel<1, 256, 4>, cudaFuncAttributeMaxDynamicSharedMemorySize, GemmSmem<256, 4>::TOTAL);
        cudaFuncSetAttribute(gemm_kernel<2, 128, 5>, cudaFuncAttributeMaxDynamicSharedMemorySize, GemmSmem<128, 5>::TOTAL);
        cudaFuncSetAttribute(gemm_kernel<3, 256, 4>, cudaFuncAttributeMaxDynamicSharedMemorySize, GemmSmem<256, 4>::TOTAL);
        cudaFuncSetAttribute(gemm_kernel<5, 128, 5>, cudaFuncAttributeMaxDynamicSharedMemorySize, GemmSmem<128, 5>::TOTAL);
        cudaFuncSetAttribute(attn_kernel, cudaFuncAttributeMaxDynamicSharedMemorySize, ATT_SMEM);
    }
    const CUtensorMapSwizzle SW128 = CU_TENSOR_MAP_SWIZZLE_128B, SW64 = CU_TENSOR_MAP_SWIZZLE_64B;
    CUtensorMap mX = make_map(enc, x, S_LEN, DM, 64, 128, SW128);
    CUtensorMap mWqkv = make_map(enc, wqkv, DM, 3 * DM, 64, 64, SW128);
    CUtensorMap mW1 = make_map(enc, w1, DM, DM, 64, 64, SW128);
    CUtensorMap mW2 = make_map(enc, w2, DM, DM, 64, 64, SW128);
    CUtensorMap mW3 = make_map(enc, w3, DM, FF, 64, 64, SW128);
    CUtensorMap mW4 = make_map(enc, w4, FF, DM, 64, 64, SW128);
    CUtensorMap mWo = make_map(enc, wo, DM, DM, 64, 64, SW128);
    CUtensorMap mQKVst = make_map(enc, p_qkv, S_LEN, 3 * DM, 64, 64, SW128);
    CUtensorMap mKV = make_map(enc, p_qkv, S_LEN, 3 * DM, 32, 128, SW64);
    CUtensorMap mHst = make_map(enc, p_h, S_LEN, DM, 64, 64, SW128);
    CUtensorMap mHld = make_map(enc, p_h, S_LEN, DM, 64, 128, SW128);
    CUtensorMap mX1st = make_map(enc, p_x1, S_LEN, DM, 64, 64, SW128);
    CUtensorMap mX1ld = make_map(enc, p_x1, S_LEN, DM, 64, 128, SW128);
    CUtensorMap mA5st = make_map(enc, p_a5, S_LEN, A5W, 64, 64, SW128);
    CUtensorMap mA5ld = make_map(enc, p_a5, S_LEN, A5W, 64, 128, SW128);
    CUtensorMap mOut = make_map(enc, d_out, S_LEN, DM, 64, 64, SW128);

    cudaStream_t st = cudaStreamPerThread;
    prep_kernel<<<256 + 72, 256, 0, st>>>(x, gate_w, w1, w3);
    gemm_kernel<1, 256, 4><<<132, 384, GemmSmem<256, 4>::TOTAL, st>>>(mX, mWqkv, mW1, mQKVst, mHst, x, 16, 16);
    attn_kernel<<<NH * 16, 256, ATT_SMEM, st>>>(mKV);
    gemm_kernel<2, 128, 5><<<128, 384, GemmSmem<128, 5>::TOTAL, st>>>(mHld, mW2, mW2, mX1st, mX1st, x, 8, 16);
    gemm_kernel<3, 256, 4><<<132, 384, GemmSmem<256, 4>::TOTAL, st>>>(mX1ld, mW3, mW3, mA5st, mA5st, x, 14, 16);
    gemm_kernel<5, 128, 5><<<128, 384, GemmSmem<128, 5>::TOTAL, st>>>(mA5ld, mWo, mW4, mOut, mOut, (const bf16*)p_x1, 8, 72);
}
```

```cpp
#include <cuda_runtime.h>
#include <cuda_bf16.h>
#include <cuda.h>
#include <stdint.h>

typedef __nv_bfloat16 bf16;

constexpr int S_LEN = 2048;
constexpr int DM = 1024;
constexpr int FF = 3584;
constexpr int NH = 32;
constexpr int DH = 32;
constexpr int A5W = DM + FF;

__device__ __align__(1024) bf16 g_qkv[S_LEN * 3 * DM];
__device__ __align__(1024) bf16 g_h[S_LEN * DM];
__device__ __align__(1024) bf16 g_x1[S_LEN * DM];
__device__ __align__(1024) bf16 g_a5[S_LEN * A5W];
__device__ __align__(16) float g_mean1[S_LEN];
__device__ __align__(16) float g_rstd1[S_LEN];
__device__ __align__(16) float g_gate[S_LEN];
__device__ __align__(16) float g_omg[S_LEN];
__device__ __align__(16) float g_cs1[DM];
__device__ __align__(16) float g_cs3[FF];
__device__ __align__(16) float2 g_stat2[S_LEN * 8];

__device__ __forceinline__ uint32_t smem_u32(const void* p) { return (uint32_t)__cvta_generic_to_shared(p); }

__device__ __forceinline__ void mbar_init(uint32_t bar, uint32_t count) {
    asm volatile("mbarrier.init.shared::cta.b64 [%0], %1;" ::"r"(bar), "r"(count));
}
__device__ __forceinline__ void mbar_expect_tx(uint32_t bar, uint32_t bytes) {
    asm volatile("mbarrier.arrive.expect_tx.shared::cta.b64 _, [%0], %1;" ::"r"(bar), "r"(bytes) : "memory");
}
__device__ __forceinline__ void mbar_arrive(uint32_t bar) {
    asm volatile("mbarrier.arrive.shared::cta.b64 _, [%0];" ::"r"(bar) : "memory");
}
__device__ __forceinline__ bool mbar_try_wait(uint32_t bar, uint32_t parity) {
    uint32_t ok;
    asm volatile(
        "{\n.reg .pred p;\n"
        "mbarrier.try_wait.parity.shared::cta.b64 p, [%1], %2;\n"
        "selp.u32 %0, 1, 0, p;\n}\n"
        : "=r"(ok)
        : "r"(bar), "r"(parity)
        : "memory");
    return ok != 0;
}
__device__ __forceinline__ void mbar_wait(uint32_t bar, uint32_t parity) {
    uint32_t spins = 0;
    while (!mbar_try_wait(bar, parity)) {
        if (++spins > (1u << 24)) __trap();
    }
}
__device__ __forceinline__ void tma_load_2d(uint32_t dst, const CUtensorMap* map, int c0, int c1, uint32_t bar) {
    asm volatile(
        "cp.async.bulk.tensor.2d.shared::cluster.global.mbarrier::complete_tx::bytes [%0], [%1, {%3, %4}], [%2];"
        ::"r"(dst), "l"(map), "r"(bar), "r"(c0), "r"(c1)
        : "memory");
}
__device__ __forceinline__ void tma_store_2d(const CUtensorMap* map, uint32_t src, int c0, int c1) {
    asm volatile("cp.async.bulk.tensor.2d.global.shared::cta.bulk_group [%0, {%2, %3}], [%1];"
                 ::"l"(map), "r"(src), "r"(c0), "r"(c1)
                 : "memory");
}
__device__ __forceinline__ void bulk_commit() { asm volatile("cp.async.bulk.commit_group;" ::: "memory"); }
__device__ __forceinline__ void bulk_wait_read0() { asm volatile("cp.async.bulk.wait_group.read 0;" ::: "memory"); }
__device__ __forceinline__ void bulk_wait0() { asm volatile("cp.async.bulk.wait_group 0;" ::: "memory"); }
__device__ __forceinline__ void fence_proxy_async() { asm volatile("fence.proxy.async.shared::cta;" ::: "memory"); }
__device__ __forceinline__ void named_bar_sync(int id, int n) { asm volatile("bar.sync %0, %1;" ::"r"(id), "r"(n) : "memory"); }
__device__ __forceinline__ void named_bar_arrive(int id, int n) { asm volatile("bar.arrive %0, %1;" ::"r"(id), "r"(n) : "memory"); }
__device__ __forceinline__ void wgmma_fence() { asm volatile("wgmma.fence.sync.aligned;" ::: "memory"); }
__device__ __forceinline__ void wgmma_commit() { asm volatile("wgmma.commit_group.sync.aligned;" ::: "memory"); }
template <int N>
__device__ __forceinline__ void wgmma_wait() { asm volatile("wgmma.wait_group.sync.aligned %0;" ::"n"(N) : "memory"); }
__device__ __forceinline__ void prefetch_tmap(const CUtensorMap* m) {
    asm volatile("prefetch.tensormap [%0];" ::"l"(m) : "memory");
}
template <int R>
__device__ __forceinline__ void reg_alloc() { asm volatile("setmaxnreg.inc.sync.aligned.u32 %0;" ::"n"(R)); }
template <int R>
__device__ __forceinline__ void reg_dealloc() { asm volatile("setmaxnreg.dec.sync.aligned.u32 %0;" ::"n"(R)); }
__device__ __forceinline__ void stmatrix_x4(uint32_t addr, uint32_t r0, uint32_t r1, uint32_t r2, uint32_t r3) {
    asm volatile("stmatrix.sync.aligned.m8n8.x4.shared.b16 [%0], {%1, %2, %3, %4};"
                 ::"r"(addr), "r"(r0), "r"(r1), "r"(r2), "r"(r3)
                 : "memory");
}
__device__ __forceinline__ uint32_t pack_bf16(float lo, float hi) {
    uint32_t r;
    asm("cvt.rn.bf16x2.f32 %0, %1, %2;" : "=r"(r) : "f"(hi), "f"(lo));
    return r;
}
__device__ __forceinline__ float bf16_round(float v) { return __bfloat162float(__float2bfloat16_rn(v)); }
__device__ __forceinline__ float ex2(float x) {
    float y;
    asm("ex2.approx.ftz.f32 %0, %1;" : "=f"(y) : "f"(x));
    return y;
}
__device__ __forceinline__ float tanh_fast(float x) {
    float y;
    asm("tanh.approx.f32 %0, %1;" : "=f"(y) : "f"(x));
    return y;
}
__device__ __forceinline__ float gelu_tanh(float v) {
    float u = 0.7978845608028654f * (v + 0.044715f * v * v * v);
    float hv = 0.5f * v;
    return fmaf(hv, tanh_fast(u), hv);
}
__device__ __forceinline__ uint64_t make_desc(uint32_t addr, uint32_t lbo_bytes, uint32_t sbo_bytes, uint32_t swz) {
    uint64_t d = 0;
    d |= (uint64_t)((addr & 0x3FFFF) >> 4);
    d |= (uint64_t)((lbo_bytes >> 4) & 0x3FFF) << 16;
    d |= (uint64_t)((sbo_bytes >> 4) & 0x3FFF) << 32;
    d |= (uint64_t)swz << 62;
    return d;
}


__device__ __forceinline__ void wgmma_ss_n128_tb1(float (&d)[64], uint64_t da, uint64_t db, int scale_d) {
    asm volatile("{\n.reg .pred p;\nsetp.ne.b32 p, %66, 0;\n"
        "wgmma.mma_async.sync.aligned.m64n128k16.f32.bf16.bf16 {%0, %1, %2, %3, %4, %5, %6, %7, %8, %9, %10, %11, %12, %13, %14, %15, %16, %17, %18, %19, %20, %21, %22, %23, %24, %25, %26, %27, %28, %29, %30, %31, %32, %33, %34, %35, %36, %37, %38, %39, %40, %41, %42, %43, %44, %45, %46, %47, %48, %49, %50, %51, %52, %53, %54, %55, %56, %57, %58, %59, %60, %61, %62, %63}, %64, %65, p, 1, 1, 0, 1;\n}\n"
        : "+f"(d[0]), "+f"(d[1]), "+f"(d[2]), "+f"(d[3]), "+f"(d[4]), "+f"(d[5]), "+f"(d[6]), "+f"(d[7]), "+f"(d[8]), "+f"(d[9]), "+f"(d[10]), "+f"(d[11]), "+f"(d[12]), "+f"(d[13]), "+f"(d[14]), "+f"(d[15]), "+f"(d[16]), "+f"(d[17]), "+f"(d[18]), "+f"(d[19]), "+f"(d[20]), "+f"(d[21]), "+f"(d[22]), "+f"(d[23]), "+f"(d[24]), "+f"(d[25]), "+f"(d[26]), "+f"(d[27]), "+f"(d[28]), "+f"(d[29]), "+f"(d[30]), "+f"(d[31]), "+f"(d[32]), "+f"(d[33]), "+f"(d[34]), "+f"(d[35]), "+f"(d[36]), "+f"(d[37]), "+f"(d[38]), "+f"(d[39]), "+f"(d[40]), "+f"(d[41]), "+f"(d[42]), "+f"(d[43]), "+f"(d[44]), "+f"(d[45]), "+f"(d[46]), "+f"(d[47]), "+f"(d[48]), "+f"(d[49]), "+f"(d[50]), "+f"(d[51]), "+f"(d[52]), "+f"(d[53]), "+f"(d[54]), "+f"(d[55]), "+f"(d[56]), "+f"(d[57]), "+f"(d[58]), "+f"(d[59]), "+f"(d[60]), "+f"(d[61]), "+f"(d[62]), "+f"(d[63])
        : "l"(da), "l"(db), "r"(scale_d));
}

__device__ __forceinline__ void wgmma_ss_n192_tb1(float (&d)[96], uint64_t da, uint64_t db, int scale_d) {
    asm volatile("{\n.reg .pred p;\nsetp.ne.b32 p, %98, 0;\n"
        "wgmma.mma_async.sync.aligned.m64n192k16.f32.bf16.bf16 {%0, %1, %2, %3, %4, %5, %6, %7, %8, %9, %10, %11, %12, %13, %14, %15, %16, %17, %18, %19, %20, %21, %22, %23, %24, %25, %26, %27, %28, %29, %30, %31, %32, %33, %34, %35, %36, %37, %38, %39, %40, %41, %42, %43, %44, %45, %46, %47, %48, %49, %50, %51, %52, %53, %54, %55, %56, %57, %58, %59, %60, %61, %62, %63, %64, %65, %66, %67, %68, %69, %70, %71, %72, %73, %74, %75, %76, %77, %78, %79, %80, %81, %82, %83, %84, %85, %86, %87, %88, %89, %90, %91, %92, %93, %94, %95}, %96, %97, p, 1, 1, 0, 1;\n}\n"
        : "+f"(d[0]), "+f"(d[1]), "+f"(d[2]), "+f"(d[3]), "+f"(d[4]), "+f"(d[5]), "+f"(d[6]), "+f"(d[7]), "+f"(d[8]), "+f"(d[9]), "+f"(d[10]), "+f"(d[11]), "+f"(d[12]), "+f"(d[13]), "+f"(d[14]), "+f"(d[15]), "+f"(d[16]), "+f"(d[17]), "+f"(d[18]), "+f"(d[19]), "+f"(d[20]), "+f"(d[21]), "+f"(d[22]), "+f"(d[23]), "+f"(d[24]), "+f"(d[25]), "+f"(d[26]), "+f"(d[27]), "+f"(d[28]), "+f"(d[29]), "+f"(d[30]), "+f"(d[31]), "+f"(d[32]), "+f"(d[33]), "+f"(d[34]), "+f"(d[35]), "+f"(d[36]), "+f"(d[37]), "+f"(d[38]), "+f"(d[39]), "+f"(d[40]), "+f"(d[41]), "+f"(d[42]), "+f"(d[43]), "+f"(d[44]), "+f"(d[45]), "+f"(d[46]), "+f"(d[47]), "+f"(d[48]), "+f"(d[49]), "+f"(d[50]), "+f"(d[51]), "+f"(d[52]), "+f"(d[53]), "+f"(d[54]), "+f"(d[55]), "+f"(d[56]), "+f"(d[57]), "+f"(d[58]), "+f"(d[59]), "+f"(d[60]), "+f"(d[61]), "+f"(d[62]), "+f"(d[63]), "+f"(d[64]), "+f"(d[65]), "+f"(d[66]), "+f"(d[67]), "+f"(d[68]), "+f"(d[69]), "+f"(d[70]), "+f"(d[71]), "+f"(d[72]), "+f"(d[73]), "+f"(d[74]), "+f"(d[75]), "+f"(d[76]), "+f"(d[77]), "+f"(d[78]), "+f"(d[79]), "+f"(d[80]), "+f"(d[81]), "+f"(d[82]), "+f"(d[83]), "+f"(d[84]), "+f"(d[85]), "+f"(d[86]), "+f"(d[87]), "+f"(d[88]), "+f"(d[89]), "+f"(d[90]), "+f"(d[91]), "+f"(d[92]), "+f"(d[93]), "+f"(d[94]), "+f"(d[95])
        : "l"(da), "l"(db), "r"(scale_d));
}

__device__ __forceinline__ void wgmma_ss_n224_tb1(float (&d)[112], uint64_t da, uint64_t db, int scale_d) {
    asm volatile("{\n.reg .pred p;\nsetp.ne.b32 p, %114, 0;\n"
        "wgmma.mma_async.sync.aligned.m64n224k16.f32.bf16.bf16 {%0, %1, %2, %3, %4, %5, %6, %7, %8, %9, %10, %11, %12, %13, %14, %15, %16, %17, %18, %19, %20, %21, %22, %23, %24, %25, %26, %27, %28, %29, %30, %31, %32, %33, %34, %35, %36, %37, %38, %39, %40, %41, %42, %43, %44, %45, %46, %47, %48, %49, %50, %51, %52, %53, %54, %55, %56, %57, %58, %59, %60, %61, %62, %63, %64, %65, %66, %67, %68, %69, %70, %71, %72, %73, %74, %75, %76, %77, %78, %79, %80, %81, %82, %83, %84, %85, %86, %87, %88, %89, %90, %91, %92, %93, %94, %95, %96, %97, %98, %99, %100, %101, %102, %103, %104, %105, %106, %107, %108, %109, %110, %111}, %112, %113, p, 1, 1, 0, 1;\n}\n"
        : "+f"(d[0]), "+f"(d[1]), "+f"(d[2]), "+f"(d[3]), "+f"(d[4]), "+f"(d[5]), "+f"(d[6]), "+f"(d[7]), "+f"(d[8]), "+f"(d[9]), "+f"(d[10]), "+f"(d[11]), "+f"(d[12]), "+f"(d[13]), "+f"(d[14]), "+f"(d[15]), "+f"(d[16]), "+f"(d[17]), "+f"(d[18]), "+f"(d[19]), "+f"(d[20]), "+f"(d[21]), "+f"(d[22]), "+f"(d[23]), "+f"(d[24]), "+f"(d[25]), "+f"(d[26]), "+f"(d[27]), "+f"(d[28]), "+f"(d[29]), "+f"(d[30]), "+f"(d[31]), "+f"(d[32]), "+f"(d[33]), "+f"(d[34]), "+f"(d[35]), "+f"(d[36]), "+f"(d[37]), "+f"(d[38]), "+f"(d[39]), "+f"(d[40]), "+f"(d[41]), "+f"(d[42]), "+f"(d[43]), "+f"(d[44]), "+f"(d[45]), "+f"(d[46]), "+f"(d[47]), "+f"(d[48]), "+f"(d[49]), "+f"(d[50]), "+f"(d[51]), "+f"(d[52]), "+f"(d[53]), "+f"(d[54]), "+f"(d[55]), "+f"(d[56]), "+f"(d[57]), "+f"(d[58]), "+f"(d[59]), "+f"(d[60]), "+f"(d[61]), "+f"(d[62]), "+f"(d[63]), "+f"(d[64]), "+f"(d[65]), "+f"(d[66]), "+f"(d[67]), "+f"(d[68]), "+f"(d[69]), "+f"(d[70]), "+f"(d[71]), "+f"(d[72]), "+f"(d[73]), "+f"(d[74]), "+f"(d[75]), "+f"(d[76]), "+f"(d[77]), "+f"(d[78]), "+f"(d[79]), "+f"(d[80]), "+f"(d[81]), "+f"(d[82]), "+f"(d[83]), "+f"(d[84]), "+f"(d[85]), "+f"(d[86]), "+f"(d[87]), "+f"(d[88]), "+f"(d[89]), "+f"(d[90]), "+f"(d[91]), "+f"(d[92]), "+f"(d[93]), "+f"(d[94]), "+f"(d[95]), "+f"(d[96]), "+f"(d[97]), "+f"(d[98]), "+f"(d[99]), "+f"(d[100]), "+f"(d[101]), "+f"(d[102]), "+f"(d[103]), "+f"(d[104]), "+f"(d[105]), "+f"(d[106]), "+f"(d[107]), "+f"(d[108]), "+f"(d[109]), "+f"(d[110]), "+f"(d[111])
        : "l"(da), "l"(db), "r"(scale_d));
}

__device__ __forceinline__ void wgmma_ss_n256_tb1(float (&d)[128], uint64_t da, uint64_t db, int scale_d) {
    asm volatile("{\n.reg .pred p;\nsetp.ne.b32 p, %130, 0;\n"
        "wgmma.mma_async.sync.aligned.m64n256k16.f32.bf16.bf16 {%0, %1, %2, %3, %4, %5, %6, %7, %8, %9, %10, %11, %12, %13, %14, %15, %16, %17, %18, %19, %20, %21, %22, %23, %24, %25, %26, %27, %28, %29, %30, %31, %32, %33, %34, %35, %36, %37, %38, %39, %40, %41, %42, %43, %44, %45, %46, %47, %48, %49, %50, %51, %52, %53, %54, %55, %56, %57, %58, %59, %60, %61, %62, %63, %64, %65, %66, %67, %68, %69, %70, %71, %72, %73, %74, %75, %76, %77, %78, %79, %80, %81, %82, %83, %84, %85, %86, %87, %88, %89, %90, %91, %92, %93, %94, %95, %96, %97, %98, %99, %100, %101, %102, %103, %104, %105, %106, %107, %108, %109, %110, %111, %112, %113, %114, %115, %116, %117, %118, %119, %120, %121, %122, %123, %124, %125, %126, %127}, %128, %129, p, 1, 1, 0, 1;\n}\n"
        : "+f"(d[0]), "+f"(d[1]), "+f"(d[2]), "+f"(d[3]), "+f"(d[4]), "+f"(d[5]), "+f"(d[6]), "+f"(d[7]), "+f"(d[8]), "+f"(d[9]), "+f"(d[10]), "+f"(d[11]), "+f"(d[12]), "+f"(d[13]), "+f"(d[14]), "+f"(d[15]), "+f"(d[16]), "+f"(d[17]), "+f"(d[18]), "+f"(d[19]), "+f"(d[20]), "+f"(d[21]), "+f"(d[22]), "+f"(d[23]), "+f"(d[24]), "+f"(d[25]), "+f"(d[26]), "+f"(d[27]), "+f"(d[28]), "+f"(d[29]), "+f"(d[30]), "+f"(d[31]), "+f"(d[32]), "+f"(d[33]), "+f"(d[34]), "+f"(d[35]), "+f"(d[36]), "+f"(d[37]), "+f"(d[38]), "+f"(d[39]), "+f"(d[40]), "+f"(d[41]), "+f"(d[42]), "+f"(d[43]), "+f"(d[44]), "+f"(d[45]), "+f"(d[46]), "+f"(d[47]), "+f"(d[48]), "+f"(d[49]), "+f"(d[50]), "+f"(d[51]), "+f"(d[52]), "+f"(d[53]), "+f"(d[54]), "+f"(d[55]), "+f"(d[56]), "+f"(d[57]), "+f"(d[58]), "+f"(d[59]), "+f"(d[60]), "+f"(d[61]), "+f"(d[62]), "+f"(d[63]), "+f"(d[64]), "+f"(d[65]), "+f"(d[66]), "+f"(d[67]), "+f"(d[68]), "+f"(d[69]), "+f"(d[70]), "+f"(d[71]), "+f"(d[72]), "+f"(d[73]), "+f"(d[74]), "+f"(d[75]), "+f"(d[76]), "+f"(d[77]), "+f"(d[78]), "+f"(d[79]), "+f"(d[80]), "+f"(d[81]), "+f"(d[82]), "+f"(d[83]), "+f"(d[84]), "+f"(d[85]), "+f"(d[86]), "+f"(d[87]), "+f"(d[88]), "+f"(d[89]), "+f"(d[90]), "+f"(d[91]), "+f"(d[92]), "+f"(d[93]), "+f"(d[94]), "+f"(d[95]), "+f"(d[96]), "+f"(d[97]), "+f"(d[98]), "+f"(d[99]), "+f"(d[100]), "+f"(d[101]), "+f"(d[102]), "+f"(d[103]), "+f"(d[104]), "+f"(d[105]), "+f"(d[106]), "+f"(d[107]), "+f"(d[108]), "+f"(d[109]), "+f"(d[110]), "+f"(d[111]), "+f"(d[112]), "+f"(d[113]), "+f"(d[114]), "+f"(d[115]), "+f"(d[116]), "+f"(d[117]), "+f"(d[118]), "+f"(d[119]), "+f"(d[120]), "+f"(d[121]), "+f"(d[122]), "+f"(d[123]), "+f"(d[124]), "+f"(d[125]), "+f"(d[126]), "+f"(d[127])
        : "l"(da), "l"(db), "r"(scale_d));
}

__device__ __forceinline__ void wgmma_ss_n64_tb0(float (&d)[32], uint64_t da, uint64_t db, int scale_d) {
    asm volatile("{\n.reg .pred p;\nsetp.ne.b32 p, %34, 0;\n"
        "wgmma.mma_async.sync.aligned.m64n64k16.f32.bf16.bf16 {%0, %1, %2, %3, %4, %5, %6, %7, %8, %9, %10, %11, %12, %13, %14, %15, %16, %17, %18, %19, %20, %21, %22, %23, %24, %25, %26, %27, %28, %29, %30, %31}, %32, %33, p, 1, 1, 0, 0;\n}\n"
        : "+f"(d[0]), "+f"(d[1]), "+f"(d[2]), "+f"(d[3]), "+f"(d[4]), "+f"(d[5]), "+f"(d[6]), "+f"(d[7]), "+f"(d[8]), "+f"(d[9]), "+f"(d[10]), "+f"(d[11]), "+f"(d[12]), "+f"(d[13]), "+f"(d[14]), "+f"(d[15]), "+f"(d[16]), "+f"(d[17]), "+f"(d[18]), "+f"(d[19]), "+f"(d[20]), "+f"(d[21]), "+f"(d[22]), "+f"(d[23]), "+f"(d[24]), "+f"(d[25]), "+f"(d[26]), "+f"(d[27]), "+f"(d[28]), "+f"(d[29]), "+f"(d[30]), "+f"(d[31])
        : "l"(da), "l"(db), "r"(scale_d));
}

__device__ __forceinline__ void wgmma_rs_n128_tb0(float (&d)[64], uint32_t a0, uint32_t a1, uint32_t a2, uint32_t a3, uint64_t db, int scale_d) {
    asm volatile("{\n.reg .pred p;\nsetp.ne.b32 p, %69, 0;\n"
        "wgmma.mma_async.sync.aligned.m64n128k16.f32.bf16.bf16 {%0, %1, %2, %3, %4, %5, %6, %7, %8, %9, %10, %11, %12, %13, %14, %15, %16, %17, %18, %19, %20, %21, %22, %23, %24, %25, %26, %27, %28, %29, %30, %31, %32, %33, %34, %35, %36, %37, %38, %39, %40, %41, %42, %43, %44, %45, %46, %47, %48, %49, %50, %51, %52, %53, %54, %55, %56, %57, %58, %59, %60, %61, %62, %63}, {%64, %65, %66, %67}, %68, p, 1, 1, 0;\n}\n"
        : "+f"(d[0]), "+f"(d[1]), "+f"(d[2]), "+f"(d[3]), "+f"(d[4]), "+f"(d[5]), "+f"(d[6]), "+f"(d[7]), "+f"(d[8]), "+f"(d[9]), "+f"(d[10]), "+f"(d[11]), "+f"(d[12]), "+f"(d[13]), "+f"(d[14]), "+f"(d[15]), "+f"(d[16]), "+f"(d[17]), "+f"(d[18]), "+f"(d[19]), "+f"(d[20]), "+f"(d[21]), "+f"(d[22]), "+f"(d[23]), "+f"(d[24]), "+f"(d[25]), "+f"(d[26]), "+f"(d[27]), "+f"(d[28]), "+f"(d[29]), "+f"(d[30]), "+f"(d[31]), "+f"(d[32]), "+f"(d[33]), "+f"(d[34]), "+f"(d[35]), "+f"(d[36]), "+f"(d[37]), "+f"(d[38]), "+f"(d[39]), "+f"(d[40]), "+f"(d[41]), "+f"(d[42]), "+f"(d[43]), "+f"(d[44]), "+f"(d[45]), "+f"(d[46]), "+f"(d[47]), "+f"(d[48]), "+f"(d[49]), "+f"(d[50]), "+f"(d[51]), "+f"(d[52]), "+f"(d[53]), "+f"(d[54]), "+f"(d[55]), "+f"(d[56]), "+f"(d[57]), "+f"(d[58]), "+f"(d[59]), "+f"(d[60]), "+f"(d[61]), "+f"(d[62]), "+f"(d[63])
        : "r"(a0), "r"(a1), "r"(a2), "r"(a3), "l"(db), "r"(scale_d));
}

__device__ __forceinline__ void wgmma_rs_n64_tb0(float (&d)[32], uint32_t a0, uint32_t a1, uint32_t a2, uint32_t a3, uint64_t db, int scale_d) {
    asm volatile("{\n.reg .pred p;\nsetp.ne.b32 p, %37, 0;\n"
        "wgmma.mma_async.sync.aligned.m64n64k16.f32.bf16.bf16 {%0, %1, %2, %3, %4, %5, %6, %7, %8, %9, %10, %11, %12, %13, %14, %15, %16, %17, %18, %19, %20, %21, %22, %23, %24, %25, %26, %27, %28, %29, %30, %31}, {%32, %33, %34, %35}, %36, p, 1, 1, 0;\n}\n"
        : "+f"(d[0]), "+f"(d[1]), "+f"(d[2]), "+f"(d[3]), "+f"(d[4]), "+f"(d[5]), "+f"(d[6]), "+f"(d[7]), "+f"(d[8]), "+f"(d[9]), "+f"(d[10]), "+f"(d[11]), "+f"(d[12]), "+f"(d[13]), "+f"(d[14]), "+f"(d[15]), "+f"(d[16]), "+f"(d[17]), "+f"(d[18]), "+f"(d[19]), "+f"(d[20]), "+f"(d[21]), "+f"(d[22]), "+f"(d[23]), "+f"(d[24]), "+f"(d[25]), "+f"(d[26]), "+f"(d[27]), "+f"(d[28]), "+f"(d[29]), "+f"(d[30]), "+f"(d[31])
        : "r"(a0), "r"(a1), "r"(a2), "r"(a3), "l"(db), "r"(scale_d));
}

__device__ __forceinline__ void wgmma_rs_n32_tb1(float (&d)[16], uint32_t a0, uint32_t a1, uint32_t a2, uint32_t a3, uint64_t db, int scale_d) {
    asm volatile("{\n.reg .pred p;\nsetp.ne.b32 p, %21, 0;\n"
        "wgmma.mma_async.sync.aligned.m64n32k16.f32.bf16.bf16 {%0, %1, %2, %3, %4, %5, %6, %7, %8, %9, %10, %11, %12, %13, %14, %15}, {%16, %17, %18, %19}, %20, p, 1, 1, 1;\n}\n"
        : "+f"(d[0]), "+f"(d[1]), "+f"(d[2]), "+f"(d[3]), "+f"(d[4]), "+f"(d[5]), "+f"(d[6]), "+f"(d[7]), "+f"(d[8]), "+f"(d[9]), "+f"(d[10]), "+f"(d[11]), "+f"(d[12]), "+f"(d[13]), "+f"(d[14]), "+f"(d[15])
        : "r"(a0), "r"(a1), "r"(a2), "r"(a3), "l"(db), "r"(scale_d));
}

__device__ __forceinline__ void wgmma_rs_n40_tb1(float (&d)[20], uint32_t a0, uint32_t a1, uint32_t a2, uint32_t a3, uint64_t db, int scale_d) {
    asm volatile("{\n.reg .pred p;\nsetp.ne.b32 p, %25, 0;\n"
        "wgmma.mma_async.sync.aligned.m64n40k16.f32.bf16.bf16 {%0, %1, %2, %3, %4, %5, %6, %7, %8, %9, %10, %11, %12, %13, %14, %15, %16, %17, %18, %19}, {%20, %21, %22, %23}, %24, p, 1, 1, 1;\n}\n"
        : "+f"(d[0]), "+f"(d[1]), "+f"(d[2]), "+f"(d[3]), "+f"(d[4]), "+f"(d[5]), "+f"(d[6]), "+f"(d[7]), "+f"(d[8]), "+f"(d[9]), "+f"(d[10]), "+f"(d[11]), "+f"(d[12]), "+f"(d[13]), "+f"(d[14]), "+f"(d[15]), "+f"(d[16]), "+f"(d[17]), "+f"(d[18]), "+f"(d[19])
        : "r"(a0), "r"(a1), "r"(a2), "r"(a3), "l"(db), "r"(scale_d));
}


template <int BN>
__device__ __forceinline__ void wgmma_tile(float (&d)[BN / 2], uint64_t da, uint64_t db, int sd) {
    if constexpr (BN == 128) wgmma_ss_n128_tb1(d, da, db, sd);
    else if constexpr (BN == 192) wgmma_ss_n192_tb1(d, da, db, sd);
    else if constexpr (BN == 224) wgmma_ss_n224_tb1(d, da, db, sd);
    else wgmma_ss_n256_tb1(d, da, db, sd);
}

__global__ void __launch_bounds__(256) prep_kernel(const bf16* __restrict__ x, const bf16* __restrict__ gate_w,
                                                   const bf16* __restrict__ w1, const bf16* __restrict__ w3) {
    const int tid = threadIdx.x;
    if (blockIdx.x < 256) {
        const int row = blockIdx.x * 8 + (tid >> 5);
        const int lane = tid & 31;
        const uint4* xr = reinterpret_cast<const uint4*>(x + (size_t)row * DM);
        const uint4* gw = reinterpret_cast<const uint4*>(gate_w);
        float v[32];
        float gsum = 0.f, sum = 0.f;
#pragma unroll
        for (int i = 0; i < 4; i++) {
            uint4 a = xr[lane + 32 * i];
            uint4 b = gw[lane + 32 * i];
            const uint32_t aa[4] = {a.x, a.y, a.z, a.w};
            const uint32_t bb[4] = {b.x, b.y, b.z, b.w};
#pragma unroll
            for (int j = 0; j < 4; j++) {
                float x0 = __uint_as_float(aa[j] << 16), x1 = __uint_as_float(aa[j] & 0xFFFF0000u);
                float g0 = __uint_as_float(bb[j] << 16), g1 = __uint_as_float(bb[j] & 0xFFFF0000u);
                v[i * 8 + j * 2] = x0;
                v[i * 8 + j * 2 + 1] = x1;
                sum += x0 + x1;
                gsum += bf16_round(x0 * g0) + bf16_round(x1 * g1);
            }
        }
#pragma unroll
        for (int o = 16; o > 0; o >>= 1) {
            sum += __shfl_xor_sync(0xffffffffu, sum, o);
            gsum += __shfl_xor_sync(0xffffffffu, gsum, o);
        }
        const float mean = sum * (1.0f / DM);
        float m2 = 0.f;
#pragma unroll
        for (int i = 0; i < 32; i++) {
            float d = v[i] - mean;
            m2 += d * d;
        }
#pragma unroll
        for (int o = 16; o > 0; o >>= 1) m2 += __shfl_xor_sync(0xffffffffu, m2, o);
        if (lane == 0) {
            g_mean1[row] = mean;
            g_rstd1[row] = rsqrtf(m2 * (1.0f / DM) + 1e-5f);
            float logit = bf16_round(gsum);
            float g = bf16_round(1.0f / (1.0f + __expf(-logit)));
            g_gate[row] = g;
            g_omg[row] = bf16_round(1.0f - g);
        }
    } else {
        __shared__ float red[32][65];
        const int strip = blockIdx.x - 256;
        const bf16* w;
        float* out;
        int ld, col0;
        if (strip < 16) { w = w1; ld = DM; col0 = strip * 64; out = g_cs1; }
        else { w = w3; ld = FF; col0 = (strip - 16) * 64; out = g_cs3; }
        const int cg = tid & 7;
        const int rg = tid >> 3;
        float acc[8];
#pragma unroll
        for (int j = 0; j < 8; j++) acc[j] = 0.f;
#pragma unroll 8
        for (int r = 0; r < 32; r++) {
            uint4 a = *reinterpret_cast<const uint4*>(w + (size_t)(r * 32 + rg) * ld + col0 + cg * 8);
            const uint32_t aa[4] = {a.x, a.y, a.z, a.w};
#pragma unroll
            for (int j = 0; j < 4; j++) {
                acc[2 * j] += __uint_as_float(aa[j] << 16);
                acc[2 * j + 1] += __uint_as_float(aa[j] & 0xFFFF0000u);
            }
        }
#pragma unroll
        for (int j = 0; j < 8; j++) red[rg][cg * 8 + j] = acc[j];
        __syncthreads();
        if (tid < 64) {
            float s = 0.f;
#pragma unroll
            for (int r = 0; r < 32; r++) s += red[r][tid];
            out[col0 + tid] = s;
        }
    }
}

template <int BN, int STAGES>
struct GemmSmem {
    static constexpr int A_BYTES = 128 * 64 * 2;
    static constexpr int B_BOXES = (BN + 63) / 64;
    static constexpr int B_BYTES = B_BOXES * 64 * 64 * 2;
    static constexpr int STAGE_BYTES = A_BYTES + B_BYTES;
    static constexpr int STG_OFF = STAGES * STAGE_BYTES;
    static constexpr int BAR_OFF = STG_OFF + 2 * 16384;
    static constexpr int TOTAL = BAR_OFF + 256 + 1024;
};

template <int MODE, int BN, int STAGES>
__global__ void __launch_bounds__(384, 1)
gemm_kernel(const __grid_constant__ CUtensorMap mA, const __grid_constant__ CUtensorMap mB0,
            const __grid_constant__ CUtensorMap mB1, const __grid_constant__ CUtensorMap mC0,
            const __grid_constant__ CUtensorMap mC1, const bf16* __restrict__ xin, int n_tiles_n, int kblocks) {
    using L = GemmSmem<BN, STAGES>;
    extern __shared__ uint8_t smem_raw[];
    const uint32_t sbase = (smem_u32(smem_raw) + 1023u) & ~1023u;
    const uint32_t bar_full = sbase + L::BAR_OFF;
    const uint32_t bar_empty = bar_full + 8 * STAGES;
    const int wg = threadIdx.x >> 7;
    const int ntiles = 16 * n_tiles_n;

    if (threadIdx.x == 0) {
        for (int s = 0; s < STAGES; s++) {
            mbar_init(bar_full + 8 * s, 1);
            mbar_init(bar_empty + 8 * s, 2);
        }
        asm volatile("fence.mbarrier_init.release.cluster;" ::: "memory");
    }
    __syncthreads();

    if (wg == 0) {
        reg_dealloc<40>();
        if (threadIdx.x == 0) {
            prefetch_tmap(&mA);
            prefetch_tmap(&mB0);
            prefetch_tmap(&mB1);
            int stage = 0;
            uint32_t phase = 1;
            for (int tile = blockIdx.x; tile < ntiles; tile += gridDim.x) {
                const int m0 = (tile & 15) * 128;
                const int n0 = (tile >> 4) * BN;
                for (int kb = 0; kb < kblocks; kb++) {
                    mbar_wait(bar_empty + 8 * stage, phase);
                    const uint32_t sa = sbase + stage * L::STAGE_BYTES;
                    const uint32_t sb = sa + L::A_BYTES;
                    const uint32_t fb = bar_full + 8 * stage;
                    mbar_expect_tx(fb, L::STAGE_BYTES);
                    int arow = m0;
                    if (MODE == 2) {
                        const int grp = kb >> 2;
                        arow += (grp == 0) ? -1 : (grp == 1) ? 1 : (grp == 2) ? -2 : 2;
                    }
                    tma_load_2d(sa, &mA, kb * 64, arow, fb);
                    const CUtensorMap* mb = &mB0;
                    int bc = n0, br = kb * 64;
                    if (MODE == 1 && n0 >= 3 * DM) { mb = &mB1; bc = n0 - 3 * DM; }
                    if (MODE == 5 && kb >= 16) { mb = &mB1; br = (kb - 16) * 64; }
#pragma unroll
                    for (int b = 0; b < L::B_BOXES; b++) tma_load_2d(sb + b * 8192, mb, bc + b * 64, br, fb);
                    if (++stage == STAGES) { stage = 0; phase ^= 1; }
                }
            }
        }
    } else {
        reg_alloc<232>();
        const int c = wg - 1;
        const int warp = (threadIdx.x >> 5) & 3;
        const int lane = threadIdx.x & 31;
        const int tid_wg = threadIdx.x & 127;
        const uint32_t stg = sbase + L::STG_OFF + c * 16384;
        int stage = 0;
        uint32_t phase = 0;
        float acc[BN / 2];
        for (int tile = blockIdx.x; tile < ntiles; tile += gridDim.x) {
            const int m0 = (tile & 15) * 128;
            const int n0 = (tile >> 4) * BN;
            int prev_stage = 0;
            for (int kb = 0; kb < kblocks; kb++) {
                mbar_wait(bar_full + 8 * stage, phase);
                const uint32_t sa = sbase + stage * L::STAGE_BYTES + c * 8192;
                const uint32_t sb = sbase + stage * L::STAGE_BYTES + L::A_BYTES;
                const uint64_t da = make_desc(sa, 16, 1024, 1);
                const uint64_t db = make_desc(sb, 8192, 1024, 1);
                wgmma_fence();
#pragma unroll
                for (int k = 0; k < 4; k++) wgmma_tile<BN>(acc, da + k * 2, db + k * 128, (kb | k) != 0);
                wgmma_commit();
                if (kb > 0) {
                    wgmma_wait<1>();
                    if (tid_wg == 0) mbar_arrive(bar_empty + 8 * prev_stage);
                }
                prev_stage = stage;
                if (++stage == STAGES) { stage = 0; phase ^= 1; }
            }
            wgmma_wait<0>();
            if (tid_wg == 0) mbar_arrive(bar_empty + 8 * prev_stage);

            const int r0 = m0 + c * 64 + warp * 16 + (lane >> 2);
            const int r1 = r0 + 8;
            const int cq = (lane & 3) * 2;
            const CUtensorMap* mc = &mC0;
            int out_c0 = n0;
            if (MODE == 1) {
                if (n0 >= 3 * DM) {
                    mc = &mC1;
                    out_c0 = n0 - 3 * DM;
                    const float mu0 = g_mean1[r0], mu1 = g_mean1[r1];
                    const float rs0 = g_rstd1[r0], rs1 = g_rstd1[r1];
#pragma unroll
                    for (int j = 0; j < BN / 8; j++) {
                        const float2 cs = *reinterpret_cast<const float2*>(&g_cs1[out_c0 + 8 * j + cq]);
                        acc[4 * j + 0] = gelu_tanh(rs0 * fmaf(-mu0, cs.x, acc[4 * j + 0]));
                        acc[4 * j + 1] = gelu_tanh(rs0 * fmaf(-mu0, cs.y, acc[4 * j + 1]));
                        acc[4 * j + 2] = gelu_tanh(rs1 * fmaf(-mu1, cs.x, acc[4 * j + 2]));
                        acc[4 * j + 3] = gelu_tanh(rs1 * fmaf(-mu1, cs.y, acc[4 * j + 3]));
                    }
                }
            } else if (MODE == 2) {
                float s0 = 0.f, s1 = 0.f;
#pragma unroll
                for (int j = 0; j < BN / 8; j++) {
                    const uint32_t xa = *reinterpret_cast<const uint32_t*>(xin + (size_t)r0 * DM + n0 + 8 * j + cq);
                    const uint32_t xb = *reinterpret_cast<const uint32_t*>(xin + (size_t)r1 * DM + n0 + 8 * j + cq);
                    acc[4 * j + 0] = bf16_round(bf16_round(acc[4 * j + 0]) + __uint_as_float(xa << 16));
                    acc[4 * j + 1] = bf16_round(bf16_round(acc[4 * j + 1]) + __uint_as_float(xa & 0xFFFF0000u));
                    acc[4 * j + 2] = bf16_round(bf16_round(acc[4 * j + 2]) + __uint_as_float(xb << 16));
                    acc[4 * j + 3] = bf16_round(bf16_round(acc[4 * j + 3]) + __uint_as_float(xb & 0xFFFF0000u));
                    s0 += acc[4 * j + 0] + acc[4 * j + 1];
                    s1 += acc[4 * j + 2] + acc[4 * j + 3];
                }
                s0 += __shfl_xor_sync(0xffffffffu, s0, 1);
                s0 += __shfl_xor_sync(0xffffffffu, s0, 2);
                s1 += __shfl_xor_sync(0xffffffffu, s1, 1);
                s1 += __shfl_xor_sync(0xffffffffu, s1, 2);
                const float mu0 = s0 * (1.0f / BN), mu1 = s1 * (1.0f / BN);
                float q0 = 0.f, q1 = 0.f;
#pragma unroll
                for (int j = 0; j < BN / 8; j++) {
                    float d;
                    d = acc[4 * j + 0] - mu0; q0 += d * d;
                    d = acc[4 * j + 1] - mu0; q0 += d * d;
                    d = acc[4 * j + 2] - mu1; q1 += d * d;
                    d = acc[4 * j + 3] - mu1; q1 += d * d;
                }
                q0 += __shfl_xor_sync(0xffffffffu, q0, 1);
                q0 += __shfl_xor_sync(0xffffffffu, q0, 2);
                q1 += __shfl_xor_sync(0xffffffffu, q1, 1);
                q1 += __shfl_xor_sync(0xffffffffu, q1, 2);
                if ((lane & 3) == 0) {
                    static_assert(MODE != 2 || BN == 128, "stats layout assumes BN=128");
                    g_stat2[r0 * 8 + (n0 >> 7)] = make_float2(s0, q0);
                    g_stat2[r1 * 8 + (n0 >> 7)] = make_float2(s1, q1);
                }
            } else if (MODE == 3) {
                out_c0 = n0 + DM;
                float mu[2], rs[2];
#pragma unroll
                for (int h = 0; h < 2; h++) {
                    const float4* sp = reinterpret_cast<const float4*>(&g_stat2[(h ? r1 : r0) * 8]);
                    float4 p[4];
                    float s = 0.f;
#pragma unroll
                    for (int i = 0; i < 4; i++) { p[i] = sp[i]; s += p[i].x + p[i].z; }
                    const float mean = s * (1.0f / DM);
                    float m2 = 0.f;
#pragma unroll
                    for (int i = 0; i < 4; i++) {
                        float d0 = p[i].x * (1.0f / 128) - mean, d1 = p[i].z * (1.0f / 128) - mean;
                        m2 += p[i].y + p[i].w + 128.0f * (d0 * d0 + d1 * d1);
                    }
                    mu[h] = mean;
                    rs[h] = rsqrtf(m2 * (1.0f / DM) + 1e-5f);
                }
                const float og0 = g_omg[r0], og1 = g_omg[r1];
#pragma unroll
                for (int j = 0; j < BN / 8; j++) {
                    const float2 cs = *reinterpret_cast<const float2*>(&g_cs3[n0 + 8 * j + cq]);
                    acc[4 * j + 0] = og0 * gelu_tanh(rs[0] * fmaf(-mu[0], cs.x, acc[4 * j + 0]));
                    acc[4 * j + 1] = og0 * gelu_tanh(rs[0] * fmaf(-mu[0], cs.y, acc[4 * j + 1]));
                    acc[4 * j + 2] = og1 * gelu_tanh(rs[1] * fmaf(-mu[1], cs.x, acc[4 * j + 2]));
                    acc[4 * j + 3] = og1 * gelu_tanh(rs[1] * fmaf(-mu[1], cs.y, acc[4 * j + 3]));
                }
            } else {
                const float og0 = g_omg[r0], og1 = g_omg[r1];
#pragma unroll
                for (int j = 0; j < BN / 8; j++) {
                    const uint32_t xa = *reinterpret_cast<const uint32_t*>(xin + (size_t)r0 * DM + n0 + 8 * j + cq);
                    const uint32_t xb = *reinterpret_cast<const uint32_t*>(xin + (size_t)r1 * DM + n0 + 8 * j + cq);
                    acc[4 * j + 0] = fmaf(og0, __uint_as_float(xa << 16), acc[4 * j + 0]);
                    acc[4 * j + 1] = fmaf(og0, __uint_as_float(xa & 0xFFFF0000u), acc[4 * j + 1]);
                    acc[4 * j + 2] = fmaf(og1, __uint_as_float(xb << 16), acc[4 * j + 2]);
                    acc[4 * j + 3] = fmaf(og1, __uint_as_float(xb & 0xFFFF0000u), acc[4 * j + 3]);
                }
            }
            const int srow = warp * 16 + (lane & 7) + ((lane >> 3) & 1) * 8;
#pragma unroll
            for (int rnd = 0; rnd < (BN + 127) / 128; rnd++) {
                if (tid_wg == 0) bulk_wait_read0();
                named_bar_sync(1 + c, 128);
#pragma unroll
                for (int jj = 0; jj < 8; jj++) {
                    const int j = rnd * 16 + jj * 2;
                    if (j * 8 < BN) {
                        const int jb = jj * 2 + (lane >> 4);
                        const uint32_t addr = stg + (jb >> 3) * 8192 + srow * 128 + (((jb & 7) ^ (srow & 7)) << 4);
                        stmatrix_x4(addr, pack_bf16(acc[4 * j + 0], acc[4 * j + 1]), pack_bf16(acc[4 * j + 2], acc[4 * j + 3]),
                                    pack_bf16(acc[4 * j + 4], acc[4 * j + 5]), pack_bf16(acc[4 * j + 6], acc[4 * j + 7]));
                    }
                }
                fence_proxy_async();
                named_bar_sync(1 + c, 128);
                if (tid_wg == 0) {
                    tma_store_2d(mc, stg, out_c0 + rnd * 128, m0 + c * 64);
                    if (rnd * 128 + 64 < BN) tma_store_2d(mc, stg + 8192, out_c0 + rnd * 128 + 64, m0 + c * 64);
                    bulk_commit();
                }
            }
        }
        if (tid_wg == 0) bulk_wait0();
    }
}

constexpr int ATT_STAGES = 4;
constexpr int ATT_DIST = 2;
constexpr int ATT_SMEM = ATT_STAGES * 16384 + 8192 + 256 + 1024;

struct AttState {
    float o[16];
    float m0, m1, l0, l1;
};

__device__ __forceinline__ void attn_step(float (&sc)[32], float (&sn)[32], uint32_t (&p)[16], uint64_t dq,
                                          AttState& st, uint64_t dk_next, uint64_t dv_prev, uint32_t release_bar) {
    const float cs = 0.17677669529663687f * 1.4426950408889634f;
    wgmma_fence();
    wgmma_ss_n64_tb0(sn, dq, dk_next, 0);
    wgmma_ss_n64_tb0(sn, dq + 2, dk_next + 2, 1);
#pragma unroll
    for (int t = 0; t < 4; t++)
        wgmma_rs_n32_tb1(st.o, p[4 * t], p[4 * t + 1], p[4 * t + 2], p[4 * t + 3], dv_prev + t * 64, 1);
    wgmma_commit();
    float mx0 = fmaxf(sc[0], sc[1]), mx1 = fmaxf(sc[2], sc[3]);
#pragma unroll
    for (int i = 1; i < 8; i++) {
        mx0 = fmaxf(mx0, fmaxf(sc[4 * i], sc[4 * i + 1]));
        mx1 = fmaxf(mx1, fmaxf(sc[4 * i + 2], sc[4 * i + 3]));
    }
    mx0 = fmaxf(mx0, __shfl_xor_sync(0xffffffffu, mx0, 1));
    mx1 = fmaxf(mx1, __shfl_xor_sync(0xffffffffu, mx1, 1));
    mx0 = fmaxf(mx0, __shfl_xor_sync(0xffffffffu, mx0, 2));
    mx1 = fmaxf(mx1, __shfl_xor_sync(0xffffffffu, mx1, 2));
    const float mn0 = fmaxf(st.m0, mx0), mn1 = fmaxf(st.m1, mx1);
    const float a0 = ex2((st.m0 - mn0) * cs), a1 = ex2((st.m1 - mn1) * cs);
    st.m0 = mn0; st.m1 = mn1;
    const float b0 = mn0 * cs, b1 = mn1 * cs;
    float t0 = 0.f, t1 = 0.f;
#pragma unroll
    for (int i = 0; i < 8; i++) {
        sc[4 * i + 0] = ex2(fmaf(sc[4 * i + 0], cs, -b0));
        sc[4 * i + 1] = ex2(fmaf(sc[4 * i + 1], cs, -b0));
        sc[4 * i + 2] = ex2(fmaf(sc[4 * i + 2], cs, -b1));
        sc[4 * i + 3] = ex2(fmaf(sc[4 * i + 3], cs, -b1));
        t0 += sc[4 * i + 0] + sc[4 * i + 1];
        t1 += sc[4 * i + 2] + sc[4 * i + 3];
    }
    st.l0 = fmaf(st.l0, a0, t0);
    st.l1 = fmaf(st.l1, a1, t1);
    wgmma_wait<0>();
    if (release_bar != 0 && (threadIdx.x & 127) == 0) mbar_arrive(release_bar);
#pragma unroll
    for (int i = 0; i < 4; i++) {
        st.o[4 * i + 0] *= a0; st.o[4 * i + 1] *= a0;
        st.o[4 * i + 2] *= a1; st.o[4 * i + 3] *= a1;
    }
#pragma unroll
    for (int i = 0; i < 8; i++) {
        p[2 * i] = pack_bf16(sc[4 * i + 0], sc[4 * i + 1]);
        p[2 * i + 1] = pack_bf16(sc[4 * i + 2], sc[4 * i + 3]);
    }
}

__global__ void __launch_bounds__(256, 2)
attn_kernel(const __grid_constant__ CUtensorMap mKV) {
    extern __shared__ uint8_t smem_raw[];
    const uint32_t sbase = (smem_u32(smem_raw) + 1023u) & ~1023u;
    const uint32_t bar_kfull = sbase + ATT_STAGES * 16384 + 8192;
    const uint32_t bar_vfull = bar_kfull + 8 * ATT_STAGES;
    const uint32_t bar_empty = bar_vfull + 8 * ATT_STAGES;
    const int head = blockIdx.x >> 4;
    const int q0 = (blockIdx.x & 15) * 128;
    const int warp_id = threadIdx.x >> 5;
    const int lane = threadIdx.x & 31;
    constexpr int NBLK = S_LEN / 128;

    if (threadIdx.x == 0) {
        for (int s = 0; s < ATT_STAGES; s++) {
            mbar_init(bar_kfull + 8 * s, 1);
            mbar_init(bar_vfull + 8 * s, 1);
            mbar_init(bar_empty + 8 * s, 2);
        }
        asm volatile("fence.mbarrier_init.release.cluster;" ::: "memory");
        prefetch_tmap(&mKV);
#pragma unroll
        for (int j = 0; j < ATT_DIST; j++) {
            const uint32_t sk = sbase + j * 16384;
            mbar_expect_tx(bar_kfull + 8 * j, j == 0 ? 16384 : 8192);
            if (j == 0) tma_load_2d(sbase + ATT_STAGES * 16384, &mKV, head * DH, q0, bar_kfull);
            tma_load_2d(sk, &mKV, DM + head * DH, j * 128, bar_kfull + 8 * j);
            mbar_expect_tx(bar_vfull + 8 * j, 8192);
            tma_load_2d(sk + 8192, &mKV, 2 * DM + head * DH, j * 128, bar_vfull + 8 * j);
        }
    }
    __syncthreads();

    const int row0 = q0 + warp_id * 16 + (lane >> 2);
    const int cq = (lane & 3) * 2;
    const uint64_t qf = make_desc(sbase + ATT_STAGES * 16384 + (threadIdx.x >> 7) * 4096, 16, 512, 2);
    AttState st;
#pragma unroll
    for (int i = 0; i < 16; i++) st.o[i] = 0.f;
    st.m0 = -INFINITY; st.m1 = -INFINITY; st.l0 = 0.f; st.l1 = 0.f;
    float s0[32], s1[32];
    const uint64_t desc0 = make_desc(sbase, 16, 512, 2);
    uint32_t p[16];
#pragma unroll
    for (int i = 0; i < 16; i++) p[i] = 0u;
    mbar_wait(bar_kfull, 0);
    wgmma_fence();
    wgmma_ss_n64_tb0(s0, qf, desc0, 0);
    wgmma_ss_n64_tb0(s0, qf + 2, desc0 + 2, 1);
    wgmma_commit();
    mbar_wait(bar_vfull, 0);
    wgmma_wait<0>();
    int stage = 0;
    uint32_t phase = 0;
    uint64_t dv_prev = desc0 + 512;
#pragma unroll 1
    for (int j = 0; j < NBLK; j++) {
        if (threadIdx.x == 0 && j + ATT_DIST < NBLK) {
            const int jn = j + ATT_DIST;
            const int sn = jn % ATT_STAGES;
            if (jn >= ATT_STAGES) mbar_wait(bar_empty + 8 * sn, ((jn / ATT_STAGES) - 1) & 1);
            const uint32_t skn = sbase + sn * 16384;
            mbar_expect_tx(bar_kfull + 8 * sn, 8192);
            tma_load_2d(skn, &mKV, DM + head * DH, jn * 128, bar_kfull + 8 * sn);
            mbar_expect_tx(bar_vfull + 8 * sn, 8192);
            tma_load_2d(skn + 8192, &mKV, 2 * DM + head * DH, jn * 128, bar_vfull + 8 * sn);
        }
        __syncwarp();
        const uint64_t dk = desc0 + (uint64_t)(stage * 1024);
        const int pstage = (stage + ATT_STAGES - 1) % ATT_STAGES;
        attn_step(s0, s1, p, qf, st, dk + 256, dv_prev, j > 0 ? bar_empty + 8 * pstage : 0u);
        int nstage = stage + 1;
        uint32_t nphase = phase;
        if (nstage == ATT_STAGES) { nstage = 0; nphase ^= 1; }
        uint64_t dkn = dk;
        if (j + 1 < NBLK) {
            mbar_wait(bar_kfull + 8 * nstage, nphase);
            dkn = desc0 + (uint64_t)(nstage * 1024);
        }
        mbar_wait(bar_vfull + 8 * stage, phase);
        attn_step(s1, s0, p, qf, st, dkn, dk + 512, 0u);
        dv_prev = dk + 512 + 256;
        stage = nstage;
        phase = nphase;
    }
    wgmma_fence();
#pragma unroll
    for (int t = 0; t < 4; t++)
        wgmma_rs_n32_tb1(st.o, p[4 * t], p[4 * t + 1], p[4 * t + 2], p[4 * t + 3], dv_prev + t * 64, 1);
    wgmma_commit();
    wgmma_wait<0>();
    float l0 = st.l0, l1 = st.l1;
    l0 += __shfl_xor_sync(0xffffffffu, l0, 1);
    l0 += __shfl_xor_sync(0xffffffffu, l0, 2);
    l1 += __shfl_xor_sync(0xffffffffu, l1, 1);
    l1 += __shfl_xor_sync(0xffffffffu, l1, 2);
    const float f0 = g_gate[row0] / l0, f1 = g_gate[row0 + 8] / l1;
    bf16* op0 = g_a5 + (size_t)row0 * A5W + head * DH + cq;
    bf16* op1 = op0 + 8 * A5W;
#pragma unroll
    for (int i = 0; i < 4; i++) {
        *reinterpret_cast<uint32_t*>(op0 + 8 * i) = pack_bf16(st.o[4 * i] * f0, st.o[4 * i + 1] * f0);
        *reinterpret_cast<uint32_t*>(op1 + 8 * i) = pack_bf16(st.o[4 * i + 2] * f1, st.o[4 * i + 3] * f1);
    }
}

typedef CUresult (*EncodeFn)(CUtensorMap*, CUtensorMapDataType, cuuint32_t, void*, const cuuint64_t*, const cuuint64_t*,
                             const cuuint32_t*, const cuuint32_t*, CUtensorMapInterleave, CUtensorMapSwizzle,
                             CUtensorMapL2promotion, CUtensorMapFloatOOBfill);

static CUtensorMap make_map(EncodeFn fn, const void* ptr, int rows, int cols, int box_cols, int box_rows,
                            CUtensorMapSwizzle swz) {
    CUtensorMap m;
    cuuint64_t dims[2] = {(cuuint64_t)cols, (cuuint64_t)rows};
    cuuint64_t strides[1] = {(cuuint64_t)cols * 2};
    cuuint32_t box[2] = {(cuuint32_t)box_cols, (cuuint32_t)box_rows};
    cuuint32_t es[2] = {1, 1};
    fn(&m, CU_TENSOR_MAP_DATA_TYPE_BFLOAT16, 2, const_cast<void*>(ptr), dims, strides, box, es,
       CU_TENSOR_MAP_INTERLEAVE_NONE, swz, CU_TENSOR_MAP_L2_PROMOTION_L2_256B, CU_TENSOR_MAP_FLOAT_OOB_FILL_NONE);
    return m;
}

extern "C" void kernel_launch(void* const* d_in, const int* in_sizes, int n_in, void* d_out, int out_size) {
    const bf16* x = (const bf16*)d_in[0];
    const bf16* wqkv = (const bf16*)d_in[1];
    const bf16* wo = (const bf16*)d_in[2];
    const bf16* w1 = (const bf16*)d_in[4];
    const bf16* w2 = (const bf16*)d_in[5];
    const bf16* w3 = (const bf16*)d_in[6];
    const bf16* w4 = (const bf16*)d_in[7];
    const bf16* gate_w = (const bf16*)d_in[8];

    static EncodeFn enc = nullptr;
    static void *p_qkv, *p_h, *p_x1, *p_a5;
    if (!enc) {
        void* fn = nullptr;
        cudaDriverEntryPointQueryResult qres;
        cudaGetDriverEntryPoint("cuTensorMapEncodeTiled", &fn, cudaEnableDefault, &qres);
        enc = (EncodeFn)fn;
        cudaGetSymbolAddress(&p_qkv, g_qkv);
        cudaGetSymbolAddress(&p_h, g_h);
        cudaGetSymbolAddress(&p_x1, g_x1);
        cudaGetSymbolAddress(&p_a5, g_a5);
        cudaFuncSetAttribute(gemm_kernel<1, 256, 4>, cudaFuncAttributeMaxDynamicSharedMemorySize, GemmSmem<256, 4>::TOTAL);
        cudaFuncSetAttribute(gemm_kernel<2, 128, 5>, cudaFuncAttributeMaxDynamicSharedMemorySize, GemmSmem<128, 5>::TOTAL);
        cudaFuncSetAttribute(gemm_kernel<3, 256, 4>, cudaFuncAttributeMaxDynamicSharedMemorySize, GemmSmem<256, 4>::TOTAL);
        cudaFuncSetAttribute(gemm_kernel<5, 128, 5>, cudaFuncAttributeMaxDynamicSharedMemorySize, GemmSmem<128, 5>::TOTAL);
        cudaFuncSetAttribute(attn_kernel, cudaFuncAttributeMaxDynamicSharedMemorySize, ATT_SMEM);
    }
    const CUtensorMapSwizzle SW128 = CU_TENSOR_MAP_SWIZZLE_128B, SW64 = CU_TENSOR_MAP_SWIZZLE_64B;
    CUtensorMap mX = make_map(enc, x, S_LEN, DM, 64, 128, SW128);
    CUtensorMap mWqkv = make_map(enc, wqkv, DM, 3 * DM, 64, 64, SW128);
    CUtensorMap mW1 = make_map(enc, w1, DM, DM, 64, 64, SW128);
    CUtensorMap mW2 = make_map(enc, w2, DM, DM, 64, 64, SW128);
    CUtensorMap mW3 = make_map(enc, w3, DM, FF, 64, 64, SW128);
    CUtensorMap mW4 = make_map(enc, w4, FF, DM, 64, 64, SW128);
    CUtensorMap mWo = make_map(enc, wo, DM, DM, 64, 64, SW128);
    CUtensorMap mQKVst = make_map(enc, p_qkv, S_LEN, 3 * DM, 64, 64, SW128);
    CUtensorMap mKV = make_map(enc, p_qkv, S_LEN, 3 * DM, 32, 128, SW64);
    CUtensorMap mHst = make_map(enc, p_h, S_LEN, DM, 64, 64, SW128);
    CUtensorMap mHld = make_map(enc, p_h, S_LEN, DM, 64, 128, SW128);
    CUtensorMap mX1st = make_map(enc, p_x1, S_LEN, DM, 64, 64, SW128);
    CUtensorMap mX1ld = make_map(enc, p_x1, S_LEN, DM, 64, 128, SW128);
    CUtensorMap mA5st = make_map(enc, p_a5, S_LEN, A5W, 64, 64, SW128);
    CUtensorMap mA5ld = make_map(enc, p_a5, S_LEN, A5W, 64, 128, SW128);
    CUtensorMap mOut = make_map(enc, d_out, S_LEN, DM, 64, 64, SW128);

    cudaStream_t st = cudaStreamPerThread;
    prep_kernel<<<256 + 72, 256, 0, st>>>(x, gate_w, w1, w3);
    gemm_kernel<1, 256, 4><<<132, 384, GemmSmem<256, 4>::TOTAL, st>>>(mX, mWqkv, mW1, mQKVst, mHst, x, 16, 16);
    attn_kernel<<<NH * 16, 256, ATT_SMEM, st>>>(mKV);
    gemm_kernel<2, 128, 5><<<128, 384, GemmSmem<128, 5>::TOTAL, st>>>(mHld, mW2, mW2, mX1st, mX1st, x, 8, 16);
    gemm_kernel<3, 256, 4><<<132, 384, GemmSmem<256, 4>::TOTAL, st>>>(mX1ld, mW3, mW3, mA5st, mA5st, x, 14, 16);
    gemm_kernel<5, 128, 5><<<128, 384, GemmSmem<128, 5>::TOTAL, st>>>(mA5ld, mWo, mW4, mOut, mOut, (const bf16*)p_x1, 8, 72);
}
```

```cpp
#include <cuda_runtime.h>
#include <cuda_bf16.h>
#include <cuda.h>
#include <stdint.h>

typedef __nv_bfloat16 bf16;

constexpr int S_LEN = 2048;
constexpr int DM = 1024;
constexpr int FF = 3584;
constexpr int NH = 32;
constexpr int DH = 32;
constexpr int A5W = DM + FF;

__device__ __align__(1024) bf16 g_qkv[S_LEN * 3 * DM];
__device__ __align__(1024) bf16 g_h[S_LEN * DM];
__device__ __align__(1024) bf16 g_x1[S_LEN * DM];
__device__ __align__(1024) bf16 g_a5[S_LEN * A5W];
__device__ __align__(16) float g_mean1[S_LEN];
__device__ __align__(16) float g_rstd1[S_LEN];
__device__ __align__(16) float g_gate[S_LEN];
__device__ __align__(16) float g_omg[S_LEN];
__device__ __align__(16) float g_cs1[DM];
__device__ __align__(16) float g_cs3[FF];
__device__ __align__(16) float2 g_stat2[S_LEN * 8];

__device__ __forceinline__ uint32_t smem_u32(const void* p) { return (uint32_t)__cvta_generic_to_shared(p); }

__device__ __forceinline__ void mbar_init(uint32_t bar, uint32_t count) {
    asm volatile("mbarrier.init.shared::cta.b64 [%0], %1;" ::"r"(bar), "r"(count));
}
__device__ __forceinline__ void mbar_expect_tx(uint32_t bar, uint32_t bytes) {
    asm volatile("mbarrier.arrive.expect_tx.shared::cta.b64 _, [%0], %1;" ::"r"(bar), "r"(bytes) : "memory");
}
__device__ __forceinline__ void mbar_arrive(uint32_t bar) {
    asm volatile("mbarrier.arrive.shared::cta.b64 _, [%0];" ::"r"(bar) : "memory");
}
__device__ __forceinline__ bool mbar_try_wait(uint32_t bar, uint32_t parity) {
    uint32_t ok;
    asm volatile(
        "{\n.reg .pred p;\n"
        "mbarrier.try_wait.parity.shared::cta.b64 p, [%1], %2;\n"
        "selp.u32 %0, 1, 0, p;\n}\n"
        : "=r"(ok)
        : "r"(bar), "r"(parity)
        : "memory");
    return ok != 0;
}
__device__ __forceinline__ void mbar_wait(uint32_t bar, uint32_t parity) {
    uint32_t spins = 0;
    while (!mbar_try_wait(bar, parity)) {
        if (++spins > (1u << 24)) __trap();
    }
}
__device__ __forceinline__ void tma_load_2d(uint32_t dst, const CUtensorMap* map, int c0, int c1, uint32_t bar) {
    asm volatile(
        "cp.async.bulk.tensor.2d.shared::cluster.global.mbarrier::complete_tx::bytes [%0], [%1, {%3, %4}], [%2];"
        ::"r"(dst), "l"(map), "r"(bar), "r"(c0), "r"(c1)
        : "memory");
}
__device__ __forceinline__ void tma_store_2d(const CUtensorMap* map, uint32_t src, int c0, int c1) {
    asm volatile("cp.async.bulk.tensor.2d.global.shared::cta.bulk_group [%0, {%2, %3}], [%1];"
                 ::"l"(map), "r"(src), "r"(c0), "r"(c1)
                 : "memory");
}
__device__ __forceinline__ void bulk_commit() { asm volatile("cp.async.bulk.commit_group;" ::: "memory"); }
__device__ __forceinline__ void bulk_wait_read0() { asm volatile("cp.async.bulk.wait_group.read 0;" ::: "memory"); }
__device__ __forceinline__ void bulk_wait0() { asm volatile("cp.async.bulk.wait_group 0;" ::: "memory"); }
__device__ __forceinline__ void fence_proxy_async() { asm volatile("fence.proxy.async.shared::cta;" ::: "memory"); }
__device__ __forceinline__ void named_bar_sync(int id, int n) { asm volatile("bar.sync %0, %1;" ::"r"(id), "r"(n) : "memory"); }
__device__ __forceinline__ void named_bar_arrive(int id, int n) { asm volatile("bar.arrive %0, %1;" ::"r"(id), "r"(n) : "memory"); }
__device__ __forceinline__ void wgmma_fence() { asm volatile("wgmma.fence.sync.aligned;" ::: "memory"); }
__device__ __forceinline__ void wgmma_commit() { asm volatile("wgmma.commit_group.sync.aligned;" ::: "memory"); }
template <int N>
__device__ __forceinline__ void wgmma_wait() { asm volatile("wgmma.wait_group.sync.aligned %0;" ::"n"(N) : "memory"); }
__device__ __forceinline__ void prefetch_tmap(const CUtensorMap* m) {
    asm volatile("prefetch.tensormap [%0];" ::"l"(m) : "memory");
}
template <int R>
__device__ __forceinline__ void reg_alloc() { asm volatile("setmaxnreg.inc.sync.aligned.u32 %0;" ::"n"(R)); }
template <int R>
__device__ __forceinline__ void reg_dealloc() { asm volatile("setmaxnreg.dec.sync.aligned.u32 %0;" ::"n"(R)); }
__device__ __forceinline__ void stmatrix_x4(uint32_t addr, uint32_t r0, uint32_t r1, uint32_t r2, uint32_t r3) {
    asm volatile("stmatrix.sync.aligned.m8n8.x4.shared.b16 [%0], {%1, %2, %3, %4};"
                 ::"r"(addr), "r"(r0), "r"(r1), "r"(r2), "r"(r3)
                 : "memory");
}
__device__ __forceinline__ uint32_t pack_bf16(float lo, float hi) {
    uint32_t r;
    asm("cvt.rn.bf16x2.f32 %0, %1, %2;" : "=r"(r) : "f"(hi), "f"(lo));
    return r;
}
__device__ __forceinline__ float bf16_round(float v) { return __bfloat162float(__float2bfloat16_rn(v)); }
__device__ __forceinline__ float ex2(float x) {
    float y;
    asm("ex2.approx.ftz.f32 %0, %1;" : "=f"(y) : "f"(x));
    return y;
}
__device__ __forceinline__ float tanh_fast(float x) {
    float y;
    asm("tanh.approx.f32 %0, %1;" : "=f"(y) : "f"(x));
    return y;
}
__device__ __forceinline__ float gelu_tanh(float v) {
    float u = 0.7978845608028654f * (v + 0.044715f * v * v * v);
    float hv = 0.5f * v;
    return fmaf(hv, tanh_fast(u), hv);
}
__device__ __forceinline__ uint32_t desc_lo(uint32_t addr, uint32_t lbo_bytes) {
    return ((addr & 0x3FFFF) >> 4) | (((lbo_bytes >> 4) & 0x3FFF) << 16);
}
__host__ __device__ constexpr uint32_t desc_hi(uint32_t sbo_bytes, uint32_t swz) {
    return ((sbo_bytes >> 4) & 0x3FFF) | (swz << 30);
}


__device__ __forceinline__ void wgmma_ss_n128_tb1(float (&d)[64], uint32_t alo, uint32_t ahi, uint32_t blo, uint32_t bhi, int scale_d) {
    asm volatile("{\n.reg .pred p;\n.reg .b64 da, db;\nsetp.ne.b32 p, %68, 0;\nmov.b64 da, {%64, %65};\nmov.b64 db, {%66, %67};\n"
        "wgmma.mma_async.sync.aligned.m64n128k16.f32.bf16.bf16 {%0, %1, %2, %3, %4, %5, %6, %7, %8, %9, %10, %11, %12, %13, %14, %15, %16, %17, %18, %19, %20, %21, %22, %23, %24, %25, %26, %27, %28, %29, %30, %31, %32, %33, %34, %35, %36, %37, %38, %39, %40, %41, %42, %43, %44, %45, %46, %47, %48, %49, %50, %51, %52, %53, %54, %55, %56, %57, %58, %59, %60, %61, %62, %63}, da, db, p, 1, 1, 0, 1;\n}\n"
        : "+f"(d[0]), "+f"(d[1]), "+f"(d[2]), "+f"(d[3]), "+f"(d[4]), "+f"(d[5]), "+f"(d[6]), "+f"(d[7]), "+f"(d[8]), "+f"(d[9]), "+f"(d[10]), "+f"(d[11]), "+f"(d[12]), "+f"(d[13]), "+f"(d[14]), "+f"(d[15]), "+f"(d[16]), "+f"(d[17]), "+f"(d[18]), "+f"(d[19]), "+f"(d[20]), "+f"(d[21]), "+f"(d[22]), "+f"(d[23]), "+f"(d[24]), "+f"(d[25]), "+f"(d[26]), "+f"(d[27]), "+f"(d[28]), "+f"(d[29]), "+f"(d[30]), "+f"(d[31]), "+f"(d[32]), "+f"(d[33]), "+f"(d[34]), "+f"(d[35]), "+f"(d[36]), "+f"(d[37]), "+f"(d[38]), "+f"(d[39]), "+f"(d[40]), "+f"(d[41]), "+f"(d[42]), "+f"(d[43]), "+f"(d[44]), "+f"(d[45]), "+f"(d[46]), "+f"(d[47]), "+f"(d[48]), "+f"(d[49]), "+f"(d[50]), "+f"(d[51]), "+f"(d[52]), "+f"(d[53]), "+f"(d[54]), "+f"(d[55]), "+f"(d[56]), "+f"(d[57]), "+f"(d[58]), "+f"(d[59]), "+f"(d[60]), "+f"(d[61]), "+f"(d[62]), "+f"(d[63])
        : "r"(alo), "r"(ahi), "r"(blo), "r"(bhi), "r"(scale_d));
}

__device__ __forceinline__ void wgmma_ss_n192_tb1(float (&d)[96], uint32_t alo, uint32_t ahi, uint32_t blo, uint32_t bhi, int scale_d) {
    asm volatile("{\n.reg .pred p;\n.reg .b64 da, db;\nsetp.ne.b32 p, %100, 0;\nmov.b64 da, {%96, %97};\nmov.b64 db, {%98, %99};\n"
        "wgmma.mma_async.sync.aligned.m64n192k16.f32.bf16.bf16 {%0, %1, %2, %3, %4, %5, %6, %7, %8, %9, %10, %11, %12, %13, %14, %15, %16, %17, %18, %19, %20, %21, %22, %23, %24, %25, %26, %27, %28, %29, %30, %31, %32, %33, %34, %35, %36, %37, %38, %39, %40, %41, %42, %43, %44, %45, %46, %47, %48, %49, %50, %51, %52, %53, %54, %55, %56, %57, %58, %59, %60, %61, %62, %63, %64, %65, %66, %67, %68, %69, %70, %71, %72, %73, %74, %75, %76, %77, %78, %79, %80, %81, %82, %83, %84, %85, %86, %87, %88, %89, %90, %91, %92, %93, %94, %95}, da, db, p, 1, 1, 0, 1;\n}\n"
        : "+f"(d[0]), "+f"(d[1]), "+f"(d[2]), "+f"(d[3]), "+f"(d[4]), "+f"(d[5]), "+f"(d[6]), "+f"(d[7]), "+f"(d[8]), "+f"(d[9]), "+f"(d[10]), "+f"(d[11]), "+f"(d[12]), "+f"(d[13]), "+f"(d[14]), "+f"(d[15]), "+f"(d[16]), "+f"(d[17]), "+f"(d[18]), "+f"(d[19]), "+f"(d[20]), "+f"(d[21]), "+f"(d[22]), "+f"(d[23]), "+f"(d[24]), "+f"(d[25]), "+f"(d[26]), "+f"(d[27]), "+f"(d[28]), "+f"(d[29]), "+f"(d[30]), "+f"(d[31]), "+f"(d[32]), "+f"(d[33]), "+f"(d[34]), "+f"(d[35]), "+f"(d[36]), "+f"(d[37]), "+f"(d[38]), "+f"(d[39]), "+f"(d[40]), "+f"(d[41]), "+f"(d[42]), "+f"(d[43]), "+f"(d[44]), "+f"(d[45]), "+f"(d[46]), "+f"(d[47]), "+f"(d[48]), "+f"(d[49]), "+f"(d[50]), "+f"(d[51]), "+f"(d[52]), "+f"(d[53]), "+f"(d[54]), "+f"(d[55]), "+f"(d[56]), "+f"(d[57]), "+f"(d[58]), "+f"(d[59]), "+f"(d[60]), "+f"(d[61]), "+f"(d[62]), "+f"(d[63]), "+f"(d[64]), "+f"(d[65]), "+f"(d[66]), "+f"(d[67]), "+f"(d[68]), "+f"(d[69]), "+f"(d[70]), "+f"(d[71]), "+f"(d[72]), "+f"(d[73]), "+f"(d[74]), "+f"(d[75]), "+f"(d[76]), "+f"(d[77]), "+f"(d[78]), "+f"(d[79]), "+f"(d[80]), "+f"(d[81]), "+f"(d[82]), "+f"(d[83]), "+f"(d[84]), "+f"(d[85]), "+f"(d[86]), "+f"(d[87]), "+f"(d[88]), "+f"(d[89]), "+f"(d[90]), "+f"(d[91]), "+f"(d[92]), "+f"(d[93]), "+f"(d[94]), "+f"(d[95])
        : "r"(alo), "r"(ahi), "r"(blo), "r"(bhi), "r"(scale_d));
}

__device__ __forceinline__ void wgmma_ss_n224_tb1(float (&d)[112], uint32_t alo, uint32_t ahi, uint32_t blo, uint32_t bhi, int scale_d) {
    asm volatile("{\n.reg .pred p;\n.reg .b64 da, db;\nsetp.ne.b32 p, %116, 0;\nmov.b64 da, {%112, %113};\nmov.b64 db, {%114, %115};\n"
        "wgmma.mma_async.sync.aligned.m64n224k16.f32.bf16.bf16 {%0, %1, %2, %3, %4, %5, %6, %7, %8, %9, %10, %11, %12, %13, %14, %15, %16, %17, %18, %19, %20, %21, %22, %23, %24, %25, %26, %27, %28, %29, %30, %31, %32, %33, %34, %35, %36, %37, %38, %39, %40, %41, %42, %43, %44, %45, %46, %47, %48, %49, %50, %51, %52, %53, %54, %55, %56, %57, %58, %59, %60, %61, %62, %63, %64, %65, %66, %67, %68, %69, %70, %71, %72, %73, %74, %75, %76, %77, %78, %79, %80, %81, %82, %83, %84, %85, %86, %87, %88, %89, %90, %91, %92, %93, %94, %95, %96, %97, %98, %99, %100, %101, %102, %103, %104, %105, %106, %107, %108, %109, %110, %111}, da, db, p, 1, 1, 0, 1;\n}\n"
        : "+f"(d[0]), "+f"(d[1]), "+f"(d[2]), "+f"(d[3]), "+f"(d[4]), "+f"(d[5]), "+f"(d[6]), "+f"(d[7]), "+f"(d[8]), "+f"(d[9]), "+f"(d[10]), "+f"(d[11]), "+f"(d[12]), "+f"(d[13]), "+f"(d[14]), "+f"(d[15]), "+f"(d[16]), "+f"(d[17]), "+f"(d[18]), "+f"(d[19]), "+f"(d[20]), "+f"(d[21]), "+f"(d[22]), "+f"(d[23]), "+f"(d[24]), "+f"(d[25]), "+f"(d[26]), "+f"(d[27]), "+f"(d[28]), "+f"(d[29]), "+f"(d[30]), "+f"(d[31]), "+f"(d[32]), "+f"(d[33]), "+f"(d[34]), "+f"(d[35]), "+f"(d[36]), "+f"(d[37]), "+f"(d[38]), "+f"(d[39]), "+f"(d[40]), "+f"(d[41]), "+f"(d[42]), "+f"(d[43]), "+f"(d[44]), "+f"(d[45]), "+f"(d[46]), "+f"(d[47]), "+f"(d[48]), "+f"(d[49]), "+f"(d[50]), "+f"(d[51]), "+f"(d[52]), "+f"(d[53]), "+f"(d[54]), "+f"(d[55]), "+f"(d[56]), "+f"(d[57]), "+f"(d[58]), "+f"(d[59]), "+f"(d[60]), "+f"(d[61]), "+f"(d[62]), "+f"(d[63]), "+f"(d[64]), "+f"(d[65]), "+f"(d[66]), "+f"(d[67]), "+f"(d[68]), "+f"(d[69]), "+f"(d[70]), "+f"(d[71]), "+f"(d[72]), "+f"(d[73]), "+f"(d[74]), "+f"(d[75]), "+f"(d[76]), "+f"(d[77]), "+f"(d[78]), "+f"(d[79]), "+f"(d[80]), "+f"(d[81]), "+f"(d[82]), "+f"(d[83]), "+f"(d[84]), "+f"(d[85]), "+f"(d[86]), "+f"(d[87]), "+f"(d[88]), "+f"(d[89]), "+f"(d[90]), "+f"(d[91]), "+f"(d[92]), "+f"(d[93]), "+f"(d[94]), "+f"(d[95]), "+f"(d[96]), "+f"(d[97]), "+f"(d[98]), "+f"(d[99]), "+f"(d[100]), "+f"(d[101]), "+f"(d[102]), "+f"(d[103]), "+f"(d[104]), "+f"(d[105]), "+f"(d[106]), "+f"(d[107]), "+f"(d[108]), "+f"(d[109]), "+f"(d[110]), "+f"(d[111])
        : "r"(alo), "r"(ahi), "r"(blo), "r"(bhi), "r"(scale_d));
}

__device__ __forceinline__ void wgmma_ss_n256_tb1(float (&d)[128], uint32_t alo, uint32_t ahi, uint32_t blo, uint32_t bhi, int scale_d) {
    asm volatile("{\n.reg .pred p;\n.reg .b64 da, db;\nsetp.ne.b32 p, %132, 0;\nmov.b64 da, {%128, %129};\nmov.b64 db, {%130, %131};\n"
        "wgmma.mma_async.sync.aligned.m64n256k16.f32.bf16.bf16 {%0, %1, %2, %3, %4, %5, %6, %7, %8, %9, %10, %11, %12, %13, %14, %15, %16, %17, %18, %19, %20, %21, %22, %23, %24, %25, %26, %27, %28, %29, %30, %31, %32, %33, %34, %35, %36, %37, %38, %39, %40, %41, %42, %43, %44, %45, %46, %47, %48, %49, %50, %51, %52, %53, %54, %55, %56, %57, %58, %59, %60, %61, %62, %63, %64, %65, %66, %67, %68, %69, %70, %71, %72, %73, %74, %75, %76, %77, %78, %79, %80, %81, %82, %83, %84, %85, %86, %87, %88, %89, %90, %91, %92, %93, %94, %95, %96, %97, %98, %99, %100, %101, %102, %103, %104, %105, %106, %107, %108, %109, %110, %111, %112, %113, %114, %115, %116, %117, %118, %119, %120, %121, %122, %123, %124, %125, %126, %127}, da, db, p, 1, 1, 0, 1;\n}\n"
        : "+f"(d[0]), "+f"(d[1]), "+f"(d[2]), "+f"(d[3]), "+f"(d[4]), "+f"(d[5]), "+f"(d[6]), "+f"(d[7]), "+f"(d[8]), "+f"(d[9]), "+f"(d[10]), "+f"(d[11]), "+f"(d[12]), "+f"(d[13]), "+f"(d[14]), "+f"(d[15]), "+f"(d[16]), "+f"(d[17]), "+f"(d[18]), "+f"(d[19]), "+f"(d[20]), "+f"(d[21]), "+f"(d[22]), "+f"(d[23]), "+f"(d[24]), "+f"(d[25]), "+f"(d[26]), "+f"(d[27]), "+f"(d[28]), "+f"(d[29]), "+f"(d[30]), "+f"(d[31]), "+f"(d[32]), "+f"(d[33]), "+f"(d[34]), "+f"(d[35]), "+f"(d[36]), "+f"(d[37]), "+f"(d[38]), "+f"(d[39]), "+f"(d[40]), "+f"(d[41]), "+f"(d[42]), "+f"(d[43]), "+f"(d[44]), "+f"(d[45]), "+f"(d[46]), "+f"(d[47]), "+f"(d[48]), "+f"(d[49]), "+f"(d[50]), "+f"(d[51]), "+f"(d[52]), "+f"(d[53]), "+f"(d[54]), "+f"(d[55]), "+f"(d[56]), "+f"(d[57]), "+f"(d[58]), "+f"(d[59]), "+f"(d[60]), "+f"(d[61]), "+f"(d[62]), "+f"(d[63]), "+f"(d[64]), "+f"(d[65]), "+f"(d[66]), "+f"(d[67]), "+f"(d[68]), "+f"(d[69]), "+f"(d[70]), "+f"(d[71]), "+f"(d[72]), "+f"(d[73]), "+f"(d[74]), "+f"(d[75]), "+f"(d[76]), "+f"(d[77]), "+f"(d[78]), "+f"(d[79]), "+f"(d[80]), "+f"(d[81]), "+f"(d[82]), "+f"(d[83]), "+f"(d[84]), "+f"(d[85]), "+f"(d[86]), "+f"(d[87]), "+f"(d[88]), "+f"(d[89]), "+f"(d[90]), "+f"(d[91]), "+f"(d[92]), "+f"(d[93]), "+f"(d[94]), "+f"(d[95]), "+f"(d[96]), "+f"(d[97]), "+f"(d[98]), "+f"(d[99]), "+f"(d[100]), "+f"(d[101]), "+f"(d[102]), "+f"(d[103]), "+f"(d[104]), "+f"(d[105]), "+f"(d[106]), "+f"(d[107]), "+f"(d[108]), "+f"(d[109]), "+f"(d[110]), "+f"(d[111]), "+f"(d[112]), "+f"(d[113]), "+f"(d[114]), "+f"(d[115]), "+f"(d[116]), "+f"(d[117]), "+f"(d[118]), "+f"(d[119]), "+f"(d[120]), "+f"(d[121]), "+f"(d[122]), "+f"(d[123]), "+f"(d[124]), "+f"(d[125]), "+f"(d[126]), "+f"(d[127])
        : "r"(alo), "r"(ahi), "r"(blo), "r"(bhi), "r"(scale_d));
}

__device__ __forceinline__ void wgmma_ss_n64_tb0(float (&d)[32], uint32_t alo, uint32_t ahi, uint32_t blo, uint32_t bhi, int scale_d) {
    asm volatile("{\n.reg .pred p;\n.reg .b64 da, db;\nsetp.ne.b32 p, %36, 0;\nmov.b64 da, {%32, %33};\nmov.b64 db, {%34, %35};\n"
        "wgmma.mma_async.sync.aligned.m64n64k16.f32.bf16.bf16 {%0, %1, %2, %3, %4, %5, %6, %7, %8, %9, %10, %11, %12, %13, %14, %15, %16, %17, %18, %19, %20, %21, %22, %23, %24, %25, %26, %27, %28, %29, %30, %31}, da, db, p, 1, 1, 0, 0;\n}\n"
        : "+f"(d[0]), "+f"(d[1]), "+f"(d[2]), "+f"(d[3]), "+f"(d[4]), "+f"(d[5]), "+f"(d[6]), "+f"(d[7]), "+f"(d[8]), "+f"(d[9]), "+f"(d[10]), "+f"(d[11]), "+f"(d[12]), "+f"(d[13]), "+f"(d[14]), "+f"(d[15]), "+f"(d[16]), "+f"(d[17]), "+f"(d[18]), "+f"(d[19]), "+f"(d[20]), "+f"(d[21]), "+f"(d[22]), "+f"(d[23]), "+f"(d[24]), "+f"(d[25]), "+f"(d[26]), "+f"(d[27]), "+f"(d[28]), "+f"(d[29]), "+f"(d[30]), "+f"(d[31])
        : "r"(alo), "r"(ahi), "r"(blo), "r"(bhi), "r"(scale_d));
}

__device__ __forceinline__ void wgmma_rs_n128_tb0(float (&d)[64], uint32_t a0, uint32_t a1, uint32_t a2, uint32_t a3, uint32_t blo, uint32_t bhi, int scale_d) {
    asm volatile("{\n.reg .pred p;\n.reg .b64 db;\nsetp.ne.b32 p, %70, 0;\nmov.b64 db, {%68, %69};\n"
        "wgmma.mma_async.sync.aligned.m64n128k16.f32.bf16.bf16 {%0, %1, %2, %3, %4, %5, %6, %7, %8, %9, %10, %11, %12, %13, %14, %15, %16, %17, %18, %19, %20, %21, %22, %23, %24, %25, %26, %27, %28, %29, %30, %31, %32, %33, %34, %35, %36, %37, %38, %39, %40, %41, %42, %43, %44, %45, %46, %47, %48, %49, %50, %51, %52, %53, %54, %55, %56, %57, %58, %59, %60, %61, %62, %63}, {%64, %65, %66, %67}, db, p, 1, 1, 0;\n}\n"
        : "+f"(d[0]), "+f"(d[1]), "+f"(d[2]), "+f"(d[3]), "+f"(d[4]), "+f"(d[5]), "+f"(d[6]), "+f"(d[7]), "+f"(d[8]), "+f"(d[9]), "+f"(d[10]), "+f"(d[11]), "+f"(d[12]), "+f"(d[13]), "+f"(d[14]), "+f"(d[15]), "+f"(d[16]), "+f"(d[17]), "+f"(d[18]), "+f"(d[19]), "+f"(d[20]), "+f"(d[21]), "+f"(d[22]), "+f"(d[23]), "+f"(d[24]), "+f"(d[25]), "+f"(d[26]), "+f"(d[27]), "+f"(d[28]), "+f"(d[29]), "+f"(d[30]), "+f"(d[31]), "+f"(d[32]), "+f"(d[33]), "+f"(d[34]), "+f"(d[35]), "+f"(d[36]), "+f"(d[37]), "+f"(d[38]), "+f"(d[39]), "+f"(d[40]), "+f"(d[41]), "+f"(d[42]), "+f"(d[43]), "+f"(d[44]), "+f"(d[45]), "+f"(d[46]), "+f"(d[47]), "+f"(d[48]), "+f"(d[49]), "+f"(d[50]), "+f"(d[51]), "+f"(d[52]), "+f"(d[53]), "+f"(d[54]), "+f"(d[55]), "+f"(d[56]), "+f"(d[57]), "+f"(d[58]), "+f"(d[59]), "+f"(d[60]), "+f"(d[61]), "+f"(d[62]), "+f"(d[63])
        : "r"(a0), "r"(a1), "r"(a2), "r"(a3), "r"(blo), "r"(bhi), "r"(scale_d));
}

__device__ __forceinline__ void wgmma_rs_n64_tb0(float (&d)[32], uint32_t a0, uint32_t a1, uint32_t a2, uint32_t a3, uint32_t blo, uint32_t bhi, int scale_d) {
    asm volatile("{\n.reg .pred p;\n.reg .b64 db;\nsetp.ne.b32 p, %38, 0;\nmov.b64 db, {%36, %37};\n"
        "wgmma.mma_async.sync.aligned.m64n64k16.f32.bf16.bf16 {%0, %1, %2, %3, %4, %5, %6, %7, %8, %9, %10, %11, %12, %13, %14, %15, %16, %17, %18, %19, %20, %21, %22, %23, %24, %25, %26, %27, %28, %29, %30, %31}, {%32, %33, %34, %35}, db, p, 1, 1, 0;\n}\n"
        : "+f"(d[0]), "+f"(d[1]), "+f"(d[2]), "+f"(d[3]), "+f"(d[4]), "+f"(d[5]), "+f"(d[6]), "+f"(d[7]), "+f"(d[8]), "+f"(d[9]), "+f"(d[10]), "+f"(d[11]), "+f"(d[12]), "+f"(d[13]), "+f"(d[14]), "+f"(d[15]), "+f"(d[16]), "+f"(d[17]), "+f"(d[18]), "+f"(d[19]), "+f"(d[20]), "+f"(d[21]), "+f"(d[22]), "+f"(d[23]), "+f"(d[24]), "+f"(d[25]), "+f"(d[26]), "+f"(d[27]), "+f"(d[28]), "+f"(d[29]), "+f"(d[30]), "+f"(d[31])
        : "r"(a0), "r"(a1), "r"(a2), "r"(a3), "r"(blo), "r"(bhi), "r"(scale_d));
}

__device__ __forceinline__ void wgmma_rs_n32_tb1(float (&d)[16], uint32_t a0, uint32_t a1, uint32_t a2, uint32_t a3, uint32_t blo, uint32_t bhi, int scale_d) {
    asm volatile("{\n.reg .pred p;\n.reg .b64 db;\nsetp.ne.b32 p, %22, 0;\nmov.b64 db, {%20, %21};\n"
        "wgmma.mma_async.sync.aligned.m64n32k16.f32.bf16.bf16 {%0, %1, %2, %3, %4, %5, %6, %7, %8, %9, %10, %11, %12, %13, %14, %15}, {%16, %17, %18, %19}, db, p, 1, 1, 1;\n}\n"
        : "+f"(d[0]), "+f"(d[1]), "+f"(d[2]), "+f"(d[3]), "+f"(d[4]), "+f"(d[5]), "+f"(d[6]), "+f"(d[7]), "+f"(d[8]), "+f"(d[9]), "+f"(d[10]), "+f"(d[11]), "+f"(d[12]), "+f"(d[13]), "+f"(d[14]), "+f"(d[15])
        : "r"(a0), "r"(a1), "r"(a2), "r"(a3), "r"(blo), "r"(bhi), "r"(scale_d));
}

__device__ __forceinline__ void wgmma_rs_n40_tb1(float (&d)[20], uint32_t a0, uint32_t a1, uint32_t a2, uint32_t a3, uint32_t blo, uint32_t bhi, int scale_d) {
    asm volatile("{\n.reg .pred p;\n.reg .b64 db;\nsetp.ne.b32 p, %26, 0;\nmov.b64 db, {%24, %25};\n"
        "wgmma.mma_async.sync.aligned.m64n40k16.f32.bf16.bf16 {%0, %1, %2, %3, %4, %5, %6, %7, %8, %9, %10, %11, %12, %13, %14, %15, %16, %17, %18, %19}, {%20, %21, %22, %23}, db, p, 1, 1, 1;\n}\n"
        : "+f"(d[0]), "+f"(d[1]), "+f"(d[2]), "+f"(d[3]), "+f"(d[4]), "+f"(d[5]), "+f"(d[6]), "+f"(d[7]), "+f"(d[8]), "+f"(d[9]), "+f"(d[10]), "+f"(d[11]), "+f"(d[12]), "+f"(d[13]), "+f"(d[14]), "+f"(d[15]), "+f"(d[16]), "+f"(d[17]), "+f"(d[18]), "+f"(d[19])
        : "r"(a0), "r"(a1), "r"(a2), "r"(a3), "r"(blo), "r"(bhi), "r"(scale_d));
}


template <int BN>
__device__ __forceinline__ void wgmma_tile(float (&d)[BN / 2], uint32_t da, uint32_t db, int sd) {
    constexpr uint32_t HI = desc_hi(1024, 1);
    if constexpr (BN == 128) wgmma_ss_n128_tb1(d, da, HI, db, HI, sd);
    else if constexpr (BN == 192) wgmma_ss_n192_tb1(d, da, HI, db, HI, sd);
    else if constexpr (BN == 224) wgmma_ss_n224_tb1(d, da, HI, db, HI, sd);
    else wgmma_ss_n256_tb1(d, da, HI, db, HI, sd);
}

__global__ void __launch_bounds__(256) prep_kernel(const bf16* __restrict__ x, const bf16* __restrict__ gate_w,
                                                   const bf16* __restrict__ w1, const bf16* __restrict__ w3) {
    const int tid = threadIdx.x;
    if (blockIdx.x < 256) {
        const int row = blockIdx.x * 8 + (tid >> 5);
        const int lane = tid & 31;
        const uint4* xr = reinterpret_cast<const uint4*>(x + (size_t)row * DM);
        const uint4* gw = reinterpret_cast<const uint4*>(gate_w);
        float v[32];
        float gsum = 0.f, sum = 0.f;
#pragma unroll
        for (int i = 0; i < 4; i++) {
            uint4 a = xr[lane + 32 * i];
            uint4 b = gw[lane + 32 * i];
            const uint32_t aa[4] = {a.x, a.y, a.z, a.w};
            const uint32_t bb[4] = {b.x, b.y, b.z, b.w};
#pragma unroll
            for (int j = 0; j < 4; j++) {
                float x0 = __uint_as_float(aa[j] << 16), x1 = __uint_as_float(aa[j] & 0xFFFF0000u);
                float g0 = __uint_as_float(bb[j] << 16), g1 = __uint_as_float(bb[j] & 0xFFFF0000u);
                v[i * 8 + j * 2] = x0;
                v[i * 8 + j * 2 + 1] = x1;
                sum += x0 + x1;
                gsum += bf16_round(x0 * g0) + bf16_round(x1 * g1);
            }
        }
#pragma unroll
        for (int o = 16; o > 0; o >>= 1) {
            sum += __shfl_xor_sync(0xffffffffu, sum, o);
            gsum += __shfl_xor_sync(0xffffffffu, gsum, o);
        }
        const float mean = sum * (1.0f / DM);
        float m2 = 0.f;
#pragma unroll
        for (int i = 0; i < 32; i++) {
            float d = v[i] - mean;
            m2 += d * d;
        }
#pragma unroll
        for (int o = 16; o > 0; o >>= 1) m2 += __shfl_xor_sync(0xffffffffu, m2, o);
        if (lane == 0) {
            g_mean1[row] = mean;
            g_rstd1[row] = rsqrtf(m2 * (1.0f / DM) + 1e-5f);
            float logit = bf16_round(gsum);
            float g = bf16_round(1.0f / (1.0f + __expf(-logit)));
            g_gate[row] = g;
            g_omg[row] = bf16_round(1.0f - g);
        }
    } else {
        __shared__ float red[32][65];
        const int strip = blockIdx.x - 256;
        const bf16* w;
        float* out;
        int ld, col0;
        if (strip < 16) { w = w1; ld = DM; col0 = strip * 64; out = g_cs1; }
        else { w = w3; ld = FF; col0 = (strip - 16) * 64; out = g_cs3; }
        const int cg = tid & 7;
        const int rg = tid >> 3;
        float acc[8];
#pragma unroll
        for (int j = 0; j < 8; j++) acc[j] = 0.f;
#pragma unroll 8
        for (int r = 0; r < 32; r++) {
            uint4 a = *reinterpret_cast<const uint4*>(w + (size_t)(r * 32 + rg) * ld + col0 + cg * 8);
            const uint32_t aa[4] = {a.x, a.y, a.z, a.w};
#pragma unroll
            for (int j = 0; j < 4; j++) {
                acc[2 * j] += __uint_as_float(aa[j] << 16);
                acc[2 * j + 1] += __uint_as_float(aa[j] & 0xFFFF0000u);
            }
        }
#pragma unroll
        for (int j = 0; j < 8; j++) red[rg][cg * 8 + j] = acc[j];
        __syncthreads();
        if (tid < 64) {
            float s = 0.f;
#pragma unroll
            for (int r = 0; r < 32; r++) s += red[r][tid];
            out[col0 + tid] = s;
        }
    }
}

template <int BN, int STAGES>
struct GemmSmem {
    static constexpr int A_BYTES = 128 * 64 * 2;
    static constexpr int B_BOXES = (BN + 63) / 64;
    static constexpr int B_BYTES = B_BOXES * 64 * 64 * 2;
    static constexpr int STAGE_BYTES = A_BYTES + B_BYTES;
    static constexpr int STG_OFF = STAGES * STAGE_BYTES;
    static constexpr int BAR_OFF = STG_OFF + 2 * 16384;
    static constexpr int TOTAL = BAR_OFF + 256 + 1024;
};

template <int MODE, int BN, int STAGES>
__global__ void __launch_bounds__(384, 1)
gemm_kernel(const __grid_constant__ CUtensorMap mA, const __grid_constant__ CUtensorMap mB0,
            const __grid_constant__ CUtensorMap mB1, const __grid_constant__ CUtensorMap mC0,
            const __grid_constant__ CUtensorMap mC1, const bf16* __restrict__ xin, int n_tiles_n, int kblocks) {
    using L = GemmSmem<BN, STAGES>;
    extern __shared__ uint8_t smem_raw[];
    const uint32_t sbase = (smem_u32(smem_raw) + 1023u) & ~1023u;
    const uint32_t bar_full = sbase + L::BAR_OFF;
    const uint32_t bar_empty = bar_full + 8 * STAGES;
    const int wg = threadIdx.x >> 7;
    const int ntiles = 16 * n_tiles_n;

    if (threadIdx.x == 0) {
        for (int s = 0; s < STAGES; s++) {
            mbar_init(bar_full + 8 * s, 1);
            mbar_init(bar_empty + 8 * s, 2);
        }
        asm volatile("fence.mbarrier_init.release.cluster;" ::: "memory");
    }
    __syncthreads();

    if (wg == 0) {
        reg_dealloc<40>();
        if (threadIdx.x == 0) {
            prefetch_tmap(&mA);
            prefetch_tmap(&mB0);
            prefetch_tmap(&mB1);
            int stage = 0;
            uint32_t phase = 1;
            for (int tile = blockIdx.x; tile < ntiles; tile += gridDim.x) {
                const int m0 = (tile & 15) * 128;
                const int n0 = (tile >> 4) * BN;
                for (int kb = 0; kb < kblocks; kb++) {
                    mbar_wait(bar_empty + 8 * stage, phase);
                    const uint32_t sa = sbase + stage * L::STAGE_BYTES;
                    const uint32_t sb = sa + L::A_BYTES;
                    const uint32_t fb = bar_full + 8 * stage;
                    mbar_expect_tx(fb, L::STAGE_BYTES);
                    int arow = m0;
                    if (MODE == 2) {
                        const int grp = kb >> 2;
                        arow += (grp == 0) ? -1 : (grp == 1) ? 1 : (grp == 2) ? -2 : 2;
                    }
                    tma_load_2d(sa, &mA, kb * 64, arow, fb);
                    const CUtensorMap* mb = &mB0;
                    int bc = n0, br = kb * 64;
                    if (MODE == 1 && n0 >= 3 * DM) { mb = &mB1; bc = n0 - 3 * DM; }
                    if (MODE == 5 && kb >= 16) { mb = &mB1; br = (kb - 16) * 64; }
#pragma unroll
                    for (int b = 0; b < L::B_BOXES; b++) tma_load_2d(sb + b * 8192, mb, bc + b * 64, br, fb);
                    if (++stage == STAGES) { stage = 0; phase ^= 1; }
                }
            }
        }
    } else {
        reg_alloc<232>();
        const int c = wg - 1;
        const int warp = (threadIdx.x >> 5) & 3;
        const int lane = threadIdx.x & 31;
        const int tid_wg = threadIdx.x & 127;
        const uint32_t stg = sbase + L::STG_OFF + c * 16384;
        int stage = 0;
        uint32_t phase = 0;
        float acc[BN / 2];
        for (int tile = blockIdx.x; tile < ntiles; tile += gridDim.x) {
            const int m0 = (tile & 15) * 128;
            const int n0 = (tile >> 4) * BN;
            int prev_stage = 0;
            for (int kb = 0; kb < kblocks; kb++) {
                mbar_wait(bar_full + 8 * stage, phase);
                const uint32_t sa = sbase + stage * L::STAGE_BYTES + c * 8192;
                const uint32_t sb = sbase + stage * L::STAGE_BYTES + L::A_BYTES;
                const uint32_t da = desc_lo(sa, 16);
                const uint32_t db = desc_lo(sb, 8192);
                wgmma_fence();
#pragma unroll
                for (int k = 0; k < 4; k++) wgmma_tile<BN>(acc, da + k * 2, db + k * 128, (kb | k) != 0);
                wgmma_commit();
                if (kb > 0) {
                    wgmma_wait<1>();
                    if (tid_wg == 0) mbar_arrive(bar_empty + 8 * prev_stage);
                }
                prev_stage = stage;
                if (++stage == STAGES) { stage = 0; phase ^= 1; }
            }
            wgmma_wait<0>();
            if (tid_wg == 0) mbar_arrive(bar_empty + 8 * prev_stage);

            const int r0 = m0 + c * 64 + warp * 16 + (lane >> 2);
            const int r1 = r0 + 8;
            const int cq = (lane & 3) * 2;
            const CUtensorMap* mc = &mC0;
            int out_c0 = n0;
            if (MODE == 1) {
                if (n0 >= 3 * DM) {
                    mc = &mC1;
                    out_c0 = n0 - 3 * DM;
                    const float mu0 = g_mean1[r0], mu1 = g_mean1[r1];
                    const float rs0 = g_rstd1[r0], rs1 = g_rstd1[r1];
#pragma unroll
                    for (int j = 0; j < BN / 8; j++) {
                        const float2 cs = *reinterpret_cast<const float2*>(&g_cs1[out_c0 + 8 * j + cq]);
                        acc[4 * j + 0] = gelu_tanh(rs0 * fmaf(-mu0, cs.x, acc[4 * j + 0]));
                        acc[4 * j + 1] = gelu_tanh(rs0 * fmaf(-mu0, cs.y, acc[4 * j + 1]));
                        acc[4 * j + 2] = gelu_tanh(rs1 * fmaf(-mu1, cs.x, acc[4 * j + 2]));
                        acc[4 * j + 3] = gelu_tanh(rs1 * fmaf(-mu1, cs.y, acc[4 * j + 3]));
                    }
                }
            } else if (MODE == 2) {
                float s0 = 0.f, s1 = 0.f;
#pragma unroll
                for (int j = 0; j < BN / 8; j++) {
                    const uint32_t xa = *reinterpret_cast<const uint32_t*>(xin + (size_t)r0 * DM + n0 + 8 * j + cq);
                    const uint32_t xb = *reinterpret_cast<const uint32_t*>(xin + (size_t)r1 * DM + n0 + 8 * j + cq);
                    acc[4 * j + 0] = bf16_round(bf16_round(acc[4 * j + 0]) + __uint_as_float(xa << 16));
                    acc[4 * j + 1] = bf16_round(bf16_round(acc[4 * j + 1]) + __uint_as_float(xa & 0xFFFF0000u));
                    acc[4 * j + 2] = bf16_round(bf16_round(acc[4 * j + 2]) + __uint_as_float(xb << 16));
                    acc[4 * j + 3] = bf16_round(bf16_round(acc[4 * j + 3]) + __uint_as_float(xb & 0xFFFF0000u));
                    s0 += acc[4 * j + 0] + acc[4 * j + 1];
                    s1 += acc[4 * j + 2] + acc[4 * j + 3];
                }
                s0 += __shfl_xor_sync(0xffffffffu, s0, 1);
                s0 += __shfl_xor_sync(0xffffffffu, s0, 2);
                s1 += __shfl_xor_sync(0xffffffffu, s1, 1);
                s1 += __shfl_xor_sync(0xffffffffu, s1, 2);
                const float mu0 = s0 * (1.0f / BN), mu1 = s1 * (1.0f / BN);
                float q0 = 0.f, q1 = 0.f;
#pragma unroll
                for (int j = 0; j < BN / 8; j++) {
                    float d;
                    d = acc[4 * j + 0] - mu0; q0 += d * d;
                    d = acc[4 * j + 1] - mu0; q0 += d * d;
                    d = acc[4 * j + 2] - mu1; q1 += d * d;
                    d = acc[4 * j + 3] - mu1; q1 += d * d;
                }
                q0 += __shfl_xor_sync(0xffffffffu, q0, 1);
                q0 += __shfl_xor_sync(0xffffffffu, q0, 2);
                q1 += __shfl_xor_sync(0xffffffffu, q1, 1);
                q1 += __shfl_xor_sync(0xffffffffu, q1, 2);
                if ((lane & 3) == 0) {
                    static_assert(MODE != 2 || BN == 128, "stats layout assumes BN=128");
                    g_stat2[r0 * 8 + (n0 >> 7)] = make_float2(s0, q0);
                    g_stat2[r1 * 8 + (n0 >> 7)] = make_float2(s1, q1);
                }
            } else if (MODE == 3) {
                out_c0 = n0 + DM;
                float mu[2], rs[2];
#pragma unroll
                for (int h = 0; h < 2; h++) {
                    const float4* sp = reinterpret_cast<const float4*>(&g_stat2[(h ? r1 : r0) * 8]);
                    float4 p[4];
                    float s = 0.f;
#pragma unroll
                    for (int i = 0; i < 4; i++) { p[i] = sp[i]; s += p[i].x + p[i].z; }
                    const float mean = s * (1.0f / DM);
                    float m2 = 0.f;
#pragma unroll
                    for (int i = 0; i < 4; i++) {
                        float d0 = p[i].x * (1.0f / 128) - mean, d1 = p[i].z * (1.0f / 128) - mean;
                        m2 += p[i].y + p[i].w + 128.0f * (d0 * d0 + d1 * d1);
                    }
                    mu[h] = mean;
                    rs[h] = rsqrtf(m2 * (1.0f / DM) + 1e-5f);
                }
                const float og0 = g_omg[r0], og1 = g_omg[r1];
#pragma unroll
                for (int j = 0; j < BN / 8; j++) {
                    const float2 cs = *reinterpret_cast<const float2*>(&g_cs3[n0 + 8 * j + cq]);
                    acc[4 * j + 0] = og0 * gelu_tanh(rs[0] * fmaf(-mu[0], cs.x, acc[4 * j + 0]));
                    acc[4 * j + 1] = og0 * gelu_tanh(rs[0] * fmaf(-mu[0], cs.y, acc[4 * j + 1]));
                    acc[4 * j + 2] = og1 * gelu_tanh(rs[1] * fmaf(-mu[1], cs.x, acc[4 * j + 2]));
                    acc[4 * j + 3] = og1 * gelu_tanh(rs[1] * fmaf(-mu[1], cs.y, acc[4 * j + 3]));
                }
            } else {
                const float og0 = g_omg[r0], og1 = g_omg[r1];
#pragma unroll
                for (int j = 0; j < BN / 8; j++) {
                    const uint32_t xa = *reinterpret_cast<const uint32_t*>(xin + (size_t)r0 * DM + n0 + 8 * j + cq);
                    const uint32_t xb = *reinterpret_cast<const uint32_t*>(xin + (size_t)r1 * DM + n0 + 8 * j + cq);
                    acc[4 * j + 0] = fmaf(og0, __uint_as_float(xa << 16), acc[4 * j + 0]);
                    acc[4 * j + 1] = fmaf(og0, __uint_as_float(xa & 0xFFFF0000u), acc[4 * j + 1]);
                    acc[4 * j + 2] = fmaf(og1, __uint_as_float(xb << 16), acc[4 * j + 2]);
                    acc[4 * j + 3] = fmaf(og1, __uint_as_float(xb & 0xFFFF0000u), acc[4 * j + 3]);
                }
            }
            const int srow = warp * 16 + (lane & 7) + ((lane >> 3) & 1) * 8;
#pragma unroll
            for (int rnd = 0; rnd < (BN + 127) / 128; rnd++) {
                if (tid_wg == 0) bulk_wait_read0();
                named_bar_sync(1 + c, 128);
#pragma unroll
                for (int jj = 0; jj < 8; jj++) {
                    const int j = rnd * 16 + jj * 2;
                    if (j * 8 < BN) {
                        const int jb = jj * 2 + (lane >> 4);
                        const uint32_t addr = stg + (jb >> 3) * 8192 + srow * 128 + (((jb & 7) ^ (srow & 7)) << 4);
                        stmatrix_x4(addr, pack_bf16(acc[4 * j + 0], acc[4 * j + 1]), pack_bf16(acc[4 * j + 2], acc[4 * j + 3]),
                                    pack_bf16(acc[4 * j + 4], acc[4 * j + 5]), pack_bf16(acc[4 * j + 6], acc[4 * j + 7]));
                    }
                }
                fence_proxy_async();
                named_bar_sync(1 + c, 128);
                if (tid_wg == 0) {
                    tma_store_2d(mc, stg, out_c0 + rnd * 128, m0 + c * 64);
                    if (rnd * 128 + 64 < BN) tma_store_2d(mc, stg + 8192, out_c0 + rnd * 128 + 64, m0 + c * 64);
                    bulk_commit();
                }
            }
        }
        if (tid_wg == 0) bulk_wait0();
    }
}

constexpr int ATT_STAGES = 4;
constexpr int ATT_DIST = 2;
constexpr int ATT_Q_OFF = ATT_STAGES * 16384;
constexpr int ATT_ONES_OFF = ATT_Q_OFF + 8192;
constexpr int ATT_BAR_OFF = ATT_ONES_OFF + 4096;
constexpr int ATT_SMEM = ATT_BAR_OFF + 256 + 1024;

struct AttState {
    float o[20];
    float m0, m1;
};

__device__ __forceinline__ void attn_step(float (&sc)[32], float (&sn)[32], uint32_t (&p)[16], uint32_t dq,
                                          AttState& st, uint32_t dk_next, uint32_t dv_prev, uint32_t release_bar) {
    const float cs = 0.17677669529663687f * 1.4426950408889634f;
    constexpr uint32_t HI = desc_hi(512, 2);
    wgmma_fence();
    wgmma_ss_n64_tb0(sn, dq, HI, dk_next, HI, 0);
    wgmma_ss_n64_tb0(sn, dq + 2, HI, dk_next + 2, HI, 1);
#pragma unroll
    for (int t = 0; t < 4; t++)
        wgmma_rs_n40_tb1(st.o, p[4 * t], p[4 * t + 1], p[4 * t + 2], p[4 * t + 3], dv_prev + t * 64, HI, 1);
    wgmma_commit();
    float mx0 = fmaxf(sc[0], sc[1]), mx1 = fmaxf(sc[2], sc[3]);
#pragma unroll
    for (int i = 1; i < 8; i++) {
        mx0 = fmaxf(mx0, fmaxf(sc[4 * i], sc[4 * i + 1]));
        mx1 = fmaxf(mx1, fmaxf(sc[4 * i + 2], sc[4 * i + 3]));
    }
    mx0 = fmaxf(mx0, __shfl_xor_sync(0xffffffffu, mx0, 1));
    mx1 = fmaxf(mx1, __shfl_xor_sync(0xffffffffu, mx1, 1));
    mx0 = fmaxf(mx0, __shfl_xor_sync(0xffffffffu, mx0, 2));
    mx1 = fmaxf(mx1, __shfl_xor_sync(0xffffffffu, mx1, 2));
    const float mo0 = st.m0, mo1 = st.m1;
    const float mn0 = fmaxf(mo0, mx0), mn1 = fmaxf(mo1, mx1);
    st.m0 = mn0; st.m1 = mn1;
    const float b0 = mn0 * cs, b1 = mn1 * cs;
#pragma unroll
    for (int i = 0; i < 8; i++) {
        sc[4 * i + 0] = ex2(fmaf(sc[4 * i + 0], cs, -b0));
        sc[4 * i + 1] = ex2(fmaf(sc[4 * i + 1], cs, -b0));
        sc[4 * i + 2] = ex2(fmaf(sc[4 * i + 2], cs, -b1));
        sc[4 * i + 3] = ex2(fmaf(sc[4 * i + 3], cs, -b1));
    }
    wgmma_wait<0>();
    if (release_bar != 0 && (threadIdx.x & 127) == 0) mbar_arrive(release_bar);
    if (__any_sync(0xffffffffu, (mn0 > mo0) || (mn1 > mo1))) {
        const float a0 = ex2((mo0 - mn0) * cs), a1 = ex2((mo1 - mn1) * cs);
#pragma unroll
        for (int i = 0; i < 5; i++) {
            st.o[4 * i + 0] *= a0; st.o[4 * i + 1] *= a0;
            st.o[4 * i + 2] *= a1; st.o[4 * i + 3] *= a1;
        }
    }
#pragma unroll
    for (int i = 0; i < 8; i++) {
        p[2 * i] = pack_bf16(sc[4 * i + 0], sc[4 * i + 1]);
        p[2 * i + 1] = pack_bf16(sc[4 * i + 2], sc[4 * i + 3]);
    }
}

__global__ void __launch_bounds__(256, 2)
attn_kernel(const __grid_constant__ CUtensorMap mKV) {
    extern __shared__ uint8_t smem_raw[];
    const uint32_t sbase = (smem_u32(smem_raw) + 1023u) & ~1023u;
    const uint32_t bar_kfull = sbase + ATT_BAR_OFF;
    const uint32_t bar_vfull = bar_kfull + 8 * ATT_STAGES;
    const uint32_t bar_empty = bar_vfull + 8 * ATT_STAGES;
    const int head = blockIdx.x >> 4;
    const int q0 = (blockIdx.x & 15) * 128;
    const int warp_id = threadIdx.x >> 5;
    const int lane = threadIdx.x & 31;
    constexpr int NBLK = S_LEN / 128;

    if (threadIdx.x == 0) {
        for (int s = 0; s < ATT_STAGES; s++) {
            mbar_init(bar_kfull + 8 * s, 1);
            mbar_init(bar_vfull + 8 * s, 1);
            mbar_init(bar_empty + 8 * s, 2);
        }
        asm volatile("fence.mbarrier_init.release.cluster;" ::: "memory");
        prefetch_tmap(&mKV);
#pragma unroll
        for (int j = 0; j < ATT_DIST; j++) {
            const uint32_t sk = sbase + j * 16384;
            mbar_expect_tx(bar_kfull + 8 * j, j == 0 ? 16384 : 8192);
            if (j == 0) tma_load_2d(sbase + ATT_Q_OFF, &mKV, head * DH, q0, bar_kfull);
            tma_load_2d(sk, &mKV, DM + head * DH, j * 128, bar_kfull + 8 * j);
            mbar_expect_tx(bar_vfull + 8 * j, 8192);
            tma_load_2d(sk + 8192, &mKV, 2 * DM + head * DH, j * 128, bar_vfull + 8 * j);
        }
    }
    asm volatile("st.shared.v4.b32 [%0], {%1, %1, %1, %1};" ::"r"(sbase + ATT_ONES_OFF + threadIdx.x * 16), "r"(0x3F803F80u) : "memory");
    fence_proxy_async();
    __syncthreads();

    const int row0 = q0 + warp_id * 16 + (lane >> 2);
    const int cq = (lane & 3) * 2;
    const uint32_t dq = desc_lo(sbase + ATT_Q_OFF + (threadIdx.x >> 7) * 4096, 16);
    AttState st;
#pragma unroll
    for (int i = 0; i < 20; i++) st.o[i] = 0.f;
    st.m0 = -INFINITY; st.m1 = -INFINITY;
    float s0[32], s1[32];
    constexpr uint32_t HI = desc_hi(512, 2);
    const uint32_t dk0 = desc_lo(sbase, 16);
    const uint32_t dv0 = desc_lo(sbase + 8192, ATT_ONES_OFF - 8192);
    uint32_t p[16];
#pragma unroll
    for (int i = 0; i < 16; i++) p[i] = 0u;
    mbar_wait(bar_kfull, 0);
    wgmma_fence();
    wgmma_ss_n64_tb0(s0, dq, HI, dk0, HI, 0);
    wgmma_ss_n64_tb0(s0, dq + 2, HI, dk0 + 2, HI, 1);
    wgmma_commit();
    mbar_wait(bar_vfull, 0);
    wgmma_wait<0>();
    int stage = 0;
    uint32_t phase = 0;
    uint32_t dv_prev = dv0;
#pragma unroll 1
    for (int j = 0; j < NBLK; j++) {
        if (threadIdx.x == 0 && j + ATT_DIST < NBLK) {
            const int jn = j + ATT_DIST;
            const int sn = jn % ATT_STAGES;
            if (jn >= ATT_STAGES) mbar_wait(bar_empty + 8 * sn, ((jn / ATT_STAGES) - 1) & 1);
            const uint32_t skn = sbase + sn * 16384;
            mbar_expect_tx(bar_kfull + 8 * sn, 8192);
            tma_load_2d(skn, &mKV, DM + head * DH, jn * 128, bar_kfull + 8 * sn);
            mbar_expect_tx(bar_vfull + 8 * sn, 8192);
            tma_load_2d(skn + 8192, &mKV, 2 * DM + head * DH, jn * 128, bar_vfull + 8 * sn);
        }
        __syncwarp();
        const uint32_t dk = dk0 + stage * 1024;
        const uint32_t dv = dv0 + stage * 1024 - ((uint32_t)(stage * 1024) << 16);
        const int pstage = (stage + ATT_STAGES - 1) % ATT_STAGES;
        attn_step(s0, s1, p, dq, st, dk + 256, dv_prev, j > 0 ? bar_empty + 8 * pstage : 0u);
        int nstage = stage + 1;
        uint32_t nphase = phase;
        if (nstage == ATT_STAGES) { nstage = 0; nphase ^= 1; }
        uint32_t dkn = dk;
        if (j + 1 < NBLK) {
            mbar_wait(bar_kfull + 8 * nstage, nphase);
            dkn = dk0 + nstage * 1024;
        }
        mbar_wait(bar_vfull + 8 * stage, phase);
        attn_step(s1, s0, p, dq, st, dkn, dv, 0u);
        dv_prev = dv + 256 - (256u << 16);
        stage = nstage;
        phase = nphase;
    }
    wgmma_fence();
#pragma unroll
    for (int t = 0; t < 4; t++)
        wgmma_rs_n40_tb1(st.o, p[4 * t], p[4 * t + 1], p[4 * t + 2], p[4 * t + 3], dv_prev + t * 64, HI, 1);
    wgmma_commit();
    wgmma_wait<0>();
    const float f0 = g_gate[row0] / st.o[16], f1 = g_gate[row0 + 8] / st.o[18];
    bf16* op0 = g_a5 + (size_t)row0 * A5W + head * DH + cq;
    bf16* op1 = op0 + 8 * A5W;
#pragma unroll
    for (int i = 0; i < 4; i++) {
        *reinterpret_cast<uint32_t*>(op0 + 8 * i) = pack_bf16(st.o[4 * i] * f0, st.o[4 * i + 1] * f0);
        *reinterpret_cast<uint32_t*>(op1 + 8 * i) = pack_bf16(st.o[4 * i + 2] * f1, st.o[4 * i + 3] * f1);
    }
}

typedef CUresult (*EncodeFn)(CUtensorMap*, CUtensorMapDataType, cuuint32_t, void*, const cuuint64_t*, const cuuint64_t*,
                             const cuuint32_t*, const cuuint32_t*, CUtensorMapInterleave, CUtensorMapSwizzle,
                             CUtensorMapL2promotion, CUtensorMapFloatOOBfill);

static CUtensorMap make_map(EncodeFn fn, const void* ptr, int rows, int cols, int box_cols, int box_rows,
                            CUtensorMapSwizzle swz) {
    CUtensorMap m;
    cuuint64_t dims[2] = {(cuuint64_t)cols, (cuuint64_t)rows};
    cuuint64_t strides[1] = {(cuuint64_t)cols * 2};
    cuuint32_t box[2] = {(cuuint32_t)box_cols, (cuuint32_t)box_rows};
    cuuint32_t es[2] = {1, 1};
    fn(&m, CU_TENSOR_MAP_DATA_TYPE_BFLOAT16, 2, const_cast<void*>(ptr), dims, strides, box, es,
       CU_TENSOR_MAP_INTERLEAVE_NONE, swz, CU_TENSOR_MAP_L2_PROMOTION_L2_256B, CU_TENSOR_MAP_FLOAT_OOB_FILL_NONE);
    return m;
}

extern "C" void kernel_launch(void* const* d_in, const int* in_sizes, int n_in, void* d_out, int out_size) {
    const bf16* x = (const bf16*)d_in[0];
    const bf16* wqkv = (const bf16*)d_in[1];
    const bf16* wo = (const bf16*)d_in[2];
    const bf16* w1 = (const bf16*)d_in[4];
    const bf16* w2 = (const bf16*)d_in[5];
    const bf16* w3 = (const bf16*)d_in[6];
    const bf16* w4 = (const bf16*)d_in[7];
    const bf16* gate_w = (const bf16*)d_in[8];

    static EncodeFn enc = nullptr;
    static void *p_qkv, *p_h, *p_x1, *p_a5;
    if (!enc) {
        void* fn = nullptr;
        cudaDriverEntryPointQueryResult qres;
        cudaGetDriverEntryPoint("cuTensorMapEncodeTiled", &fn, cudaEnableDefault, &qres);
        enc = (EncodeFn)fn;
        cudaGetSymbolAddress(&p_qkv, g_qkv);
        cudaGetSymbolAddress(&p_h, g_h);
        cudaGetSymbolAddress(&p_x1, g_x1);
        cudaGetSymbolAddress(&p_a5, g_a5);
        cudaFuncSetAttribute(gemm_kernel<1, 256, 4>, cudaFuncAttributeMaxDynamicSharedMemorySize, GemmSmem<256, 4>::TOTAL);
        cudaFuncSetAttribute(gemm_kernel<2, 128, 5>, cudaFuncAttributeMaxDynamicSharedMemorySize, GemmSmem<128, 5>::TOTAL);
        cudaFuncSetAttribute(gemm_kernel<3, 256, 4>, cudaFuncAttributeMaxDynamicSharedMemorySize, GemmSmem<256, 4>::TOTAL);
        cudaFuncSetAttribute(gemm_kernel<5, 128, 5>, cudaFuncAttributeMaxDynamicSharedMemorySize, GemmSmem<128, 5>::TOTAL);
        cudaFuncSetAttribute(attn_kernel, cudaFuncAttributeMaxDynamicSharedMemorySize, ATT_SMEM);
    }
    const CUtensorMapSwizzle SW128 = CU_TENSOR_MAP_SWIZZLE_128B, SW64 = CU_TENSOR_MAP_SWIZZLE_64B;
    CUtensorMap mX = make_map(enc, x, S_LEN, DM, 64, 128, SW128);
    CUtensorMap mWqkv = make_map(enc, wqkv, DM, 3 * DM, 64, 64, SW128);
    CUtensorMap mW1 = make_map(enc, w1, DM, DM, 64, 64, SW128);
    CUtensorMap mW2 = make_map(enc, w2, DM, DM, 64, 64, SW128);
    CUtensorMap mW3 = make_map(enc, w3, DM, FF, 64, 64, SW128);
    CUtensorMap mW4 = make_map(enc, w4, FF, DM, 64, 64, SW128);
    CUtensorMap mWo = make_map(enc, wo, DM, DM, 64, 64, SW128);
    CUtensorMap mQKVst = make_map(enc, p_qkv, S_LEN, 3 * DM, 64, 64, SW128);
    CUtensorMap mKV = make_map(enc, p_qkv, S_LEN, 3 * DM, 32, 128, SW64);
    CUtensorMap mHst = make_map(enc, p_h, S_LEN, DM, 64, 64, SW128);
    CUtensorMap mHld = make_map(enc, p_h, S_LEN, DM, 64, 128, SW128);
    CUtensorMap mX1st = make_map(enc, p_x1, S_LEN, DM, 64, 64, SW128);
    CUtensorMap mX1ld = make_map(enc, p_x1, S_LEN, DM, 64, 128, SW128);
    CUtensorMap mA5st = make_map(enc, p_a5, S_LEN, A5W, 64, 64, SW128);
    CUtensorMap mA5ld = make_map(enc, p_a5, S_LEN, A5W, 64, 128, SW128);
    CUtensorMap mOut = make_map(enc, d_out, S_LEN, DM, 64, 64, SW128);

    cudaStream_t st = cudaStreamPerThread;
    prep_kernel<<<256 + 72, 256, 0, st>>>(x, gate_w, w1, w3);
    gemm_kernel<1, 256, 4><<<132, 384, GemmSmem<256, 4>::TOTAL, st>>>(mX, mWqkv, mW1, mQKVst, mHst, x, 16, 16);
    attn_kernel<<<NH * 16, 256, ATT_SMEM, st>>>(mKV);
    gemm_kernel<2, 128, 5><<<128, 384, GemmSmem<128, 5>::TOTAL, st>>>(mHld, mW2, mW2, mX1st, mX1st, x, 8, 16);
    gemm_kernel<3, 256, 4><<<132, 384, GemmSmem<256, 4>::TOTAL, st>>>(mX1ld, mW3, mW3, mA5st, mA5st, x, 14, 16);
    gemm_kernel<5, 128, 5><<<128, 384, GemmSmem<128, 5>::TOTAL, st>>>(mA5ld, mWo, mW4, mOut, mOut, (const bf16*)p_x1, 8, 72);
}
```

```cpp
#include <cuda_runtime.h>
#include <cuda_bf16.h>
#include <cuda.h>
#include <stdint.h>

typedef __nv_bfloat16 bf16;

constexpr int S_LEN = 2048;
constexpr int DM = 1024;
constexpr int FF = 3584;
constexpr int NH = 32;
constexpr int DH = 32;
constexpr int A5W = DM + FF;

__device__ __align__(1024) bf16 g_qkv[S_LEN * 3 * DM];
__device__ __align__(1024) bf16 g_h[S_LEN * DM];
__device__ __align__(1024) bf16 g_x1[S_LEN * DM];
__device__ __align__(1024) bf16 g_a5[S_LEN * A5W];
__device__ __align__(16) float g_mean1[S_LEN];
__device__ __align__(16) float g_rstd1[S_LEN];
__device__ __align__(16) float g_gate[S_LEN];
__device__ __align__(16) float g_omg[S_LEN];
__device__ __align__(16) float g_cs1[DM];
__device__ __align__(16) float g_cs3[FF];
__device__ __align__(16) float2 g_stat2[S_LEN * 8];

__device__ __forceinline__ uint32_t smem_u32(const void* p) { return (uint32_t)__cvta_generic_to_shared(p); }

__device__ __forceinline__ void mbar_init(uint32_t bar, uint32_t count) {
    asm volatile("mbarrier.init.shared::cta.b64 [%0], %1;" ::"r"(bar), "r"(count));
}
__device__ __forceinline__ void mbar_expect_tx(uint32_t bar, uint32_t bytes) {
    asm volatile("mbarrier.arrive.expect_tx.shared::cta.b64 _, [%0], %1;" ::"r"(bar), "r"(bytes) : "memory");
}
__device__ __forceinline__ void mbar_arrive(uint32_t bar) {
    asm volatile("mbarrier.arrive.shared::cta.b64 _, [%0];" ::"r"(bar) : "memory");
}
__device__ __forceinline__ bool mbar_try_wait(uint32_t bar, uint32_t parity) {
    uint32_t ok;
    asm volatile(
        "{\n.reg .pred p;\n"
        "mbarrier.try_wait.parity.shared::cta.b64 p, [%1], %2;\n"
        "selp.u32 %0, 1, 0, p;\n}\n"
        : "=r"(ok)
        : "r"(bar), "r"(parity)
        : "memory");
    return ok != 0;
}
__device__ __forceinline__ void mbar_wait(uint32_t bar, uint32_t parity) {
    uint32_t spins = 0;
    while (!mbar_try_wait(bar, parity)) {
        if (++spins > (1u << 24)) __trap();
    }
}
__device__ __forceinline__ void tma_load_2d(uint32_t dst, const CUtensorMap* map, int c0, int c1, uint32_t bar) {
    asm volatile(
        "cp.async.bulk.tensor.2d.shared::cluster.global.mbarrier::complete_tx::bytes [%0], [%1, {%3, %4}], [%2];"
        ::"r"(dst), "l"(map), "r"(bar), "r"(c0), "r"(c1)
        : "memory");
}
__device__ __forceinline__ void tma_store_2d(const CUtensorMap* map, uint32_t src, int c0, int c1) {
    asm volatile("cp.async.bulk.tensor.2d.global.shared::cta.bulk_group [%0, {%2, %3}], [%1];"
                 ::"l"(map), "r"(src), "r"(c0), "r"(c1)
                 : "memory");
}
__device__ __forceinline__ void bulk_commit() { asm volatile("cp.async.bulk.commit_group;" ::: "memory"); }
__device__ __forceinline__ void bulk_wait_read0() { asm volatile("cp.async.bulk.wait_group.read 0;" ::: "memory"); }
__device__ __forceinline__ void bulk_wait0() { asm volatile("cp.async.bulk.wait_group 0;" ::: "memory"); }
__device__ __forceinline__ void fence_proxy_async() { asm volatile("fence.proxy.async.shared::cta;" ::: "memory"); }
__device__ __forceinline__ void named_bar_sync(int id, int n) { asm volatile("bar.sync %0, %1;" ::"r"(id), "r"(n) : "memory"); }
__device__ __forceinline__ void named_bar_arrive(int id, int n) { asm volatile("bar.arrive %0, %1;" ::"r"(id), "r"(n) : "memory"); }
__device__ __forceinline__ void wgmma_fence() { asm volatile("wgmma.fence.sync.aligned;" ::: "memory"); }
__device__ __forceinline__ void wgmma_commit() { asm volatile("wgmma.commit_group.sync.aligned;" ::: "memory"); }
template <int N>
__device__ __forceinline__ void wgmma_wait() { asm volatile("wgmma.wait_group.sync.aligned %0;" ::"n"(N) : "memory"); }
__device__ __forceinline__ void prefetch_tmap(const CUtensorMap* m) {
    asm volatile("prefetch.tensormap [%0];" ::"l"(m) : "memory");
}
template <int R>
__device__ __forceinline__ void reg_alloc() { asm volatile("setmaxnreg.inc.sync.aligned.u32 %0;" ::"n"(R)); }
template <int R>
__device__ __forceinline__ void reg_dealloc() { asm volatile("setmaxnreg.dec.sync.aligned.u32 %0;" ::"n"(R)); }
__device__ __forceinline__ void stmatrix_x4(uint32_t addr, uint32_t r0, uint32_t r1, uint32_t r2, uint32_t r3) {
    asm volatile("stmatrix.sync.aligned.m8n8.x4.shared.b16 [%0], {%1, %2, %3, %4};"
                 ::"r"(addr), "r"(r0), "r"(r1), "r"(r2), "r"(r3)
                 : "memory");
}
__device__ __forceinline__ uint32_t pack_bf16(float lo, float hi) {
    uint32_t r;
    asm("cvt.rn.bf16x2.f32 %0, %1, %2;" : "=r"(r) : "f"(hi), "f"(lo));
    return r;
}
__device__ __forceinline__ float bf16_round(float v) { return __bfloat162float(__float2bfloat16_rn(v)); }
__device__ __forceinline__ float ex2(float x) {
    float y;
    asm("ex2.approx.ftz.f32 %0, %1;" : "=f"(y) : "f"(x));
    return y;
}
__device__ __forceinline__ float tanh_fast(float x) {
    float y;
    asm("tanh.approx.f32 %0, %1;" : "=f"(y) : "f"(x));
    return y;
}
__device__ __forceinline__ float gelu_tanh(float v) {
    float u = 0.7978845608028654f * (v + 0.044715f * v * v * v);
    float hv = 0.5f * v;
    return fmaf(hv, tanh_fast(u), hv);
}
__device__ __forceinline__ uint32_t desc_lo(uint32_t addr, uint32_t lbo_bytes) {
    return ((addr & 0x3FFFF) >> 4) | (((lbo_bytes >> 4) & 0x3FFF) << 16);
}
__host__ __device__ constexpr uint32_t desc_hi(uint32_t sbo_bytes, uint32_t swz) {
    return ((sbo_bytes >> 4) & 0x3FFF) | (swz << 30);
}


__device__ __forceinline__ void wgmma_ss_n128_tb1(float (&d)[64], uint32_t alo, uint32_t ahi, uint32_t blo, uint32_t bhi, int scale_d) {
    asm volatile("{\n.reg .pred p;\n.reg .b64 da, db;\nsetp.ne.b32 p, %68, 0;\nmov.b64 da, {%64, %65};\nmov.b64 db, {%66, %67};\n"
        "wgmma.mma_async.sync.aligned.m64n128k16.f32.bf16.bf16 {%0, %1, %2, %3, %4, %5, %6, %7, %8, %9, %10, %11, %12, %13, %14, %15, %16, %17, %18, %19, %20, %21, %22, %23, %24, %25, %26, %27, %28, %29, %30, %31, %32, %33, %34, %35, %36, %37, %38, %39, %40, %41, %42, %43, %44, %45, %46, %47, %48, %49, %50, %51, %52, %53, %54, %55, %56, %57, %58, %59, %60, %61, %62, %63}, da, db, p, 1, 1, 0, 1;\n}\n"
        : "+f"(d[0]), "+f"(d[1]), "+f"(d[2]), "+f"(d[3]), "+f"(d[4]), "+f"(d[5]), "+f"(d[6]), "+f"(d[7]), "+f"(d[8]), "+f"(d[9]), "+f"(d[10]), "+f"(d[11]), "+f"(d[12]), "+f"(d[13]), "+f"(d[14]), "+f"(d[15]), "+f"(d[16]), "+f"(d[17]), "+f"(d[18]), "+f"(d[19]), "+f"(d[20]), "+f"(d[21]), "+f"(d[22]), "+f"(d[23]), "+f"(d[24]), "+f"(d[25]), "+f"(d[26]), "+f"(d[27]), "+f"(d[28]), "+f"(d[29]), "+f"(d[30]), "+f"(d[31]), "+f"(d[32]), "+f"(d[33]), "+f"(d[34]), "+f"(d[35]), "+f"(d[36]), "+f"(d[37]), "+f"(d[38]), "+f"(d[39]), "+f"(d[40]), "+f"(d[41]), "+f"(d[42]), "+f"(d[43]), "+f"(d[44]), "+f"(d[45]), "+f"(d[46]), "+f"(d[47]), "+f"(d[48]), "+f"(d[49]), "+f"(d[50]), "+f"(d[51]), "+f"(d[52]), "+f"(d[53]), "+f"(d[54]), "+f"(d[55]), "+f"(d[56]), "+f"(d[57]), "+f"(d[58]), "+f"(d[59]), "+f"(d[60]), "+f"(d[61]), "+f"(d[62]), "+f"(d[63])
        : "r"(alo), "r"(ahi), "r"(blo), "r"(bhi), "r"(scale_d));
}

__device__ __forceinline__ void wgmma_ss_n192_tb1(float (&d)[96], uint32_t alo, uint32_t ahi, uint32_t blo, uint32_t bhi, int scale_d) {
    asm volatile("{\n.reg .pred p;\n.reg .b64 da, db;\nsetp.ne.b32 p, %100, 0;\nmov.b64 da, {%96, %97};\nmov.b64 db, {%98, %99};\n"
        "wgmma.mma_async.sync.aligned.m64n192k16.f32.bf16.bf16 {%0, %1, %2, %3, %4, %5, %6, %7, %8, %9, %10, %11, %12, %13, %14, %15, %16, %17, %18, %19, %20, %21, %22, %23, %24, %25, %26, %27, %28, %29, %30, %31, %32, %33, %34, %35, %36, %37, %38, %39, %40, %41, %42, %43, %44, %45, %46, %47, %48, %49, %50, %51, %52, %53, %54, %55, %56, %57, %58, %59, %60, %61, %62, %63, %64, %65, %66, %67, %68, %69, %70, %71, %72, %73, %74, %75, %76, %77, %78, %79, %80, %81, %82, %83, %84, %85, %86, %87, %88, %89, %90, %91, %92, %93, %94, %95}, da, db, p, 1, 1, 0, 1;\n}\n"
        : "+f"(d[0]), "+f"(d[1]), "+f"(d[2]), "+f"(d[3]), "+f"(d[4]), "+f"(d[5]), "+f"(d[6]), "+f"(d[7]), "+f"(d[8]), "+f"(d[9]), "+f"(d[10]), "+f"(d[11]), "+f"(d[12]), "+f"(d[13]), "+f"(d[14]), "+f"(d[15]), "+f"(d[16]), "+f"(d[17]), "+f"(d[18]), "+f"(d[19]), "+f"(d[20]), "+f"(d[21]), "+f"(d[22]), "+f"(d[23]), "+f"(d[24]), "+f"(d[25]), "+f"(d[26]), "+f"(d[27]), "+f"(d[28]), "+f"(d[29]), "+f"(d[30]), "+f"(d[31]), "+f"(d[32]), "+f"(d[33]), "+f"(d[34]), "+f"(d[35]), "+f"(d[36]), "+f"(d[37]), "+f"(d[38]), "+f"(d[39]), "+f"(d[40]), "+f"(d[41]), "+f"(d[42]), "+f"(d[43]), "+f"(d[44]), "+f"(d[45]), "+f"(d[46]), "+f"(d[47]), "+f"(d[48]), "+f"(d[49]), "+f"(d[50]), "+f"(d[51]), "+f"(d[52]), "+f"(d[53]), "+f"(d[54]), "+f"(d[55]), "+f"(d[56]), "+f"(d[57]), "+f"(d[58]), "+f"(d[59]), "+f"(d[60]), "+f"(d[61]), "+f"(d[62]), "+f"(d[63]), "+f"(d[64]), "+f"(d[65]), "+f"(d[66]), "+f"(d[67]), "+f"(d[68]), "+f"(d[69]), "+f"(d[70]), "+f"(d[71]), "+f"(d[72]), "+f"(d[73]), "+f"(d[74]), "+f"(d[75]), "+f"(d[76]), "+f"(d[77]), "+f"(d[78]), "+f"(d[79]), "+f"(d[80]), "+f"(d[81]), "+f"(d[82]), "+f"(d[83]), "+f"(d[84]), "+f"(d[85]), "+f"(d[86]), "+f"(d[87]), "+f"(d[88]), "+f"(d[89]), "+f"(d[90]), "+f"(d[91]), "+f"(d[92]), "+f"(d[93]), "+f"(d[94]), "+f"(d[95])
        : "r"(alo), "r"(ahi), "r"(blo), "r"(bhi), "r"(scale_d));
}

__device__ __forceinline__ void wgmma_ss_n224_tb1(float (&d)[112], uint32_t alo, uint32_t ahi, uint32_t blo, uint32_t bhi, int scale_d) {
    asm volatile("{\n.reg .pred p;\n.reg .b64 da, db;\nsetp.ne.b32 p, %116, 0;\nmov.b64 da, {%112, %113};\nmov.b64 db, {%114, %115};\n"
        "wgmma.mma_async.sync.aligned.m64n224k16.f32.bf16.bf16 {%0, %1, %2, %3, %4, %5, %6, %7, %8, %9, %10, %11, %12, %13, %14, %15, %16, %17, %18, %19, %20, %21, %22, %23, %24, %25, %26, %27, %28, %29, %30, %31, %32, %33, %34, %35, %36, %37, %38, %39, %40, %41, %42, %43, %44, %45, %46, %47, %48, %49, %50, %51, %52, %53, %54, %55, %56, %57, %58, %59, %60, %61, %62, %63, %64, %65, %66, %67, %68, %69, %70, %71, %72, %73, %74, %75, %76, %77, %78, %79, %80, %81, %82, %83, %84, %85, %86, %87, %88, %89, %90, %91, %92, %93, %94, %95, %96, %97, %98, %99, %100, %101, %102, %103, %104, %105, %106, %107, %108, %109, %110, %111}, da, db, p, 1, 1, 0, 1;\n}\n"
        : "+f"(d[0]), "+f"(d[1]), "+f"(d[2]), "+f"(d[3]), "+f"(d[4]), "+f"(d[5]), "+f"(d[6]), "+f"(d[7]), "+f"(d[8]), "+f"(d[9]), "+f"(d[10]), "+f"(d[11]), "+f"(d[12]), "+f"(d[13]), "+f"(d[14]), "+f"(d[15]), "+f"(d[16]), "+f"(d[17]), "+f"(d[18]), "+f"(d[19]), "+f"(d[20]), "+f"(d[21]), "+f"(d[22]), "+f"(d[23]), "+f"(d[24]), "+f"(d[25]), "+f"(d[26]), "+f"(d[27]), "+f"(d[28]), "+f"(d[29]), "+f"(d[30]), "+f"(d[31]), "+f"(d[32]), "+f"(d[33]), "+f"(d[34]), "+f"(d[35]), "+f"(d[36]), "+f"(d[37]), "+f"(d[38]), "+f"(d[39]), "+f"(d[40]), "+f"(d[41]), "+f"(d[42]), "+f"(d[43]), "+f"(d[44]), "+f"(d[45]), "+f"(d[46]), "+f"(d[47]), "+f"(d[48]), "+f"(d[49]), "+f"(d[50]), "+f"(d[51]), "+f"(d[52]), "+f"(d[53]), "+f"(d[54]), "+f"(d[55]), "+f"(d[56]), "+f"(d[57]), "+f"(d[58]), "+f"(d[59]), "+f"(d[60]), "+f"(d[61]), "+f"(d[62]), "+f"(d[63]), "+f"(d[64]), "+f"(d[65]), "+f"(d[66]), "+f"(d[67]), "+f"(d[68]), "+f"(d[69]), "+f"(d[70]), "+f"(d[71]), "+f"(d[72]), "+f"(d[73]), "+f"(d[74]), "+f"(d[75]), "+f"(d[76]), "+f"(d[77]), "+f"(d[78]), "+f"(d[79]), "+f"(d[80]), "+f"(d[81]), "+f"(d[82]), "+f"(d[83]), "+f"(d[84]), "+f"(d[85]), "+f"(d[86]), "+f"(d[87]), "+f"(d[88]), "+f"(d[89]), "+f"(d[90]), "+f"(d[91]), "+f"(d[92]), "+f"(d[93]), "+f"(d[94]), "+f"(d[95]), "+f"(d[96]), "+f"(d[97]), "+f"(d[98]), "+f"(d[99]), "+f"(d[100]), "+f"(d[101]), "+f"(d[102]), "+f"(d[103]), "+f"(d[104]), "+f"(d[105]), "+f"(d[106]), "+f"(d[107]), "+f"(d[108]), "+f"(d[109]), "+f"(d[110]), "+f"(d[111])
        : "r"(alo), "r"(ahi), "r"(blo), "r"(bhi), "r"(scale_d));
}

__device__ __forceinline__ void wgmma_ss_n256_tb1(float (&d)[128], uint32_t alo, uint32_t ahi, uint32_t blo, uint32_t bhi, int scale_d) {
    asm volatile("{\n.reg .pred p;\n.reg .b64 da, db;\nsetp.ne.b32 p, %132, 0;\nmov.b64 da, {%128, %129};\nmov.b64 db, {%130, %131};\n"
        "wgmma.mma_async.sync.aligned.m64n256k16.f32.bf16.bf16 {%0, %1, %2, %3, %4, %5, %6, %7, %8, %9, %10, %11, %12, %13, %14, %15, %16, %17, %18, %19, %20, %21, %22, %23, %24, %25, %26, %27, %28, %29, %30, %31, %32, %33, %34, %35, %36, %37, %38, %39, %40, %41, %42, %43, %44, %45, %46, %47, %48, %49, %50, %51, %52, %53, %54, %55, %56, %57, %58, %59, %60, %61, %62, %63, %64, %65, %66, %67, %68, %69, %70, %71, %72, %73, %74, %75, %76, %77, %78, %79, %80, %81, %82, %83, %84, %85, %86, %87, %88, %89, %90, %91, %92, %93, %94, %95, %96, %97, %98, %99, %100, %101, %102, %103, %104, %105, %106, %107, %108, %109, %110, %111, %112, %113, %114, %115, %116, %117, %118, %119, %120, %121, %122, %123, %124, %125, %126, %127}, da, db, p, 1, 1, 0, 1;\n}\n"
        : "+f"(d[0]), "+f"(d[1]), "+f"(d[2]), "+f"(d[3]), "+f"(d[4]), "+f"(d[5]), "+f"(d[6]), "+f"(d[7]), "+f"(d[8]), "+f"(d[9]), "+f"(d[10]), "+f"(d[11]), "+f"(d[12]), "+f"(d[13]), "+f"(d[14]), "+f"(d[15]), "+f"(d[16]), "+f"(d[17]), "+f"(d[18]), "+f"(d[19]), "+f"(d[20]), "+f"(d[21]), "+f"(d[22]), "+f"(d[23]), "+f"(d[24]), "+f"(d[25]), "+f"(d[26]), "+f"(d[27]), "+f"(d[28]), "+f"(d[29]), "+f"(d[30]), "+f"(d[31]), "+f"(d[32]), "+f"(d[33]), "+f"(d[34]), "+f"(d[35]), "+f"(d[36]), "+f"(d[37]), "+f"(d[38]), "+f"(d[39]), "+f"(d[40]), "+f"(d[41]), "+f"(d[42]), "+f"(d[43]), "+f"(d[44]), "+f"(d[45]), "+f"(d[46]), "+f"(d[47]), "+f"(d[48]), "+f"(d[49]), "+f"(d[50]), "+f"(d[51]), "+f"(d[52]), "+f"(d[53]), "+f"(d[54]), "+f"(d[55]), "+f"(d[56]), "+f"(d[57]), "+f"(d[58]), "+f"(d[59]), "+f"(d[60]), "+f"(d[61]), "+f"(d[62]), "+f"(d[63]), "+f"(d[64]), "+f"(d[65]), "+f"(d[66]), "+f"(d[67]), "+f"(d[68]), "+f"(d[69]), "+f"(d[70]), "+f"(d[71]), "+f"(d[72]), "+f"(d[73]), "+f"(d[74]), "+f"(d[75]), "+f"(d[76]), "+f"(d[77]), "+f"(d[78]), "+f"(d[79]), "+f"(d[80]), "+f"(d[81]), "+f"(d[82]), "+f"(d[83]), "+f"(d[84]), "+f"(d[85]), "+f"(d[86]), "+f"(d[87]), "+f"(d[88]), "+f"(d[89]), "+f"(d[90]), "+f"(d[91]), "+f"(d[92]), "+f"(d[93]), "+f"(d[94]), "+f"(d[95]), "+f"(d[96]), "+f"(d[97]), "+f"(d[98]), "+f"(d[99]), "+f"(d[100]), "+f"(d[101]), "+f"(d[102]), "+f"(d[103]), "+f"(d[104]), "+f"(d[105]), "+f"(d[106]), "+f"(d[107]), "+f"(d[108]), "+f"(d[109]), "+f"(d[110]), "+f"(d[111]), "+f"(d[112]), "+f"(d[113]), "+f"(d[114]), "+f"(d[115]), "+f"(d[116]), "+f"(d[117]), "+f"(d[118]), "+f"(d[119]), "+f"(d[120]), "+f"(d[121]), "+f"(d[122]), "+f"(d[123]), "+f"(d[124]), "+f"(d[125]), "+f"(d[126]), "+f"(d[127])
        : "r"(alo), "r"(ahi), "r"(blo), "r"(bhi), "r"(scale_d));
}

__device__ __forceinline__ void wgmma_ss_n64_tb0(float (&d)[32], uint32_t alo, uint32_t ahi, uint32_t blo, uint32_t bhi, int scale_d) {
    asm volatile("{\n.reg .pred p;\n.reg .b64 da, db;\nsetp.ne.b32 p, %36, 0;\nmov.b64 da, {%32, %33};\nmov.b64 db, {%34, %35};\n"
        "wgmma.mma_async.sync.aligned.m64n64k16.f32.bf16.bf16 {%0, %1, %2, %3, %4, %5, %6, %7, %8, %9, %10, %11, %12, %13, %14, %15, %16, %17, %18, %19, %20, %21, %22, %23, %24, %25, %26, %27, %28, %29, %30, %31}, da, db, p, 1, 1, 0, 0;\n}\n"
        : "+f"(d[0]), "+f"(d[1]), "+f"(d[2]), "+f"(d[3]), "+f"(d[4]), "+f"(d[5]), "+f"(d[6]), "+f"(d[7]), "+f"(d[8]), "+f"(d[9]), "+f"(d[10]), "+f"(d[11]), "+f"(d[12]), "+f"(d[13]), "+f"(d[14]), "+f"(d[15]), "+f"(d[16]), "+f"(d[17]), "+f"(d[18]), "+f"(d[19]), "+f"(d[20]), "+f"(d[21]), "+f"(d[22]), "+f"(d[23]), "+f"(d[24]), "+f"(d[25]), "+f"(d[26]), "+f"(d[27]), "+f"(d[28]), "+f"(d[29]), "+f"(d[30]), "+f"(d[31])
        : "r"(alo), "r"(ahi), "r"(blo), "r"(bhi), "r"(scale_d));
}

__device__ __forceinline__ void wgmma_rs_n128_tb0(float (&d)[64], uint32_t a0, uint32_t a1, uint32_t a2, uint32_t a3, uint32_t blo, uint32_t bhi, int scale_d) {
    asm volatile("{\n.reg .pred p;\n.reg .b64 db;\nsetp.ne.b32 p, %70, 0;\nmov.b64 db, {%68, %69};\n"
        "wgmma.mma_async.sync.aligned.m64n128k16.f32.bf16.bf16 {%0, %1, %2, %3, %4, %5, %6, %7, %8, %9, %10, %11, %12, %13, %14, %15, %16, %17, %18, %19, %20, %21, %22, %23, %24, %25, %26, %27, %28, %29, %30, %31, %32, %33, %34, %35, %36, %37, %38, %39, %40, %41, %42, %43, %44, %45, %46, %47, %48, %49, %50, %51, %52, %53, %54, %55, %56, %57, %58, %59, %60, %61, %62, %63}, {%64, %65, %66, %67}, db, p, 1, 1, 0;\n}\n"
        : "+f"(d[0]), "+f"(d[1]), "+f"(d[2]), "+f"(d[3]), "+f"(d[4]), "+f"(d[5]), "+f"(d[6]), "+f"(d[7]), "+f"(d[8]), "+f"(d[9]), "+f"(d[10]), "+f"(d[11]), "+f"(d[12]), "+f"(d[13]), "+f"(d[14]), "+f"(d[15]), "+f"(d[16]), "+f"(d[17]), "+f"(d[18]), "+f"(d[19]), "+f"(d[20]), "+f"(d[21]), "+f"(d[22]), "+f"(d[23]), "+f"(d[24]), "+f"(d[25]), "+f"(d[26]), "+f"(d[27]), "+f"(d[28]), "+f"(d[29]), "+f"(d[30]), "+f"(d[31]), "+f"(d[32]), "+f"(d[33]), "+f"(d[34]), "+f"(d[35]), "+f"(d[36]), "+f"(d[37]), "+f"(d[38]), "+f"(d[39]), "+f"(d[40]), "+f"(d[41]), "+f"(d[42]), "+f"(d[43]), "+f"(d[44]), "+f"(d[45]), "+f"(d[46]), "+f"(d[47]), "+f"(d[48]), "+f"(d[49]), "+f"(d[50]), "+f"(d[51]), "+f"(d[52]), "+f"(d[53]), "+f"(d[54]), "+f"(d[55]), "+f"(d[56]), "+f"(d[57]), "+f"(d[58]), "+f"(d[59]), "+f"(d[60]), "+f"(d[61]), "+f"(d[62]), "+f"(d[63])
        : "r"(a0), "r"(a1), "r"(a2), "r"(a3), "r"(blo), "r"(bhi), "r"(scale_d));
}

__device__ __forceinline__ void wgmma_rs_n64_tb0(float (&d)[32], uint32_t a0, uint32_t a1, uint32_t a2, uint32_t a3, uint32_t blo, uint32_t bhi, int scale_d) {
    asm volatile("{\n.reg .pred p;\n.reg .b64 db;\nsetp.ne.b32 p, %38, 0;\nmov.b64 db, {%36, %37};\n"
        "wgmma.mma_async.sync.aligned.m64n64k16.f32.bf16.bf16 {%0, %1, %2, %3, %4, %5, %6, %7, %8, %9, %10, %11, %12, %13, %14, %15, %16, %17, %18, %19, %20, %21, %22, %23, %24, %25, %26, %27, %28, %29, %30, %31}, {%32, %33, %34, %35}, db, p, 1, 1, 0;\n}\n"
        : "+f"(d[0]), "+f"(d[1]), "+f"(d[2]), "+f"(d[3]), "+f"(d[4]), "+f"(d[5]), "+f"(d[6]), "+f"(d[7]), "+f"(d[8]), "+f"(d[9]), "+f"(d[10]), "+f"(d[11]), "+f"(d[12]), "+f"(d[13]), "+f"(d[14]), "+f"(d[15]), "+f"(d[16]), "+f"(d[17]), "+f"(d[18]), "+f"(d[19]), "+f"(d[20]), "+f"(d[21]), "+f"(d[22]), "+f"(d[23]), "+f"(d[24]), "+f"(d[25]), "+f"(d[26]), "+f"(d[27]), "+f"(d[28]), "+f"(d[29]), "+f"(d[30]), "+f"(d[31])
        : "r"(a0), "r"(a1), "r"(a2), "r"(a3), "r"(blo), "r"(bhi), "r"(scale_d));
}

__device__ __forceinline__ void wgmma_rs_n32_tb1(float (&d)[16], uint32_t a0, uint32_t a1, uint32_t a2, uint32_t a3, uint32_t blo, uint32_t bhi, int scale_d) {
    asm volatile("{\n.reg .pred p;\n.reg .b64 db;\nsetp.ne.b32 p, %22, 0;\nmov.b64 db, {%20, %21};\n"
        "wgmma.mma_async.sync.aligned.m64n32k16.f32.bf16.bf16 {%0, %1, %2, %3, %4, %5, %6, %7, %8, %9, %10, %11, %12, %13, %14, %15}, {%16, %17, %18, %19}, db, p, 1, 1, 1;\n}\n"
        : "+f"(d[0]), "+f"(d[1]), "+f"(d[2]), "+f"(d[3]), "+f"(d[4]), "+f"(d[5]), "+f"(d[6]), "+f"(d[7]), "+f"(d[8]), "+f"(d[9]), "+f"(d[10]), "+f"(d[11]), "+f"(d[12]), "+f"(d[13]), "+f"(d[14]), "+f"(d[15])
        : "r"(a0), "r"(a1), "r"(a2), "r"(a3), "r"(blo), "r"(bhi), "r"(scale_d));
}

__device__ __forceinline__ void wgmma_rs_n40_tb1(float (&d)[20], uint32_t a0, uint32_t a1, uint32_t a2, uint32_t a3, uint32_t blo, uint32_t bhi, int scale_d) {
    asm volatile("{\n.reg .pred p;\n.reg .b64 db;\nsetp.ne.b32 p, %26, 0;\nmov.b64 db, {%24, %25};\n"
        "wgmma.mma_async.sync.aligned.m64n40k16.f32.bf16.bf16 {%0, %1, %2, %3, %4, %5, %6, %7, %8, %9, %10, %11, %12, %13, %14, %15, %16, %17, %18, %19}, {%20, %21, %22, %23}, db, p, 1, 1, 1;\n}\n"
        : "+f"(d[0]), "+f"(d[1]), "+f"(d[2]), "+f"(d[3]), "+f"(d[4]), "+f"(d[5]), "+f"(d[6]), "+f"(d[7]), "+f"(d[8]), "+f"(d[9]), "+f"(d[10]), "+f"(d[11]), "+f"(d[12]), "+f"(d[13]), "+f"(d[14]), "+f"(d[15]), "+f"(d[16]), "+f"(d[17]), "+f"(d[18]), "+f"(d[19])
        : "r"(a0), "r"(a1), "r"(a2), "r"(a3), "r"(blo), "r"(bhi), "r"(scale_d));
}


template <int BN>
__device__ __forceinline__ void wgmma_tile(float (&d)[BN / 2], uint32_t da, uint32_t db, int sd) {
    constexpr uint32_t HI = desc_hi(1024, 1);
    if constexpr (BN == 128) wgmma_ss_n128_tb1(d, da, HI, db, HI, sd);
    else if constexpr (BN == 192) wgmma_ss_n192_tb1(d, da, HI, db, HI, sd);
    else if constexpr (BN == 224) wgmma_ss_n224_tb1(d, da, HI, db, HI, sd);
    else wgmma_ss_n256_tb1(d, da, HI, db, HI, sd);
}

__global__ void __launch_bounds__(256) prep_kernel(const bf16* __restrict__ x, const bf16* __restrict__ gate_w,
                                                   const bf16* __restrict__ w1, const bf16* __restrict__ w3) {
    const int tid = threadIdx.x;
    if (blockIdx.x < 256) {
        const int row = blockIdx.x * 8 + (tid >> 5);
        const int lane = tid & 31;
        const uint4* xr = reinterpret_cast<const uint4*>(x + (size_t)row * DM);
        const uint4* gw = reinterpret_cast<const uint4*>(gate_w);
        float v[32];
        float gsum = 0.f, sum = 0.f;
#pragma unroll
        for (int i = 0; i < 4; i++) {
            uint4 a = xr[lane + 32 * i];
            uint4 b = gw[lane + 32 * i];
            const uint32_t aa[4] = {a.x, a.y, a.z, a.w};
            const uint32_t bb[4] = {b.x, b.y, b.z, b.w};
#pragma unroll
            for (int j = 0; j < 4; j++) {
                float x0 = __uint_as_float(aa[j] << 16), x1 = __uint_as_float(aa[j] & 0xFFFF0000u);
                float g0 = __uint_as_float(bb[j] << 16), g1 = __uint_as_float(bb[j] & 0xFFFF0000u);
                v[i * 8 + j * 2] = x0;
                v[i * 8 + j * 2 + 1] = x1;
                sum += x0 + x1;
                gsum += bf16_round(x0 * g0) + bf16_round(x1 * g1);
            }
        }
#pragma unroll
        for (int o = 16; o > 0; o >>= 1) {
            sum += __shfl_xor_sync(0xffffffffu, sum, o);
            gsum += __shfl_xor_sync(0xffffffffu, gsum, o);
        }
        const float mean = sum * (1.0f / DM);
        float m2 = 0.f;
#pragma unroll
        for (int i = 0; i < 32; i++) {
            float d = v[i] - mean;
            m2 += d * d;
        }
#pragma unroll
        for (int o = 16; o > 0; o >>= 1) m2 += __shfl_xor_sync(0xffffffffu, m2, o);
        if (lane == 0) {
            g_mean1[row] = mean;
            g_rstd1[row] = rsqrtf(m2 * (1.0f / DM) + 1e-5f);
            float logit = bf16_round(gsum);
            float g = bf16_round(1.0f / (1.0f + __expf(-logit)));
            g_gate[row] = g;
            g_omg[row] = bf16_round(1.0f - g);
        }
    } else {
        __shared__ float red[32][65];
        const int strip = blockIdx.x - 256;
        const bf16* w;
        float* out;
        int ld, col0;
        if (strip < 16) { w = w1; ld = DM; col0 = strip * 64; out = g_cs1; }
        else { w = w3; ld = FF; col0 = (strip - 16) * 64; out = g_cs3; }
        const int cg = tid & 7;
        const int rg = tid >> 3;
        float acc[8];
#pragma unroll
        for (int j = 0; j < 8; j++) acc[j] = 0.f;
#pragma unroll 8
        for (int r = 0; r < 32; r++) {
            uint4 a = *reinterpret_cast<const uint4*>(w + (size_t)(r * 32 + rg) * ld + col0 + cg * 8);
            const uint32_t aa[4] = {a.x, a.y, a.z, a.w};
#pragma unroll
            for (int j = 0; j < 4; j++) {
                acc[2 * j] += __uint_as_float(aa[j] << 16);
                acc[2 * j + 1] += __uint_as_float(aa[j] & 0xFFFF0000u);
            }
        }
#pragma unroll
        for (int j = 0; j < 8; j++) red[rg][cg * 8 + j] = acc[j];
        __syncthreads();
        if (tid < 64) {
            float s = 0.f;
#pragma unroll
            for (int r = 0; r < 32; r++) s += red[r][tid];
            out[col0 + tid] = s;
        }
    }
}

template <int BN, int STAGES>
struct GemmSmem {
    static constexpr int A_BYTES = 128 * 64 * 2;
    static constexpr int B_BOXES = (BN + 63) / 64;
    static constexpr int B_BYTES = B_BOXES * 64 * 64 * 2;
    static constexpr int STAGE_BYTES = A_BYTES + B_BYTES;
    static constexpr int STG_OFF = STAGES * STAGE_BYTES;
    static constexpr int BAR_OFF = STG_OFF + 2 * 16384;
    static constexpr int TOTAL = BAR_OFF + 256 + 1024;
};

template <int MODE, int BN, int STAGES>
__global__ void __launch_bounds__(384, 1)
gemm_kernel(const __grid_constant__ CUtensorMap mA, const __grid_constant__ CUtensorMap mB0,
            const __grid_constant__ CUtensorMap mB1, const __grid_constant__ CUtensorMap mC0,
            const __grid_constant__ CUtensorMap mC1, const bf16* __restrict__ xin, int n_tiles_n, int kblocks) {
    using L = GemmSmem<BN, STAGES>;
    extern __shared__ uint8_t smem_raw[];
    const uint32_t sbase = (smem_u32(smem_raw) + 1023u) & ~1023u;
    const uint32_t bar_full = sbase + L::BAR_OFF;
    const uint32_t bar_empty = bar_full + 8 * STAGES;
    const int wg = threadIdx.x >> 7;
    const int ntiles = 16 * n_tiles_n;

    if (threadIdx.x == 0) {
        for (int s = 0; s < STAGES; s++) {
            mbar_init(bar_full + 8 * s, 1);
            mbar_init(bar_empty + 8 * s, 2);
        }
        asm volatile("fence.mbarrier_init.release.cluster;" ::: "memory");
    }
    __syncthreads();

    if (wg == 0) {
        reg_dealloc<40>();
        if (threadIdx.x == 0) {
            prefetch_tmap(&mA);
            prefetch_tmap(&mB0);
            prefetch_tmap(&mB1);
            int stage = 0;
            uint32_t phase = 1;
            for (int tile = blockIdx.x; tile < ntiles; tile += gridDim.x) {
                const int m0 = (tile & 15) * 128;
                const int n0 = (tile >> 4) * BN;
                for (int kb = 0; kb < kblocks; kb++) {
                    mbar_wait(bar_empty + 8 * stage, phase);
                    const uint32_t sa = sbase + stage * L::STAGE_BYTES;
                    const uint32_t sb = sa + L::A_BYTES;
                    const uint32_t fb = bar_full + 8 * stage;
                    mbar_expect_tx(fb, L::STAGE_BYTES);
                    int arow = m0;
                    if (MODE == 2) {
                        const int grp = kb >> 2;
                        arow += (grp == 0) ? -1 : (grp == 1) ? 1 : (grp == 2) ? -2 : 2;
                    }
                    tma_load_2d(sa, &mA, kb * 64, arow, fb);
                    const CUtensorMap* mb = &mB0;
                    int bc = n0, br = kb * 64;
                    if (MODE == 1 && n0 >= 3 * DM) { mb = &mB1; bc = n0 - 3 * DM; }
                    if (MODE == 5 && kb >= 16) { mb = &mB1; br = (kb - 16) * 64; }
#pragma unroll
                    for (int b = 0; b < L::B_BOXES; b++) tma_load_2d(sb + b * 8192, mb, bc + b * 64, br, fb);
                    if (++stage == STAGES) { stage = 0; phase ^= 1; }
                }
            }
        }
    } else {
        reg_alloc<232>();
        const int c = wg - 1;
        const int warp = (threadIdx.x >> 5) & 3;
        const int lane = threadIdx.x & 31;
        const int tid_wg = threadIdx.x & 127;
        const uint32_t stg = sbase + L::STG_OFF + c * 16384;
        int stage = 0;
        uint32_t phase = 0;
        float acc[BN / 2];
        for (int tile = blockIdx.x; tile < ntiles; tile += gridDim.x) {
            const int m0 = (tile & 15) * 128;
            const int n0 = (tile >> 4) * BN;
            int prev_stage = 0;
            for (int kb = 0; kb < kblocks; kb++) {
                mbar_wait(bar_full + 8 * stage, phase);
                const uint32_t sa = sbase + stage * L::STAGE_BYTES + c * 8192;
                const uint32_t sb = sbase + stage * L::STAGE_BYTES + L::A_BYTES;
                const uint32_t da = desc_lo(sa, 16);
                const uint32_t db = desc_lo(sb, 8192);
                wgmma_fence();
#pragma unroll
                for (int k = 0; k < 4; k++) wgmma_tile<BN>(acc, da + k * 2, db + k * 128, (kb | k) != 0);
                wgmma_commit();
                if (kb > 0) {
                    wgmma_wait<1>();
                    if (tid_wg == 0) mbar_arrive(bar_empty + 8 * prev_stage);
                }
                prev_stage = stage;
                if (++stage == STAGES) { stage = 0; phase ^= 1; }
            }
            wgmma_wait<0>();
            if (tid_wg == 0) mbar_arrive(bar_empty + 8 * prev_stage);

            const int r0 = m0 + c * 64 + warp * 16 + (lane >> 2);
            const int r1 = r0 + 8;
            const int cq = (lane & 3) * 2;
            const CUtensorMap* mc = &mC0;
            int out_c0 = n0;
            if (MODE == 1) {
                if (n0 >= 3 * DM) {
                    mc = &mC1;
                    out_c0 = n0 - 3 * DM;
                    const float mu0 = g_mean1[r0], mu1 = g_mean1[r1];
                    const float rs0 = g_rstd1[r0], rs1 = g_rstd1[r1];
#pragma unroll
                    for (int j = 0; j < BN / 8; j++) {
                        const float2 cs = *reinterpret_cast<const float2*>(&g_cs1[out_c0 + 8 * j + cq]);
                        acc[4 * j + 0] = gelu_tanh(rs0 * fmaf(-mu0, cs.x, acc[4 * j + 0]));
                        acc[4 * j + 1] = gelu_tanh(rs0 * fmaf(-mu0, cs.y, acc[4 * j + 1]));
                        acc[4 * j + 2] = gelu_tanh(rs1 * fmaf(-mu1, cs.x, acc[4 * j + 2]));
                        acc[4 * j + 3] = gelu_tanh(rs1 * fmaf(-mu1, cs.y, acc[4 * j + 3]));
                    }
                }
            } else if (MODE == 2) {
                float s0 = 0.f, s1 = 0.f;
#pragma unroll
                for (int j = 0; j < BN / 8; j++) {
                    const uint32_t xa = *reinterpret_cast<const uint32_t*>(xin + (size_t)r0 * DM + n0 + 8 * j + cq);
                    const uint32_t xb = *reinterpret_cast<const uint32_t*>(xin + (size_t)r1 * DM + n0 + 8 * j + cq);
                    acc[4 * j + 0] = bf16_round(bf16_round(acc[4 * j + 0]) + __uint_as_float(xa << 16));
                    acc[4 * j + 1] = bf16_round(bf16_round(acc[4 * j + 1]) + __uint_as_float(xa & 0xFFFF0000u));
                    acc[4 * j + 2] = bf16_round(bf16_round(acc[4 * j + 2]) + __uint_as_float(xb << 16));
                    acc[4 * j + 3] = bf16_round(bf16_round(acc[4 * j + 3]) + __uint_as_float(xb & 0xFFFF0000u));
                    s0 += acc[4 * j + 0] + acc[4 * j + 1];
                    s1 += acc[4 * j + 2] + acc[4 * j + 3];
                }
                s0 += __shfl_xor_sync(0xffffffffu, s0, 1);
                s0 += __shfl_xor_sync(0xffffffffu, s0, 2);
                s1 += __shfl_xor_sync(0xffffffffu, s1, 1);
                s1 += __shfl_xor_sync(0xffffffffu, s1, 2);
                const float mu0 = s0 * (1.0f / BN), mu1 = s1 * (1.0f / BN);
                float q0 = 0.f, q1 = 0.f;
#pragma unroll
                for (int j = 0; j < BN / 8; j++) {
                    float d;
                    d = acc[4 * j + 0] - mu0; q0 += d * d;
                    d = acc[4 * j + 1] - mu0; q0 += d * d;
                    d = acc[4 * j + 2] - mu1; q1 += d * d;
                    d = acc[4 * j + 3] - mu1; q1 += d * d;
                }
                q0 += __shfl_xor_sync(0xffffffffu, q0, 1);
                q0 += __shfl_xor_sync(0xffffffffu, q0, 2);
                q1 += __shfl_xor_sync(0xffffffffu, q1, 1);
                q1 += __shfl_xor_sync(0xffffffffu, q1, 2);
                if ((lane & 3) == 0) {
                    static_assert(MODE != 2 || BN == 128, "stats layout assumes BN=128");
                    g_stat2[r0 * 8 + (n0 >> 7)] = make_float2(s0, q0);
                    g_stat2[r1 * 8 + (n0 >> 7)] = make_float2(s1, q1);
                }
            } else if (MODE == 3) {
                out_c0 = n0 + DM;
                float mu[2], rs[2];
#pragma unroll
                for (int h = 0; h < 2; h++) {
                    const float4* sp = reinterpret_cast<const float4*>(&g_stat2[(h ? r1 : r0) * 8]);
                    float4 p[4];
                    float s = 0.f;
#pragma unroll
                    for (int i = 0; i < 4; i++) { p[i] = sp[i]; s += p[i].x + p[i].z; }
                    const float mean = s * (1.0f / DM);
                    float m2 = 0.f;
#pragma unroll
                    for (int i = 0; i < 4; i++) {
                        float d0 = p[i].x * (1.0f / 128) - mean, d1 = p[i].z * (1.0f / 128) - mean;
                        m2 += p[i].y + p[i].w + 128.0f * (d0 * d0 + d1 * d1);
                    }
                    mu[h] = mean;
                    rs[h] = rsqrtf(m2 * (1.0f / DM) + 1e-5f);
                }
                const float og0 = g_omg[r0], og1 = g_omg[r1];
#pragma unroll
                for (int j = 0; j < BN / 8; j++) {
                    const float2 cs = *reinterpret_cast<const float2*>(&g_cs3[n0 + 8 * j + cq]);
                    acc[4 * j + 0] = og0 * gelu_tanh(rs[0] * fmaf(-mu[0], cs.x, acc[4 * j + 0]));
                    acc[4 * j + 1] = og0 * gelu_tanh(rs[0] * fmaf(-mu[0], cs.y, acc[4 * j + 1]));
                    acc[4 * j + 2] = og1 * gelu_tanh(rs[1] * fmaf(-mu[1], cs.x, acc[4 * j + 2]));
                    acc[4 * j + 3] = og1 * gelu_tanh(rs[1] * fmaf(-mu[1], cs.y, acc[4 * j + 3]));
                }
            } else {
                const float og0 = g_omg[r0], og1 = g_omg[r1];
#pragma unroll
                for (int j = 0; j < BN / 8; j++) {
                    const uint32_t xa = *reinterpret_cast<const uint32_t*>(xin + (size_t)r0 * DM + n0 + 8 * j + cq);
                    const uint32_t xb = *reinterpret_cast<const uint32_t*>(xin + (size_t)r1 * DM + n0 + 8 * j + cq);
                    acc[4 * j + 0] = fmaf(og0, __uint_as_float(xa << 16), acc[4 * j + 0]);
                    acc[4 * j + 1] = fmaf(og0, __uint_as_float(xa & 0xFFFF0000u), acc[4 * j + 1]);
                    acc[4 * j + 2] = fmaf(og1, __uint_as_float(xb << 16), acc[4 * j + 2]);
                    acc[4 * j + 3] = fmaf(og1, __uint_as_float(xb & 0xFFFF0000u), acc[4 * j + 3]);
                }
            }
            const int srow = warp * 16 + (lane & 7) + ((lane >> 3) & 1) * 8;
#pragma unroll
            for (int rnd = 0; rnd < (BN + 127) / 128; rnd++) {
                if (tid_wg == 0) bulk_wait_read0();
                named_bar_sync(1 + c, 128);
#pragma unroll
                for (int jj = 0; jj < 8; jj++) {
                    const int j = rnd * 16 + jj * 2;
                    if (j * 8 < BN) {
                        const int jb = jj * 2 + (lane >> 4);
                        const uint32_t addr = stg + (jb >> 3) * 8192 + srow * 128 + (((jb & 7) ^ (srow & 7)) << 4);
                        stmatrix_x4(addr, pack_bf16(acc[4 * j + 0], acc[4 * j + 1]), pack_bf16(acc[4 * j + 2], acc[4 * j + 3]),
                                    pack_bf16(acc[4 * j + 4], acc[4 * j + 5]), pack_bf16(acc[4 * j + 6], acc[4 * j + 7]));
                    }
                }
                fence_proxy_async();
                named_bar_sync(1 + c, 128);
                if (tid_wg == 0) {
                    tma_store_2d(mc, stg, out_c0 + rnd * 128, m0 + c * 64);
                    if (rnd * 128 + 64 < BN) tma_store_2d(mc, stg + 8192, out_c0 + rnd * 128 + 64, m0 + c * 64);
                    bulk_commit();
                }
            }
        }
        if (tid_wg == 0) bulk_wait0();
    }
}

constexpr int ATT_STAGES = 4;
constexpr int ATT_DIST = 2;
constexpr int ATT_Q_OFF = ATT_STAGES * 16384;
constexpr int ATT_ONES_OFF = ATT_Q_OFF + 8192;
constexpr int ATT_BAR_OFF = ATT_ONES_OFF + 4096;
constexpr int ATT_SMEM = ATT_BAR_OFF + 256 + 1024;

struct AttState {
    float o[20];
    float m0, m1;
    float mp0, mp1;
};

__device__ __forceinline__ void row_max(const float (&s)[32], float& m0, float& m1) {
    float mx0 = fmaxf(s[0], s[1]), mx1 = fmaxf(s[2], s[3]);
#pragma unroll
    for (int i = 1; i < 8; i++) {
        mx0 = fmaxf(mx0, fmaxf(s[4 * i], s[4 * i + 1]));
        mx1 = fmaxf(mx1, fmaxf(s[4 * i + 2], s[4 * i + 3]));
    }
    mx0 = fmaxf(mx0, __shfl_xor_sync(0xffffffffu, mx0, 1));
    mx1 = fmaxf(mx1, __shfl_xor_sync(0xffffffffu, mx1, 1));
    mx0 = fmaxf(mx0, __shfl_xor_sync(0xffffffffu, mx0, 2));
    mx1 = fmaxf(mx1, __shfl_xor_sync(0xffffffffu, mx1, 2));
    m0 = fmaxf(m0, mx0);
    m1 = fmaxf(m1, mx1);
}

__device__ __forceinline__ void attn_step(float (&sc)[32], float (&sn)[32], uint32_t (&p)[16], uint32_t dq,
                                          AttState& st, uint32_t dk_next2, uint32_t dv_cur, uint32_t release_bar) {
    const float cs = 0.17677669529663687f * 1.4426950408889634f;
    constexpr uint32_t HI = desc_hi(512, 2);
    const float mc0 = st.m0, mc1 = st.m1;
    const float b0 = mc0 * cs, b1 = mc1 * cs;
#pragma unroll
    for (int i = 0; i < 4; i++) {
        sc[4 * i + 0] = ex2(fmaf(sc[4 * i + 0], cs, -b0));
        sc[4 * i + 1] = ex2(fmaf(sc[4 * i + 1], cs, -b0));
        sc[4 * i + 2] = ex2(fmaf(sc[4 * i + 2], cs, -b1));
        sc[4 * i + 3] = ex2(fmaf(sc[4 * i + 3], cs, -b1));
    }
    wgmma_wait<0>();
    if (release_bar != 0 && (threadIdx.x & 127) == 0) mbar_arrive(release_bar);
    row_max(sn, st.m0, st.m1);
#pragma unroll
    for (int i = 4; i < 8; i++) {
        sc[4 * i + 0] = ex2(fmaf(sc[4 * i + 0], cs, -b0));
        sc[4 * i + 1] = ex2(fmaf(sc[4 * i + 1], cs, -b0));
        sc[4 * i + 2] = ex2(fmaf(sc[4 * i + 2], cs, -b1));
        sc[4 * i + 3] = ex2(fmaf(sc[4 * i + 3], cs, -b1));
    }
    {
        const float a0 = ex2((st.mp0 - mc0) * cs), a1 = ex2((st.mp1 - mc1) * cs);
#pragma unroll
        for (int i = 0; i < 5; i++) {
            st.o[4 * i + 0] *= a0; st.o[4 * i + 1] *= a0;
            st.o[4 * i + 2] *= a1; st.o[4 * i + 3] *= a1;
        }
        st.mp0 = mc0; st.mp1 = mc1;
    }
#pragma unroll
    for (int i = 0; i < 8; i++) {
        p[2 * i] = pack_bf16(sc[4 * i + 0], sc[4 * i + 1]);
        p[2 * i + 1] = pack_bf16(sc[4 * i + 2], sc[4 * i + 3]);
    }
    wgmma_fence();
    wgmma_ss_n64_tb0(sc, dq, HI, dk_next2, HI, 0);
    wgmma_ss_n64_tb0(sc, dq + 2, HI, dk_next2 + 2, HI, 1);
#pragma unroll
    for (int t = 0; t < 4; t++)
        wgmma_rs_n40_tb1(st.o, p[4 * t], p[4 * t + 1], p[4 * t + 2], p[4 * t + 3], dv_cur + t * 64, HI, 1);
    wgmma_commit();
}

__global__ void __launch_bounds__(256, 2)
attn_kernel(const __grid_constant__ CUtensorMap mKV) {
    extern __shared__ uint8_t smem_raw[];
    const uint32_t sbase = (smem_u32(smem_raw) + 1023u) & ~1023u;
    const uint32_t bar_kfull = sbase + ATT_BAR_OFF;
    const uint32_t bar_vfull = bar_kfull + 8 * ATT_STAGES;
    const uint32_t bar_empty = bar_vfull + 8 * ATT_STAGES;
    const int head = blockIdx.x >> 4;
    const int q0 = (blockIdx.x & 15) * 128;
    const int warp_id = threadIdx.x >> 5;
    const int lane = threadIdx.x & 31;
    constexpr int NBLK = S_LEN / 128;

    if (threadIdx.x == 0) {
        for (int s = 0; s < ATT_STAGES; s++) {
            mbar_init(bar_kfull + 8 * s, 1);
            mbar_init(bar_vfull + 8 * s, 1);
            mbar_init(bar_empty + 8 * s, 2);
        }
        asm volatile("fence.mbarrier_init.release.cluster;" ::: "memory");
        prefetch_tmap(&mKV);
#pragma unroll
        for (int j = 0; j < ATT_DIST; j++) {
            const uint32_t sk = sbase + j * 16384;
            mbar_expect_tx(bar_kfull + 8 * j, j == 0 ? 16384 : 8192);
            if (j == 0) tma_load_2d(sbase + ATT_Q_OFF, &mKV, head * DH, q0, bar_kfull);
            tma_load_2d(sk, &mKV, DM + head * DH, j * 128, bar_kfull + 8 * j);
            mbar_expect_tx(bar_vfull + 8 * j, 8192);
            tma_load_2d(sk + 8192, &mKV, 2 * DM + head * DH, j * 128, bar_vfull + 8 * j);
        }
    }
    asm volatile("st.shared.v4.b32 [%0], {%1, %1, %1, %1};" ::"r"(sbase + ATT_ONES_OFF + threadIdx.x * 16), "r"(0x3F803F80u) : "memory");
    fence_proxy_async();
    __syncthreads();

    const int row0 = q0 + warp_id * 16 + (lane >> 2);
    const int cq = (lane & 3) * 2;
    const uint32_t dq = desc_lo(sbase + ATT_Q_OFF + (threadIdx.x >> 7) * 4096, 16);
    AttState st;
#pragma unroll
    for (int i = 0; i < 20; i++) st.o[i] = 0.f;
    st.m0 = -INFINITY; st.m1 = -INFINITY;
    float s0[32], s1[32];
    constexpr uint32_t HI = desc_hi(512, 2);
    const uint32_t dk0 = desc_lo(sbase, 16);
    const uint32_t dv0 = desc_lo(sbase + 8192, ATT_ONES_OFF - 8192);
    uint32_t p[16];
    mbar_wait(bar_kfull, 0);
    wgmma_fence();
    wgmma_ss_n64_tb0(s0, dq, HI, dk0, HI, 0);
    wgmma_ss_n64_tb0(s0, dq + 2, HI, dk0 + 2, HI, 1);
    wgmma_commit();
    wgmma_wait<0>();
    row_max(s0, st.m0, st.m1);
    st.mp0 = st.m0; st.mp1 = st.m1;
    wgmma_fence();
    wgmma_ss_n64_tb0(s1, dq, HI, dk0 + 256, HI, 0);
    wgmma_ss_n64_tb0(s1, dq + 2, HI, dk0 + 256 + 2, HI, 1);
    wgmma_commit();
    int stage = 0;
    uint32_t phase = 0;
#pragma unroll 1
    for (int j = 0; j < NBLK; j++) {
        if (threadIdx.x == 0 && j + ATT_DIST < NBLK) {
            const int jn = j + ATT_DIST;
            const int sn = jn % ATT_STAGES;
            if (jn >= ATT_STAGES) mbar_wait(bar_empty + 8 * sn, ((jn / ATT_STAGES) - 1) & 1);
            const uint32_t skn = sbase + sn * 16384;
            mbar_expect_tx(bar_kfull + 8 * sn, 8192);
            tma_load_2d(skn, &mKV, DM + head * DH, jn * 128, bar_kfull + 8 * sn);
            mbar_expect_tx(bar_vfull + 8 * sn, 8192);
            tma_load_2d(skn + 8192, &mKV, 2 * DM + head * DH, jn * 128, bar_vfull + 8 * sn);
        }
        __syncwarp();
        const uint32_t dv = dv0 + stage * 1024 - ((uint32_t)(stage * 1024) << 16);
        const int pstage = (stage + ATT_STAGES - 1) % ATT_STAGES;
        int nstage = stage + 1;
        uint32_t nphase = phase;
        if (nstage == ATT_STAGES) { nstage = 0; nphase ^= 1; }
        uint32_t dkn = dk0 + stage * 1024;
        if (j + 1 < NBLK) {
            mbar_wait(bar_kfull + 8 * nstage, nphase);
            dkn = dk0 + nstage * 1024;
        }
        mbar_wait(bar_vfull + 8 * stage, phase);
        attn_step(s0, s1, p, dq, st, dkn, dv, j > 0 ? bar_empty + 8 * pstage : 0u);
        attn_step(s1, s0, p, dq, st, dkn + 256, dv + 256 - (256u << 16), 0u);
        stage = nstage;
        phase = nphase;
    }
    wgmma_wait<0>();
    const float f0 = g_gate[row0] / st.o[16], f1 = g_gate[row0 + 8] / st.o[18];
    bf16* op0 = g_a5 + (size_t)row0 * A5W + head * DH + cq;
    bf16* op1 = op0 + 8 * A5W;
#pragma unroll
    for (int i = 0; i < 4; i++) {
        *reinterpret_cast<uint32_t*>(op0 + 8 * i) = pack_bf16(st.o[4 * i] * f0, st.o[4 * i + 1] * f0);
        *reinterpret_cast<uint32_t*>(op1 + 8 * i) = pack_bf16(st.o[4 * i + 2] * f1, st.o[4 * i + 3] * f1);
    }
}

typedef CUresult (*EncodeFn)(CUtensorMap*, CUtensorMapDataType, cuuint32_t, void*, const cuuint64_t*, const cuuint64_t*,
                             const cuuint32_t*, const cuuint32_t*, CUtensorMapInterleave, CUtensorMapSwizzle,
                             CUtensorMapL2promotion, CUtensorMapFloatOOBfill);

static CUtensorMap make_map(EncodeFn fn, const void* ptr, int rows, int cols, int box_cols, int box_rows,
                            CUtensorMapSwizzle swz) {
    CUtensorMap m;
    cuuint64_t dims[2] = {(cuuint64_t)cols, (cuuint64_t)rows};
    cuuint64_t strides[1] = {(cuuint64_t)cols * 2};
    cuuint32_t box[2] = {(cuuint32_t)box_cols, (cuuint32_t)box_rows};
    cuuint32_t es[2] = {1, 1};
    fn(&m, CU_TENSOR_MAP_DATA_TYPE_BFLOAT16, 2, const_cast<void*>(ptr), dims, strides, box, es,
       CU_TENSOR_MAP_INTERLEAVE_NONE, swz, CU_TENSOR_MAP_L2_PROMOTION_L2_256B, CU_TENSOR_MAP_FLOAT_OOB_FILL_NONE);
    return m;
}

extern "C" void kernel_launch(void* const* d_in, const int* in_sizes, int n_in, void* d_out, int out_size) {
    const bf16* x = (const bf16*)d_in[0];
    const bf16* wqkv = (const bf16*)d_in[1];
    const bf16* wo = (const bf16*)d_in[2];
    const bf16* w1 = (const bf16*)d_in[4];
    const bf16* w2 = (const bf16*)d_in[5];
    const bf16* w3 = (const bf16*)d_in[6];
    const bf16* w4 = (const bf16*)d_in[7];
    const bf16* gate_w = (const bf16*)d_in[8];

    static EncodeFn enc = nullptr;
    static void *p_qkv, *p_h, *p_x1, *p_a5;
    if (!enc) {
        void* fn = nullptr;
        cudaDriverEntryPointQueryResult qres;
        cudaGetDriverEntryPoint("cuTensorMapEncodeTiled", &fn, cudaEnableDefault, &qres);
        enc = (EncodeFn)fn;
        cudaGetSymbolAddress(&p_qkv, g_qkv);
        cudaGetSymbolAddress(&p_h, g_h);
        cudaGetSymbolAddress(&p_x1, g_x1);
        cudaGetSymbolAddress(&p_a5, g_a5);
        cudaFuncSetAttribute(gemm_kernel<1, 256, 4>, cudaFuncAttributeMaxDynamicSharedMemorySize, GemmSmem<256, 4>::TOTAL);
        cudaFuncSetAttribute(gemm_kernel<2, 128, 5>, cudaFuncAttributeMaxDynamicSharedMemorySize, GemmSmem<128, 5>::TOTAL);
        cudaFuncSetAttribute(gemm_kernel<3, 256, 4>, cudaFuncAttributeMaxDynamicSharedMemorySize, GemmSmem<256, 4>::TOTAL);
        cudaFuncSetAttribute(gemm_kernel<5, 128, 5>, cudaFuncAttributeMaxDynamicSharedMemorySize, GemmSmem<128, 5>::TOTAL);
        cudaFuncSetAttribute(attn_kernel, cudaFuncAttributeMaxDynamicSharedMemorySize, ATT_SMEM);
    }
    const CUtensorMapSwizzle SW128 = CU_TENSOR_MAP_SWIZZLE_128B, SW64 = CU_TENSOR_MAP_SWIZZLE_64B;
    CUtensorMap mX = make_map(enc, x, S_LEN, DM, 64, 128, SW128);
    CUtensorMap mWqkv = make_map(enc, wqkv, DM, 3 * DM, 64, 64, SW128);
    CUtensorMap mW1 = make_map(enc, w1, DM, DM, 64, 64, SW128);
    CUtensorMap mW2 = make_map(enc, w2, DM, DM, 64, 64, SW128);
    CUtensorMap mW3 = make_map(enc, w3, DM, FF, 64, 64, SW128);
    CUtensorMap mW4 = make_map(enc, w4, FF, DM, 64, 64, SW128);
    CUtensorMap mWo = make_map(enc, wo, DM, DM, 64, 64, SW128);
    CUtensorMap mQKVst = make_map(enc, p_qkv, S_LEN, 3 * DM, 64, 64, SW128);
    CUtensorMap mKV = make_map(enc, p_qkv, S_LEN, 3 * DM, 32, 128, SW64);
    CUtensorMap mHst = make_map(enc, p_h, S_LEN, DM, 64, 64, SW128);
    CUtensorMap mHld = make_map(enc, p_h, S_LEN, DM, 64, 128, SW128);
    CUtensorMap mX1st = make_map(enc, p_x1, S_LEN, DM, 64, 64, SW128);
    CUtensorMap mX1ld = make_map(enc, p_x1, S_LEN, DM, 64, 128, SW128);
    CUtensorMap mA5st = make_map(enc, p_a5, S_LEN, A5W, 64, 64, SW128);
    CUtensorMap mA5ld = make_map(enc, p_a5, S_LEN, A5W, 64, 128, SW128);
    CUtensorMap mOut = make_map(enc, d_out, S_LEN, DM, 64, 64, SW128);

    cudaStream_t st = cudaStreamPerThread;
    prep_kernel<<<256 + 72, 256, 0, st>>>(x, gate_w, w1, w3);
    gemm_kernel<1, 256, 4><<<132, 384, GemmSmem<256, 4>::TOTAL, st>>>(mX, mWqkv, mW1, mQKVst, mHst, x, 16, 16);
    attn_kernel<<<NH * 16, 256, ATT_SMEM, st>>>(mKV);
    gemm_kernel<2, 128, 5><<<128, 384, GemmSmem<128, 5>::TOTAL, st>>>(mHld, mW2, mW2, mX1st, mX1st, x, 8, 16);
    gemm_kernel<3, 256, 4><<<132, 384, GemmSmem<256, 4>::TOTAL, st>>>(mX1ld, mW3, mW3, mA5st, mA5st, x, 14, 16);
    gemm_kernel<5, 128, 5><<<128, 384, GemmSmem<128, 5>::TOTAL, st>>>(mA5ld, mWo, mW4, mOut, mOut, (const bf16*)p_x1, 8, 72);
}
```

```cpp
#include <cuda_runtime.h>
#include <cuda_bf16.h>
#include <cuda.h>
#include <stdint.h>

typedef __nv_bfloat16 bf16;

constexpr int S_LEN = 2048;
constexpr int DM = 1024;
constexpr int FF = 3584;
constexpr int NH = 32;
constexpr int DH = 32;
constexpr int A5W = DM + FF;

__device__ __align__(1024) bf16 g_qkv[S_LEN * 3 * DM];
__device__ __align__(1024) bf16 g_h[S_LEN * DM];
__device__ __align__(1024) bf16 g_x1[S_LEN * DM];
__device__ __align__(1024) bf16 g_a5[S_LEN * A5W];
__device__ __align__(16) float g_mean1[S_LEN];
__device__ __align__(16) float g_rstd1[S_LEN];
__device__ __align__(16) float g_gate[S_LEN];
__device__ __align__(16) float g_omg[S_LEN];
__device__ __align__(16) float g_cs1[DM];
__device__ __align__(16) float g_cs3[FF];
__device__ __align__(16) float2 g_stat2[S_LEN * 8];

__device__ __forceinline__ uint32_t smem_u32(const void* p) { return (uint32_t)__cvta_generic_to_shared(p); }

__device__ __forceinline__ void mbar_init(uint32_t bar, uint32_t count) {
    asm volatile("mbarrier.init.shared::cta.b64 [%0], %1;" ::"r"(bar), "r"(count));
}
__device__ __forceinline__ void mbar_expect_tx(uint32_t bar, uint32_t bytes) {
    asm volatile("mbarrier.arrive.expect_tx.shared::cta.b64 _, [%0], %1;" ::"r"(bar), "r"(bytes) : "memory");
}
__device__ __forceinline__ void mbar_arrive(uint32_t bar) {
    asm volatile("mbarrier.arrive.shared::cta.b64 _, [%0];" ::"r"(bar) : "memory");
}
__device__ __forceinline__ bool mbar_try_wait(uint32_t bar, uint32_t parity) {
    uint32_t ok;
    asm volatile(
        "{\n.reg .pred p;\n"
        "mbarrier.try_wait.parity.shared::cta.b64 p, [%1], %2;\n"
        "selp.u32 %0, 1, 0, p;\n}\n"
        : "=r"(ok)
        : "r"(bar), "r"(parity)
        : "memory");
    return ok != 0;
}
__device__ __forceinline__ void mbar_wait(uint32_t bar, uint32_t parity) {
    uint32_t spins = 0;
    while (!mbar_try_wait(bar, parity)) {
        if (++spins > (1u << 24)) __trap();
    }
}
__device__ __forceinline__ void tma_load_2d(uint32_t dst, const CUtensorMap* map, int c0, int c1, uint32_t bar) {
    asm volatile(
        "cp.async.bulk.tensor.2d.shared::cluster.global.mbarrier::complete_tx::bytes [%0], [%1, {%3, %4}], [%2];"
        ::"r"(dst), "l"(map), "r"(bar), "r"(c0), "r"(c1)
        : "memory");
}
__device__ __forceinline__ void tma_store_2d(const CUtensorMap* map, uint32_t src, int c0, int c1) {
    asm volatile("cp.async.bulk.tensor.2d.global.shared::cta.bulk_group [%0, {%2, %3}], [%1];"
                 ::"l"(map), "r"(src), "r"(c0), "r"(c1)
                 : "memory");
}
__device__ __forceinline__ void bulk_commit() { asm volatile("cp.async.bulk.commit_group;" ::: "memory"); }
__device__ __forceinline__ void bulk_wait_read0() { asm volatile("cp.async.bulk.wait_group.read 0;" ::: "memory"); }
__device__ __forceinline__ void bulk_wait0() { asm volatile("cp.async.bulk.wait_group 0;" ::: "memory"); }
__device__ __forceinline__ void fence_proxy_async() { asm volatile("fence.proxy.async.shared::cta;" ::: "memory"); }
__device__ __forceinline__ void named_bar_sync(int id, int n) { asm volatile("bar.sync %0, %1;" ::"r"(id), "r"(n) : "memory"); }
__device__ __forceinline__ void named_bar_arrive(int id, int n) { asm volatile("bar.arrive %0, %1;" ::"r"(id), "r"(n) : "memory"); }
__device__ __forceinline__ void wgmma_fence() { asm volatile("wgmma.fence.sync.aligned;" ::: "memory"); }
__device__ __forceinline__ void wgmma_commit() { asm volatile("wgmma.commit_group.sync.aligned;" ::: "memory"); }
template <int N>
__device__ __forceinline__ void wgmma_wait() { asm volatile("wgmma.wait_group.sync.aligned %0;" ::"n"(N) : "memory"); }
__device__ __forceinline__ void prefetch_tmap(const CUtensorMap* m) {
    asm volatile("prefetch.tensormap [%0];" ::"l"(m) : "memory");
}
template <int R>
__device__ __forceinline__ void reg_alloc() { asm volatile("setmaxnreg.inc.sync.aligned.u32 %0;" ::"n"(R)); }
template <int R>
__device__ __forceinline__ void reg_dealloc() { asm volatile("setmaxnreg.dec.sync.aligned.u32 %0;" ::"n"(R)); }
__device__ __forceinline__ void stmatrix_x4(uint32_t addr, uint32_t r0, uint32_t r1, uint32_t r2, uint32_t r3) {
    asm volatile("stmatrix.sync.aligned.m8n8.x4.shared.b16 [%0], {%1, %2, %3, %4};"
                 ::"r"(addr), "r"(r0), "r"(r1), "r"(r2), "r"(r3)
                 : "memory");
}
__device__ __forceinline__ uint32_t pack_bf16(float lo, float hi) {
    uint32_t r;
    asm("cvt.rn.bf16x2.f32 %0, %1, %2;" : "=r"(r) : "f"(hi), "f"(lo));
    return r;
}
__device__ __forceinline__ float bf16_round(float v) { return __bfloat162float(__float2bfloat16_rn(v)); }
__device__ __forceinline__ float ex2(float x) {
    float y;
    asm("ex2.approx.ftz.f32 %0, %1;" : "=f"(y) : "f"(x));
    return y;
}
__device__ __forceinline__ float tanh_fast(float x) {
    float y;
    asm("tanh.approx.f32 %0, %1;" : "=f"(y) : "f"(x));
    return y;
}
__device__ __forceinline__ float gelu_tanh(float v) {
    float u = 0.7978845608028654f * (v + 0.044715f * v * v * v);
    float hv = 0.5f * v;
    return fmaf(hv, tanh_fast(u), hv);
}
__device__ __forceinline__ uint32_t desc_lo(uint32_t addr, uint32_t lbo_bytes) {
    return ((addr & 0x3FFFF) >> 4) | (((lbo_bytes >> 4) & 0x3FFF) << 16);
}
__host__ __device__ constexpr uint32_t desc_hi(uint32_t sbo_bytes, uint32_t swz) {
    return ((sbo_bytes >> 4) & 0x3FFF) | (swz << 30);
}


__device__ __forceinline__ void wgmma_ss_n128_tb1(float (&d)[64], uint32_t alo, uint32_t ahi, uint32_t blo, uint32_t bhi, int scale_d) {
    asm volatile("{\n.reg .pred p;\n.reg .b64 da, db;\nsetp.ne.b32 p, %68, 0;\nmov.b64 da, {%64, %65};\nmov.b64 db, {%66, %67};\n"
        "wgmma.mma_async.sync.aligned.m64n128k16.f32.bf16.bf16 {%0, %1, %2, %3, %4, %5, %6, %7, %8, %9, %10, %11, %12, %13, %14, %15, %16, %17, %18, %19, %20, %21, %22, %23, %24, %25, %26, %27, %28, %29, %30, %31, %32, %33, %34, %35, %36, %37, %38, %39, %40, %41, %42, %43, %44, %45, %46, %47, %48, %49, %50, %51, %52, %53, %54, %55, %56, %57, %58, %59, %60, %61, %62, %63}, da, db, p, 1, 1, 0, 1;\n}\n"
        : "+f"(d[0]), "+f"(d[1]), "+f"(d[2]), "+f"(d[3]), "+f"(d[4]), "+f"(d[5]), "+f"(d[6]), "+f"(d[7]), "+f"(d[8]), "+f"(d[9]), "+f"(d[10]), "+f"(d[11]), "+f"(d[12]), "+f"(d[13]), "+f"(d[14]), "+f"(d[15]), "+f"(d[16]), "+f"(d[17]), "+f"(d[18]), "+f"(d[19]), "+f"(d[20]), "+f"(d[21]), "+f"(d[22]), "+f"(d[23]), "+f"(d[24]), "+f"(d[25]), "+f"(d[26]), "+f"(d[27]), "+f"(d[28]), "+f"(d[29]), "+f"(d[30]), "+f"(d[31]), "+f"(d[32]), "+f"(d[33]), "+f"(d[34]), "+f"(d[35]), "+f"(d[36]), "+f"(d[37]), "+f"(d[38]), "+f"(d[39]), "+f"(d[40]), "+f"(d[41]), "+f"(d[42]), "+f"(d[43]), "+f"(d[44]), "+f"(d[45]), "+f"(d[46]), "+f"(d[47]), "+f"(d[48]), "+f"(d[49]), "+f"(d[50]), "+f"(d[51]), "+f"(d[52]), "+f"(d[53]), "+f"(d[54]), "+f"(d[55]), "+f"(d[56]), "+f"(d[57]), "+f"(d[58]), "+f"(d[59]), "+f"(d[60]), "+f"(d[61]), "+f"(d[62]), "+f"(d[63])
        : "r"(alo), "r"(ahi), "r"(blo), "r"(bhi), "r"(scale_d));
}

__device__ __forceinline__ void wgmma_ss_n192_tb1(float (&d)[96], uint32_t alo, uint32_t ahi, uint32_t blo, uint32_t bhi, int scale_d) {
    asm volatile("{\n.reg .pred p;\n.reg .b64 da, db;\nsetp.ne.b32 p, %100, 0;\nmov.b64 da, {%96, %97};\nmov.b64 db, {%98, %99};\n"
        "wgmma.mma_async.sync.aligned.m64n192k16.f32.bf16.bf16 {%0, %1, %2, %3, %4, %5, %6, %7, %8, %9, %10, %11, %12, %13, %14, %15, %16, %17, %18, %19, %20, %21, %22, %23, %24, %25, %26, %27, %28, %29, %30, %31, %32, %33, %34, %35, %36, %37, %38, %39, %40, %41, %42, %43, %44, %45, %46, %47, %48, %49, %50, %51, %52, %53, %54, %55, %56, %57, %58, %59, %60, %61, %62, %63, %64, %65, %66, %67, %68, %69, %70, %71, %72, %73, %74, %75, %76, %77, %78, %79, %80, %81, %82, %83, %84, %85, %86, %87, %88, %89, %90, %91, %92, %93, %94, %95}, da, db, p, 1, 1, 0, 1;\n}\n"
        : "+f"(d[0]), "+f"(d[1]), "+f"(d[2]), "+f"(d[3]), "+f"(d[4]), "+f"(d[5]), "+f"(d[6]), "+f"(d[7]), "+f"(d[8]), "+f"(d[9]), "+f"(d[10]), "+f"(d[11]), "+f"(d[12]), "+f"(d[13]), "+f"(d[14]), "+f"(d[15]), "+f"(d[16]), "+f"(d[17]), "+f"(d[18]), "+f"(d[19]), "+f"(d[20]), "+f"(d[21]), "+f"(d[22]), "+f"(d[23]), "+f"(d[24]), "+f"(d[25]), "+f"(d[26]), "+f"(d[27]), "+f"(d[28]), "+f"(d[29]), "+f"(d[30]), "+f"(d[31]), "+f"(d[32]), "+f"(d[33]), "+f"(d[34]), "+f"(d[35]), "+f"(d[36]), "+f"(d[37]), "+f"(d[38]), "+f"(d[39]), "+f"(d[40]), "+f"(d[41]), "+f"(d[42]), "+f"(d[43]), "+f"(d[44]), "+f"(d[45]), "+f"(d[46]), "+f"(d[47]), "+f"(d[48]), "+f"(d[49]), "+f"(d[50]), "+f"(d[51]), "+f"(d[52]), "+f"(d[53]), "+f"(d[54]), "+f"(d[55]), "+f"(d[56]), "+f"(d[57]), "+f"(d[58]), "+f"(d[59]), "+f"(d[60]), "+f"(d[61]), "+f"(d[62]), "+f"(d[63]), "+f"(d[64]), "+f"(d[65]), "+f"(d[66]), "+f"(d[67]), "+f"(d[68]), "+f"(d[69]), "+f"(d[70]), "+f"(d[71]), "+f"(d[72]), "+f"(d[73]), "+f"(d[74]), "+f"(d[75]), "+f"(d[76]), "+f"(d[77]), "+f"(d[78]), "+f"(d[79]), "+f"(d[80]), "+f"(d[81]), "+f"(d[82]), "+f"(d[83]), "+f"(d[84]), "+f"(d[85]), "+f"(d[86]), "+f"(d[87]), "+f"(d[88]), "+f"(d[89]), "+f"(d[90]), "+f"(d[91]), "+f"(d[92]), "+f"(d[93]), "+f"(d[94]), "+f"(d[95])
        : "r"(alo), "r"(ahi), "r"(blo), "r"(bhi), "r"(scale_d));
}

__device__ __forceinline__ void wgmma_ss_n224_tb1(float (&d)[112], uint32_t alo, uint32_t ahi, uint32_t blo, uint32_t bhi, int scale_d) {
    asm volatile("{\n.reg .pred p;\n.reg .b64 da, db;\nsetp.ne.b32 p, %116, 0;\nmov.b64 da, {%112, %113};\nmov.b64 db, {%114, %115};\n"
        "wgmma.mma_async.sync.aligned.m64n224k16.f32.bf16.bf16 {%0, %1, %2, %3, %4, %5, %6, %7, %8, %9, %10, %11, %12, %13, %14, %15, %16, %17, %18, %19, %20, %21, %22, %23, %24, %25, %26, %27, %28, %29, %30, %31, %32, %33, %34, %35, %36, %37, %38, %39, %40, %41, %42, %43, %44, %45, %46, %47, %48, %49, %50, %51, %52, %53, %54, %55, %56, %57, %58, %59, %60, %61, %62, %63, %64, %65, %66, %67, %68, %69, %70, %71, %72, %73, %74, %75, %76, %77, %78, %79, %80, %81, %82, %83, %84, %85, %86, %87, %88, %89, %90, %91, %92, %93, %94, %95, %96, %97, %98, %99, %100, %101, %102, %103, %104, %105, %106, %107, %108, %109, %110, %111}, da, db, p, 1, 1, 0, 1;\n}\n"
        : "+f"(d[0]), "+f"(d[1]), "+f"(d[2]), "+f"(d[3]), "+f"(d[4]), "+f"(d[5]), "+f"(d[6]), "+f"(d[7]), "+f"(d[8]), "+f"(d[9]), "+f"(d[10]), "+f"(d[11]), "+f"(d[12]), "+f"(d[13]), "+f"(d[14]), "+f"(d[15]), "+f"(d[16]), "+f"(d[17]), "+f"(d[18]), "+f"(d[19]), "+f"(d[20]), "+f"(d[21]), "+f"(d[22]), "+f"(d[23]), "+f"(d[24]), "+f"(d[25]), "+f"(d[26]), "+f"(d[27]), "+f"(d[28]), "+f"(d[29]), "+f"(d[30]), "+f"(d[31]), "+f"(d[32]), "+f"(d[33]), "+f"(d[34]), "+f"(d[35]), "+f"(d[36]), "+f"(d[37]), "+f"(d[38]), "+f"(d[39]), "+f"(d[40]), "+f"(d[41]), "+f"(d[42]), "+f"(d[43]), "+f"(d[44]), "+f"(d[45]), "+f"(d[46]), "+f"(d[47]), "+f"(d[48]), "+f"(d[49]), "+f"(d[50]), "+f"(d[51]), "+f"(d[52]), "+f"(d[53]), "+f"(d[54]), "+f"(d[55]), "+f"(d[56]), "+f"(d[57]), "+f"(d[58]), "+f"(d[59]), "+f"(d[60]), "+f"(d[61]), "+f"(d[62]), "+f"(d[63]), "+f"(d[64]), "+f"(d[65]), "+f"(d[66]), "+f"(d[67]), "+f"(d[68]), "+f"(d[69]), "+f"(d[70]), "+f"(d[71]), "+f"(d[72]), "+f"(d[73]), "+f"(d[74]), "+f"(d[75]), "+f"(d[76]), "+f"(d[77]), "+f"(d[78]), "+f"(d[79]), "+f"(d[80]), "+f"(d[81]), "+f"(d[82]), "+f"(d[83]), "+f"(d[84]), "+f"(d[85]), "+f"(d[86]), "+f"(d[87]), "+f"(d[88]), "+f"(d[89]), "+f"(d[90]), "+f"(d[91]), "+f"(d[92]), "+f"(d[93]), "+f"(d[94]), "+f"(d[95]), "+f"(d[96]), "+f"(d[97]), "+f"(d[98]), "+f"(d[99]), "+f"(d[100]), "+f"(d[101]), "+f"(d[102]), "+f"(d[103]), "+f"(d[104]), "+f"(d[105]), "+f"(d[106]), "+f"(d[107]), "+f"(d[108]), "+f"(d[109]), "+f"(d[110]), "+f"(d[111])
        : "r"(alo), "r"(ahi), "r"(blo), "r"(bhi), "r"(scale_d));
}

__device__ __forceinline__ void wgmma_ss_n256_tb1(float (&d)[128], uint32_t alo, uint32_t ahi, uint32_t blo, uint32_t bhi, int scale_d) {
    asm volatile("{\n.reg .pred p;\n.reg .b64 da, db;\nsetp.ne.b32 p, %132, 0;\nmov.b64 da, {%128, %129};\nmov.b64 db, {%130, %131};\n"
        "wgmma.mma_async.sync.aligned.m64n256k16.f32.bf16.bf16 {%0, %1, %2, %3, %4, %5, %6, %7, %8, %9, %10, %11, %12, %13, %14, %15, %16, %17, %18, %19, %20, %21, %22, %23, %24, %25, %26, %27, %28, %29, %30, %31, %32, %33, %34, %35, %36, %37, %38, %39, %40, %41, %42, %43, %44, %45, %46, %47, %48, %49, %50, %51, %52, %53, %54, %55, %56, %57, %58, %59, %60, %61, %62, %63, %64, %65, %66, %67, %68, %69, %70, %71, %72, %73, %74, %75, %76, %77, %78, %79, %80, %81, %82, %83, %84, %85, %86, %87, %88, %89, %90, %91, %92, %93, %94, %95, %96, %97, %98, %99, %100, %101, %102, %103, %104, %105, %106, %107, %108, %109, %110, %111, %112, %113, %114, %115, %116, %117, %118, %119, %120, %121, %122, %123, %124, %125, %126, %127}, da, db, p, 1, 1, 0, 1;\n}\n"
        : "+f"(d[0]), "+f"(d[1]), "+f"(d[2]), "+f"(d[3]), "+f"(d[4]), "+f"(d[5]), "+f"(d[6]), "+f"(d[7]), "+f"(d[8]), "+f"(d[9]), "+f"(d[10]), "+f"(d[11]), "+f"(d[12]), "+f"(d[13]), "+f"(d[14]), "+f"(d[15]), "+f"(d[16]), "+f"(d[17]), "+f"(d[18]), "+f"(d[19]), "+f"(d[20]), "+f"(d[21]), "+f"(d[22]), "+f"(d[23]), "+f"(d[24]), "+f"(d[25]), "+f"(d[26]), "+f"(d[27]), "+f"(d[28]), "+f"(d[29]), "+f"(d[30]), "+f"(d[31]), "+f"(d[32]), "+f"(d[33]), "+f"(d[34]), "+f"(d[35]), "+f"(d[36]), "+f"(d[37]), "+f"(d[38]), "+f"(d[39]), "+f"(d[40]), "+f"(d[41]), "+f"(d[42]), "+f"(d[43]), "+f"(d[44]), "+f"(d[45]), "+f"(d[46]), "+f"(d[47]), "+f"(d[48]), "+f"(d[49]), "+f"(d[50]), "+f"(d[51]), "+f"(d[52]), "+f"(d[53]), "+f"(d[54]), "+f"(d[55]), "+f"(d[56]), "+f"(d[57]), "+f"(d[58]), "+f"(d[59]), "+f"(d[60]), "+f"(d[61]), "+f"(d[62]), "+f"(d[63]), "+f"(d[64]), "+f"(d[65]), "+f"(d[66]), "+f"(d[67]), "+f"(d[68]), "+f"(d[69]), "+f"(d[70]), "+f"(d[71]), "+f"(d[72]), "+f"(d[73]), "+f"(d[74]), "+f"(d[75]), "+f"(d[76]), "+f"(d[77]), "+f"(d[78]), "+f"(d[79]), "+f"(d[80]), "+f"(d[81]), "+f"(d[82]), "+f"(d[83]), "+f"(d[84]), "+f"(d[85]), "+f"(d[86]), "+f"(d[87]), "+f"(d[88]), "+f"(d[89]), "+f"(d[90]), "+f"(d[91]), "+f"(d[92]), "+f"(d[93]), "+f"(d[94]), "+f"(d[95]), "+f"(d[96]), "+f"(d[97]), "+f"(d[98]), "+f"(d[99]), "+f"(d[100]), "+f"(d[101]), "+f"(d[102]), "+f"(d[103]), "+f"(d[104]), "+f"(d[105]), "+f"(d[106]), "+f"(d[107]), "+f"(d[108]), "+f"(d[109]), "+f"(d[110]), "+f"(d[111]), "+f"(d[112]), "+f"(d[113]), "+f"(d[114]), "+f"(d[115]), "+f"(d[116]), "+f"(d[117]), "+f"(d[118]), "+f"(d[119]), "+f"(d[120]), "+f"(d[121]), "+f"(d[122]), "+f"(d[123]), "+f"(d[124]), "+f"(d[125]), "+f"(d[126]), "+f"(d[127])
        : "r"(alo), "r"(ahi), "r"(blo), "r"(bhi), "r"(scale_d));
}

__device__ __forceinline__ void wgmma_ss_n64_tb0(float (&d)[32], uint32_t alo, uint32_t ahi, uint32_t blo, uint32_t bhi, int scale_d) {
    asm volatile("{\n.reg .pred p;\n.reg .b64 da, db;\nsetp.ne.b32 p, %36, 0;\nmov.b64 da, {%32, %33};\nmov.b64 db, {%34, %35};\n"
        "wgmma.mma_async.sync.aligned.m64n64k16.f32.bf16.bf16 {%0, %1, %2, %3, %4, %5, %6, %7, %8, %9, %10, %11, %12, %13, %14, %15, %16, %17, %18, %19, %20, %21, %22, %23, %24, %25, %26, %27, %28, %29, %30, %31}, da, db, p, 1, 1, 0, 0;\n}\n"
        : "+f"(d[0]), "+f"(d[1]), "+f"(d[2]), "+f"(d[3]), "+f"(d[4]), "+f"(d[5]), "+f"(d[6]), "+f"(d[7]), "+f"(d[8]), "+f"(d[9]), "+f"(d[10]), "+f"(d[11]), "+f"(d[12]), "+f"(d[13]), "+f"(d[14]), "+f"(d[15]), "+f"(d[16]), "+f"(d[17]), "+f"(d[18]), "+f"(d[19]), "+f"(d[20]), "+f"(d[21]), "+f"(d[22]), "+f"(d[23]), "+f"(d[24]), "+f"(d[25]), "+f"(d[26]), "+f"(d[27]), "+f"(d[28]), "+f"(d[29]), "+f"(d[30]), "+f"(d[31])
        : "r"(alo), "r"(ahi), "r"(blo), "r"(bhi), "r"(scale_d));
}

__device__ __forceinline__ void wgmma_rs_n128_tb0(float (&d)[64], uint32_t a0, uint32_t a1, uint32_t a2, uint32_t a3, uint32_t blo, uint32_t bhi, int scale_d) {
    asm volatile("{\n.reg .pred p;\n.reg .b64 db;\nsetp.ne.b32 p, %70, 0;\nmov.b64 db, {%68, %69};\n"
        "wgmma.mma_async.sync.aligned.m64n128k16.f32.bf16.bf16 {%0, %1, %2, %3, %4, %5, %6, %7, %8, %9, %10, %11, %12, %13, %14, %15, %16, %17, %18, %19, %20, %21, %22, %23, %24, %25, %26, %27, %28, %29, %30, %31, %32, %33, %34, %35, %36, %37, %38, %39, %40, %41, %42, %43, %44, %45, %46, %47, %48, %49, %50, %51, %52, %53, %54, %55, %56, %57, %58, %59, %60, %61, %62, %63}, {%64, %65, %66, %67}, db, p, 1, 1, 0;\n}\n"
        : "+f"(d[0]), "+f"(d[1]), "+f"(d[2]), "+f"(d[3]), "+f"(d[4]), "+f"(d[5]), "+f"(d[6]), "+f"(d[7]), "+f"(d[8]), "+f"(d[9]), "+f"(d[10]), "+f"(d[11]), "+f"(d[12]), "+f"(d[13]), "+f"(d[14]), "+f"(d[15]), "+f"(d[16]), "+f"(d[17]), "+f"(d[18]), "+f"(d[19]), "+f"(d[20]), "+f"(d[21]), "+f"(d[22]), "+f"(d[23]), "+f"(d[24]), "+f"(d[25]), "+f"(d[26]), "+f"(d[27]), "+f"(d[28]), "+f"(d[29]), "+f"(d[30]), "+f"(d[31]), "+f"(d[32]), "+f"(d[33]), "+f"(d[34]), "+f"(d[35]), "+f"(d[36]), "+f"(d[37]), "+f"(d[38]), "+f"(d[39]), "+f"(d[40]), "+f"(d[41]), "+f"(d[42]), "+f"(d[43]), "+f"(d[44]), "+f"(d[45]), "+f"(d[46]), "+f"(d[47]), "+f"(d[48]), "+f"(d[49]), "+f"(d[50]), "+f"(d[51]), "+f"(d[52]), "+f"(d[53]), "+f"(d[54]), "+f"(d[55]), "+f"(d[56]), "+f"(d[57]), "+f"(d[58]), "+f"(d[59]), "+f"(d[60]), "+f"(d[61]), "+f"(d[62]), "+f"(d[63])
        : "r"(a0), "r"(a1), "r"(a2), "r"(a3), "r"(blo), "r"(bhi), "r"(scale_d));
}

__device__ __forceinline__ void wgmma_rs_n64_tb0(float (&d)[32], uint32_t a0, uint32_t a1, uint32_t a2, uint32_t a3, uint32_t blo, uint32_t bhi, int scale_d) {
    asm volatile("{\n.reg .pred p;\n.reg .b64 db;\nsetp.ne.b32 p, %38, 0;\nmov.b64 db, {%36, %37};\n"
        "wgmma.mma_async.sync.aligned.m64n64k16.f32.bf16.bf16 {%0, %1, %2, %3, %4, %5, %6, %7, %8, %9, %10, %11, %12, %13, %14, %15, %16, %17, %18, %19, %20, %21, %22, %23, %24, %25, %26, %27, %28, %29, %30, %31}, {%32, %33, %34, %35}, db, p, 1, 1, 0;\n}\n"
        : "+f"(d[0]), "+f"(d[1]), "+f"(d[2]), "+f"(d[3]), "+f"(d[4]), "+f"(d[5]), "+f"(d[6]), "+f"(d[7]), "+f"(d[8]), "+f"(d[9]), "+f"(d[10]), "+f"(d[11]), "+f"(d[12]), "+f"(d[13]), "+f"(d[14]), "+f"(d[15]), "+f"(d[16]), "+f"(d[17]), "+f"(d[18]), "+f"(d[19]), "+f"(d[20]), "+f"(d[21]), "+f"(d[22]), "+f"(d[23]), "+f"(d[24]), "+f"(d[25]), "+f"(d[26]), "+f"(d[27]), "+f"(d[28]), "+f"(d[29]), "+f"(d[30]), "+f"(d[31])
        : "r"(a0), "r"(a1), "r"(a2), "r"(a3), "r"(blo), "r"(bhi), "r"(scale_d));
}

__device__ __forceinline__ void wgmma_rs_n32_tb1(float (&d)[16], uint32_t a0, uint32_t a1, uint32_t a2, uint32_t a3, uint32_t blo, uint32_t bhi, int scale_d) {
    asm volatile("{\n.reg .pred p;\n.reg .b64 db;\nsetp.ne.b32 p, %22, 0;\nmov.b64 db, {%20, %21};\n"
        "wgmma.mma_async.sync.aligned.m64n32k16.f32.bf16.bf16 {%0, %1, %2, %3, %4, %5, %6, %7, %8, %9, %10, %11, %12, %13, %14, %15}, {%16, %17, %18, %19}, db, p, 1, 1, 1;\n}\n"
        : "+f"(d[0]), "+f"(d[1]), "+f"(d[2]), "+f"(d[3]), "+f"(d[4]), "+f"(d[5]), "+f"(d[6]), "+f"(d[7]), "+f"(d[8]), "+f"(d[9]), "+f"(d[10]), "+f"(d[11]), "+f"(d[12]), "+f"(d[13]), "+f"(d[14]), "+f"(d[15])
        : "r"(a0), "r"(a1), "r"(a2), "r"(a3), "r"(blo), "r"(bhi), "r"(scale_d));
}

__device__ __forceinline__ void wgmma_rs_n40_tb1(float (&d)[20], uint32_t a0, uint32_t a1, uint32_t a2, uint32_t a3, uint32_t blo, uint32_t bhi, int scale_d) {
    asm volatile("{\n.reg .pred p;\n.reg .b64 db;\nsetp.ne.b32 p, %26, 0;\nmov.b64 db, {%24, %25};\n"
        "wgmma.mma_async.sync.aligned.m64n40k16.f32.bf16.bf16 {%0, %1, %2, %3, %4, %5, %6, %7, %8, %9, %10, %11, %12, %13, %14, %15, %16, %17, %18, %19}, {%20, %21, %22, %23}, db, p, 1, 1, 1;\n}\n"
        : "+f"(d[0]), "+f"(d[1]), "+f"(d[2]), "+f"(d[3]), "+f"(d[4]), "+f"(d[5]), "+f"(d[6]), "+f"(d[7]), "+f"(d[8]), "+f"(d[9]), "+f"(d[10]), "+f"(d[11]), "+f"(d[12]), "+f"(d[13]), "+f"(d[14]), "+f"(d[15]), "+f"(d[16]), "+f"(d[17]), "+f"(d[18]), "+f"(d[19])
        : "r"(a0), "r"(a1), "r"(a2), "r"(a3), "r"(blo), "r"(bhi), "r"(scale_d));
}


template <int BN>
__device__ __forceinline__ void wgmma_tile(float (&d)[BN / 2], uint32_t da, uint32_t db, int sd) {
    constexpr uint32_t HI = desc_hi(1024, 1);
    if constexpr (BN == 128) wgmma_ss_n128_tb1(d, da, HI, db, HI, sd);
    else if constexpr (BN == 192) wgmma_ss_n192_tb1(d, da, HI, db, HI, sd);
    else if constexpr (BN == 224) wgmma_ss_n224_tb1(d, da, HI, db, HI, sd);
    else wgmma_ss_n256_tb1(d, da, HI, db, HI, sd);
}

__global__ void __launch_bounds__(256) prep_kernel(const bf16* __restrict__ x, const bf16* __restrict__ gate_w,
                                                   const bf16* __restrict__ w1, const bf16* __restrict__ w3) {
    const int tid = threadIdx.x;
    if (blockIdx.x < 256) {
        const int row = blockIdx.x * 8 + (tid >> 5);
        const int lane = tid & 31;
        const uint4* xr = reinterpret_cast<const uint4*>(x + (size_t)row * DM);
        const uint4* gw = reinterpret_cast<const uint4*>(gate_w);
        float v[32];
        float gsum = 0.f, sum = 0.f;
#pragma unroll
        for (int i = 0; i < 4; i++) {
            uint4 a = xr[lane + 32 * i];
            uint4 b = gw[lane + 32 * i];
            const uint32_t aa[4] = {a.x, a.y, a.z, a.w};
            const uint32_t bb[4] = {b.x, b.y, b.z, b.w};
#pragma unroll
            for (int j = 0; j < 4; j++) {
                float x0 = __uint_as_float(aa[j] << 16), x1 = __uint_as_float(aa[j] & 0xFFFF0000u);
                float g0 = __uint_as_float(bb[j] << 16), g1 = __uint_as_float(bb[j] & 0xFFFF0000u);
                v[i * 8 + j * 2] = x0;
                v[i * 8 + j * 2 + 1] = x1;
                sum += x0 + x1;
                gsum += bf16_round(x0 * g0) + bf16_round(x1 * g1);
            }
        }
#pragma unroll
        for (int o = 16; o > 0; o >>= 1) {
            sum += __shfl_xor_sync(0xffffffffu, sum, o);
            gsum += __shfl_xor_sync(0xffffffffu, gsum, o);
        }
        const float mean = sum * (1.0f / DM);
        float m2 = 0.f;
#pragma unroll
        for (int i = 0; i < 32; i++) {
            float d = v[i] - mean;
            m2 += d * d;
        }
#pragma unroll
        for (int o = 16; o > 0; o >>= 1) m2 += __shfl_xor_sync(0xffffffffu, m2, o);
        if (lane == 0) {
            g_mean1[row] = mean;
            g_rstd1[row] = rsqrtf(m2 * (1.0f / DM) + 1e-5f);
            float logit = bf16_round(gsum);
            float g = bf16_round(1.0f / (1.0f + __expf(-logit)));
            g_gate[row] = g;
            g_omg[row] = bf16_round(1.0f - g);
        }
    } else {
        __shared__ float red[32][65];
        const int strip = blockIdx.x - 256;
        const bf16* w;
        float* out;
        int ld, col0;
        if (strip < 16) { w = w1; ld = DM; col0 = strip * 64; out = g_cs1; }
        else { w = w3; ld = FF; col0 = (strip - 16) * 64; out = g_cs3; }
        const int cg = tid & 7;
        const int rg = tid >> 3;
        float acc[8];
#pragma unroll
        for (int j = 0; j < 8; j++) acc[j] = 0.f;
#pragma unroll 8
        for (int r = 0; r < 32; r++) {
            uint4 a = *reinterpret_cast<const uint4*>(w + (size_t)(r * 32 + rg) * ld + col0 + cg * 8);
            const uint32_t aa[4] = {a.x, a.y, a.z, a.w};
#pragma unroll
            for (int j = 0; j < 4; j++) {
                acc[2 * j] += __uint_as_float(aa[j] << 16);
                acc[2 * j + 1] += __uint_as_float(aa[j] & 0xFFFF0000u);
            }
        }
#pragma unroll
        for (int j = 0; j < 8; j++) red[rg][cg * 8 + j] = acc[j];
        __syncthreads();
        if (tid < 64) {
            float s = 0.f;
#pragma unroll
            for (int r = 0; r < 32; r++) s += red[r][tid];
            out[col0 + tid] = s;
        }
    }
}

template <int BN, int STAGES>
struct GemmSmem {
    static constexpr int A_BYTES = 128 * 64 * 2;
    static constexpr int B_BOXES = (BN + 63) / 64;
    static constexpr int B_BYTES = B_BOXES * 64 * 64 * 2;
    static constexpr int STAGE_BYTES = A_BYTES + B_BYTES;
    static constexpr int STG_OFF = STAGES * STAGE_BYTES;
    static constexpr int BAR_OFF = STG_OFF + 2 * 16384;
    static constexpr int TOTAL = BAR_OFF + 256 + 1024;
};

template <int MODE, int BN, int STAGES>
__global__ void __launch_bounds__(384, 1)
gemm_kernel(const __grid_constant__ CUtensorMap mA, const __grid_constant__ CUtensorMap mB0,
            const __grid_constant__ CUtensorMap mB1, const __grid_constant__ CUtensorMap mC0,
            const __grid_constant__ CUtensorMap mC1, const bf16* __restrict__ xin, int n_tiles_n, int kblocks) {
    using L = GemmSmem<BN, STAGES>;
    extern __shared__ uint8_t smem_raw[];
    const uint32_t sbase = (smem_u32(smem_raw) + 1023u) & ~1023u;
    const uint32_t bar_full = sbase + L::BAR_OFF;
    const uint32_t bar_empty = bar_full + 8 * STAGES;
    const int wg = threadIdx.x >> 7;
    const int ntiles = 16 * n_tiles_n;

    if (threadIdx.x == 0) {
        for (int s = 0; s < STAGES; s++) {
            mbar_init(bar_full + 8 * s, 1);
            mbar_init(bar_empty + 8 * s, 2);
        }
        asm volatile("fence.mbarrier_init.release.cluster;" ::: "memory");
    }
    __syncthreads();

    if (wg == 0) {
        reg_dealloc<40>();
        if (threadIdx.x == 0) {
            prefetch_tmap(&mA);
            prefetch_tmap(&mB0);
            prefetch_tmap(&mB1);
            int stage = 0;
            uint32_t phase = 1;
            for (int tile = blockIdx.x; tile < ntiles; tile += gridDim.x) {
                const int m0 = (tile & 15) * 128;
                const int n0 = (tile >> 4) * BN;
                for (int kb = 0; kb < kblocks; kb++) {
                    mbar_wait(bar_empty + 8 * stage, phase);
                    const uint32_t sa = sbase + stage * L::STAGE_BYTES;
                    const uint32_t sb = sa + L::A_BYTES;
                    const uint32_t fb = bar_full + 8 * stage;
                    mbar_expect_tx(fb, L::STAGE_BYTES);
                    int arow = m0;
                    if (MODE == 2) {
                        const int grp = kb >> 2;
                        arow += (grp == 0) ? -1 : (grp == 1) ? 1 : (grp == 2) ? -2 : 2;
                    }
                    tma_load_2d(sa, &mA, kb * 64, arow, fb);
                    const CUtensorMap* mb = &mB0;
                    int bc = n0, br = kb * 64;
                    if (MODE == 1 && n0 >= 3 * DM) { mb = &mB1; bc = n0 - 3 * DM; }
                    if (MODE == 5 && kb >= 16) { mb = &mB1; br = (kb - 16) * 64; }
#pragma unroll
                    for (int b = 0; b < L::B_BOXES; b++) tma_load_2d(sb + b * 8192, mb, bc + b * 64, br, fb);
                    if (++stage == STAGES) { stage = 0; phase ^= 1; }
                }
            }
        }
    } else {
        reg_alloc<232>();
        const int c = wg - 1;
        const int warp = (threadIdx.x >> 5) & 3;
        const int lane = threadIdx.x & 31;
        const int tid_wg = threadIdx.x & 127;
        const uint32_t stg = sbase + L::STG_OFF + c * 16384;
        int stage = 0;
        uint32_t phase = 0;
        float acc[BN / 2];
        for (int tile = blockIdx.x; tile < ntiles; tile += gridDim.x) {
            const int m0 = (tile & 15) * 128;
            const int n0 = (tile >> 4) * BN;
            int prev_stage = 0;
            for (int kb = 0; kb < kblocks; kb++) {
                mbar_wait(bar_full + 8 * stage, phase);
                const uint32_t sa = sbase + stage * L::STAGE_BYTES + c * 8192;
                const uint32_t sb = sbase + stage * L::STAGE_BYTES + L::A_BYTES;
                const uint32_t da = desc_lo(sa, 16);
                const uint32_t db = desc_lo(sb, 8192);
                wgmma_fence();
#pragma unroll
                for (int k = 0; k < 4; k++) wgmma_tile<BN>(acc, da + k * 2, db + k * 128, (kb | k) != 0);
                wgmma_commit();
                if (kb > 0) {
                    wgmma_wait<1>();
                    if (tid_wg == 0) mbar_arrive(bar_empty + 8 * prev_stage);
                }
                prev_stage = stage;
                if (++stage == STAGES) { stage = 0; phase ^= 1; }
            }
            wgmma_wait<0>();
            if (tid_wg == 0) mbar_arrive(bar_empty + 8 * prev_stage);

            const int r0 = m0 + c * 64 + warp * 16 + (lane >> 2);
            const int r1 = r0 + 8;
            const int cq = (lane & 3) * 2;
            const CUtensorMap* mc = &mC0;
            int out_c0 = n0;
            if (MODE == 1) {
                if (n0 >= 3 * DM) {
                    mc = &mC1;
                    out_c0 = n0 - 3 * DM;
                    const float mu0 = g_mean1[r0], mu1 = g_mean1[r1];
                    const float rs0 = g_rstd1[r0], rs1 = g_rstd1[r1];
#pragma unroll
                    for (int j = 0; j < BN / 8; j++) {
                        const float2 cs = *reinterpret_cast<const float2*>(&g_cs1[out_c0 + 8 * j + cq]);
                        acc[4 * j + 0] = gelu_tanh(rs0 * fmaf(-mu0, cs.x, acc[4 * j + 0]));
                        acc[4 * j + 1] = gelu_tanh(rs0 * fmaf(-mu0, cs.y, acc[4 * j + 1]));
                        acc[4 * j + 2] = gelu_tanh(rs1 * fmaf(-mu1, cs.x, acc[4 * j + 2]));
                        acc[4 * j + 3] = gelu_tanh(rs1 * fmaf(-mu1, cs.y, acc[4 * j + 3]));
                    }
                }
            } else if (MODE == 2) {
                float s0 = 0.f, s1 = 0.f;
#pragma unroll
                for (int j = 0; j < BN / 8; j++) {
                    const uint32_t xa = *reinterpret_cast<const uint32_t*>(xin + (size_t)r0 * DM + n0 + 8 * j + cq);
                    const uint32_t xb = *reinterpret_cast<const uint32_t*>(xin + (size_t)r1 * DM + n0 + 8 * j + cq);
                    acc[4 * j + 0] = bf16_round(bf16_round(acc[4 * j + 0]) + __uint_as_float(xa << 16));
                    acc[4 * j + 1] = bf16_round(bf16_round(acc[4 * j + 1]) + __uint_as_float(xa & 0xFFFF0000u));
                    acc[4 * j + 2] = bf16_round(bf16_round(acc[4 * j + 2]) + __uint_as_float(xb << 16));
                    acc[4 * j + 3] = bf16_round(bf16_round(acc[4 * j + 3]) + __uint_as_float(xb & 0xFFFF0000u));
                    s0 += acc[4 * j + 0] + acc[4 * j + 1];
                    s1 += acc[4 * j + 2] + acc[4 * j + 3];
                }
                s0 += __shfl_xor_sync(0xffffffffu, s0, 1);
                s0 += __shfl_xor_sync(0xffffffffu, s0, 2);
                s1 += __shfl_xor_sync(0xffffffffu, s1, 1);
                s1 += __shfl_xor_sync(0xffffffffu, s1, 2);
                const float mu0 = s0 * (1.0f / BN), mu1 = s1 * (1.0f / BN);
                float q0 = 0.f, q1 = 0.f;
#pragma unroll
                for (int j = 0; j < BN / 8; j++) {
                    float d;
                    d = acc[4 * j + 0] - mu0; q0 += d * d;
                    d = acc[4 * j + 1] - mu0; q0 += d * d;
                    d = acc[4 * j + 2] - mu1; q1 += d * d;
                    d = acc[4 * j + 3] - mu1; q1 += d * d;
                }
                q0 += __shfl_xor_sync(0xffffffffu, q0, 1);
                q0 += __shfl_xor_sync(0xffffffffu, q0, 2);
                q1 += __shfl_xor_sync(0xffffffffu, q1, 1);
                q1 += __shfl_xor_sync(0xffffffffu, q1, 2);
                if ((lane & 3) == 0) {
                    static_assert(MODE != 2 || BN == 128, "stats layout assumes BN=128");
                    g_stat2[r0 * 8 + (n0 >> 7)] = make_float2(s0, q0);
                    g_stat2[r1 * 8 + (n0 >> 7)] = make_float2(s1, q1);
                }
            } else if (MODE == 3) {
                out_c0 = n0 + DM;
                float mu[2], rs[2];
#pragma unroll
                for (int h = 0; h < 2; h++) {
                    const float4* sp = reinterpret_cast<const float4*>(&g_stat2[(h ? r1 : r0) * 8]);
                    float4 p[4];
                    float s = 0.f;
#pragma unroll
                    for (int i = 0; i < 4; i++) { p[i] = sp[i]; s += p[i].x + p[i].z; }
                    const float mean = s * (1.0f / DM);
                    float m2 = 0.f;
#pragma unroll
                    for (int i = 0; i < 4; i++) {
                        float d0 = p[i].x * (1.0f / 128) - mean, d1 = p[i].z * (1.0f / 128) - mean;
                        m2 += p[i].y + p[i].w + 128.0f * (d0 * d0 + d1 * d1);
                    }
                    mu[h] = mean;
                    rs[h] = rsqrtf(m2 * (1.0f / DM) + 1e-5f);
                }
                const float og0 = g_omg[r0], og1 = g_omg[r1];
#pragma unroll
                for (int j = 0; j < BN / 8; j++) {
                    const float2 cs = *reinterpret_cast<const float2*>(&g_cs3[n0 + 8 * j + cq]);
                    acc[4 * j + 0] = og0 * gelu_tanh(rs[0] * fmaf(-mu[0], cs.x, acc[4 * j + 0]));
                    acc[4 * j + 1] = og0 * gelu_tanh(rs[0] * fmaf(-mu[0], cs.y, acc[4 * j + 1]));
                    acc[4 * j + 2] = og1 * gelu_tanh(rs[1] * fmaf(-mu[1], cs.x, acc[4 * j + 2]));
                    acc[4 * j + 3] = og1 * gelu_tanh(rs[1] * fmaf(-mu[1], cs.y, acc[4 * j + 3]));
                }
            } else {
                const float og0 = g_omg[r0], og1 = g_omg[r1];
#pragma unroll
                for (int j = 0; j < BN / 8; j++) {
                    const uint32_t xa = *reinterpret_cast<const uint32_t*>(xin + (size_t)r0 * DM + n0 + 8 * j + cq);
                    const uint32_t xb = *reinterpret_cast<const uint32_t*>(xin + (size_t)r1 * DM + n0 + 8 * j + cq);
                    acc[4 * j + 0] = fmaf(og0, __uint_as_float(xa << 16), acc[4 * j + 0]);
                    acc[4 * j + 1] = fmaf(og0, __uint_as_float(xa & 0xFFFF0000u), acc[4 * j + 1]);
                    acc[4 * j + 2] = fmaf(og1, __uint_as_float(xb << 16), acc[4 * j + 2]);
                    acc[4 * j + 3] = fmaf(og1, __uint_as_float(xb & 0xFFFF0000u), acc[4 * j + 3]);
                }
            }
            const int srow = warp * 16 + (lane & 7) + ((lane >> 3) & 1) * 8;
#pragma unroll
            for (int rnd = 0; rnd < (BN + 127) / 128; rnd++) {
                if (tid_wg == 0) bulk_wait_read0();
                named_bar_sync(1 + c, 128);
#pragma unroll
                for (int jj = 0; jj < 8; jj++) {
                    const int j = rnd * 16 + jj * 2;
                    if (j * 8 < BN) {
                        const int jb = jj * 2 + (lane >> 4);
                        const uint32_t addr = stg + (jb >> 3) * 8192 + srow * 128 + (((jb & 7) ^ (srow & 7)) << 4);
                        stmatrix_x4(addr, pack_bf16(acc[4 * j + 0], acc[4 * j + 1]), pack_bf16(acc[4 * j + 2], acc[4 * j + 3]),
                                    pack_bf16(acc[4 * j + 4], acc[4 * j + 5]), pack_bf16(acc[4 * j + 6], acc[4 * j + 7]));
                    }
                }
                fence_proxy_async();
                named_bar_sync(1 + c, 128);
                if (tid_wg == 0) {
                    tma_store_2d(mc, stg, out_c0 + rnd * 128, m0 + c * 64);
                    if (rnd * 128 + 64 < BN) tma_store_2d(mc, stg + 8192, out_c0 + rnd * 128 + 64, m0 + c * 64);
                    bulk_commit();
                }
            }
        }
        if (tid_wg == 0) bulk_wait0();
    }
}

constexpr int ATT_STAGES = 4;
constexpr int ATT_DIST = 2;
constexpr int ATT_Q_OFF = ATT_STAGES * 16384;
constexpr int ATT_ONES_OFF = ATT_Q_OFF + 8192;
constexpr int ATT_BAR_OFF = ATT_ONES_OFF + 4096;
constexpr int ATT_SMEM = ATT_BAR_OFF + 256 + 1024;

struct AttState {
    float o[20];
    float m0, m1;
    float mp0, mp1;
};

__device__ __forceinline__ void row_max(const float (&s)[32], float& m0, float& m1) {
    float mx0 = fmaxf(s[0], s[1]), mx1 = fmaxf(s[2], s[3]);
#pragma unroll
    for (int i = 1; i < 8; i++) {
        mx0 = fmaxf(mx0, fmaxf(s[4 * i], s[4 * i + 1]));
        mx1 = fmaxf(mx1, fmaxf(s[4 * i + 2], s[4 * i + 3]));
    }
    mx0 = fmaxf(mx0, __shfl_xor_sync(0xffffffffu, mx0, 1));
    mx1 = fmaxf(mx1, __shfl_xor_sync(0xffffffffu, mx1, 1));
    mx0 = fmaxf(mx0, __shfl_xor_sync(0xffffffffu, mx0, 2));
    mx1 = fmaxf(mx1, __shfl_xor_sync(0xffffffffu, mx1, 2));
    m0 = fmaxf(m0, mx0);
    m1 = fmaxf(m1, mx1);
}

__device__ __forceinline__ void attn_step(float (&sc)[32], float (&sn)[32], uint32_t (&p)[16], uint32_t dq,
                                          AttState& st, uint32_t dk_next, uint32_t dv_prev, uint32_t release_bar) {
    const float cs = 0.17677669529663687f * 1.4426950408889634f;
    constexpr uint32_t HI = desc_hi(512, 2);
    wgmma_fence();
    wgmma_ss_n64_tb0(sn, dq, HI, dk_next, HI, 0);
    wgmma_ss_n64_tb0(sn, dq + 2, HI, dk_next + 2, HI, 1);
#pragma unroll
    for (int t = 0; t < 4; t++)
        wgmma_rs_n40_tb1(st.o, p[4 * t], p[4 * t + 1], p[4 * t + 2], p[4 * t + 3], dv_prev + t * 64, HI, 1);
    wgmma_commit();
    const float mc0 = st.m0, mc1 = st.m1;
    const float b0 = mc0 * cs, b1 = mc1 * cs;
#pragma unroll
    for (int i = 0; i < 4; i++) {
        sc[4 * i + 0] = ex2(fmaf(sc[4 * i + 0], cs, -b0));
        sc[4 * i + 1] = ex2(fmaf(sc[4 * i + 1], cs, -b0));
        sc[4 * i + 2] = ex2(fmaf(sc[4 * i + 2], cs, -b1));
        sc[4 * i + 3] = ex2(fmaf(sc[4 * i + 3], cs, -b1));
    }
    wgmma_wait<0>();
    if (release_bar != 0 && (threadIdx.x & 127) == 0) mbar_arrive(release_bar);
    row_max(sn, st.m0, st.m1);
#pragma unroll
    for (int i = 4; i < 8; i++) {
        sc[4 * i + 0] = ex2(fmaf(sc[4 * i + 0], cs, -b0));
        sc[4 * i + 1] = ex2(fmaf(sc[4 * i + 1], cs, -b0));
        sc[4 * i + 2] = ex2(fmaf(sc[4 * i + 2], cs, -b1));
        sc[4 * i + 3] = ex2(fmaf(sc[4 * i + 3], cs, -b1));
    }
    {
        const float a0 = ex2((st.mp0 - mc0) * cs), a1 = ex2((st.mp1 - mc1) * cs);
#pragma unroll
        for (int i = 0; i < 5; i++) {
            st.o[4 * i + 0] *= a0; st.o[4 * i + 1] *= a0;
            st.o[4 * i + 2] *= a1; st.o[4 * i + 3] *= a1;
        }
        st.mp0 = mc0; st.mp1 = mc1;
    }
#pragma unroll
    for (int i = 0; i < 8; i++) {
        p[2 * i] = pack_bf16(sc[4 * i + 0], sc[4 * i + 1]);
        p[2 * i + 1] = pack_bf16(sc[4 * i + 2], sc[4 * i + 3]);
    }
}

__global__ void __launch_bounds__(256, 2)
attn_kernel(const __grid_constant__ CUtensorMap mKV) {
    extern __shared__ uint8_t smem_raw[];
    const uint32_t sbase = (smem_u32(smem_raw) + 1023u) & ~1023u;
    const uint32_t bar_kfull = sbase + ATT_BAR_OFF;
    const uint32_t bar_vfull = bar_kfull + 8 * ATT_STAGES;
    const uint32_t bar_empty = bar_vfull + 8 * ATT_STAGES;
    const int head = blockIdx.x >> 4;
    const int q0 = (blockIdx.x & 15) * 128;
    const int warp_id = threadIdx.x >> 5;
    const int lane = threadIdx.x & 31;
    constexpr int NBLK = S_LEN / 128;

    if (threadIdx.x == 0) {
        for (int s = 0; s < ATT_STAGES; s++) {
            mbar_init(bar_kfull + 8 * s, 1);
            mbar_init(bar_vfull + 8 * s, 1);
            mbar_init(bar_empty + 8 * s, 2);
        }
        asm volatile("fence.mbarrier_init.release.cluster;" ::: "memory");
        prefetch_tmap(&mKV);
#pragma unroll
        for (int j = 0; j < ATT_DIST; j++) {
            const uint32_t sk = sbase + j * 16384;
            mbar_expect_tx(bar_kfull + 8 * j, j == 0 ? 16384 : 8192);
            if (j == 0) tma_load_2d(sbase + ATT_Q_OFF, &mKV, head * DH, q0, bar_kfull);
            tma_load_2d(sk, &mKV, DM + head * DH, j * 128, bar_kfull + 8 * j);
            mbar_expect_tx(bar_vfull + 8 * j, 8192);
            tma_load_2d(sk + 8192, &mKV, 2 * DM + head * DH, j * 128, bar_vfull + 8 * j);
        }
    }
    asm volatile("st.shared.v4.b32 [%0], {%1, %1, %1, %1};" ::"r"(sbase + ATT_ONES_OFF + threadIdx.x * 16), "r"(0x3F803F80u) : "memory");
    fence_proxy_async();
    __syncthreads();

    const int row0 = q0 + warp_id * 16 + (lane >> 2);
    const int cq = (lane & 3) * 2;
    const uint32_t dq = desc_lo(sbase + ATT_Q_OFF + (threadIdx.x >> 7) * 4096, 16);
    AttState st;
#pragma unroll
    for (int i = 0; i < 20; i++) st.o[i] = 0.f;
    st.m0 = -INFINITY; st.m1 = -INFINITY;
    float s0[32], s1[32];
    constexpr uint32_t HI = desc_hi(512, 2);
    const uint32_t dk0 = desc_lo(sbase, 16);
    const uint32_t dv0 = desc_lo(sbase + 8192, ATT_ONES_OFF - 8192);
    uint32_t p[16];
#pragma unroll
    for (int i = 0; i < 16; i++) p[i] = 0u;
    mbar_wait(bar_kfull, 0);
    wgmma_fence();
    wgmma_ss_n64_tb0(s0, dq, HI, dk0, HI, 0);
    wgmma_ss_n64_tb0(s0, dq + 2, HI, dk0 + 2, HI, 1);
    wgmma_commit();
    mbar_wait(bar_vfull, 0);
    wgmma_wait<0>();
    row_max(s0, st.m0, st.m1);
    st.mp0 = st.m0; st.mp1 = st.m1;
    int stage = 0;
    uint32_t phase = 0;
    uint32_t dv_prev = dv0;
#pragma unroll 1
    for (int j = 0; j < NBLK; j++) {
        if (threadIdx.x == 0 && j + ATT_DIST < NBLK) {
            const int jn = j + ATT_DIST;
            const int sn = jn % ATT_STAGES;
            if (jn >= ATT_STAGES) mbar_wait(bar_empty + 8 * sn, ((jn / ATT_STAGES) - 1) & 1);
            const uint32_t skn = sbase + sn * 16384;
            mbar_expect_tx(bar_kfull + 8 * sn, 8192);
            tma_load_2d(skn, &mKV, DM + head * DH, jn * 128, bar_kfull + 8 * sn);
            mbar_expect_tx(bar_vfull + 8 * sn, 8192);
            tma_load_2d(skn + 8192, &mKV, 2 * DM + head * DH, jn * 128, bar_vfull + 8 * sn);
        }
        __syncwarp();
        const uint32_t dk = dk0 + stage * 1024;
        const uint32_t dv = dv0 + stage * 1024 - ((uint32_t)(stage * 1024) << 16);
        const int pstage = (stage + ATT_STAGES - 1) % ATT_STAGES;
        attn_step(s0, s1, p, dq, st, dk + 256, dv_prev, j > 0 ? bar_empty + 8 * pstage : 0u);
        int nstage = stage + 1;
        uint32_t nphase = phase;
        if (nstage == ATT_STAGES) { nstage = 0; nphase ^= 1; }
        uint32_t dkn = dk;
        if (j + 1 < NBLK) {
            mbar_wait(bar_kfull + 8 * nstage, nphase);
            dkn = dk0 + nstage * 1024;
        }
        mbar_wait(bar_vfull + 8 * stage, phase);
        attn_step(s1, s0, p, dq, st, dkn, dv, 0u);
        dv_prev = dv + 256 - (256u << 16);
        stage = nstage;
        phase = nphase;
    }
    wgmma_fence();
#pragma unroll
    for (int t = 0; t < 4; t++)
        wgmma_rs_n40_tb1(st.o, p[4 * t], p[4 * t + 1], p[4 * t + 2], p[4 * t + 3], dv_prev + t * 64, HI, 1);
    wgmma_commit();
    wgmma_wait<0>();
    const float f0 = g_gate[row0] / st.o[16], f1 = g_gate[row0 + 8] / st.o[18];
    bf16* op0 = g_a5 + (size_t)row0 * A5W + head * DH + cq;
    bf16* op1 = op0 + 8 * A5W;
#pragma unroll
    for (int i = 0; i < 4; i++) {
        *reinterpret_cast<uint32_t*>(op0 + 8 * i) = pack_bf16(st.o[4 * i] * f0, st.o[4 * i + 1] * f0);
        *reinterpret_cast<uint32_t*>(op1 + 8 * i) = pack_bf16(st.o[4 * i + 2] * f1, st.o[4 * i + 3] * f1);
    }
}

typedef CUresult (*EncodeFn)(CUtensorMap*, CUtensorMapDataType, cuuint32_t, void*, const cuuint64_t*, const cuuint64_t*,
                             const cuuint32_t*, const cuuint32_t*, CUtensorMapInterleave, CUtensorMapSwizzle,
                             CUtensorMapL2promotion, CUtensorMapFloatOOBfill);

static CUtensorMap make_map(EncodeFn fn, const void* ptr, int rows, int cols, int box_cols, int box_rows,
                            CUtensorMapSwizzle swz) {
    CUtensorMap m;
    cuuint64_t dims[2] = {(cuuint64_t)cols, (cuuint64_t)rows};
    cuuint64_t strides[1] = {(cuuint64_t)cols * 2};
    cuuint32_t box[2] = {(cuuint32_t)box_cols, (cuuint32_t)box_rows};
    cuuint32_t es[2] = {1, 1};
    fn(&m, CU_TENSOR_MAP_DATA_TYPE_BFLOAT16, 2, const_cast<void*>(ptr), dims, strides, box, es,
       CU_TENSOR_MAP_INTERLEAVE_NONE, swz, CU_TENSOR_MAP_L2_PROMOTION_L2_256B, CU_TENSOR_MAP_FLOAT_OOB_FILL_NONE);
    return m;
}

extern "C" void kernel_launch(void* const* d_in, const int* in_sizes, int n_in, void* d_out, int out_size) {
    const bf16* x = (const bf16*)d_in[0];
    const bf16* wqkv = (const bf16*)d_in[1];
    const bf16* wo = (const bf16*)d_in[2];
    const bf16* w1 = (const bf16*)d_in[4];
    const bf16* w2 = (const bf16*)d_in[5];
    const bf16* w3 = (const bf16*)d_in[6];
    const bf16* w4 = (const bf16*)d_in[7];
    const bf16* gate_w = (const bf16*)d_in[8];

    static EncodeFn enc = nullptr;
    static void *p_qkv, *p_h, *p_x1, *p_a5;
    if (!enc) {
        void* fn = nullptr;
        cudaDriverEntryPointQueryResult qres;
        cudaGetDriverEntryPoint("cuTensorMapEncodeTiled", &fn, cudaEnableDefault, &qres);
        enc = (EncodeFn)fn;
        cudaGetSymbolAddress(&p_qkv, g_qkv);
        cudaGetSymbolAddress(&p_h, g_h);
        cudaGetSymbolAddress(&p_x1, g_x1);
        cudaGetSymbolAddress(&p_a5, g_a5);
        cudaFuncSetAttribute(gemm_kernel<1, 256, 4>, cudaFuncAttributeMaxDynamicSharedMemorySize, GemmSmem<256, 4>::TOTAL);
        cudaFuncSetAttribute(gemm_kernel<2, 128, 5>, cudaFuncAttributeMaxDynamicSharedMemorySize, GemmSmem<128, 5>::TOTAL);
        cudaFuncSetAttribute(gemm_kernel<3, 256, 4>, cudaFuncAttributeMaxDynamicSharedMemorySize, GemmSmem<256, 4>::TOTAL);
        cudaFuncSetAttribute(gemm_kernel<5, 128, 5>, cudaFuncAttributeMaxDynamicSharedMemorySize, GemmSmem<128, 5>::TOTAL);
        cudaFuncSetAttribute(attn_kernel, cudaFuncAttributeMaxDynamicSharedMemorySize, ATT_SMEM);
    }
    const CUtensorMapSwizzle SW128 = CU_TENSOR_MAP_SWIZZLE_128B, SW64 = CU_TENSOR_MAP_SWIZZLE_64B;
    CUtensorMap mX = make_map(enc, x, S_LEN, DM, 64, 128, SW128);
    CUtensorMap mWqkv = make_map(enc, wqkv, DM, 3 * DM, 64, 64, SW128);
    CUtensorMap mW1 = make_map(enc, w1, DM, DM, 64, 64, SW128);
    CUtensorMap mW2 = make_map(enc, w2, DM, DM, 64, 64, SW128);
    CUtensorMap mW3 = make_map(enc, w3, DM, FF, 64, 64, SW128);
    CUtensorMap mW4 = make_map(enc, w4, FF, DM, 64, 64, SW128);
    CUtensorMap mWo = make_map(enc, wo, DM, DM, 64, 64, SW128);
    CUtensorMap mQKVst = make_map(enc, p_qkv, S_LEN, 3 * DM, 64, 64, SW128);
    CUtensorMap mKV = make_map(enc, p_qkv, S_LEN, 3 * DM, 32, 128, SW64);
    CUtensorMap mHst = make_map(enc, p_h, S_LEN, DM, 64, 64, SW128);
    CUtensorMap mHld = make_map(enc, p_h, S_LEN, DM, 64, 128, SW128);
    CUtensorMap mX1st = make_map(enc, p_x1, S_LEN, DM, 64, 64, SW128);
    CUtensorMap mX1ld = make_map(enc, p_x1, S_LEN, DM, 64, 128, SW128);
    CUtensorMap mA5st = make_map(enc, p_a5, S_LEN, A5W, 64, 64, SW128);
    CUtensorMap mA5ld = make_map(enc, p_a5, S_LEN, A5W, 64, 128, SW128);
    CUtensorMap mOut = make_map(enc, d_out, S_LEN, DM, 64, 64, SW128);

    cudaStream_t st = cudaStreamPerThread;
    prep_kernel<<<256 + 72, 256, 0, st>>>(x, gate_w, w1, w3);
    gemm_kernel<1, 256, 4><<<132, 384, GemmSmem<256, 4>::TOTAL, st>>>(mX, mWqkv, mW1, mQKVst, mHst, x, 16, 16);
    attn_kernel<<<NH * 16, 256, ATT_SMEM, st>>>(mKV);
    gemm_kernel<2, 128, 5><<<128, 384, GemmSmem<128, 5>::TOTAL, st>>>(mHld, mW2, mW2, mX1st, mX1st, x, 8, 16);
    gemm_kernel<3, 256, 4><<<132, 384, GemmSmem<256, 4>::TOTAL, st>>>(mX1ld, mW3, mW3, mA5st, mA5st, x, 14, 16);
    gemm_kernel<5, 128, 5><<<128, 384, GemmSmem<128, 5>::TOTAL, st>>>(mA5ld, mWo, mW4, mOut, mOut, (const bf16*)p_x1, 8, 72);
}
```

```cpp
#include <cuda_runtime.h>
#include <cuda_bf16.h>
#include <cuda.h>
#include <stdint.h>

typedef __nv_bfloat16 bf16;

constexpr int S_LEN = 2048;
constexpr int DM = 1024;
constexpr int FF = 3584;
constexpr int NH = 32;
constexpr int DH = 32;
constexpr int A5W = DM + FF;

__device__ __align__(1024) bf16 g_qkv[S_LEN * 3 * DM];
__device__ __align__(1024) bf16 g_h[S_LEN * DM];
__device__ __align__(1024) bf16 g_x1[S_LEN * DM];
__device__ __align__(1024) bf16 g_a5[S_LEN * A5W];
__device__ __align__(16) float g_mean1[S_LEN];
__device__ __align__(16) float g_rstd1[S_LEN];
__device__ __align__(16) float g_gate[S_LEN];
__device__ __align__(16) float g_omg[S_LEN];
__device__ __align__(16) float g_cs1[DM];
__device__ __align__(16) float g_cs3[FF];
__device__ __align__(16) float2 g_stat2[S_LEN * 8];

__device__ __forceinline__ uint32_t smem_u32(const void* p) { return (uint32_t)__cvta_generic_to_shared(p); }

__device__ __forceinline__ void mbar_init(uint32_t bar, uint32_t count) {
    asm volatile("mbarrier.init.shared::cta.b64 [%0], %1;" ::"r"(bar), "r"(count));
}
__device__ __forceinline__ void mbar_expect_tx(uint32_t bar, uint32_t bytes) {
    asm volatile("mbarrier.arrive.expect_tx.shared::cta.b64 _, [%0], %1;" ::"r"(bar), "r"(bytes) : "memory");
}
__device__ __forceinline__ void mbar_arrive(uint32_t bar) {
    asm volatile("mbarrier.arrive.shared::cta.b64 _, [%0];" ::"r"(bar) : "memory");
}
__device__ __forceinline__ bool mbar_try_wait(uint32_t bar, uint32_t parity) {
    uint32_t ok;
    asm volatile(
        "{\n.reg .pred p;\n"
        "mbarrier.try_wait.parity.shared::cta.b64 p, [%1], %2;\n"
        "selp.u32 %0, 1, 0, p;\n}\n"
        : "=r"(ok)
        : "r"(bar), "r"(parity)
        : "memory");
    return ok != 0;
}
__device__ __forceinline__ void mbar_wait(uint32_t bar, uint32_t parity) {
    uint32_t spins = 0;
    while (!mbar_try_wait(bar, parity)) {
        if (++spins > (1u << 24)) __trap();
    }
}
__device__ __forceinline__ void tma_load_2d(uint32_t dst, const CUtensorMap* map, int c0, int c1, uint32_t bar) {
    asm volatile(
        "cp.async.bulk.tensor.2d.shared::cluster.global.mbarrier::complete_tx::bytes [%0], [%1, {%3, %4}], [%2];"
        ::"r"(dst), "l"(map), "r"(bar), "r"(c0), "r"(c1)
        : "memory");
}
__device__ __forceinline__ void tma_store_2d(const CUtensorMap* map, uint32_t src, int c0, int c1) {
    asm volatile("cp.async.bulk.tensor.2d.global.shared::cta.bulk_group [%0, {%2, %3}], [%1];"
                 ::"l"(map), "r"(src), "r"(c0), "r"(c1)
                 : "memory");
}
__device__ __forceinline__ void bulk_commit() { asm volatile("cp.async.bulk.commit_group;" ::: "memory"); }
__device__ __forceinline__ void bulk_wait_read0() { asm volatile("cp.async.bulk.wait_group.read 0;" ::: "memory"); }
__device__ __forceinline__ void bulk_wait0() { asm volatile("cp.async.bulk.wait_group 0;" ::: "memory"); }
__device__ __forceinline__ void fence_proxy_async() { asm volatile("fence.proxy.async.shared::cta;" ::: "memory"); }
__device__ __forceinline__ void named_bar_sync(int id, int n) { asm volatile("bar.sync %0, %1;" ::"r"(id), "r"(n) : "memory"); }
__device__ __forceinline__ void named_bar_arrive(int id, int n) { asm volatile("bar.arrive %0, %1;" ::"r"(id), "r"(n) : "memory"); }
__device__ __forceinline__ void wgmma_fence() { asm volatile("wgmma.fence.sync.aligned;" ::: "memory"); }
__device__ __forceinline__ void wgmma_commit() { asm volatile("wgmma.commit_group.sync.aligned;" ::: "memory"); }
template <int N>
__device__ __forceinline__ void wgmma_wait() { asm volatile("wgmma.wait_group.sync.aligned %0;" ::"n"(N) : "memory"); }
__device__ __forceinline__ void prefetch_tmap(const CUtensorMap* m) {
    asm volatile("prefetch.tensormap [%0];" ::"l"(m) : "memory");
}
template <int R>
__device__ __forceinline__ void reg_alloc() { asm volatile("setmaxnreg.inc.sync.aligned.u32 %0;" ::"n"(R)); }
template <int R>
__device__ __forceinline__ void reg_dealloc() { asm volatile("setmaxnreg.dec.sync.aligned.u32 %0;" ::"n"(R)); }
__device__ __forceinline__ void stmatrix_x4(uint32_t addr, uint32_t r0, uint32_t r1, uint32_t r2, uint32_t r3) {
    asm volatile("stmatrix.sync.aligned.m8n8.x4.shared.b16 [%0], {%1, %2, %3, %4};"
                 ::"r"(addr), "r"(r0), "r"(r1), "r"(r2), "r"(r3)
                 : "memory");
}
__device__ __forceinline__ uint32_t pack_bf16(float lo, float hi) {
    uint32_t r;
    asm("cvt.rn.bf16x2.f32 %0, %1, %2;" : "=r"(r) : "f"(hi), "f"(lo));
    return r;
}
__device__ __forceinline__ float bf16_round(float v) { return __bfloat162float(__float2bfloat16_rn(v)); }
__device__ __forceinline__ float ex2(float x) {
    float y;
    asm volatile("ex2.approx.ftz.f32 %0, %1;" : "=f"(y) : "f"(x));
    return y;
}
__device__ __forceinline__ float tanh_fast(float x) {
    float y;
    asm("tanh.approx.f32 %0, %1;" : "=f"(y) : "f"(x));
    return y;
}
__device__ __forceinline__ float gelu_tanh(float v) {
    float u = 0.7978845608028654f * (v + 0.044715f * v * v * v);
    float hv = 0.5f * v;
    return fmaf(hv, tanh_fast(u), hv);
}
__device__ __forceinline__ uint32_t desc_lo(uint32_t addr, uint32_t lbo_bytes) {
    return ((addr & 0x3FFFF) >> 4) | (((lbo_bytes >> 4) & 0x3FFF) << 16);
}
__host__ __device__ constexpr uint32_t desc_hi(uint32_t sbo_bytes, uint32_t swz) {
    return ((sbo_bytes >> 4) & 0x3FFF) | (swz << 30);
}

__device__ __forceinline__ void wgmma_ss_n128_tb1(float (&d)[64], uint32_t alo, uint32_t ahi, uint32_t blo, uint32_t bhi, int scale_d) {
    asm volatile("{\n.reg .pred p;\n.reg .b64 da, db;\nsetp.ne.b32 p, %68, 0;\nmov.b64 da, {%64, %65};\nmov.b64 db, {%66, %67};\n"
        "wgmma.mma_async.sync.aligned.m64n128k16.f32.bf16.bf16 {%0, %1, %2, %3, %4, %5, %6, %7, %8, %9, %10, %11, %12, %13, %14, %15, %16, %17, %18, %19, %20, %21, %22, %23, %24, %25, %26, %27, %28, %29, %30, %31, %32, %33, %34, %35, %36, %37, %38, %39, %40, %41, %42, %43, %44, %45, %46, %47, %48, %49, %50, %51, %52, %53, %54, %55, %56, %57, %58, %59, %60, %61, %62, %63}, da, db, p, 1, 1, 0, 1;\n}\n"
        : "+f"(d[0]), "+f"(d[1]), "+f"(d[2]), "+f"(d[3]), "+f"(d[4]), "+f"(d[5]), "+f"(d[6]), "+f"(d[7]), "+f"(d[8]), "+f"(d[9]), "+f"(d[10]), "+f"(d[11]), "+f"(d[12]), "+f"(d[13]), "+f"(d[14]), "+f"(d[15]), "+f"(d[16]), "+f"(d[17]), "+f"(d[18]), "+f"(d[19]), "+f"(d[20]), "+f"(d[21]), "+f"(d[22]), "+f"(d[23]), "+f"(d[24]), "+f"(d[25]), "+f"(d[26]), "+f"(d[27]), "+f"(d[28]), "+f"(d[29]), "+f"(d[30]), "+f"(d[31]), "+f"(d[32]), "+f"(d[33]), "+f"(d[34]), "+f"(d[35]), "+f"(d[36]), "+f"(d[37]), "+f"(d[38]), "+f"(d[39]), "+f"(d[40]), "+f"(d[41]), "+f"(d[42]), "+f"(d[43]), "+f"(d[44]), "+f"(d[45]), "+f"(d[46]), "+f"(d[47]), "+f"(d[48]), "+f"(d[49]), "+f"(d[50]), "+f"(d[51]), "+f"(d[52]), "+f"(d[53]), "+f"(d[54]), "+f"(d[55]), "+f"(d[56]), "+f"(d[57]), "+f"(d[58]), "+f"(d[59]), "+f"(d[60]), "+f"(d[61]), "+f"(d[62]), "+f"(d[63])
        : "r"(alo), "r"(ahi), "r"(blo), "r"(bhi), "r"(scale_d));
}

__device__ __forceinline__ void wgmma_ss_n192_tb1(float (&d)[96], uint32_t alo, uint32_t ahi, uint32_t blo, uint32_t bhi, int scale_d) {
    asm volatile("{\n.reg .pred p;\n.reg .b64 da, db;\nsetp.ne.b32 p, %100, 0;\nmov.b64 da, {%96, %97};\nmov.b64 db, {%98, %99};\n"
        "wgmma.mma_async.sync.aligned.m64n192k16.f32.bf16.bf16 {%0, %1, %2, %3, %4, %5, %6, %7, %8, %9, %10, %11, %12, %13, %14, %15, %16, %17, %18, %19, %20, %21, %22, %23, %24, %25, %26, %27, %28, %29, %30, %31, %32, %33, %34, %35, %36, %37, %38, %39, %40, %41, %42, %43, %44, %45, %46, %47, %48, %49, %50, %51, %52, %53, %54, %55, %56, %57, %58, %59, %60, %61, %62, %63, %64, %65, %66, %67, %68, %69, %70, %71, %72, %73, %74, %75, %76, %77, %78, %79, %80, %81, %82, %83, %84, %85, %86, %87, %88, %89, %90, %91, %92, %93, %94, %95}, da, db, p, 1, 1, 0, 1;\n}\n"
        : "+f"(d[0]), "+f"(d[1]), "+f"(d[2]), "+f"(d[3]), "+f"(d[4]), "+f"(d[5]), "+f"(d[6]), "+f"(d[7]), "+f"(d[8]), "+f"(d[9]), "+f"(d[10]), "+f"(d[11]), "+f"(d[12]), "+f"(d[13]), "+f"(d[14]), "+f"(d[15]), "+f"(d[16]), "+f"(d[17]), "+f"(d[18]), "+f"(d[19]), "+f"(d[20]), "+f"(d[21]), "+f"(d[22]), "+f"(d[23]), "+f"(d[24]), "+f"(d[25]), "+f"(d[26]), "+f"(d[27]), "+f"(d[28]), "+f"(d[29]), "+f"(d[30]), "+f"(d[31]), "+f"(d[32]), "+f"(d[33]), "+f"(d[34]), "+f"(d[35]), "+f"(d[36]), "+f"(d[37]), "+f"(d[38]), "+f"(d[39]), "+f"(d[40]), "+f"(d[41]), "+f"(d[42]), "+f"(d[43]), "+f"(d[44]), "+f"(d[45]), "+f"(d[46]), "+f"(d[47]), "+f"(d[48]), "+f"(d[49]), "+f"(d[50]), "+f"(d[51]), "+f"(d[52]), "+f"(d[53]), "+f"(d[54]), "+f"(d[55]), "+f"(d[56]), "+f"(d[57]), "+f"(d[58]), "+f"(d[59]), "+f"(d[60]), "+f"(d[61]), "+f"(d[62]), "+f"(d[63]), "+f"(d[64]), "+f"(d[65]), "+f"(d[66]), "+f"(d[67]), "+f"(d[68]), "+f"(d[69]), "+f"(d[70]), "+f"(d[71]), "+f"(d[72]), "+f"(d[73]), "+f"(d[74]), "+f"(d[75]), "+f"(d[76]), "+f"(d[77]), "+f"(d[78]), "+f"(d[79]), "+f"(d[80]), "+f"(d[81]), "+f"(d[82]), "+f"(d[83]), "+f"(d[84]), "+f"(d[85]), "+f"(d[86]), "+f"(d[87]), "+f"(d[88]), "+f"(d[89]), "+f"(d[90]), "+f"(d[91]), "+f"(d[92]), "+f"(d[93]), "+f"(d[94]), "+f"(d[95])
        : "r"(alo), "r"(ahi), "r"(blo), "r"(bhi), "r"(scale_d));
}

__device__ __forceinline__ void wgmma_ss_n224_tb1(float (&d)[112], uint32_t alo, uint32_t ahi, uint32_t blo, uint32_t bhi, int scale_d) {
    asm volatile("{\n.reg .pred p;\n.reg .b64 da, db;\nsetp.ne.b32 p, %116, 0;\nmov.b64 da, {%112, %113};\nmov.b64 db, {%114, %115};\n"
        "wgmma.mma_async.sync.aligned.m64n224k16.f32.bf16.bf16 {%0, %1, %2, %3, %4, %5, %6, %7, %8, %9, %10, %11, %12, %13, %14, %15, %16, %17, %18, %19, %20, %21, %22, %23, %24, %25, %26, %27, %28, %29, %30, %31, %32, %33, %34, %35, %36, %37, %38, %39, %40, %41, %42, %43, %44, %45, %46, %47, %48, %49, %50, %51, %52, %53, %54, %55, %56, %57, %58, %59, %60, %61, %62, %63, %64, %65, %66, %67, %68, %69, %70, %71, %72, %73, %74, %75, %76, %77, %78, %79, %80, %81, %82, %83, %84, %85, %86, %87, %88, %89, %90, %91, %92, %93, %94, %95, %96, %97, %98, %99, %100, %101, %102, %103, %104, %105, %106, %107, %108, %109, %110, %111}, da, db, p, 1, 1, 0, 1;\n}\n"
        : "+f"(d[0]), "+f"(d[1]), "+f"(d[2]), "+f"(d[3]), "+f"(d[4]), "+f"(d[5]), "+f"(d[6]), "+f"(d[7]), "+f"(d[8]), "+f"(d[9]), "+f"(d[10]), "+f"(d[11]), "+f"(d[12]), "+f"(d[13]), "+f"(d[14]), "+f"(d[15]), "+f"(d[16]), "+f"(d[17]), "+f"(d[18]), "+f"(d[19]), "+f"(d[20]), "+f"(d[21]), "+f"(d[22]), "+f"(d[23]), "+f"(d[24]), "+f"(d[25]), "+f"(d[26]), "+f"(d[27]), "+f"(d[28]), "+f"(d[29]), "+f"(d[30]), "+f"(d[31]), "+f"(d[32]), "+f"(d[33]), "+f"(d[34]), "+f"(d[35]), "+f"(d[36]), "+f"(d[37]), "+f"(d[38]), "+f"(d[39]), "+f"(d[40]), "+f"(d[41]), "+f"(d[42]), "+f"(d[43]), "+f"(d[44]), "+f"(d[45]), "+f"(d[46]), "+f"(d[47]), "+f"(d[48]), "+f"(d[49]), "+f"(d[50]), "+f"(d[51]), "+f"(d[52]), "+f"(d[53]), "+f"(d[54]), "+f"(d[55]), "+f"(d[56]), "+f"(d[57]), "+f"(d[58]), "+f"(d[59]), "+f"(d[60]), "+f"(d[61]), "+f"(d[62]), "+f"(d[63]), "+f"(d[64]), "+f"(d[65]), "+f"(d[66]), "+f"(d[67]), "+f"(d[68]), "+f"(d[69]), "+f"(d[70]), "+f"(d[71]), "+f"(d[72]), "+f"(d[73]), "+f"(d[74]), "+f"(d[75]), "+f"(d[76]), "+f"(d[77]), "+f"(d[78]), "+f"(d[79]), "+f"(d[80]), "+f"(d[81]), "+f"(d[82]), "+f"(d[83]), "+f"(d[84]), "+f"(d[85]), "+f"(d[86]), "+f"(d[87]), "+f"(d[88]), "+f"(d[89]), "+f"(d[90]), "+f"(d[91]), "+f"(d[92]), "+f"(d[93]), "+f"(d[94]), "+f"(d[95]), "+f"(d[96]), "+f"(d[97]), "+f"(d[98]), "+f"(d[99]), "+f"(d[100]), "+f"(d[101]), "+f"(d[102]), "+f"(d[103]), "+f"(d[104]), "+f"(d[105]), "+f"(d[106]), "+f"(d[107]), "+f"(d[108]), "+f"(d[109]), "+f"(d[110]), "+f"(d[111])
        : "r"(alo), "r"(ahi), "r"(blo), "r"(bhi), "r"(scale_d));
}

__device__ __forceinline__ void wgmma_ss_n256_tb1(float (&d)[128], uint32_t alo, uint32_t ahi, uint32_t blo, uint32_t bhi, int scale_d) {
    asm volatile("{\n.reg .pred p;\n.reg .b64 da, db;\nsetp.ne.b32 p, %132, 0;\nmov.b64 da, {%128, %129};\nmov.b64 db, {%130, %131};\n"
        "wgmma.mma_async.sync.aligned.m64n256k16.f32.bf16.bf16 {%0, %1, %2, %3, %4, %5, %6, %7, %8, %9, %10, %11, %12, %13, %14, %15, %16, %17, %18, %19, %20, %21, %22, %23, %24, %25, %26, %27, %28, %29, %30, %31, %32, %33, %34, %35, %36, %37, %38, %39, %40, %41, %42, %43, %44, %45, %46, %47, %48, %49, %50, %51, %52, %53, %54, %55, %56, %57, %58, %59, %60, %61, %62, %63, %64, %65, %66, %67, %68, %69, %70, %71, %72, %73, %74, %75, %76, %77, %78, %79, %80, %81, %82, %83, %84, %85, %86, %87, %88, %89, %90, %91, %92, %93, %94, %95, %96, %97, %98, %99, %100, %101, %102, %103, %104, %105, %106, %107, %108, %109, %110, %111, %112, %113, %114, %115, %116, %117, %118, %119, %120, %121, %122, %123, %124, %125, %126, %127}, da, db, p, 1, 1, 0, 1;\n}\n"
        : "+f"(d[0]), "+f"(d[1]), "+f"(d[2]), "+f"(d[3]), "+f"(d[4]), "+f"(d[5]), "+f"(d[6]), "+f"(d[7]), "+f"(d[8]), "+f"(d[9]), "+f"(d[10]), "+f"(d[11]), "+f"(d[12]), "+f"(d[13]), "+f"(d[14]), "+f"(d[15]), "+f"(d[16]), "+f"(d[17]), "+f"(d[18]), "+f"(d[19]), "+f"(d[20]), "+f"(d[21]), "+f"(d[22]), "+f"(d[23]), "+f"(d[24]), "+f"(d[25]), "+f"(d[26]), "+f"(d[27]), "+f"(d[28]), "+f"(d[29]), "+f"(d[30]), "+f"(d[31]), "+f"(d[32]), "+f"(d[33]), "+f"(d[34]), "+f"(d[35]), "+f"(d[36]), "+f"(d[37]), "+f"(d[38]), "+f"(d[39]), "+f"(d[40]), "+f"(d[41]), "+f"(d[42]), "+f"(d[43]), "+f"(d[44]), "+f"(d[45]), "+f"(d[46]), "+f"(d[47]), "+f"(d[48]), "+f"(d[49]), "+f"(d[50]), "+f"(d[51]), "+f"(d[52]), "+f"(d[53]), "+f"(d[54]), "+f"(d[55]), "+f"(d[56]), "+f"(d[57]), "+f"(d[58]), "+f"(d[59]), "+f"(d[60]), "+f"(d[61]), "+f"(d[62]), "+f"(d[63]), "+f"(d[64]), "+f"(d[65]), "+f"(d[66]), "+f"(d[67]), "+f"(d[68]), "+f"(d[69]), "+f"(d[70]), "+f"(d[71]), "+f"(d[72]), "+f"(d[73]), "+f"(d[74]), "+f"(d[75]), "+f"(d[76]), "+f"(d[77]), "+f"(d[78]), "+f"(d[79]), "+f"(d[80]), "+f"(d[81]), "+f"(d[82]), "+f"(d[83]), "+f"(d[84]), "+f"(d[85]), "+f"(d[86]), "+f"(d[87]), "+f"(d[88]), "+f"(d[89]), "+f"(d[90]), "+f"(d[91]), "+f"(d[92]), "+f"(d[93]), "+f"(d[94]), "+f"(d[95]), "+f"(d[96]), "+f"(d[97]), "+f"(d[98]), "+f"(d[99]), "+f"(d[100]), "+f"(d[101]), "+f"(d[102]), "+f"(d[103]), "+f"(d[104]), "+f"(d[105]), "+f"(d[106]), "+f"(d[107]), "+f"(d[108]), "+f"(d[109]), "+f"(d[110]), "+f"(d[111]), "+f"(d[112]), "+f"(d[113]), "+f"(d[114]), "+f"(d[115]), "+f"(d[116]), "+f"(d[117]), "+f"(d[118]), "+f"(d[119]), "+f"(d[120]), "+f"(d[121]), "+f"(d[122]), "+f"(d[123]), "+f"(d[124]), "+f"(d[125]), "+f"(d[126]), "+f"(d[127])
        : "r"(alo), "r"(ahi), "r"(blo), "r"(bhi), "r"(scale_d));
}

__device__ __forceinline__ void wgmma_ss_n64_tb0(float (&d)[32], uint32_t alo, uint32_t ahi, uint32_t blo, uint32_t bhi, int scale_d) {
    asm volatile("{\n.reg .pred p;\n.reg .b64 da, db;\nsetp.ne.b32 p, %36, 0;\nmov.b64 da, {%32, %33};\nmov.b64 db, {%34, %35};\n"
        "wgmma.mma_async.sync.aligned.m64n64k16.f32.bf16.bf16 {%0, %1, %2, %3, %4, %5, %6, %7, %8, %9, %10, %11, %12, %13, %14, %15, %16, %17, %18, %19, %20, %21, %22, %23, %24, %25, %26, %27, %28, %29, %30, %31}, da, db, p, 1, 1, 0, 0;\n}\n"
        : "+f"(d[0]), "+f"(d[1]), "+f"(d[2]), "+f"(d[3]), "+f"(d[4]), "+f"(d[5]), "+f"(d[6]), "+f"(d[7]), "+f"(d[8]), "+f"(d[9]), "+f"(d[10]), "+f"(d[11]), "+f"(d[12]), "+f"(d[13]), "+f"(d[14]), "+f"(d[15]), "+f"(d[16]), "+f"(d[17]), "+f"(d[18]), "+f"(d[19]), "+f"(d[20]), "+f"(d[21]), "+f"(d[22]), "+f"(d[23]), "+f"(d[24]), "+f"(d[25]), "+f"(d[26]), "+f"(d[27]), "+f"(d[28]), "+f"(d[29]), "+f"(d[30]), "+f"(d[31])
        : "r"(alo), "r"(ahi), "r"(blo), "r"(bhi), "r"(scale_d));
}

__device__ __forceinline__ void wgmma_rs_n128_tb0(float (&d)[64], uint32_t a0, uint32_t a1, uint32_t a2, uint32_t a3, uint32_t blo, uint32_t bhi, int scale_d) {
    asm volatile("{\n.reg .pred p;\n.reg .b64 db;\nsetp.ne.b32 p, %70, 0;\nmov.b64 db, {%68, %69};\n"
        "wgmma.mma_async.sync.aligned.m64n128k16.f32.bf16.bf16 {%0, %1, %2, %3, %4, %5, %6, %7, %8, %9, %10, %11, %12, %13, %14, %15, %16, %17, %18, %19, %20, %21, %22, %23, %24, %25, %26, %27, %28, %29, %30, %31, %32, %33, %34, %35, %36, %37, %38, %39, %40, %41, %42, %43, %44, %45, %46, %47, %48, %49, %50, %51, %52, %53, %54, %55, %56, %57, %58, %59, %60, %61, %62, %63}, {%64, %65, %66, %67}, db, p, 1, 1, 0;\n}\n"
        : "+f"(d[0]), "+f"(d[1]), "+f"(d[2]), "+f"(d[3]), "+f"(d[4]), "+f"(d[5]), "+f"(d[6]), "+f"(d[7]), "+f"(d[8]), "+f"(d[9]), "+f"(d[10]), "+f"(d[11]), "+f"(d[12]), "+f"(d[13]), "+f"(d[14]), "+f"(d[15]), "+f"(d[16]), "+f"(d[17]), "+f"(d[18]), "+f"(d[19]), "+f"(d[20]), "+f"(d[21]), "+f"(d[22]), "+f"(d[23]), "+f"(d[24]), "+f"(d[25]), "+f"(d[26]), "+f"(d[27]), "+f"(d[28]), "+f"(d[29]), "+f"(d[30]), "+f"(d[31]), "+f"(d[32]), "+f"(d[33]), "+f"(d[34]), "+f"(d[35]), "+f"(d[36]), "+f"(d[37]), "+f"(d[38]), "+f"(d[39]), "+f"(d[40]), "+f"(d[41]), "+f"(d[42]), "+f"(d[43]), "+f"(d[44]), "+f"(d[45]), "+f"(d[46]), "+f"(d[47]), "+f"(d[48]), "+f"(d[49]), "+f"(d[50]), "+f"(d[51]), "+f"(d[52]), "+f"(d[53]), "+f"(d[54]), "+f"(d[55]), "+f"(d[56]), "+f"(d[57]), "+f"(d[58]), "+f"(d[59]), "+f"(d[60]), "+f"(d[61]), "+f"(d[62]), "+f"(d[63])
        : "r"(a0), "r"(a1), "r"(a2), "r"(a3), "r"(blo), "r"(bhi), "r"(scale_d));
}

__device__ __forceinline__ void wgmma_rs_n64_tb0(float (&d)[32], uint32_t a0, uint32_t a1, uint32_t a2, uint32_t a3, uint32_t blo, uint32_t bhi, int scale_d) {
    asm volatile("{\n.reg .pred p;\n.reg .b64 db;\nsetp.ne.b32 p, %38, 0;\nmov.b64 db, {%36, %37};\n"
        "wgmma.mma_async.sync.aligned.m64n64k16.f32.bf16.bf16 {%0, %1, %2, %3, %4, %5, %6, %7, %8, %9, %10, %11, %12, %13, %14, %15, %16, %17, %18, %19, %20, %21, %22, %23, %24, %25, %26, %27, %28, %29, %30, %31}, {%32, %33, %34, %35}, db, p, 1, 1, 0;\n}\n"
        : "+f"(d[0]), "+f"(d[1]), "+f"(d[2]), "+f"(d[3]), "+f"(d[4]), "+f"(d[5]), "+f"(d[6]), "+f"(d[7]), "+f"(d[8]), "+f"(d[9]), "+f"(d[10]), "+f"(d[11]), "+f"(d[12]), "+f"(d[13]), "+f"(d[14]), "+f"(d[15]), "+f"(d[16]), "+f"(d[17]), "+f"(d[18]), "+f"(d[19]), "+f"(d[20]), "+f"(d[21]), "+f"(d[22]), "+f"(d[23]), "+f"(d[24]), "+f"(d[25]), "+f"(d[26]), "+f"(d[27]), "+f"(d[28]), "+f"(d[29]), "+f"(d[30]), "+f"(d[31])
        : "r"(a0), "r"(a1), "r"(a2), "r"(a3), "r"(blo), "r"(bhi), "r"(scale_d));
}

__device__ __forceinline__ void wgmma_rs_n32_tb1(float (&d)[16], uint32_t a0, uint32_t a1, uint32_t a2, uint32_t a3, uint32_t blo, uint32_t bhi, int scale_d) {
    asm volatile("{\n.reg .pred p;\n.reg .b64 db;\nsetp.ne.b32 p, %22, 0;\nmov.b64 db, {%20, %21};\n"
        "wgmma.mma_async.sync.aligned.m64n32k16.f32.bf16.bf16 {%0, %1, %2, %3, %4, %5, %6, %7, %8, %9, %10, %11, %12, %13, %14, %15}, {%16, %17, %18, %19}, db, p, 1, 1, 1;\n}\n"
        : "+f"(d[0]), "+f"(d[1]), "+f"(d[2]), "+f"(d[3]), "+f"(d[4]), "+f"(d[5]), "+f"(d[6]), "+f"(d[7]), "+f"(d[8]), "+f"(d[9]), "+f"(d[10]), "+f"(d[11]), "+f"(d[12]), "+f"(d[13]), "+f"(d[14]), "+f"(d[15])
        : "r"(a0), "r"(a1), "r"(a2), "r"(a3), "r"(blo), "r"(bhi), "r"(scale_d));
}

__device__ __forceinline__ void wgmma_rs_n40_tb1(float (&d)[20], uint32_t a0, uint32_t a1, uint32_t a2, uint32_t a3, uint32_t blo, uint32_t bhi, int scale_d) {
    asm volatile("{\n.reg .pred p;\n.reg .b64 db;\nsetp.ne.b32 p, %26, 0;\nmov.b64 db, {%24, %25};\n"
        "wgmma.mma_async.sync.aligned.m64n40k16.f32.bf16.bf16 {%0, %1, %2, %3, %4, %5, %6, %7, %8, %9, %10, %11, %12, %13, %14, %15, %16, %17, %18, %19}, {%20, %21, %22, %23}, db, p, 1, 1, 1;\n}\n"
        : "+f"(d[0]), "+f"(d[1]), "+f"(d[2]), "+f"(d[3]), "+f"(d[4]), "+f"(d[5]), "+f"(d[6]), "+f"(d[7]), "+f"(d[8]), "+f"(d[9]), "+f"(d[10]), "+f"(d[11]), "+f"(d[12]), "+f"(d[13]), "+f"(d[14]), "+f"(d[15]), "+f"(d[16]), "+f"(d[17]), "+f"(d[18]), "+f"(d[19])
        : "r"(a0), "r"(a1), "r"(a2), "r"(a3), "r"(blo), "r"(bhi), "r"(scale_d));
}

template <int BN>
__device__ __forceinline__ void wgmma_tile(float (&d)[BN / 2], uint32_t da, uint32_t db, int sd) {
    constexpr uint32_t HI = desc_hi(1024, 1);
    if constexpr (BN == 128) wgmma_ss_n128_tb1(d, da, HI, db, HI, sd);
    else if constexpr (BN == 192) wgmma_ss_n192_tb1(d, da, HI, db, HI, sd);
    else if constexpr (BN == 224) wgmma_ss_n224_tb1(d, da, HI, db, HI, sd);
    else wgmma_ss_n256_tb1(d, da, HI, db, HI, sd);
}

__global__ void __launch_bounds__(256) prep_kernel(const bf16* __restrict__ x, const bf16* __restrict__ gate_w,
                                                   const bf16* __restrict__ w1, const bf16* __restrict__ w3) {
    const int tid = threadIdx.x;
    if (blockIdx.x < 256) {
        const int row = blockIdx.x * 8 + (tid >> 5);
        const int lane = tid & 31;
        const uint4* xr = reinterpret_cast<const uint4*>(x + (size_t)row * DM);
        const uint4* gw = reinterpret_cast<const uint4*>(gate_w);
        float v[32];
        float gsum = 0.f, sum = 0.f;
#pragma unroll
        for (int i = 0; i < 4; i++) {
            uint4 a = xr[lane + 32 * i];
            uint4 b = gw[lane + 32 * i];
            const uint32_t aa[4] = {a.x, a.y, a.z, a.w};
            const uint32_t bb[4] = {b.x, b.y, b.z, b.w};
#pragma unroll
            for (int j = 0; j < 4; j++) {
                float x0 = __uint_as_float(aa[j] << 16), x1 = __uint_as_float(aa[j] & 0xFFFF0000u);
                float g0 = __uint_as_float(bb[j] << 16), g1 = __uint_as_float(bb[j] & 0xFFFF0000u);
                v[i * 8 + j * 2] = x0;
                v[i * 8 + j * 2 + 1] = x1;
                sum += x0 + x1;
                gsum += bf16_round(x0 * g0) + bf16_round(x1 * g1);
            }
        }
#pragma unroll
        for (int o = 16; o > 0; o >>= 1) {
            sum += __shfl_xor_sync(0xffffffffu, sum, o);
            gsum += __shfl_xor_sync(0xffffffffu, gsum, o);
        }
        const float mean = sum * (1.0f / DM);
        float m2 = 0.f;
#pragma unroll
        for (int i = 0; i < 32; i++) {
            float d = v[i] - mean;
            m2 += d * d;
        }
#pragma unroll
        for (int o = 16; o > 0; o >>= 1) m2 += __shfl_xor_sync(0xffffffffu, m2, o);
        if (lane == 0) {
            g_mean1[row] = mean;
            g_rstd1[row] = rsqrtf(m2 * (1.0f / DM) + 1e-5f);
            float logit = bf16_round(gsum);
            float g = bf16_round(1.0f / (1.0f + __expf(-logit)));
            g_gate[row] = g;
            g_omg[row] = bf16_round(1.0f - g);
        }
    } else {
        __shared__ float red[32][65];
        const int strip = blockIdx.x - 256;
        const bf16* w;
        float* out;
        int ld, col0;
        if (strip < 16) { w = w1; ld = DM; col0 = strip * 64; out = g_cs1; }
        else { w = w3; ld = FF; col0 = (strip - 16) * 64; out = g_cs3; }
        const int cg = tid & 7;
        const int rg = tid >> 3;
        float acc[8];
#pragma unroll
        for (int j = 0; j < 8; j++) acc[j] = 0.f;
#pragma unroll 8
        for (int r = 0; r < 32; r++) {
            uint4 a = *reinterpret_cast<const uint4*>(w + (size_t)(r * 32 + rg) * ld + col0 + cg * 8);
            const uint32_t aa[4] = {a.x, a.y, a.z, a.w};
#pragma unroll
            for (int j = 0; j < 4; j++) {
                acc[2 * j] += __uint_as_float(aa[j] << 16);
                acc[2 * j + 1] += __uint_as_float(aa[j] & 0xFFFF0000u);
            }
        }
#pragma unroll
        for (int j = 0; j < 8; j++) red[rg][cg * 8 + j] = acc[j];
        __syncthreads();
        if (tid < 64) {
            float s = 0.f;
#pragma unroll
            for (int r = 0; r < 32; r++) s += red[r][tid];
            out[col0 + tid] = s;
        }
    }
}

template <int BN, int STAGES>
struct GemmSmem {
    static constexpr int A_BYTES = 128 * 64 * 2;
    static constexpr int B_BOXES = (BN + 63) / 64;
    static constexpr int B_BYTES = B_BOXES * 64 * 64 * 2;
    static constexpr int STAGE_BYTES = A_BYTES + B_BYTES;
    static constexpr int STG_OFF = STAGES * STAGE_BYTES;
    static constexpr int BAR_OFF = STG_OFF + 2 * 16384;
    static constexpr int TOTAL = BAR_OFF + 256 + 1024;
};

template <int MODE, int BN, int STAGES>
__global__ void __launch_bounds__(384, 1)
gemm_kernel(const __grid_constant__ CUtensorMap mA, const __grid_constant__ CUtensorMap mB0,
            const __grid_constant__ CUtensorMap mB1, const __grid_constant__ CUtensorMap mC0,
            const __grid_constant__ CUtensorMap mC1, const bf16* __restrict__ xin, int n_tiles_n, int kblocks) {
    using L = GemmSmem<BN, STAGES>;
    extern __shared__ uint8_t smem_raw[];
    const uint32_t sbase = (smem_u32(smem_raw) + 1023u) & ~1023u;
    const uint32_t bar_full = sbase + L::BAR_OFF;
    const uint32_t bar_empty = bar_full + 8 * STAGES;
    const int wg = threadIdx.x >> 7;
    const int ntiles = 16 * n_tiles_n;

    if (threadIdx.x == 0) {
        for (int s = 0; s < STAGES; s++) {
            mbar_init(bar_full + 8 * s, 1);
            mbar_init(bar_empty + 8 * s, 2);
        }
        asm volatile("fence.mbarrier_init.release.cluster;" ::: "memory");
    }
    __syncthreads();

    if (wg == 0) {
        reg_dealloc<40>();
        if (threadIdx.x == 0) {
            prefetch_tmap(&mA);
            prefetch_tmap(&mB0);
            prefetch_tmap(&mB1);
            int stage = 0;
            uint32_t phase = 1;
            for (int tile = blockIdx.x; tile < ntiles; tile += gridDim.x) {
                const int m0 = (tile & 15) * 128;
                const int n0 = (tile >> 4) * BN;
                for (int kb = 0; kb < kblocks; kb++) {
                    mbar_wait(bar_empty + 8 * stage, phase);
                    const uint32_t sa = sbase + stage * L::STAGE_BYTES;
                    const uint32_t sb = sa + L::A_BYTES;
                    const uint32_t fb = bar_full + 8 * stage;
                    mbar_expect_tx(fb, L::STAGE_BYTES);
                    int arow = m0;
                    if (MODE == 2) {
                        const int grp = kb >> 2;
                        arow += (grp == 0) ? -1 : (grp == 1) ? 1 : (grp == 2) ? -2 : 2;
                    }
                    tma_load_2d(sa, &mA, kb * 64, arow, fb);
                    const CUtensorMap* mb = &mB0;
                    int bc = n0, br = kb * 64;
                    if (MODE == 1 && n0 >= 3 * DM) { mb = &mB1; bc = n0 - 3 * DM; }
                    if (MODE == 5 && kb >= 16) { mb = &mB1; br = (kb - 16) * 64; }
#pragma unroll
                    for (int b = 0; b < L::B_BOXES; b++) tma_load_2d(sb + b * 8192, mb, bc + b * 64, br, fb);
                    if (++stage == STAGES) { stage = 0; phase ^= 1; }
                }
            }
        }
    } else {
        reg_alloc<232>();
        const int c = wg - 1;
        const int warp = (threadIdx.x >> 5) & 3;
        const int lane = threadIdx.x & 31;
        const int tid_wg = threadIdx.x & 127;
        const uint32_t stg = sbase + L::STG_OFF + c * 16384;
        int stage = 0;
        uint32_t phase = 0;
        float acc[BN / 2];
        for (int tile = blockIdx.x; tile < ntiles; tile += gridDim.x) {
            const int m0 = (tile & 15) * 128;
            const int n0 = (tile >> 4) * BN;
            int prev_stage = 0;
            for (int kb = 0; kb < kblocks; kb++) {
                mbar_wait(bar_full + 8 * stage, phase);
                const uint32_t sa = sbase + stage * L::STAGE_BYTES + c * 8192;
                const uint32_t sb = sbase + stage * L::STAGE_BYTES + L::A_BYTES;
                const uint32_t da = desc_lo(sa, 16);
                const uint32_t db = desc_lo(sb, 8192);
                wgmma_fence();
#pragma unroll
                for (int k = 0; k < 4; k++) wgmma_tile<BN>(acc, da + k * 2, db + k * 128, (kb | k) != 0);
                wgmma_commit();
                if (kb > 0) {
                    wgmma_wait<1>();
                    if (tid_wg == 0) mbar_arrive(bar_empty + 8 * prev_stage);
                }
                prev_stage = stage;
                if (++stage == STAGES) { stage = 0; phase ^= 1; }
            }
            wgmma_wait<0>();
            if (tid_wg == 0) mbar_arrive(bar_empty + 8 * prev_stage);

            const int r0 = m0 + c * 64 + warp * 16 + (lane >> 2);
            const int r1 = r0 + 8;
            const int cq = (lane & 3) * 2;
            const CUtensorMap* mc = &mC0;
            int out_c0 = n0;
            if (MODE == 1) {
                if (n0 >= 3 * DM) {
                    mc = &mC1;
                    out_c0 = n0 - 3 * DM;
                    const float mu0 = g_mean1[r0], mu1 = g_mean1[r1];
                    const float rs0 = g_rstd1[r0], rs1 = g_rstd1[r1];
#pragma unroll
                    for (int j = 0; j < BN / 8; j++) {
                        const float2 cs = *reinterpret_cast<const float2*>(&g_cs1[out_c0 + 8 * j + cq]);
                        acc[4 * j + 0] = gelu_tanh(rs0 * fmaf(-mu0, cs.x, acc[4 * j + 0]));
                        acc[4 * j + 1] = gelu_tanh(rs0 * fmaf(-mu0, cs.y, acc[4 * j + 1]));
                        acc[4 * j + 2] = gelu_tanh(rs1 * fmaf(-mu1, cs.x, acc[4 * j + 2]));
                        acc[4 * j + 3] = gelu_tanh(rs1 * fmaf(-mu1, cs.y, acc[4 * j + 3]));
                    }
                }
            } else if (MODE == 2) {
                float s0 = 0.f, s1 = 0.f;
#pragma unroll
                for (int j = 0; j < BN / 8; j++) {
                    const uint32_t xa = *reinterpret_cast<const uint32_t*>(xin + (size_t)r0 * DM + n0 + 8 * j + cq);
                    const uint32_t xb = *reinterpret_cast<const uint32_t*>(xin + (size_t)r1 * DM + n0 + 8 * j + cq);
                    acc[4 * j + 0] = bf16_round(bf16_round(acc[4 * j + 0]) + __uint_as_float(xa << 16));
                    acc[4 * j + 1] = bf16_round(bf16_round(acc[4 * j + 1]) + __uint_as_float(xa & 0xFFFF0000u));
                    acc[4 * j + 2] = bf16_round(bf16_round(acc[4 * j + 2]) + __uint_as_float(xb << 16));
                    acc[4 * j + 3] = bf16_round(bf16_round(acc[4 * j + 3]) + __uint_as_float(xb & 0xFFFF0000u));
                    s0 += acc[4 * j + 0] + acc[4 * j + 1];
                    s1 += acc[4 * j + 2] + acc[4 * j + 3];
                }
                s0 += __shfl_xor_sync(0xffffffffu, s0, 1);
                s0 += __shfl_xor_sync(0xffffffffu, s0, 2);
                s1 += __shfl_xor_sync(0xffffffffu, s1, 1);
                s1 += __shfl_xor_sync(0xffffffffu, s1, 2);
                const float mu0 = s0 * (1.0f / BN), mu1 = s1 * (1.0f / BN);
                float q0 = 0.f, q1 = 0.f;
#pragma unroll
                for (int j = 0; j < BN / 8; j++) {
                    float d;
                    d = acc[4 * j + 0] - mu0; q0 += d * d;
                    d = acc[4 * j + 1] - mu0; q0 += d * d;
                    d = acc[4 * j + 2] - mu1; q1 += d * d;
                    d = acc[4 * j + 3] - mu1; q1 += d * d;
                }
                q0 += __shfl_xor_sync(0xffffffffu, q0, 1);
                q0 += __shfl_xor_sync(0xffffffffu, q0, 2);
                q1 += __shfl_xor_sync(0xffffffffu, q1, 1);
                q1 += __shfl_xor_sync(0xffffffffu, q1, 2);
                if ((lane & 3) == 0) {
                    static_assert(MODE != 2 || BN == 128, "stats layout assumes BN=128");
                    g_stat2[r0 * 8 + (n0 >> 7)] = make_float2(s0, q0);
                    g_stat2[r1 * 8 + (n0 >> 7)] = make_float2(s1, q1);
                }
            } else if (MODE == 3) {
                out_c0 = n0 + DM;
                float mu[2], rs[2];
#pragma unroll
                for (int h = 0; h < 2; h++) {
                    const float4* sp = reinterpret_cast<const float4*>(&g_stat2[(h ? r1 : r0) * 8]);
                    float4 p[4];
                    float s = 0.f;
#pragma unroll
                    for (int i = 0; i < 4; i++) { p[i] = sp[i]; s += p[i].x + p[i].z; }
                    const float mean = s * (1.0f / DM);
                    float m2 = 0.f;
#pragma unroll
                    for (int i = 0; i < 4; i++) {
                        float d0 = p[i].x * (1.0f / 128) - mean, d1 = p[i].z * (1.0f / 128) - mean;
                        m2 += p[i].y + p[i].w + 128.0f * (d0 * d0 + d1 * d1);
                    }
                    mu[h] = mean;
                    rs[h] = rsqrtf(m2 * (1.0f / DM) + 1e-5f);
                }
                const float og0 = g_omg[r0], og1 = g_omg[r1];
#pragma unroll
                for (int j = 0; j < BN / 8; j++) {
                    const float2 cs = *reinterpret_cast<const float2*>(&g_cs3[n0 + 8 * j + cq]);
                    acc[4 * j + 0] = og0 * gelu_tanh(rs[0] * fmaf(-mu[0], cs.x, acc[4 * j + 0]));
                    acc[4 * j + 1] = og0 * gelu_tanh(rs[0] * fmaf(-mu[0], cs.y, acc[4 * j + 1]));
                    acc[4 * j + 2] = og1 * gelu_tanh(rs[1] * fmaf(-mu[1], cs.x, acc[4 * j + 2]));
                    acc[4 * j + 3] = og1 * gelu_tanh(rs[1] * fmaf(-mu[1], cs.y, acc[4 * j + 3]));
                }
            } else {
                const float og0 = g_omg[r0], og1 = g_omg[r1];
#pragma unroll
                for (int j = 0; j < BN / 8; j++) {
                    const uint32_t xa = *reinterpret_cast<const uint32_t*>(xin + (size_t)r0 * DM + n0 + 8 * j + cq);
                    const uint32_t xb = *reinterpret_cast<const uint32_t*>(xin + (size_t)r1 * DM + n0 + 8 * j + cq);
                    acc[4 * j + 0] = fmaf(og0, __uint_as_float(xa << 16), acc[4 * j + 0]);
                    acc[4 * j + 1] = fmaf(og0, __uint_as_float(xa & 0xFFFF0000u), acc[4 * j + 1]);
                    acc[4 * j + 2] = fmaf(og1, __uint_as_float(xb << 16), acc[4 * j + 2]);
                    acc[4 * j + 3] = fmaf(og1, __uint_as_float(xb & 0xFFFF0000u), acc[4 * j + 3]);
                }
            }
            const int srow = warp * 16 + (lane & 7) + ((lane >> 3) & 1) * 8;
#pragma unroll
            for (int rnd = 0; rnd < (BN + 127) / 128; rnd++) {
                if (tid_wg == 0) bulk_wait_read0();
                named_bar_sync(1 + c, 128);
#pragma unroll
                for (int jj = 0; jj < 8; jj++) {
                    const int j = rnd * 16 + jj * 2;
                    if (j * 8 < BN) {
                        const int jb = jj * 2 + (lane >> 4);
                        const uint32_t addr = stg + (jb >> 3) * 8192 + srow * 128 + (((jb & 7) ^ (srow & 7)) << 4);
                        stmatrix_x4(addr, pack_bf16(acc[4 * j + 0], acc[4 * j + 1]), pack_bf16(acc[4 * j + 2], acc[4 * j + 3]),
                                    pack_bf16(acc[4 * j + 4], acc[4 * j + 5]), pack_bf16(acc[4 * j + 6], acc[4 * j + 7]));
                    }
                }
                fence_proxy_async();
                named_bar_sync(1 + c, 128);
                if (tid_wg == 0) {
                    tma_store_2d(mc, stg, out_c0 + rnd * 128, m0 + c * 64);
                    if (rnd * 128 + 64 < BN) tma_store_2d(mc, stg + 8192, out_c0 + rnd * 128 + 64, m0 + c * 64);
                    bulk_commit();
                }
            }
        }
        if (tid_wg == 0) bulk_wait0();
    }
}

#define ATT_SPLIT 4
constexpr int ATT_GRID = NH * 16;
constexpr int ATT_THREADS = 256;
constexpr int ATT_STAGES = 4;
constexpr int ATT_DIST = 2;
constexpr int ATT_Q_OFF = ATT_STAGES * 16384;
constexpr int ATT_ONES_OFF = ATT_Q_OFF + 8192;
constexpr int ATT_BAR_OFF = ATT_ONES_OFF + 4096;
constexpr int ATT_SMEM = ATT_BAR_OFF + 256 + 1024;

struct AttState {
    float o[20];
    float m0, m1;
    float mp0, mp1;
};

__device__ __forceinline__ void row_max(const float (&s)[32], float& m0, float& m1) {
    float mx0 = fmaxf(s[0], s[1]), mx1 = fmaxf(s[2], s[3]);
#pragma unroll
    for (int i = 1; i < 8; i++) {
        mx0 = fmaxf(mx0, fmaxf(s[4 * i], s[4 * i + 1]));
        mx1 = fmaxf(mx1, fmaxf(s[4 * i + 2], s[4 * i + 3]));
    }
    mx0 = fmaxf(mx0, __shfl_xor_sync(0xffffffffu, mx0, 1));
    mx1 = fmaxf(mx1, __shfl_xor_sync(0xffffffffu, mx1, 1));
    mx0 = fmaxf(mx0, __shfl_xor_sync(0xffffffffu, mx0, 2));
    mx1 = fmaxf(mx1, __shfl_xor_sync(0xffffffffu, mx1, 2));
    m0 = fmaxf(m0, mx0);
    m1 = fmaxf(m1, mx1);
}

__device__ __forceinline__ void attn_step(float (&sc)[32], float (&sn)[32], uint32_t (&p)[16], uint32_t dq,
                                          AttState& st, uint32_t dk_next, uint32_t dv_prev, uint32_t release_bar, int one) {
    const float cs = 0.17677669529663687f * 1.4426950408889634f;
    constexpr uint32_t HI = desc_hi(512, 2);
    wgmma_fence();
    wgmma_ss_n64_tb0(sn, dq, HI, dk_next, HI, 0);
    wgmma_ss_n64_tb0(sn, dq + 2, HI, dk_next + 2, HI, 1);
#pragma unroll
    for (int t = 0; t < 4; t++)
        wgmma_rs_n40_tb1(st.o, p[4 * t], p[4 * t + 1], p[4 * t + 2], p[4 * t + 3], dv_prev + t * 64, HI, 1);
    wgmma_commit();
    const float mc0 = st.m0, mc1 = st.m1;
    const float b0 = mc0 * cs, b1 = mc1 * cs;
    if (one) {
#pragma unroll
        for (int i = 0; i < ATT_SPLIT; i++) {
            sc[4 * i + 0] = ex2(fmaf(sc[4 * i + 0], cs, -b0));
            sc[4 * i + 1] = ex2(fmaf(sc[4 * i + 1], cs, -b0));
            sc[4 * i + 2] = ex2(fmaf(sc[4 * i + 2], cs, -b1));
            sc[4 * i + 3] = ex2(fmaf(sc[4 * i + 3], cs, -b1));
        }
    }
    wgmma_wait<0>();
    if (release_bar != 0 && (threadIdx.x & 127) == 0) mbar_arrive(release_bar);
    if (one) {
        row_max(sn, st.m0, st.m1);
#pragma unroll
        for (int i = ATT_SPLIT; i < 8; i++) {
            sc[4 * i + 0] = ex2(fmaf(sc[4 * i + 0], cs, -b0));
            sc[4 * i + 1] = ex2(fmaf(sc[4 * i + 1], cs, -b0));
            sc[4 * i + 2] = ex2(fmaf(sc[4 * i + 2], cs, -b1));
            sc[4 * i + 3] = ex2(fmaf(sc[4 * i + 3], cs, -b1));
        }
        const float a0 = ex2((st.mp0 - mc0) * cs), a1 = ex2((st.mp1 - mc1) * cs);
#pragma unroll
        for (int i = 0; i < 5; i++) {
            st.o[4 * i + 0] *= a0; st.o[4 * i + 1] *= a0;
            st.o[4 * i + 2] *= a1; st.o[4 * i + 3] *= a1;
        }
        st.mp0 = mc0; st.mp1 = mc1;
#pragma unroll
        for (int i = 0; i < 8; i++) {
            p[2 * i] = pack_bf16(sc[4 * i + 0], sc[4 * i + 1]);
            p[2 * i + 1] = pack_bf16(sc[4 * i + 2], sc[4 * i + 3]);
        }
    }
}

__global__ void __launch_bounds__(256, 2)
attn_kernel(const __grid_constant__ CUtensorMap mKV, int one) {
    extern __shared__ uint8_t smem_raw[];
    const uint32_t sbase = (smem_u32(smem_raw) + 1023u) & ~1023u;
    const uint32_t bar_kfull = sbase + ATT_BAR_OFF;
    const uint32_t bar_vfull = bar_kfull + 8 * ATT_STAGES;
    const uint32_t bar_empty = bar_vfull + 8 * ATT_STAGES;
    const int head = blockIdx.x >> 4;
    const int q0 = (blockIdx.x & 15) * 128;
    const int warp_id = threadIdx.x >> 5;
    const int lane = threadIdx.x & 31;
    constexpr int NBLK = S_LEN / 128;

    if (threadIdx.x == 0) {
        for (int s = 0; s < ATT_STAGES; s++) {
            mbar_init(bar_kfull + 8 * s, 1);
            mbar_init(bar_vfull + 8 * s, 1);
            mbar_init(bar_empty + 8 * s, 2);
        }
        asm volatile("fence.mbarrier_init.release.cluster;" ::: "memory");
        prefetch_tmap(&mKV);
#pragma unroll
        for (int j = 0; j < ATT_DIST; j++) {
            const uint32_t sk = sbase + j * 16384;
            mbar_expect_tx(bar_kfull + 8 * j, j == 0 ? 16384 : 8192);
            if (j == 0) tma_load_2d(sbase + ATT_Q_OFF, &mKV, head * DH, q0, bar_kfull);
            tma_load_2d(sk, &mKV, DM + head * DH, j * 128, bar_kfull + 8 * j);
            mbar_expect_tx(bar_vfull + 8 * j, 8192);
            tma_load_2d(sk + 8192, &mKV, 2 * DM + head * DH, j * 128, bar_vfull + 8 * j);
        }
    }
    asm volatile("st.shared.v4.b32 [%0], {%1, %1, %1, %1};" ::"r"(sbase + ATT_ONES_OFF + threadIdx.x * 16), "r"(0x3F803F80u) : "memory");
    fence_proxy_async();
    __syncthreads();

    const int row0 = q0 + warp_id * 16 + (lane >> 2);
    const int cq = (lane & 3) * 2;
    const uint32_t dq = desc_lo(sbase + ATT_Q_OFF + (threadIdx.x >> 7) * 4096, 16);
    AttState st;
#pragma unroll
    for (int i = 0; i < 20; i++) st.o[i] = 0.f;
    st.m0 = -INFINITY; st.m1 = -INFINITY;
    float s0[32], s1[32];
    constexpr uint32_t HI = desc_hi(512, 2);
    const uint32_t dk0 = desc_lo(sbase, 16);
    const uint32_t dv0 = desc_lo(sbase + 8192, ATT_ONES_OFF - 8192);
    uint32_t p[16];
#pragma unroll
    for (int i = 0; i < 16; i++) p[i] = 0u;
    mbar_wait(bar_kfull, 0);
    wgmma_fence();
    wgmma_ss_n64_tb0(s0, dq, HI, dk0, HI, 0);
    wgmma_ss_n64_tb0(s0, dq + 2, HI, dk0 + 2, HI, 1);
    wgmma_commit();
    mbar_wait(bar_vfull, 0);
    wgmma_wait<0>();
    row_max(s0, st.m0, st.m1);
    st.mp0 = st.m0; st.mp1 = st.m1;
    int stage = 0;
    uint32_t phase = 0;
    uint32_t dv_prev = dv0;
#pragma unroll 1
    for (int j = 0; j < NBLK; j++) {
        if (threadIdx.x == 0 && j + ATT_DIST < NBLK) {
            const int jn = j + ATT_DIST;
            const int sn = jn % ATT_STAGES;
            if (jn >= ATT_STAGES) mbar_wait(bar_empty + 8 * sn, ((jn / ATT_STAGES) - 1) & 1);
            const uint32_t skn = sbase + sn * 16384;
            mbar_expect_tx(bar_kfull + 8 * sn, 8192);
            tma_load_2d(skn, &mKV, DM + head * DH, jn * 128, bar_kfull + 8 * sn);
            mbar_expect_tx(bar_vfull + 8 * sn, 8192);
            tma_load_2d(skn + 8192, &mKV, 2 * DM + head * DH, jn * 128, bar_vfull + 8 * sn);
        }
        __syncwarp();
        const uint32_t dk = dk0 + stage * 1024;
        const uint32_t dv = dv0 + stage * 1024 - ((uint32_t)(stage * 1024) << 16);
        const int pstage = (stage + ATT_STAGES - 1) % ATT_STAGES;
        attn_step(s0, s1, p, dq, st, dk + 256, dv_prev, j > 0 ? bar_empty + 8 * pstage : 0u, one);
        int nstage = stage + 1;
        uint32_t nphase = phase;
        if (nstage == ATT_STAGES) { nstage = 0; nphase ^= 1; }
        uint32_t dkn = dk;
        if (j + 1 < NBLK) {
            mbar_wait(bar_kfull + 8 * nstage, nphase);
            dkn = dk0 + nstage * 1024;
        }
        mbar_wait(bar_vfull + 8 * stage, phase);
        attn_step(s1, s0, p, dq, st, dkn, dv, 0u, one);
        dv_prev = dv + 256 - (256u << 16);
        stage = nstage;
        phase = nphase;
    }
    wgmma_fence();
#pragma unroll
    for (int t = 0; t < 4; t++)
        wgmma_rs_n40_tb1(st.o, p[4 * t], p[4 * t + 1], p[4 * t + 2], p[4 * t + 3], dv_prev + t * 64, HI, 1);
    wgmma_commit();
    wgmma_wait<0>();
    const float f0 = g_gate[row0] / st.o[16], f1 = g_gate[row0 + 8] / st.o[18];
    bf16* op0 = g_a5 + (size_t)row0 * A5W + head * DH + cq;
    bf16* op1 = op0 + 8 * A5W;
#pragma unroll
    for (int i = 0; i < 4; i++) {
        *reinterpret_cast<uint32_t*>(op0 + 8 * i) = pack_bf16(st.o[4 * i] * f0, st.o[4 * i + 1] * f0);
        *reinterpret_cast<uint32_t*>(op1 + 8 * i) = pack_bf16(st.o[4 * i + 2] * f1, st.o[4 * i + 3] * f1);
    }
}

typedef CUresult (*EncodeFn)(CUtensorMap*, CUtensorMapDataType, cuuint32_t, void*, const cuuint64_t*, const cuuint64_t*,
                             const cuuint32_t*, const cuuint32_t*, CUtensorMapInterleave, CUtensorMapSwizzle,
                             CUtensorMapL2promotion, CUtensorMapFloatOOBfill);

static CUtensorMap make_map(EncodeFn fn, const void* ptr, int rows, int cols, int box_cols, int box_rows,
                            CUtensorMapSwizzle swz) {
    CUtensorMap m;
    cuuint64_t dims[2] = {(cuuint64_t)cols, (cuuint64_t)rows};
    cuuint64_t strides[1] = {(cuuint64_t)cols * 2};
    cuuint32_t box[2] = {(cuuint32_t)box_cols, (cuuint32_t)box_rows};
    cuuint32_t es[2] = {1, 1};
    fn(&m, CU_TENSOR_MAP_DATA_TYPE_BFLOAT16, 2, const_cast<void*>(ptr), dims, strides, box, es,
       CU_TENSOR_MAP_INTERLEAVE_NONE, swz, CU_TENSOR_MAP_L2_PROMOTION_L2_256B, CU_TENSOR_MAP_FLOAT_OOB_FILL_NONE);
    return m;
}

extern "C" void kernel_launch(void* const* d_in, const int* in_sizes, int n_in, void* d_out, int out_size) {
    const bf16* x = (const bf16*)d_in[0];
    const bf16* wqkv = (const bf16*)d_in[1];
    const bf16* wo = (const bf16*)d_in[2];
    const bf16* w1 = (const bf16*)d_in[4];
    const bf16* w2 = (const bf16*)d_in[5];
    const bf16* w3 = (const bf16*)d_in[6];
    const bf16* w4 = (const bf16*)d_in[7];
    const bf16* gate_w = (const bf16*)d_in[8];

    static EncodeFn enc = nullptr;
    static void *p_qkv, *p_h, *p_x1, *p_a5;
    if (!enc) {
        void* fn = nullptr;
        cudaDriverEntryPointQueryResult qres;
        cudaGetDriverEntryPoint("cuTensorMapEncodeTiled", &fn, cudaEnableDefault, &qres);
        enc = (EncodeFn)fn;
        cudaGetSymbolAddress(&p_qkv, g_qkv);
        cudaGetSymbolAddress(&p_h, g_h);
        cudaGetSymbolAddress(&p_x1, g_x1);
        cudaGetSymbolAddress(&p_a5, g_a5);
        cudaFuncSetAttribute(gemm_kernel<1, 256, 4>, cudaFuncAttributeMaxDynamicSharedMemorySize, GemmSmem<256, 4>::TOTAL);
        cudaFuncSetAttribute(gemm_kernel<2, 128, 5>, cudaFuncAttributeMaxDynamicSharedMemorySize, GemmSmem<128, 5>::TOTAL);
        cudaFuncSetAttribute(gemm_kernel<3, 256, 4>, cudaFuncAttributeMaxDynamicSharedMemorySize, GemmSmem<256, 4>::TOTAL);
        cudaFuncSetAttribute(gemm_kernel<5, 128, 5>, cudaFuncAttributeMaxDynamicSharedMemorySize, GemmSmem<128, 5>::TOTAL);
        cudaFuncSetAttribute(attn_kernel, cudaFuncAttributeMaxDynamicSharedMemorySize, ATT_SMEM);
    }
    const CUtensorMapSwizzle SW128 = CU_TENSOR_MAP_SWIZZLE_128B, SW64 = CU_TENSOR_MAP_SWIZZLE_64B;
    CUtensorMap mX = make_map(enc, x, S_LEN, DM, 64, 128, SW128);
    CUtensorMap mWqkv = make_map(enc, wqkv, DM, 3 * DM, 64, 64, SW128);
    CUtensorMap mW1 = make_map(enc, w1, DM, DM, 64, 64, SW128);
    CUtensorMap mW2 = make_map(enc, w2, DM, DM, 64, 64, SW128);
    CUtensorMap mW3 = make_map(enc, w3, DM, FF, 64, 64, SW128);
    CUtensorMap mW4 = make_map(enc, w4, FF, DM, 64, 64, SW128);
    CUtensorMap mWo = make_map(enc, wo, DM, DM, 64, 64, SW128);
    CUtensorMap mQKVst = make_map(enc, p_qkv, S_LEN, 3 * DM, 64, 64, SW128);
    CUtensorMap mKV = make_map(enc, p_qkv, S_LEN, 3 * DM, 32, 128, SW64);
    CUtensorMap mHst = make_map(enc, p_h, S_LEN, DM, 64, 64, SW128);
    CUtensorMap mHld = make_map(enc, p_h, S_LEN, DM, 64, 128, SW128);
    CUtensorMap mX1st = make_map(enc, p_x1, S_LEN, DM, 64, 64, SW128);
    CUtensorMap mX1ld = make_map(enc, p_x1, S_LEN, DM, 64, 128, SW128);
    CUtensorMap mA5st = make_map(enc, p_a5, S_LEN, A5W, 64, 64, SW128);
    CUtensorMap mA5ld = make_map(enc, p_a5, S_LEN, A5W, 64, 128, SW128);
    CUtensorMap mOut = make_map(enc, d_out, S_LEN, DM, 64, 64, SW128);

    cudaStream_t st = cudaStreamPerThread;
    prep_kernel<<<256 + 72, 256, 0, st>>>(x, gate_w, w1, w3);
    gemm_kernel<1, 256, 4><<<132, 384, GemmSmem<256, 4>::TOTAL, st>>>(mX, mWqkv, mW1, mQKVst, mHst, x, 16, 16);
    attn_kernel<<<ATT_GRID, ATT_THREADS, ATT_SMEM, st>>>(mKV, 1);
    gemm_kernel<2, 128, 5><<<128, 384, GemmSmem<128, 5>::TOTAL, st>>>(mHld, mW2, mW2, mX1st, mX1st, x, 8, 16);
    gemm_kernel<3, 256, 4><<<132, 384, GemmSmem<256, 4>::TOTAL, st>>>(mX1ld, mW3, mW3, mA5st, mA5st, x, 14, 16);
    gemm_kernel<5, 128, 5><<<128, 384, GemmSmem<128, 5>::TOTAL, st>>>(mA5ld, mWo, mW4, mOut, mOut, (const bf16*)p_x1, 8, 72);
}
```

```cpp
#include <cuda_runtime.h>
#include <cuda_bf16.h>
#include <cuda.h>
#include <stdint.h>

typedef __nv_bfloat16 bf16;

constexpr int S_LEN = 2048;
constexpr int DM = 1024;
constexpr int FF = 3584;
constexpr int NH = 32;
constexpr int DH = 32;

__device__ __align__(1024) bf16 g_qkv[S_LEN * 3 * DM];
__device__ __align__(1024) bf16 g_h[S_LEN * DM];
__device__ __align__(1024) bf16 g_x1[S_LEN * DM];
__device__ __align__(1024) bf16 g_o[S_LEN * DM];
__device__ __align__(1024) bf16 g_h3[S_LEN * FF];
__device__ __align__(1024) bf16 g_t[S_LEN * DM];
__device__ __align__(16) float g_mean1[S_LEN];
__device__ __align__(16) float g_rstd1[S_LEN];
__device__ __align__(16) float g_gate[S_LEN];
__device__ __align__(16) float g_omg[S_LEN];
__device__ __align__(16) float g_cs1[DM];
__device__ __align__(16) float g_cs3[FF];
__device__ __align__(16) float2 g_stat2[S_LEN * 8];

#define TL_START(k)
#define TL_END(k)

__device__ __forceinline__ uint32_t smem_u32(const void* p) { return (uint32_t)__cvta_generic_to_shared(p); }

__device__ __forceinline__ void mbar_init(uint32_t bar, uint32_t count) {
    asm volatile("mbarrier.init.shared::cta.b64 [%0], %1;" ::"r"(bar), "r"(count));
}
__device__ __forceinline__ void mbar_expect_tx(uint32_t bar, uint32_t bytes) {
    asm volatile("mbarrier.arrive.expect_tx.shared::cta.b64 _, [%0], %1;" ::"r"(bar), "r"(bytes) : "memory");
}
__device__ __forceinline__ void mbar_arrive(uint32_t bar) {
    asm volatile("mbarrier.arrive.shared::cta.b64 _, [%0];" ::"r"(bar) : "memory");
}
__device__ __forceinline__ bool mbar_try_wait(uint32_t bar, uint32_t parity) {
    uint32_t ok;
    asm volatile(
        "{\n.reg .pred p;\n"
        "mbarrier.try_wait.parity.shared::cta.b64 p, [%1], %2;\n"
        "selp.u32 %0, 1, 0, p;\n}\n"
        : "=r"(ok)
        : "r"(bar), "r"(parity)
        : "memory");
    return ok != 0;
}
__device__ __forceinline__ void mbar_wait(uint32_t bar, uint32_t parity) {
    uint32_t spins = 0;
    while (!mbar_try_wait(bar, parity)) {
        if (++spins > (1u << 24)) __trap();
    }
}
__device__ __forceinline__ void tma_load_2d(uint32_t dst, const CUtensorMap* map, int c0, int c1, uint32_t bar) {
    asm volatile(
        "cp.async.bulk.tensor.2d.shared::cluster.global.mbarrier::complete_tx::bytes [%0], [%1, {%3, %4}], [%2];"
        ::"r"(dst), "l"(map), "r"(bar), "r"(c0), "r"(c1)
        : "memory");
}
__device__ __forceinline__ void tma_store_2d(const CUtensorMap* map, uint32_t src, int c0, int c1) {
    asm volatile("cp.async.bulk.tensor.2d.global.shared::cta.bulk_group [%0, {%2, %3}], [%1];"
                 ::"l"(map), "r"(src), "r"(c0), "r"(c1)
                 : "memory");
}
__device__ __forceinline__ void bulk_commit() { asm volatile("cp.async.bulk.commit_group;" ::: "memory"); }
__device__ __forceinline__ void bulk_wait_read0() { asm volatile("cp.async.bulk.wait_group.read 0;" ::: "memory"); }
__device__ __forceinline__ void bulk_wait0() { asm volatile("cp.async.bulk.wait_group 0;" ::: "memory"); }
__device__ __forceinline__ void fence_proxy_async() { asm volatile("fence.proxy.async.shared::cta;" ::: "memory"); }
__device__ __forceinline__ void named_bar_sync(int id, int n) { asm volatile("bar.sync %0, %1;" ::"r"(id), "r"(n) : "memory"); }
__device__ __forceinline__ void named_bar_arrive(int id, int n) { asm volatile("bar.arrive %0, %1;" ::"r"(id), "r"(n) : "memory"); }
__device__ __forceinline__ void wgmma_fence() { asm volatile("wgmma.fence.sync.aligned;" ::: "memory"); }
__device__ __forceinline__ void wgmma_commit() { asm volatile("wgmma.commit_group.sync.aligned;" ::: "memory"); }
template <int N>
__device__ __forceinline__ void wgmma_wait() { asm volatile("wgmma.wait_group.sync.aligned %0;" ::"n"(N) : "memory"); }
__device__ __forceinline__ void prefetch_tmap(const CUtensorMap* m) {
    asm volatile("prefetch.tensormap [%0];" ::"l"(m) : "memory");
}
template <int R>
__device__ __forceinline__ void reg_alloc() { asm volatile("setmaxnreg.inc.sync.aligned.u32 %0;" ::"n"(R)); }
template <int R>
__device__ __forceinline__ void reg_dealloc() { asm volatile("setmaxnreg.dec.sync.aligned.u32 %0;" ::"n"(R)); }
__device__ __forceinline__ void stmatrix_x4(uint32_t addr, uint32_t r0, uint32_t r1, uint32_t r2, uint32_t r3) {
    asm volatile("stmatrix.sync.aligned.m8n8.x4.shared.b16 [%0], {%1, %2, %3, %4};"
                 ::"r"(addr), "r"(r0), "r"(r1), "r"(r2), "r"(r3)
                 : "memory");
}
__device__ __forceinline__ uint32_t pack_bf16(float lo, float hi) {
    uint32_t r;
    asm("cvt.rn.bf16x2.f32 %0, %1, %2;" : "=r"(r) : "f"(hi), "f"(lo));
    return r;
}
__device__ __forceinline__ float bf16_round(float v) { return __bfloat162float(__float2bfloat16_rn(v)); }
__device__ __forceinline__ float ex2(float x) {
    float y;
    asm volatile("ex2.approx.ftz.f32 %0, %1;" : "=f"(y) : "f"(x));
    return y;
}
__device__ __forceinline__ float tanh_fast(float x) {
    float y;
    asm("tanh.approx.f32 %0, %1;" : "=f"(y) : "f"(x));
    return y;
}
__device__ __forceinline__ float gelu_tanh(float v) {
    float u = 0.7978845608028654f * (v + 0.044715f * v * v * v);
    float hv = 0.5f * v;
    return fmaf(hv, tanh_fast(u), hv);
}
__device__ __forceinline__ uint32_t desc_lo(uint32_t addr, uint32_t lbo_bytes) {
    return ((addr & 0x3FFFF) >> 4) | (((lbo_bytes >> 4) & 0x3FFF) << 16);
}
__host__ __device__ constexpr uint32_t desc_hi(uint32_t sbo_bytes, uint32_t swz) {
    return ((sbo_bytes >> 4) & 0x3FFF) | (swz << 30);
}

__device__ __forceinline__ void wgmma_ss_n128_tb1(float (&d)[64], uint32_t alo, uint32_t ahi, uint32_t blo, uint32_t bhi, int scale_d) {
    asm volatile("{\n.reg .pred p;\n.reg .b64 da, db;\nsetp.ne.b32 p, %68, 0;\nmov.b64 da, {%64, %65};\nmov.b64 db, {%66, %67};\n"
        "wgmma.mma_async.sync.aligned.m64n128k16.f32.bf16.bf16 {%0, %1, %2, %3, %4, %5, %6, %7, %8, %9, %10, %11, %12, %13, %14, %15, %16, %17, %18, %19, %20, %21, %22, %23, %24, %25, %26, %27, %28, %29, %30, %31, %32, %33, %34, %35, %36, %37, %38, %39, %40, %41, %42, %43, %44, %45, %46, %47, %48, %49, %50, %51, %52, %53, %54, %55, %56, %57, %58, %59, %60, %61, %62, %63}, da, db, p, 1, 1, 0, 1;\n}\n"
        : "+f"(d[0]), "+f"(d[1]), "+f"(d[2]), "+f"(d[3]), "+f"(d[4]), "+f"(d[5]), "+f"(d[6]), "+f"(d[7]), "+f"(d[8]), "+f"(d[9]), "+f"(d[10]), "+f"(d[11]), "+f"(d[12]), "+f"(d[13]), "+f"(d[14]), "+f"(d[15]), "+f"(d[16]), "+f"(d[17]), "+f"(d[18]), "+f"(d[19]), "+f"(d[20]), "+f"(d[21]), "+f"(d[22]), "+f"(d[23]), "+f"(d[24]), "+f"(d[25]), "+f"(d[26]), "+f"(d[27]), "+f"(d[28]), "+f"(d[29]), "+f"(d[30]), "+f"(d[31]), "+f"(d[32]), "+f"(d[33]), "+f"(d[34]), "+f"(d[35]), "+f"(d[36]), "+f"(d[37]), "+f"(d[38]), "+f"(d[39]), "+f"(d[40]), "+f"(d[41]), "+f"(d[42]), "+f"(d[43]), "+f"(d[44]), "+f"(d[45]), "+f"(d[46]), "+f"(d[47]), "+f"(d[48]), "+f"(d[49]), "+f"(d[50]), "+f"(d[51]), "+f"(d[52]), "+f"(d[53]), "+f"(d[54]), "+f"(d[55]), "+f"(d[56]), "+f"(d[57]), "+f"(d[58]), "+f"(d[59]), "+f"(d[60]), "+f"(d[61]), "+f"(d[62]), "+f"(d[63])
        : "r"(alo), "r"(ahi), "r"(blo), "r"(bhi), "r"(scale_d));
}

__device__ __forceinline__ void wgmma_ss_n192_tb1(float (&d)[96], uint32_t alo, uint32_t ahi, uint32_t blo, uint32_t bhi, int scale_d) {
    asm volatile("{\n.reg .pred p;\n.reg .b64 da, db;\nsetp.ne.b32 p, %100, 0;\nmov.b64 da, {%96, %97};\nmov.b64 db, {%98, %99};\n"
        "wgmma.mma_async.sync.aligned.m64n192k16.f32.bf16.bf16 {%0, %1, %2, %3, %4, %5, %6, %7, %8, %9, %10, %11, %12, %13, %14, %15, %16, %17, %18, %19, %20, %21, %22, %23, %24, %25, %26, %27, %28, %29, %30, %31, %32, %33, %34, %35, %36, %37, %38, %39, %40, %41, %42, %43, %44, %45, %46, %47, %48, %49, %50, %51, %52, %53, %54, %55, %56, %57, %58, %59, %60, %61, %62, %63, %64, %65, %66, %67, %68, %69, %70, %71, %72, %73, %74, %75, %76, %77, %78, %79, %80, %81, %82, %83, %84, %85, %86, %87, %88, %89, %90, %91, %92, %93, %94, %95}, da, db, p, 1, 1, 0, 1;\n}\n"
        : "+f"(d[0]), "+f"(d[1]), "+f"(d[2]), "+f"(d[3]), "+f"(d[4]), "+f"(d[5]), "+f"(d[6]), "+f"(d[7]), "+f"(d[8]), "+f"(d[9]), "+f"(d[10]), "+f"(d[11]), "+f"(d[12]), "+f"(d[13]), "+f"(d[14]), "+f"(d[15]), "+f"(d[16]), "+f"(d[17]), "+f"(d[18]), "+f"(d[19]), "+f"(d[20]), "+f"(d[21]), "+f"(d[22]), "+f"(d[23]), "+f"(d[24]), "+f"(d[25]), "+f"(d[26]), "+f"(d[27]), "+f"(d[28]), "+f"(d[29]), "+f"(d[30]), "+f"(d[31]), "+f"(d[32]), "+f"(d[33]), "+f"(d[34]), "+f"(d[35]), "+f"(d[36]), "+f"(d[37]), "+f"(d[38]), "+f"(d[39]), "+f"(d[40]), "+f"(d[41]), "+f"(d[42]), "+f"(d[43]), "+f"(d[44]), "+f"(d[45]), "+f"(d[46]), "+f"(d[47]), "+f"(d[48]), "+f"(d[49]), "+f"(d[50]), "+f"(d[51]), "+f"(d[52]), "+f"(d[53]), "+f"(d[54]), "+f"(d[55]), "+f"(d[56]), "+f"(d[57]), "+f"(d[58]), "+f"(d[59]), "+f"(d[60]), "+f"(d[61]), "+f"(d[62]), "+f"(d[63]), "+f"(d[64]), "+f"(d[65]), "+f"(d[66]), "+f"(d[67]), "+f"(d[68]), "+f"(d[69]), "+f"(d[70]), "+f"(d[71]), "+f"(d[72]), "+f"(d[73]), "+f"(d[74]), "+f"(d[75]), "+f"(d[76]), "+f"(d[77]), "+f"(d[78]), "+f"(d[79]), "+f"(d[80]), "+f"(d[81]), "+f"(d[82]), "+f"(d[83]), "+f"(d[84]), "+f"(d[85]), "+f"(d[86]), "+f"(d[87]), "+f"(d[88]), "+f"(d[89]), "+f"(d[90]), "+f"(d[91]), "+f"(d[92]), "+f"(d[93]), "+f"(d[94]), "+f"(d[95])
        : "r"(alo), "r"(ahi), "r"(blo), "r"(bhi), "r"(scale_d));
}

__device__ __forceinline__ void wgmma_ss_n224_tb1(float (&d)[112], uint32_t alo, uint32_t ahi, uint32_t blo, uint32_t bhi, int scale_d) {
    asm volatile("{\n.reg .pred p;\n.reg .b64 da, db;\nsetp.ne.b32 p, %116, 0;\nmov.b64 da, {%112, %113};\nmov.b64 db, {%114, %115};\n"
        "wgmma.mma_async.sync.aligned.m64n224k16.f32.bf16.bf16 {%0, %1, %2, %3, %4, %5, %6, %7, %8, %9, %10, %11, %12, %13, %14, %15, %16, %17, %18, %19, %20, %21, %22, %23, %24, %25, %26, %27, %28, %29, %30, %31, %32, %33, %34, %35, %36, %37, %38, %39, %40, %41, %42, %43, %44, %45, %46, %47, %48, %49, %50, %51, %52, %53, %54, %55, %56, %57, %58, %59, %60, %61, %62, %63, %64, %65, %66, %67, %68, %69, %70, %71, %72, %73, %74, %75, %76, %77, %78, %79, %80, %81, %82, %83, %84, %85, %86, %87, %88, %89, %90, %91, %92, %93, %94, %95, %96, %97, %98, %99, %100, %101, %102, %103, %104, %105, %106, %107, %108, %109, %110, %111}, da, db, p, 1, 1, 0, 1;\n}\n"
        : "+f"(d[0]), "+f"(d[1]), "+f"(d[2]), "+f"(d[3]), "+f"(d[4]), "+f"(d[5]), "+f"(d[6]), "+f"(d[7]), "+f"(d[8]), "+f"(d[9]), "+f"(d[10]), "+f"(d[11]), "+f"(d[12]), "+f"(d[13]), "+f"(d[14]), "+f"(d[15]), "+f"(d[16]), "+f"(d[17]), "+f"(d[18]), "+f"(d[19]), "+f"(d[20]), "+f"(d[21]), "+f"(d[22]), "+f"(d[23]), "+f"(d[24]), "+f"(d[25]), "+f"(d[26]), "+f"(d[27]), "+f"(d[28]), "+f"(d[29]), "+f"(d[30]), "+f"(d[31]), "+f"(d[32]), "+f"(d[33]), "+f"(d[34]), "+f"(d[35]), "+f"(d[36]), "+f"(d[37]), "+f"(d[38]), "+f"(d[39]), "+f"(d[40]), "+f"(d[41]), "+f"(d[42]), "+f"(d[43]), "+f"(d[44]), "+f"(d[45]), "+f"(d[46]), "+f"(d[47]), "+f"(d[48]), "+f"(d[49]), "+f"(d[50]), "+f"(d[51]), "+f"(d[52]), "+f"(d[53]), "+f"(d[54]), "+f"(d[55]), "+f"(d[56]), "+f"(d[57]), "+f"(d[58]), "+f"(d[59]), "+f"(d[60]), "+f"(d[61]), "+f"(d[62]), "+f"(d[63]), "+f"(d[64]), "+f"(d[65]), "+f"(d[66]), "+f"(d[67]), "+f"(d[68]), "+f"(d[69]), "+f"(d[70]), "+f"(d[71]), "+f"(d[72]), "+f"(d[73]), "+f"(d[74]), "+f"(d[75]), "+f"(d[76]), "+f"(d[77]), "+f"(d[78]), "+f"(d[79]), "+f"(d[80]), "+f"(d[81]), "+f"(d[82]), "+f"(d[83]), "+f"(d[84]), "+f"(d[85]), "+f"(d[86]), "+f"(d[87]), "+f"(d[88]), "+f"(d[89]), "+f"(d[90]), "+f"(d[91]), "+f"(d[92]), "+f"(d[93]), "+f"(d[94]), "+f"(d[95]), "+f"(d[96]), "+f"(d[97]), "+f"(d[98]), "+f"(d[99]), "+f"(d[100]), "+f"(d[101]), "+f"(d[102]), "+f"(d[103]), "+f"(d[104]), "+f"(d[105]), "+f"(d[106]), "+f"(d[107]), "+f"(d[108]), "+f"(d[109]), "+f"(d[110]), "+f"(d[111])
        : "r"(alo), "r"(ahi), "r"(blo), "r"(bhi), "r"(scale_d));
}

__device__ __forceinline__ void wgmma_ss_n256_tb1(float (&d)[128], uint32_t alo, uint32_t ahi, uint32_t blo, uint32_t bhi, int scale_d) {
    asm volatile("{\n.reg .pred p;\n.reg .b64 da, db;\nsetp.ne.b32 p, %132, 0;\nmov.b64 da, {%128, %129};\nmov.b64 db, {%130, %131};\n"
        "wgmma.mma_async.sync.aligned.m64n256k16.f32.bf16.bf16 {%0, %1, %2, %3, %4, %5, %6, %7, %8, %9, %10, %11, %12, %13, %14, %15, %16, %17, %18, %19, %20, %21, %22, %23, %24, %25, %26, %27, %28, %29, %30, %31, %32, %33, %34, %35, %36, %37, %38, %39, %40, %41, %42, %43, %44, %45, %46, %47, %48, %49, %50, %51, %52, %53, %54, %55, %56, %57, %58, %59, %60, %61, %62, %63, %64, %65, %66, %67, %68, %69, %70, %71, %72, %73, %74, %75, %76, %77, %78, %79, %80, %81, %82, %83, %84, %85, %86, %87, %88, %89, %90, %91, %92, %93, %94, %95, %96, %97, %98, %99, %100, %101, %102, %103, %104, %105, %106, %107, %108, %109, %110, %111, %112, %113, %114, %115, %116, %117, %118, %119, %120, %121, %122, %123, %124, %125, %126, %127}, da, db, p, 1, 1, 0, 1;\n}\n"
        : "+f"(d[0]), "+f"(d[1]), "+f"(d[2]), "+f"(d[3]), "+f"(d[4]), "+f"(d[5]), "+f"(d[6]), "+f"(d[7]), "+f"(d[8]), "+f"(d[9]), "+f"(d[10]), "+f"(d[11]), "+f"(d[12]), "+f"(d[13]), "+f"(d[14]), "+f"(d[15]), "+f"(d[16]), "+f"(d[17]), "+f"(d[18]), "+f"(d[19]), "+f"(d[20]), "+f"(d[21]), "+f"(d[22]), "+f"(d[23]), "+f"(d[24]), "+f"(d[25]), "+f"(d[26]), "+f"(d[27]), "+f"(d[28]), "+f"(d[29]), "+f"(d[30]), "+f"(d[31]), "+f"(d[32]), "+f"(d[33]), "+f"(d[34]), "+f"(d[35]), "+f"(d[36]), "+f"(d[37]), "+f"(d[38]), "+f"(d[39]), "+f"(d[40]), "+f"(d[41]), "+f"(d[42]), "+f"(d[43]), "+f"(d[44]), "+f"(d[45]), "+f"(d[46]), "+f"(d[47]), "+f"(d[48]), "+f"(d[49]), "+f"(d[50]), "+f"(d[51]), "+f"(d[52]), "+f"(d[53]), "+f"(d[54]), "+f"(d[55]), "+f"(d[56]), "+f"(d[57]), "+f"(d[58]), "+f"(d[59]), "+f"(d[60]), "+f"(d[61]), "+f"(d[62]), "+f"(d[63]), "+f"(d[64]), "+f"(d[65]), "+f"(d[66]), "+f"(d[67]), "+f"(d[68]), "+f"(d[69]), "+f"(d[70]), "+f"(d[71]), "+f"(d[72]), "+f"(d[73]), "+f"(d[74]), "+f"(d[75]), "+f"(d[76]), "+f"(d[77]), "+f"(d[78]), "+f"(d[79]), "+f"(d[80]), "+f"(d[81]), "+f"(d[82]), "+f"(d[83]), "+f"(d[84]), "+f"(d[85]), "+f"(d[86]), "+f"(d[87]), "+f"(d[88]), "+f"(d[89]), "+f"(d[90]), "+f"(d[91]), "+f"(d[92]), "+f"(d[93]), "+f"(d[94]), "+f"(d[95]), "+f"(d[96]), "+f"(d[97]), "+f"(d[98]), "+f"(d[99]), "+f"(d[100]), "+f"(d[101]), "+f"(d[102]), "+f"(d[103]), "+f"(d[104]), "+f"(d[105]), "+f"(d[106]), "+f"(d[107]), "+f"(d[108]), "+f"(d[109]), "+f"(d[110]), "+f"(d[111]), "+f"(d[112]), "+f"(d[113]), "+f"(d[114]), "+f"(d[115]), "+f"(d[116]), "+f"(d[117]), "+f"(d[118]), "+f"(d[119]), "+f"(d[120]), "+f"(d[121]), "+f"(d[122]), "+f"(d[123]), "+f"(d[124]), "+f"(d[125]), "+f"(d[126]), "+f"(d[127])
        : "r"(alo), "r"(ahi), "r"(blo), "r"(bhi), "r"(scale_d));
}

__device__ __forceinline__ void wgmma_ss_n64_tb0(float (&d)[32], uint32_t alo, uint32_t ahi, uint32_t blo, uint32_t bhi, int scale_d) {
    asm volatile("{\n.reg .pred p;\n.reg .b64 da, db;\nsetp.ne.b32 p, %36, 0;\nmov.b64 da, {%32, %33};\nmov.b64 db, {%34, %35};\n"
        "wgmma.mma_async.sync.aligned.m64n64k16.f32.bf16.bf16 {%0, %1, %2, %3, %4, %5, %6, %7, %8, %9, %10, %11, %12, %13, %14, %15, %16, %17, %18, %19, %20, %21, %22, %23, %24, %25, %26, %27, %28, %29, %30, %31}, da, db, p, 1, 1, 0, 0;\n}\n"
        : "+f"(d[0]), "+f"(d[1]), "+f"(d[2]), "+f"(d[3]), "+f"(d[4]), "+f"(d[5]), "+f"(d[6]), "+f"(d[7]), "+f"(d[8]), "+f"(d[9]), "+f"(d[10]), "+f"(d[11]), "+f"(d[12]), "+f"(d[13]), "+f"(d[14]), "+f"(d[15]), "+f"(d[16]), "+f"(d[17]), "+f"(d[18]), "+f"(d[19]), "+f"(d[20]), "+f"(d[21]), "+f"(d[22]), "+f"(d[23]), "+f"(d[24]), "+f"(d[25]), "+f"(d[26]), "+f"(d[27]), "+f"(d[28]), "+f"(d[29]), "+f"(d[30]), "+f"(d[31])
        : "r"(alo), "r"(ahi), "r"(blo), "r"(bhi), "r"(scale_d));
}

__device__ __forceinline__ void wgmma_rs_n128_tb0(float (&d)[64], uint32_t a0, uint32_t a1, uint32_t a2, uint32_t a3, uint32_t blo, uint32_t bhi, int scale_d) {
    asm volatile("{\n.reg .pred p;\n.reg .b64 db;\nsetp.ne.b32 p, %70, 0;\nmov.b64 db, {%68, %69};\n"
        "wgmma.mma_async.sync.aligned.m64n128k16.f32.bf16.bf16 {%0, %1, %2, %3, %4, %5, %6, %7, %8, %9, %10, %11, %12, %13, %14, %15, %16, %17, %18, %19, %20, %21, %22, %23, %24, %25, %26, %27, %28, %29, %30, %31, %32, %33, %34, %35, %36, %37, %38, %39, %40, %41, %42, %43, %44, %45, %46, %47, %48, %49, %50, %51, %52, %53, %54, %55, %56, %57, %58, %59, %60, %61, %62, %63}, {%64, %65, %66, %67}, db, p, 1, 1, 0;\n}\n"
        : "+f"(d[0]), "+f"(d[1]), "+f"(d[2]), "+f"(d[3]), "+f"(d[4]), "+f"(d[5]), "+f"(d[6]), "+f"(d[7]), "+f"(d[8]), "+f"(d[9]), "+f"(d[10]), "+f"(d[11]), "+f"(d[12]), "+f"(d[13]), "+f"(d[14]), "+f"(d[15]), "+f"(d[16]), "+f"(d[17]), "+f"(d[18]), "+f"(d[19]), "+f"(d[20]), "+f"(d[21]), "+f"(d[22]), "+f"(d[23]), "+f"(d[24]), "+f"(d[25]), "+f"(d[26]), "+f"(d[27]), "+f"(d[28]), "+f"(d[29]), "+f"(d[30]), "+f"(d[31]), "+f"(d[32]), "+f"(d[33]), "+f"(d[34]), "+f"(d[35]), "+f"(d[36]), "+f"(d[37]), "+f"(d[38]), "+f"(d[39]), "+f"(d[40]), "+f"(d[41]), "+f"(d[42]), "+f"(d[43]), "+f"(d[44]), "+f"(d[45]), "+f"(d[46]), "+f"(d[47]), "+f"(d[48]), "+f"(d[49]), "+f"(d[50]), "+f"(d[51]), "+f"(d[52]), "+f"(d[53]), "+f"(d[54]), "+f"(d[55]), "+f"(d[56]), "+f"(d[57]), "+f"(d[58]), "+f"(d[59]), "+f"(d[60]), "+f"(d[61]), "+f"(d[62]), "+f"(d[63])
        : "r"(a0), "r"(a1), "r"(a2), "r"(a3), "r"(blo), "r"(bhi), "r"(scale_d));
}

__device__ __forceinline__ void wgmma_rs_n64_tb0(float (&d)[32], uint32_t a0, uint32_t a1, uint32_t a2, uint32_t a3, uint32_t blo, uint32_t bhi, int scale_d) {
    asm volatile("{\n.reg .pred p;\n.reg .b64 db;\nsetp.ne.b32 p, %38, 0;\nmov.b64 db, {%36, %37};\n"
        "wgmma.mma_async.sync.aligned.m64n64k16.f32.bf16.bf16 {%0, %1, %2, %3, %4, %5, %6, %7, %8, %9, %10, %11, %12, %13, %14, %15, %16, %17, %18, %19, %20, %21, %22, %23, %24, %25, %26, %27, %28, %29, %30, %31}, {%32, %33, %34, %35}, db, p, 1, 1, 0;\n}\n"
        : "+f"(d[0]), "+f"(d[1]), "+f"(d[2]), "+f"(d[3]), "+f"(d[4]), "+f"(d[5]), "+f"(d[6]), "+f"(d[7]), "+f"(d[8]), "+f"(d[9]), "+f"(d[10]), "+f"(d[11]), "+f"(d[12]), "+f"(d[13]), "+f"(d[14]), "+f"(d[15]), "+f"(d[16]), "+f"(d[17]), "+f"(d[18]), "+f"(d[19]), "+f"(d[20]), "+f"(d[21]), "+f"(d[22]), "+f"(d[23]), "+f"(d[24]), "+f"(d[25]), "+f"(d[26]), "+f"(d[27]), "+f"(d[28]), "+f"(d[29]), "+f"(d[30]), "+f"(d[31])
        : "r"(a0), "r"(a1), "r"(a2), "r"(a3), "r"(blo), "r"(bhi), "r"(scale_d));
}

__device__ __forceinline__ void wgmma_rs_n32_tb1(float (&d)[16], uint32_t a0, uint32_t a1, uint32_t a2, uint32_t a3, uint32_t blo, uint32_t bhi, int scale_d) {
    asm volatile("{\n.reg .pred p;\n.reg .b64 db;\nsetp.ne.b32 p, %22, 0;\nmov.b64 db, {%20, %21};\n"
        "wgmma.mma_async.sync.aligned.m64n32k16.f32.bf16.bf16 {%0, %1, %2, %3, %4, %5, %6, %7, %8, %9, %10, %11, %12, %13, %14, %15}, {%16, %17, %18, %19}, db, p, 1, 1, 1;\n}\n"
        : "+f"(d[0]), "+f"(d[1]), "+f"(d[2]), "+f"(d[3]), "+f"(d[4]), "+f"(d[5]), "+f"(d[6]), "+f"(d[7]), "+f"(d[8]), "+f"(d[9]), "+f"(d[10]), "+f"(d[11]), "+f"(d[12]), "+f"(d[13]), "+f"(d[14]), "+f"(d[15])
        : "r"(a0), "r"(a1), "r"(a2), "r"(a3), "r"(blo), "r"(bhi), "r"(scale_d));
}

__device__ __forceinline__ void wgmma_rs_n40_tb1(float (&d)[20], uint32_t a0, uint32_t a1, uint32_t a2, uint32_t a3, uint32_t blo, uint32_t bhi, int scale_d) {
    asm volatile("{\n.reg .pred p;\n.reg .b64 db;\nsetp.ne.b32 p, %26, 0;\nmov.b64 db, {%24, %25};\n"
        "wgmma.mma_async.sync.aligned.m64n40k16.f32.bf16.bf16 {%0, %1, %2, %3, %4, %5, %6, %7, %8, %9, %10, %11, %12, %13, %14, %15, %16, %17, %18, %19}, {%20, %21, %22, %23}, db, p, 1, 1, 1;\n}\n"
        : "+f"(d[0]), "+f"(d[1]), "+f"(d[2]), "+f"(d[3]), "+f"(d[4]), "+f"(d[5]), "+f"(d[6]), "+f"(d[7]), "+f"(d[8]), "+f"(d[9]), "+f"(d[10]), "+f"(d[11]), "+f"(d[12]), "+f"(d[13]), "+f"(d[14]), "+f"(d[15]), "+f"(d[16]), "+f"(d[17]), "+f"(d[18]), "+f"(d[19])
        : "r"(a0), "r"(a1), "r"(a2), "r"(a3), "r"(blo), "r"(bhi), "r"(scale_d));
}

template <int BN>
__device__ __forceinline__ void wgmma_tile(float (&d)[BN / 2], uint32_t da, uint32_t db, int sd) {
    constexpr uint32_t HI = desc_hi(1024, 1);
    if constexpr (BN == 128) wgmma_ss_n128_tb1(d, da, HI, db, HI, sd);
    else if constexpr (BN == 192) wgmma_ss_n192_tb1(d, da, HI, db, HI, sd);
    else if constexpr (BN == 224) wgmma_ss_n224_tb1(d, da, HI, db, HI, sd);
    else wgmma_ss_n256_tb1(d, da, HI, db, HI, sd);
}

__global__ void __launch_bounds__(256) prep_kernel(const bf16* __restrict__ x, const bf16* __restrict__ gate_w,
                                                   const bf16* __restrict__ w1, const bf16* __restrict__ w3) {
    const int tid = threadIdx.x;
    TL_START(0)
    if (blockIdx.x < 256) {
        const int row = blockIdx.x * 8 + (tid >> 5);
        const int lane = tid & 31;
        const uint4* xr = reinterpret_cast<const uint4*>(x + (size_t)row * DM);
        const uint4* gw = reinterpret_cast<const uint4*>(gate_w);
        float v[32];
        float gsum = 0.f, sum = 0.f;
#pragma unroll
        for (int i = 0; i < 4; i++) {
            uint4 a = xr[lane + 32 * i];
            uint4 b = gw[lane + 32 * i];
            const uint32_t aa[4] = {a.x, a.y, a.z, a.w};
            const uint32_t bb[4] = {b.x, b.y, b.z, b.w};
#pragma unroll
            for (int j = 0; j < 4; j++) {
                float x0 = __uint_as_float(aa[j] << 16), x1 = __uint_as_float(aa[j] & 0xFFFF0000u);
                float g0 = __uint_as_float(bb[j] << 16), g1 = __uint_as_float(bb[j] & 0xFFFF0000u);
                v[i * 8 + j * 2] = x0;
                v[i * 8 + j * 2 + 1] = x1;
                sum += x0 + x1;
                gsum += bf16_round(x0 * g0) + bf16_round(x1 * g1);
            }
        }
#pragma unroll
        for (int o = 16; o > 0; o >>= 1) {
            sum += __shfl_xor_sync(0xffffffffu, sum, o);
            gsum += __shfl_xor_sync(0xffffffffu, gsum, o);
        }
        const float mean = sum * (1.0f / DM);
        float m2 = 0.f;
#pragma unroll
        for (int i = 0; i < 32; i++) {
            float d = v[i] - mean;
            m2 += d * d;
        }
#pragma unroll
        for (int o = 16; o > 0; o >>= 1) m2 += __shfl_xor_sync(0xffffffffu, m2, o);
        if (lane == 0) {
            g_mean1[row] = mean;
            g_rstd1[row] = rsqrtf(m2 * (1.0f / DM) + 1e-5f);
            float logit = bf16_round(gsum);
            float g = bf16_round(1.0f / (1.0f + __expf(-logit)));
            g_gate[row] = g;
            g_omg[row] = bf16_round(1.0f - g);
        }
    } else {
        __shared__ float red[32][65];
        const int strip = blockIdx.x - 256;
        const bf16* w;
        float* out;
        int ld, col0;
        if (strip < 16) { w = w1; ld = DM; col0 = strip * 64; out = g_cs1; }
        else { w = w3; ld = FF; col0 = (strip - 16) * 64; out = g_cs3; }
        const int cg = tid & 7;
        const int rg = tid >> 3;
        float acc[8];
#pragma unroll
        for (int j = 0; j < 8; j++) acc[j] = 0.f;
#pragma unroll 8
        for (int r = 0; r < 32; r++) {
            uint4 a = *reinterpret_cast<const uint4*>(w + (size_t)(r * 32 + rg) * ld + col0 + cg * 8);
            const uint32_t aa[4] = {a.x, a.y, a.z, a.w};
#pragma unroll
            for (int j = 0; j < 4; j++) {
                acc[2 * j] += __uint_as_float(aa[j] << 16);
                acc[2 * j + 1] += __uint_as_float(aa[j] & 0xFFFF0000u);
            }
        }
#pragma unroll
        for (int j = 0; j < 8; j++) red[rg][cg * 8 + j] = acc[j];
        __syncthreads();
        if (tid < 64) {
            float s = 0.f;
#pragma unroll
            for (int r = 0; r < 32; r++) s += red[r][tid];
            out[col0 + tid] = s;
        }
    }
    TL_END(0)
}

template <int BN, int STAGES, bool SMALL>
struct GemmSmem {
    static constexpr int A_BYTES = 128 * 64 * 2;
    static constexpr int B_BOXES = (BN + 63) / 64;
    static constexpr int B_BYTES = B_BOXES * 64 * 64 * 2;
    static constexpr int STAGE_BYTES = A_BYTES + B_BYTES;
    static constexpr int STG_OFF = SMALL ? 0 : STAGES * STAGE_BYTES;
    static constexpr int BAR_OFF = STAGES * STAGE_BYTES + (SMALL ? 0 : 2 * 16384);
    static constexpr int TOTAL = BAR_OFF + 256 + 1024;
};

template <int MODE, int BN, int STAGES, bool SMALL>
__global__ void __launch_bounds__(SMALL ? 256 : 384, SMALL ? 2 : 1)
gemm_kernel(const __grid_constant__ CUtensorMap mA, const __grid_constant__ CUtensorMap mB0,
            const __grid_constant__ CUtensorMap mB1, const __grid_constant__ CUtensorMap mC0,
            const __grid_constant__ CUtensorMap mC1, const bf16* __restrict__ xin, int n_tiles_n, int kblocks) {
    using L = GemmSmem<BN, STAGES, SMALL>;
    extern __shared__ uint8_t smem_raw[];
    const uint32_t sbase = (smem_u32(smem_raw) + 1023u) & ~1023u;
    const uint32_t bar_full = sbase + L::BAR_OFF;
    const uint32_t bar_empty = bar_full + 8 * STAGES;
    const int wg = (threadIdx.x >> 7) + (SMALL ? 1 : 0);
    const int ntiles = 16 * n_tiles_n;
    TL_START(MODE)

    if (threadIdx.x == 0) {
        for (int s = 0; s < STAGES; s++) {
            mbar_init(bar_full + 8 * s, 1);
            mbar_init(bar_empty + 8 * s, 2);
        }
        asm volatile("fence.mbarrier_init.release.cluster;" ::: "memory");
    }
    __syncthreads();

    auto issue_loads = [&](int m0, int n0, int kb, int stage) {
        const uint32_t sa = sbase + stage * L::STAGE_BYTES;
        const uint32_t sb = sa + L::A_BYTES;
        const uint32_t fb = bar_full + 8 * stage;
        mbar_expect_tx(fb, L::STAGE_BYTES);
        int arow = m0;
        if (MODE == 2) {
            const int grp = kb >> 2;
            arow += (grp == 0) ? -1 : (grp == 1) ? 1 : (grp == 2) ? -2 : 2;
        }
        tma_load_2d(sa, &mA, kb * 64, arow, fb);
        const CUtensorMap* mb = &mB0;
        int bc = n0;
        if (MODE == 1 && n0 >= 3 * DM) { mb = &mB1; bc = n0 - 3 * DM; }
#pragma unroll
        for (int b = 0; b < L::B_BOXES; b++) tma_load_2d(sb + b * 8192, mb, bc + b * 64, kb * 64, fb);
    };

    if (!SMALL && wg == 0) {
        reg_dealloc<40>();
        if (threadIdx.x == 0) {
            prefetch_tmap(&mA);
            prefetch_tmap(&mB0);
            if (MODE == 1) prefetch_tmap(&mB1);
            int stage = 0;
            uint32_t phase = 1;
            for (int tile = blockIdx.x; tile < ntiles; tile += gridDim.x) {
                const int m0 = (tile & 15) * 128;
                const int n0 = (tile >> 4) * BN;
                for (int kb = 0; kb < kblocks; kb++) {
                    mbar_wait(bar_empty + 8 * stage, phase);
                    issue_loads(m0, n0, kb, stage);
                    if (++stage == STAGES) { stage = 0; phase ^= 1; }
                }
            }
        }
    } else {
        if (!SMALL) reg_alloc<232>();
        const int c = wg - 1;
        const int warp = (threadIdx.x >> 5) & 3;
        const int lane = threadIdx.x & 31;
        const int tid_wg = threadIdx.x & 127;
        const uint32_t stg = sbase + L::STG_OFF + c * 16384;
        int stage = 0;
        uint32_t phase = 0;
        float acc[BN / 2];
        for (int tile = blockIdx.x; tile < ntiles; tile += gridDim.x) {
            const int m0 = (tile & 15) * 128;
            const int n0 = (tile >> 4) * BN;
            int prev_stage = 0;
            if (SMALL && threadIdx.x == 0) {
#pragma unroll
                for (int kb = 0; kb < STAGES; kb++) issue_loads(m0, n0, kb, kb);
            }
            for (int kb = 0; kb < kblocks; kb++) {
                mbar_wait(bar_full + 8 * stage, phase);
                const uint32_t sa = sbase + stage * L::STAGE_BYTES + c * 8192;
                const uint32_t sb = sbase + stage * L::STAGE_BYTES + L::A_BYTES;
                const uint32_t da = desc_lo(sa, 16);
                const uint32_t db = desc_lo(sb, 8192);
                wgmma_fence();
#pragma unroll
                for (int k = 0; k < 4; k++) wgmma_tile<BN>(acc, da + k * 2, db + k * 128, (kb | k) != 0);
                wgmma_commit();
                if (kb > 0) {
                    wgmma_wait<1>();
                    if (tid_wg == 0) mbar_arrive(bar_empty + 8 * prev_stage);
                    if (SMALL && threadIdx.x == 0 && kb - 1 + STAGES < kblocks) {
                        mbar_wait(bar_empty + 8 * prev_stage, ((kb - 1) / STAGES) & 1);
                        issue_loads(m0, n0, kb - 1 + STAGES, prev_stage);
                    }
                    __syncwarp();
                }
                prev_stage = stage;
                if (++stage == STAGES) { stage = 0; phase ^= 1; }
            }
            wgmma_wait<0>();
            if (tid_wg == 0) mbar_arrive(bar_empty + 8 * prev_stage);
            if (SMALL) named_bar_sync(3, 256);

            const int r0 = m0 + c * 64 + warp * 16 + (lane >> 2);
            const int r1 = r0 + 8;
            const int cq = (lane & 3) * 2;
            const CUtensorMap* mc = &mC0;
            int out_c0 = n0;
            if (MODE == 1) {
                if (n0 >= 3 * DM) {
                    mc = &mC1;
                    out_c0 = n0 - 3 * DM;
                    const float mu0 = g_mean1[r0], mu1 = g_mean1[r1];
                    const float rs0 = g_rstd1[r0], rs1 = g_rstd1[r1];
#pragma unroll
                    for (int j = 0; j < BN / 8; j++) {
                        const float2 cs = *reinterpret_cast<const float2*>(&g_cs1[out_c0 + 8 * j + cq]);
                        acc[4 * j + 0] = gelu_tanh(rs0 * fmaf(-mu0, cs.x, acc[4 * j + 0]));
                        acc[4 * j + 1] = gelu_tanh(rs0 * fmaf(-mu0, cs.y, acc[4 * j + 1]));
                        acc[4 * j + 2] = gelu_tanh(rs1 * fmaf(-mu1, cs.x, acc[4 * j + 2]));
                        acc[4 * j + 3] = gelu_tanh(rs1 * fmaf(-mu1, cs.y, acc[4 * j + 3]));
                    }
                }
            } else if (MODE == 2) {
                float s0 = 0.f, s1 = 0.f;
#pragma unroll
                for (int j = 0; j < BN / 8; j++) {
                    const uint32_t xa = *reinterpret_cast<const uint32_t*>(xin + (size_t)r0 * DM + n0 + 8 * j + cq);
                    const uint32_t xb = *reinterpret_cast<const uint32_t*>(xin + (size_t)r1 * DM + n0 + 8 * j + cq);
                    acc[4 * j + 0] = bf16_round(bf16_round(acc[4 * j + 0]) + __uint_as_float(xa << 16));
                    acc[4 * j + 1] = bf16_round(bf16_round(acc[4 * j + 1]) + __uint_as_float(xa & 0xFFFF0000u));
                    acc[4 * j + 2] = bf16_round(bf16_round(acc[4 * j + 2]) + __uint_as_float(xb << 16));
                    acc[4 * j + 3] = bf16_round(bf16_round(acc[4 * j + 3]) + __uint_as_float(xb & 0xFFFF0000u));
                    s0 += acc[4 * j + 0] + acc[4 * j + 1];
                    s1 += acc[4 * j + 2] + acc[4 * j + 3];
                }
                s0 += __shfl_xor_sync(0xffffffffu, s0, 1);
                s0 += __shfl_xor_sync(0xffffffffu, s0, 2);
                s1 += __shfl_xor_sync(0xffffffffu, s1, 1);
                s1 += __shfl_xor_sync(0xffffffffu, s1, 2);
                const float mu0 = s0 * (1.0f / BN), mu1 = s1 * (1.0f / BN);
                float q0 = 0.f, q1 = 0.f;
#pragma unroll
                for (int j = 0; j < BN / 8; j++) {
                    float d;
                    d = acc[4 * j + 0] - mu0; q0 += d * d;
                    d = acc[4 * j + 1] - mu0; q0 += d * d;
                    d = acc[4 * j + 2] - mu1; q1 += d * d;
                    d = acc[4 * j + 3] - mu1; q1 += d * d;
                }
                q0 += __shfl_xor_sync(0xffffffffu, q0, 1);
                q0 += __shfl_xor_sync(0xffffffffu, q0, 2);
                q1 += __shfl_xor_sync(0xffffffffu, q1, 1);
                q1 += __shfl_xor_sync(0xffffffffu, q1, 2);
                if ((lane & 3) == 0) {
                    static_assert(MODE != 2 || BN == 128, "stats layout assumes BN=128");
                    g_stat2[r0 * 8 + (n0 >> 7)] = make_float2(s0, q0);
                    g_stat2[r1 * 8 + (n0 >> 7)] = make_float2(s1, q1);
                }
            } else if (MODE == 3) {
                float mu[2], rs[2];
#pragma unroll
                for (int h = 0; h < 2; h++) {
                    const float4* sp = reinterpret_cast<const float4*>(&g_stat2[(h ? r1 : r0) * 8]);
                    float4 p[4];
                    float s = 0.f;
#pragma unroll
                    for (int i = 0; i < 4; i++) { p[i] = sp[i]; s += p[i].x + p[i].z; }
                    const float mean = s * (1.0f / DM);
                    float m2 = 0.f;
#pragma unroll
                    for (int i = 0; i < 4; i++) {
                        float d0 = p[i].x * (1.0f / 128) - mean, d1 = p[i].z * (1.0f / 128) - mean;
                        m2 += p[i].y + p[i].w + 128.0f * (d0 * d0 + d1 * d1);
                    }
                    mu[h] = mean;
                    rs[h] = rsqrtf(m2 * (1.0f / DM) + 1e-5f);
                }
#pragma unroll
                for (int j = 0; j < BN / 8; j++) {
                    const float2 cs = *reinterpret_cast<const float2*>(&g_cs3[n0 + 8 * j + cq]);
                    acc[4 * j + 0] = gelu_tanh(rs[0] * fmaf(-mu[0], cs.x, acc[4 * j + 0]));
                    acc[4 * j + 1] = gelu_tanh(rs[0] * fmaf(-mu[0], cs.y, acc[4 * j + 1]));
                    acc[4 * j + 2] = gelu_tanh(rs[1] * fmaf(-mu[1], cs.x, acc[4 * j + 2]));
                    acc[4 * j + 3] = gelu_tanh(rs[1] * fmaf(-mu[1], cs.y, acc[4 * j + 3]));
                }
            } else if (MODE == 4) {
                const float og0 = g_omg[r0], og1 = g_omg[r1];
#pragma unroll
                for (int j = 0; j < BN / 8; j++) {
                    const uint32_t xa = *reinterpret_cast<const uint32_t*>(xin + (size_t)r0 * DM + n0 + 8 * j + cq);
                    const uint32_t xb = *reinterpret_cast<const uint32_t*>(xin + (size_t)r1 * DM + n0 + 8 * j + cq);
                    acc[4 * j + 0] = og0 * (__uint_as_float(xa << 16) + acc[4 * j + 0]);
                    acc[4 * j + 1] = og0 * (__uint_as_float(xa & 0xFFFF0000u) + acc[4 * j + 1]);
                    acc[4 * j + 2] = og1 * (__uint_as_float(xb << 16) + acc[4 * j + 2]);
                    acc[4 * j + 3] = og1 * (__uint_as_float(xb & 0xFFFF0000u) + acc[4 * j + 3]);
                }
            } else {
#pragma unroll
                for (int j = 0; j < BN / 8; j++) {
                    const uint32_t xa = *reinterpret_cast<const uint32_t*>(xin + (size_t)r0 * DM + n0 + 8 * j + cq);
                    const uint32_t xb = *reinterpret_cast<const uint32_t*>(xin + (size_t)r1 * DM + n0 + 8 * j + cq);
                    acc[4 * j + 0] += __uint_as_float(xa << 16);
                    acc[4 * j + 1] += __uint_as_float(xa & 0xFFFF0000u);
                    acc[4 * j + 2] += __uint_as_float(xb << 16);
                    acc[4 * j + 3] += __uint_as_float(xb & 0xFFFF0000u);
                }
            }
            const int srow = warp * 16 + (lane & 7) + ((lane >> 3) & 1) * 8;
#pragma unroll
            for (int rnd = 0; rnd < (BN + 127) / 128; rnd++) {
                if (!SMALL || rnd > 0) {
                    if (tid_wg == 0) bulk_wait_read0();
                    named_bar_sync(1 + c, 128);
                }
#pragma unroll
                for (int jj = 0; jj < 8; jj++) {
                    const int j = rnd * 16 + jj * 2;
                    if (j * 8 < BN) {
                        const int jb = jj * 2 + (lane >> 4);
                        const uint32_t addr = stg + (jb >> 3) * 8192 + srow * 128 + (((jb & 7) ^ (srow & 7)) << 4);
                        stmatrix_x4(addr, pack_bf16(acc[4 * j + 0], acc[4 * j + 1]), pack_bf16(acc[4 * j + 2], acc[4 * j + 3]),
                                    pack_bf16(acc[4 * j + 4], acc[4 * j + 5]), pack_bf16(acc[4 * j + 6], acc[4 * j + 7]));
                    }
                }
                fence_proxy_async();
                named_bar_sync(1 + c, 128);
                if (tid_wg == 0) {
                    tma_store_2d(mc, stg, out_c0 + rnd * 128, m0 + c * 64);
                    if (rnd * 128 + 64 < BN) tma_store_2d(mc, stg + 8192, out_c0 + rnd * 128 + 64, m0 + c * 64);
                    bulk_commit();
                }
            }
        }
        if (tid_wg == 0) bulk_wait0();
        TL_END(MODE)
    }
}

#define ATT_SPLIT 4
constexpr int ATT_NTILES = NH * 16;
#define ATT_GRID_N 132
constexpr int ATT_GRID = ATT_GRID_N;
constexpr int ATT_THREADS = 256;
constexpr int ATT_STAGES = 4;
constexpr int ATT_DIST = 2;
constexpr int ATT_Q_OFF = ATT_STAGES * 16384;
constexpr int ATT_ONES_OFF = ATT_Q_OFF + 16384;
constexpr int ATT_BAR_OFF = ATT_ONES_OFF + 4096;
#define ATT_SMEM_BYTES (114 * 1024)
constexpr int ATT_SMEM = ATT_SMEM_BYTES;

struct AttState {
    float o[20];
    float m0, m1;
    float mp0, mp1;
};

__device__ __forceinline__ void row_max(const float (&s)[32], float& m0, float& m1) {
    float mx0 = fmaxf(s[0], s[1]), mx1 = fmaxf(s[2], s[3]);
#pragma unroll
    for (int i = 1; i < 8; i++) {
        mx0 = fmaxf(mx0, fmaxf(s[4 * i], s[4 * i + 1]));
        mx1 = fmaxf(mx1, fmaxf(s[4 * i + 2], s[4 * i + 3]));
    }
    mx0 = fmaxf(mx0, __shfl_xor_sync(0xffffffffu, mx0, 1));
    mx1 = fmaxf(mx1, __shfl_xor_sync(0xffffffffu, mx1, 1));
    mx0 = fmaxf(mx0, __shfl_xor_sync(0xffffffffu, mx0, 2));
    mx1 = fmaxf(mx1, __shfl_xor_sync(0xffffffffu, mx1, 2));
    m0 = fmaxf(m0, mx0);
    m1 = fmaxf(m1, mx1);
}

__device__ __forceinline__ void attn_step(float (&sc)[32], float (&sn)[32], uint32_t (&p)[16], uint32_t dq,
                                          AttState& st, uint32_t dk_next, uint32_t dv_prev, uint32_t release_bar, int one) {
    const float cs = 0.17677669529663687f * 1.4426950408889634f;
    constexpr uint32_t HI = desc_hi(512, 2);
    wgmma_fence();
    wgmma_ss_n64_tb0(sn, dq, HI, dk_next, HI, 0);
    wgmma_ss_n64_tb0(sn, dq + 2, HI, dk_next + 2, HI, 1);
#pragma unroll
    for (int t = 0; t < 4; t++)
        wgmma_rs_n40_tb1(st.o, p[4 * t], p[4 * t + 1], p[4 * t + 2], p[4 * t + 3], dv_prev + t * 64, HI, 1);
    wgmma_commit();
    const float mc0 = st.m0, mc1 = st.m1;
    const float b0 = mc0 * cs, b1 = mc1 * cs;
    if (one) {
#pragma unroll
        for (int i = 0; i < ATT_SPLIT; i++) {
            sc[4 * i + 0] = ex2(fmaf(sc[4 * i + 0], cs, -b0));
            sc[4 * i + 1] = ex2(fmaf(sc[4 * i + 1], cs, -b0));
            sc[4 * i + 2] = ex2(fmaf(sc[4 * i + 2], cs, -b1));
            sc[4 * i + 3] = ex2(fmaf(sc[4 * i + 3], cs, -b1));
        }
    }
    wgmma_wait<0>();
    if (release_bar != 0 && (threadIdx.x & 127) == 0) mbar_arrive(release_bar);
    if (one) {
        row_max(sn, st.m0, st.m1);
#pragma unroll
        for (int i = ATT_SPLIT; i < 8; i++) {
            sc[4 * i + 0] = ex2(fmaf(sc[4 * i + 0], cs, -b0));
            sc[4 * i + 1] = ex2(fmaf(sc[4 * i + 1], cs, -b0));
            sc[4 * i + 2] = ex2(fmaf(sc[4 * i + 2], cs, -b1));
            sc[4 * i + 3] = ex2(fmaf(sc[4 * i + 3], cs, -b1));
        }
        const float a0 = ex2((st.mp0 - mc0) * cs), a1 = ex2((st.mp1 - mc1) * cs);
#pragma unroll
        for (int i = 0; i < 5; i++) {
            st.o[4 * i + 0] *= a0; st.o[4 * i + 1] *= a0;
            st.o[4 * i + 2] *= a1; st.o[4 * i + 3] *= a1;
        }
        st.mp0 = mc0; st.mp1 = mc1;
#pragma unroll
        for (int i = 0; i < 8; i++) {
            p[2 * i] = pack_bf16(sc[4 * i + 0], sc[4 * i + 1]);
            p[2 * i + 1] = pack_bf16(sc[4 * i + 2], sc[4 * i + 3]);
        }
    }
}

__global__ void __launch_bounds__(256, 2)
attn_kernel(const __grid_constant__ CUtensorMap mKV, int one) {
    extern __shared__ uint8_t smem_raw[];
    const uint32_t sbase = (smem_u32(smem_raw) + 1023u) & ~1023u;
    const uint32_t bar_kfull = sbase + ATT_BAR_OFF;
    const uint32_t bar_vfull = bar_kfull + 8 * ATT_STAGES;
    const uint32_t bar_empty = bar_vfull + 8 * ATT_STAGES;
    const uint32_t bar_q = bar_empty + 8 * ATT_STAGES;
    const int warp_id = threadIdx.x >> 5;
    const int lane = threadIdx.x & 31;
    constexpr int NBLK = S_LEN / 128;
    TL_START(6)
    const int my_tiles = (ATT_NTILES - (int)blockIdx.x + (int)gridDim.x - 1) / (int)gridDim.x;
    const int total_blocks = my_tiles * NBLK;

    auto issue_kv = [&](int g) {
        const int tile = blockIdx.x + (g >> 4) * gridDim.x;
        const int hd = tile >> 4;
        const int sn = g % ATT_STAGES;
        if (g >= ATT_STAGES) mbar_wait(bar_empty + 8 * sn, ((g / ATT_STAGES) - 1) & 1);
        const uint32_t skn = sbase + sn * 16384;
        mbar_expect_tx(bar_kfull + 8 * sn, 8192);
        tma_load_2d(skn, &mKV, DM + hd * DH, (g & 15) * 128, bar_kfull + 8 * sn);
        mbar_expect_tx(bar_vfull + 8 * sn, 8192);
        tma_load_2d(skn + 8192, &mKV, 2 * DM + hd * DH, (g & 15) * 128, bar_vfull + 8 * sn);
    };
    auto issue_q = [&](int it) {
        const int tile = blockIdx.x + it * gridDim.x;
        mbar_expect_tx(bar_q + 8 * (it & 1), 8192);
        tma_load_2d(sbase + ATT_Q_OFF + (it & 1) * 8192, &mKV, (tile >> 4) * DH, (tile & 15) * 128, bar_q + 8 * (it & 1));
    };

    if (threadIdx.x == 0) {
        for (int s = 0; s < ATT_STAGES; s++) {
            mbar_init(bar_kfull + 8 * s, 1);
            mbar_init(bar_vfull + 8 * s, 1);
            mbar_init(bar_empty + 8 * s, 2);
        }
        mbar_init(bar_q, 1);
        mbar_init(bar_q + 8, 1);
        asm volatile("fence.mbarrier_init.release.cluster;" ::: "memory");
        prefetch_tmap(&mKV);
        issue_q(0);
#pragma unroll
        for (int j = 0; j < ATT_DIST; j++) issue_kv(j);
    }
    asm volatile("st.shared.v4.b32 [%0], {%1, %1, %1, %1};" ::"r"(sbase + ATT_ONES_OFF + threadIdx.x * 16), "r"(0x3F803F80u) : "memory");
    fence_proxy_async();
    __syncthreads();

    const int cq = (lane & 3) * 2;
    constexpr uint32_t HI = desc_hi(512, 2);
    const uint32_t dk0 = desc_lo(sbase, 16);
    const uint32_t dv0 = desc_lo(sbase + 8192, ATT_ONES_OFF - 8192);
    int stage = 0;
    uint32_t phase = 0;
#pragma unroll 1
    for (int it = 0; it < my_tiles; it++) {
        const int tile = blockIdx.x + it * gridDim.x;
        const int head = tile >> 4;
        const int row0 = (tile & 15) * 128 + warp_id * 16 + (lane >> 2);
        const uint32_t dq = desc_lo(sbase + ATT_Q_OFF + (it & 1) * 8192 + (threadIdx.x >> 7) * 4096, 16);
        if (threadIdx.x == 0 && it + 1 < my_tiles) issue_q(it + 1);
        AttState st;
#pragma unroll
        for (int i = 0; i < 20; i++) st.o[i] = 0.f;
        st.m0 = -INFINITY; st.m1 = -INFINITY;
        float s0[32], s1[32];
        uint32_t p[16];
#pragma unroll
        for (int i = 0; i < 16; i++) p[i] = 0u;
        mbar_wait(bar_q + 8 * (it & 1), (it >> 1) & 1);
        mbar_wait(bar_kfull + 8 * stage, phase);
        wgmma_fence();
        wgmma_ss_n64_tb0(s0, dq, HI, dk0 + stage * 1024, HI, 0);
        wgmma_ss_n64_tb0(s0, dq + 2, HI, dk0 + stage * 1024 + 2, HI, 1);
        wgmma_commit();
        mbar_wait(bar_vfull + 8 * stage, phase);
        wgmma_wait<0>();
        row_max(s0, st.m0, st.m1);
        st.mp0 = st.m0; st.mp1 = st.m1;
        uint32_t dv_prev = dv0 + stage * 1024 - ((uint32_t)(stage * 1024) << 16);
        int pstage = stage;
#pragma unroll 1
        for (int j = 0; j < NBLK; j++) {
            if (threadIdx.x == 0 && it * NBLK + j + ATT_DIST < total_blocks) issue_kv(it * NBLK + j + ATT_DIST);
            __syncwarp();
            const uint32_t dk = dk0 + stage * 1024;
            const uint32_t dv = dv0 + stage * 1024 - ((uint32_t)(stage * 1024) << 16);
            attn_step(s0, s1, p, dq, st, dk + 256, dv_prev, j > 0 ? bar_empty + 8 * pstage : 0u, one);
            int nstage = stage + 1;
            uint32_t nphase = phase;
            if (nstage == ATT_STAGES) { nstage = 0; nphase ^= 1; }
            uint32_t dkn = dk;
            if (j + 1 < NBLK) {
                mbar_wait(bar_kfull + 8 * nstage, nphase);
                dkn = dk0 + nstage * 1024;
            }
            mbar_wait(bar_vfull + 8 * stage, phase);
            attn_step(s1, s0, p, dq, st, dkn, dv, 0u, one);
            dv_prev = dv + 256 - (256u << 16);
            pstage = stage;
            stage = nstage;
            phase = nphase;
        }
        wgmma_fence();
#pragma unroll
        for (int t = 0; t < 4; t++)
            wgmma_rs_n40_tb1(st.o, p[4 * t], p[4 * t + 1], p[4 * t + 2], p[4 * t + 3], dv_prev + t * 64, HI, 1);
        wgmma_commit();
        wgmma_wait<0>();
        if ((threadIdx.x & 127) == 0) mbar_arrive(bar_empty + 8 * pstage);
        const float f0 = g_gate[row0] / st.o[16], f1 = g_gate[row0 + 8] / st.o[18];
        bf16* op0 = g_o + (size_t)row0 * DM + head * DH + cq;
        bf16* op1 = op0 + 8 * DM;
#pragma unroll
        for (int i = 0; i < 4; i++) {
            *reinterpret_cast<uint32_t*>(op0 + 8 * i) = pack_bf16(st.o[4 * i] * f0, st.o[4 * i + 1] * f0);
            *reinterpret_cast<uint32_t*>(op1 + 8 * i) = pack_bf16(st.o[4 * i + 2] * f1, st.o[4 * i + 3] * f1);
        }
        __syncthreads();
    }
    TL_END(6)
}

typedef CUresult (*EncodeFn)(CUtensorMap*, CUtensorMapDataType, cuuint32_t, void*, const cuuint64_t*, const cuuint64_t*,
                             const cuuint32_t*, const cuuint32_t*, CUtensorMapInterleave, CUtensorMapSwizzle,
                             CUtensorMapL2promotion, CUtensorMapFloatOOBfill);

static CUtensorMap make_map(EncodeFn fn, const void* ptr, int rows, int cols, int box_cols, int box_rows,
                            CUtensorMapSwizzle swz) {
    CUtensorMap m;
    cuuint64_t dims[2] = {(cuuint64_t)cols, (cuuint64_t)rows};
    cuuint64_t strides[1] = {(cuuint64_t)cols * 2};
    cuuint32_t box[2] = {(cuuint32_t)box_cols, (cuuint32_t)box_rows};
    cuuint32_t es[2] = {1, 1};
    fn(&m, CU_TENSOR_MAP_DATA_TYPE_BFLOAT16, 2, const_cast<void*>(ptr), dims, strides, box, es,
       CU_TENSOR_MAP_INTERLEAVE_NONE, swz, CU_TENSOR_MAP_L2_PROMOTION_L2_256B, CU_TENSOR_MAP_FLOAT_OOB_FILL_NONE);
    return m;
}

extern "C" void kernel_launch(void* const* d_in, const int* in_sizes, int n_in, void* d_out, int out_size) {
    const bf16* x = (const bf16*)d_in[0];
    const bf16* wqkv = (const bf16*)d_in[1];
    const bf16* wo = (const bf16*)d_in[2];
    const bf16* w1 = (const bf16*)d_in[4];
    const bf16* w2 = (const bf16*)d_in[5];
    const bf16* w3 = (const bf16*)d_in[6];
    const bf16* w4 = (const bf16*)d_in[7];
    const bf16* gate_w = (const bf16*)d_in[8];

    static EncodeFn enc = nullptr;
    static void *p_qkv, *p_h, *p_x1, *p_o, *p_h3, *p_t;
    static cudaStream_t s2;
    static cudaEvent_t ev_fork, ev_join;
    using G1 = GemmSmem<256, 4, false>;
    using GS = GemmSmem<128, 3, true>;
    using G5 = GemmSmem<128, 5, false>;
    if (!enc) {
        void* fn = nullptr;
        cudaDriverEntryPointQueryResult qres;
        cudaGetDriverEntryPoint("cuTensorMapEncodeTiled", &fn, cudaEnableDefault, &qres);
        enc = (EncodeFn)fn;
        cudaGetSymbolAddress(&p_qkv, g_qkv);
        cudaGetSymbolAddress(&p_h, g_h);
        cudaGetSymbolAddress(&p_x1, g_x1);
        cudaGetSymbolAddress(&p_o, g_o);
        cudaGetSymbolAddress(&p_h3, g_h3);
        cudaGetSymbolAddress(&p_t, g_t);
        cudaFuncSetAttribute(gemm_kernel<1, 256, 4, false>, cudaFuncAttributeMaxDynamicSharedMemorySize, G1::TOTAL);
        cudaFuncSetAttribute(gemm_kernel<2, 128, 3, true>, cudaFuncAttributeMaxDynamicSharedMemorySize, GS::TOTAL);
        cudaFuncSetAttribute(gemm_kernel<3, 128, 3, true>, cudaFuncAttributeMaxDynamicSharedMemorySize, GS::TOTAL);
        cudaFuncSetAttribute(gemm_kernel<4, 128, 3, true>, cudaFuncAttributeMaxDynamicSharedMemorySize, GS::TOTAL);
        cudaFuncSetAttribute(gemm_kernel<5, 128, 5, false>, cudaFuncAttributeMaxDynamicSharedMemorySize, G5::TOTAL);
        cudaFuncSetAttribute(attn_kernel, cudaFuncAttributeMaxDynamicSharedMemorySize, ATT_SMEM);
        int prio_lo, prio_hi;
        cudaDeviceGetStreamPriorityRange(&prio_lo, &prio_hi);
        cudaStreamCreateWithPriority(&s2, cudaStreamNonBlocking, prio_hi);
        cudaEventCreateWithFlags(&ev_fork, cudaEventDisableTiming);
        cudaEventCreateWithFlags(&ev_join, cudaEventDisableTiming);
    }
    const CUtensorMapSwizzle SW128 = CU_TENSOR_MAP_SWIZZLE_128B, SW64 = CU_TENSOR_MAP_SWIZZLE_64B;
    CUtensorMap mX = make_map(enc, x, S_LEN, DM, 64, 128, SW128);
    CUtensorMap mWqkv = make_map(enc, wqkv, DM, 3 * DM, 64, 64, SW128);
    CUtensorMap mW1 = make_map(enc, w1, DM, DM, 64, 64, SW128);
    CUtensorMap mW2 = make_map(enc, w2, DM, DM, 64, 64, SW128);
    CUtensorMap mW3 = make_map(enc, w3, DM, FF, 64, 64, SW128);
    CUtensorMap mW4 = make_map(enc, w4, FF, DM, 64, 64, SW128);
    CUtensorMap mWo = make_map(enc, wo, DM, DM, 64, 64, SW128);
    CUtensorMap mQKVst = make_map(enc, p_qkv, S_LEN, 3 * DM, 64, 64, SW128);
    CUtensorMap mKV = make_map(enc, p_qkv, S_LEN, 3 * DM, 32, 128, SW64);
    CUtensorMap mHst = make_map(enc, p_h, S_LEN, DM, 64, 64, SW128);
    CUtensorMap mHld = make_map(enc, p_h, S_LEN, DM, 64, 128, SW128);
    CUtensorMap mX1st = make_map(enc, p_x1, S_LEN, DM, 64, 64, SW128);
    CUtensorMap mX1ld = make_map(enc, p_x1, S_LEN, DM, 64, 128, SW128);
    CUtensorMap mH3st = make_map(enc, p_h3, S_LEN, FF, 64, 64, SW128);
    CUtensorMap mH3ld = make_map(enc, p_h3, S_LEN, FF, 64, 128, SW128);
    CUtensorMap mTst = make_map(enc, p_t, S_LEN, DM, 64, 64, SW128);
    CUtensorMap mOld = make_map(enc, p_o, S_LEN, DM, 64, 128, SW128);
    CUtensorMap mOut = make_map(enc, d_out, S_LEN, DM, 64, 64, SW128);

    cudaStream_t st = cudaStreamPerThread;
    prep_kernel<<<256 + 72, 256, 0, st>>>(x, gate_w, w1, w3);
    gemm_kernel<1, 256, 4, false><<<132, 384, G1::TOTAL, st>>>(mX, mWqkv, mW1, mQKVst, mHst, x, 16, 16);
    cudaEventRecord(ev_fork, st);
    cudaStreamWaitEvent(s2, ev_fork, 0);
    cudaStream_t sb = s2;
    gemm_kernel<2, 128, 3, true><<<128, 256, GS::TOTAL, sb>>>(mHld, mW2, mW2, mX1st, mX1st, x, 8, 16);
    gemm_kernel<3, 128, 3, true><<<448, 256, GS::TOTAL, sb>>>(mX1ld, mW3, mW3, mH3st, mH3st, x, 28, 16);
    gemm_kernel<4, 128, 3, true><<<128, 256, GS::TOTAL, sb>>>(mH3ld, mW4, mW4, mTst, mTst, (const bf16*)p_x1, 8, 56);
    attn_kernel<<<ATT_GRID, ATT_THREADS, ATT_SMEM, st>>>(mKV, 1);
    cudaEventRecord(ev_join, s2);
    cudaStreamWaitEvent(st, ev_join, 0);
    gemm_kernel<5, 128, 5, false><<<128, 384, G5::TOTAL, st>>>(mOld, mWo, mWo, mOut, mOut, (const bf16*)p_t, 8, 16);
}
```

```cpp
#include <cuda_runtime.h>
#include <cuda_bf16.h>
#include <cuda.h>
#include <stdint.h>

typedef __nv_bfloat16 bf16;

constexpr int S_LEN = 2048;
constexpr int DM = 1024;
constexpr int FF = 3584;
constexpr int NH = 32;
constexpr int DH = 32;
constexpr int A5W = DM + FF;

__device__ __align__(1024) bf16 g_qkv[S_LEN * 3 * DM];
__device__ __align__(1024) bf16 g_h[S_LEN * DM];
__device__ __align__(1024) bf16 g_x1[S_LEN * DM];
__device__ __align__(1024) bf16 g_a5[S_LEN * A5W];
__device__ __align__(16) float g_mean1[S_LEN];
__device__ __align__(16) float g_rstd1[S_LEN];
__device__ __align__(16) float g_gate[S_LEN];
__device__ __align__(16) float g_omg[S_LEN];
__device__ __align__(16) float g_cs1[DM];
__device__ __align__(16) float g_cs3[FF];
__device__ __align__(16) float2 g_stat2[S_LEN * 8];

#define TL_START(k)
#define TL_END(k)

__device__ __forceinline__ uint32_t smem_u32(const void* p) { return (uint32_t)__cvta_generic_to_shared(p); }

__device__ __forceinline__ void mbar_init(uint32_t bar, uint32_t count) {
    asm volatile("mbarrier.init.shared::cta.b64 [%0], %1;" ::"r"(bar), "r"(count));
}
__device__ __forceinline__ void mbar_expect_tx(uint32_t bar, uint32_t bytes) {
    asm volatile("mbarrier.arrive.expect_tx.shared::cta.b64 _, [%0], %1;" ::"r"(bar), "r"(bytes) : "memory");
}
__device__ __forceinline__ void mbar_arrive(uint32_t bar) {
    asm volatile("mbarrier.arrive.shared::cta.b64 _, [%0];" ::"r"(bar) : "memory");
}
__device__ __forceinline__ bool mbar_try_wait(uint32_t bar, uint32_t parity) {
    uint32_t ok;
    asm volatile(
        "{\n.reg .pred p;\n"
        "mbarrier.try_wait.parity.shared::cta.b64 p, [%1], %2;\n"
        "selp.u32 %0, 1, 0, p;\n}\n"
        : "=r"(ok)
        : "r"(bar), "r"(parity)
        : "memory");
    return ok != 0;
}
__device__ __forceinline__ void mbar_wait(uint32_t bar, uint32_t parity) {
    uint32_t spins = 0;
    while (!mbar_try_wait(bar, parity)) {
        if (++spins > (1u << 24)) __trap();
    }
}
__device__ __forceinline__ void tma_load_2d(uint32_t dst, const CUtensorMap* map, int c0, int c1, uint32_t bar) {
    asm volatile(
        "cp.async.bulk.tensor.2d.shared::cluster.global.mbarrier::complete_tx::bytes [%0], [%1, {%3, %4}], [%2];"
        ::"r"(dst), "l"(map), "r"(bar), "r"(c0), "r"(c1)
        : "memory");
}
__device__ __forceinline__ void tma_store_2d(const CUtensorMap* map, uint32_t src, int c0, int c1) {
    asm volatile("cp.async.bulk.tensor.2d.global.shared::cta.bulk_group [%0, {%2, %3}], [%1];"
                 ::"l"(map), "r"(src), "r"(c0), "r"(c1)
                 : "memory");
}
__device__ __forceinline__ void tma_load_2d_mc(uint32_t dst, const CUtensorMap* map, int c0, int c1, uint32_t bar, uint16_t mask) {
    asm volatile(
        "cp.async.bulk.tensor.2d.shared::cluster.global.mbarrier::complete_tx::bytes.multicast::cluster [%0], [%1, {%3, %4}], [%2], %5;"
        ::"r"(dst), "l"(map), "r"(bar), "r"(c0), "r"(c1), "h"(mask)
        : "memory");
}
__device__ __forceinline__ void mbar_arrive_cluster(uint32_t bar, uint32_t cta) {
    asm volatile(
        "{\n.reg .b32 ra;\nmapa.shared::cluster.u32 ra, %0, %1;\n"
        "mbarrier.arrive.release.cluster.shared::cluster.b64 _, [ra];\n}\n" ::"r"(bar), "r"(cta)
        : "memory");
}
__device__ __forceinline__ void cluster_sync_all() {
    asm volatile("barrier.cluster.arrive.release.aligned;\nbarrier.cluster.wait.acquire.aligned;" ::: "memory");
}
__device__ __forceinline__ uint32_t cluster_rank() { uint32_t r; asm volatile("mov.u32 %0, %%cluster_ctarank;" : "=r"(r)); return r; }
__device__ __forceinline__ void pdl_wait() { asm volatile("griddepcontrol.wait;" ::: "memory"); }
__device__ __forceinline__ void pdl_launch() { asm volatile("griddepcontrol.launch_dependents;" ::: "memory"); }
__device__ __forceinline__ void bulk_commit() { asm volatile("cp.async.bulk.commit_group;" ::: "memory"); }
__device__ __forceinline__ void bulk_wait_read0() { asm volatile("cp.async.bulk.wait_group.read 0;" ::: "memory"); }
__device__ __forceinline__ void bulk_wait0() { asm volatile("cp.async.bulk.wait_group 0;" ::: "memory"); }
__device__ __forceinline__ void fence_proxy_async() { asm volatile("fence.proxy.async.shared::cta;" ::: "memory"); }
__device__ __forceinline__ void named_bar_sync(int id, int n) { asm volatile("bar.sync %0, %1;" ::"r"(id), "r"(n) : "memory"); }
__device__ __forceinline__ void named_bar_arrive(int id, int n) { asm volatile("bar.arrive %0, %1;" ::"r"(id), "r"(n) : "memory"); }
__device__ __forceinline__ void wgmma_fence() { asm volatile("wgmma.fence.sync.aligned;" ::: "memory"); }
__device__ __forceinline__ void wgmma_commit() { asm volatile("wgmma.commit_group.sync.aligned;" ::: "memory"); }
template <int N>
__device__ __forceinline__ void wgmma_wait() { asm volatile("wgmma.wait_group.sync.aligned %0;" ::"n"(N) : "memory"); }
__device__ __forceinline__ void prefetch_tmap(const CUtensorMap* m) {
    asm volatile("prefetch.tensormap [%0];" ::"l"(m) : "memory");
}
template <int R>
__device__ __forceinline__ void reg_alloc() { asm volatile("setmaxnreg.inc.sync.aligned.u32 %0;" ::"n"(R)); }
template <int R>
__device__ __forceinline__ void reg_dealloc() { asm volatile("setmaxnreg.dec.sync.aligned.u32 %0;" ::"n"(R)); }
__device__ __forceinline__ void stmatrix_x4(uint32_t addr, uint32_t r0, uint32_t r1, uint32_t r2, uint32_t r3) {
    asm volatile("stmatrix.sync.aligned.m8n8.x4.shared.b16 [%0], {%1, %2, %3, %4};"
                 ::"r"(addr), "r"(r0), "r"(r1), "r"(r2), "r"(r3)
                 : "memory");
}
__device__ __forceinline__ uint32_t pack_bf16(float lo, float hi) {
    uint32_t r;
    asm("cvt.rn.bf16x2.f32 %0, %1, %2;" : "=r"(r) : "f"(hi), "f"(lo));
    return r;
}
__device__ __forceinline__ float bf16_round(float v) { return __bfloat162float(__float2bfloat16_rn(v)); }
__device__ __forceinline__ float ex2(float x) {
    float y;
    asm volatile("ex2.approx.ftz.f32 %0, %1;" : "=f"(y) : "f"(x));
    return y;
}
__device__ __forceinline__ float tanh_fast(float x) {
    float y;
    asm("tanh.approx.f32 %0, %1;" : "=f"(y) : "f"(x));
    return y;
}
__device__ __forceinline__ float gelu_tanh(float v) {
    float u = 0.7978845608028654f * (v + 0.044715f * v * v * v);
    float hv = 0.5f * v;
    return fmaf(hv, tanh_fast(u), hv);
}
__device__ __forceinline__ uint32_t desc_lo(uint32_t addr, uint32_t lbo_bytes) {
    return ((addr & 0x3FFFF) >> 4) | (((lbo_bytes >> 4) & 0x3FFF) << 16);
}
__host__ __device__ constexpr uint32_t desc_hi(uint32_t sbo_bytes, uint32_t swz) {
    return ((sbo_bytes >> 4) & 0x3FFF) | (swz << 30);
}

__device__ __forceinline__ void wgmma_ss_n128_tb1(float (&d)[64], uint32_t alo, uint32_t ahi, uint32_t blo, uint32_t bhi, int scale_d) {
    asm volatile("{\n.reg .pred p;\n.reg .b64 da, db;\nsetp.ne.b32 p, %68, 0;\nmov.b64 da, {%64, %65};\nmov.b64 db, {%66, %67};\n"
        "wgmma.mma_async.sync.aligned.m64n128k16.f32.bf16.bf16 {%0, %1, %2, %3, %4, %5, %6, %7, %8, %9, %10, %11, %12, %13, %14, %15, %16, %17, %18, %19, %20, %21, %22, %23, %24, %25, %26, %27, %28, %29, %30, %31, %32, %33, %34, %35, %36, %37, %38, %39, %40, %41, %42, %43, %44, %45, %46, %47, %48, %49, %50, %51, %52, %53, %54, %55, %56, %57, %58, %59, %60, %61, %62, %63}, da, db, p, 1, 1, 0, 1;\n}\n"
        : "+f"(d[0]), "+f"(d[1]), "+f"(d[2]), "+f"(d[3]), "+f"(d[4]), "+f"(d[5]), "+f"(d[6]), "+f"(d[7]), "+f"(d[8]), "+f"(d[9]), "+f"(d[10]), "+f"(d[11]), "+f"(d[12]), "+f"(d[13]), "+f"(d[14]), "+f"(d[15]), "+f"(d[16]), "+f"(d[17]), "+f"(d[18]), "+f"(d[19]), "+f"(d[20]), "+f"(d[21]), "+f"(d[22]), "+f"(d[23]), "+f"(d[24]), "+f"(d[25]), "+f"(d[26]), "+f"(d[27]), "+f"(d[28]), "+f"(d[29]), "+f"(d[30]), "+f"(d[31]), "+f"(d[32]), "+f"(d[33]), "+f"(d[34]), "+f"(d[35]), "+f"(d[36]), "+f"(d[37]), "+f"(d[38]), "+f"(d[39]), "+f"(d[40]), "+f"(d[41]), "+f"(d[42]), "+f"(d[43]), "+f"(d[44]), "+f"(d[45]), "+f"(d[46]), "+f"(d[47]), "+f"(d[48]), "+f"(d[49]), "+f"(d[50]), "+f"(d[51]), "+f"(d[52]), "+f"(d[53]), "+f"(d[54]), "+f"(d[55]), "+f"(d[56]), "+f"(d[57]), "+f"(d[58]), "+f"(d[59]), "+f"(d[60]), "+f"(d[61]), "+f"(d[62]), "+f"(d[63])
        : "r"(alo), "r"(ahi), "r"(blo), "r"(bhi), "r"(scale_d));
}

__device__ __forceinline__ void wgmma_ss_n192_tb1(float (&d)[96], uint32_t alo, uint32_t ahi, uint32_t blo, uint32_t bhi, int scale_d) {
    asm volatile("{\n.reg .pred p;\n.reg .b64 da, db;\nsetp.ne.b32 p, %100, 0;\nmov.b64 da, {%96, %97};\nmov.b64 db, {%98, %99};\n"
        "wgmma.mma_async.sync.aligned.m64n192k16.f32.bf16.bf16 {%0, %1, %2, %3, %4, %5, %6, %7, %8, %9, %10, %11, %12, %13, %14, %15, %16, %17, %18, %19, %20, %21, %22, %23, %24, %25, %26, %27, %28, %29, %30, %31, %32, %33, %34, %35, %36, %37, %38, %39, %40, %41, %42, %43, %44, %45, %46, %47, %48, %49, %50, %51, %52, %53, %54, %55, %56, %57, %58, %59, %60, %61, %62, %63, %64, %65, %66, %67, %68, %69, %70, %71, %72, %73, %74, %75, %76, %77, %78, %79, %80, %81, %82, %83, %84, %85, %86, %87, %88, %89, %90, %91, %92, %93, %94, %95}, da, db, p, 1, 1, 0, 1;\n}\n"
        : "+f"(d[0]), "+f"(d[1]), "+f"(d[2]), "+f"(d[3]), "+f"(d[4]), "+f"(d[5]), "+f"(d[6]), "+f"(d[7]), "+f"(d[8]), "+f"(d[9]), "+f"(d[10]), "+f"(d[11]), "+f"(d[12]), "+f"(d[13]), "+f"(d[14]), "+f"(d[15]), "+f"(d[16]), "+f"(d[17]), "+f"(d[18]), "+f"(d[19]), "+f"(d[20]), "+f"(d[21]), "+f"(d[22]), "+f"(d[23]), "+f"(d[24]), "+f"(d[25]), "+f"(d[26]), "+f"(d[27]), "+f"(d[28]), "+f"(d[29]), "+f"(d[30]), "+f"(d[31]), "+f"(d[32]), "+f"(d[33]), "+f"(d[34]), "+f"(d[35]), "+f"(d[36]), "+f"(d[37]), "+f"(d[38]), "+f"(d[39]), "+f"(d[40]), "+f"(d[41]), "+f"(d[42]), "+f"(d[43]), "+f"(d[44]), "+f"(d[45]), "+f"(d[46]), "+f"(d[47]), "+f"(d[48]), "+f"(d[49]), "+f"(d[50]), "+f"(d[51]), "+f"(d[52]), "+f"(d[53]), "+f"(d[54]), "+f"(d[55]), "+f"(d[56]), "+f"(d[57]), "+f"(d[58]), "+f"(d[59]), "+f"(d[60]), "+f"(d[61]), "+f"(d[62]), "+f"(d[63]), "+f"(d[64]), "+f"(d[65]), "+f"(d[66]), "+f"(d[67]), "+f"(d[68]), "+f"(d[69]), "+f"(d[70]), "+f"(d[71]), "+f"(d[72]), "+f"(d[73]), "+f"(d[74]), "+f"(d[75]), "+f"(d[76]), "+f"(d[77]), "+f"(d[78]), "+f"(d[79]), "+f"(d[80]), "+f"(d[81]), "+f"(d[82]), "+f"(d[83]), "+f"(d[84]), "+f"(d[85]), "+f"(d[86]), "+f"(d[87]), "+f"(d[88]), "+f"(d[89]), "+f"(d[90]), "+f"(d[91]), "+f"(d[92]), "+f"(d[93]), "+f"(d[94]), "+f"(d[95])
        : "r"(alo), "r"(ahi), "r"(blo), "r"(bhi), "r"(scale_d));
}

__device__ __forceinline__ void wgmma_ss_n224_tb1(float (&d)[112], uint32_t alo, uint32_t ahi, uint32_t blo, uint32_t bhi, int scale_d) {
    asm volatile("{\n.reg .pred p;\n.reg .b64 da, db;\nsetp.ne.b32 p, %116, 0;\nmov.b64 da, {%112, %113};\nmov.b64 db, {%114, %115};\n"
        "wgmma.mma_async.sync.aligned.m64n224k16.f32.bf16.bf16 {%0, %1, %2, %3, %4, %5, %6, %7, %8, %9, %10, %11, %12, %13, %14, %15, %16, %17, %18, %19, %20, %21, %22, %23, %24, %25, %26, %27, %28, %29, %30, %31, %32, %33, %34, %35, %36, %37, %38, %39, %40, %41, %42, %43, %44, %45, %46, %47, %48, %49, %50, %51, %52, %53, %54, %55, %56, %57, %58, %59, %60, %61, %62, %63, %64, %65, %66, %67, %68, %69, %70, %71, %72, %73, %74, %75, %76, %77, %78, %79, %80, %81, %82, %83, %84, %85, %86, %87, %88, %89, %90, %91, %92, %93, %94, %95, %96, %97, %98, %99, %100, %101, %102, %103, %104, %105, %106, %107, %108, %109, %110, %111}, da, db, p, 1, 1, 0, 1;\n}\n"
        : "+f"(d[0]), "+f"(d[1]), "+f"(d[2]), "+f"(d[3]), "+f"(d[4]), "+f"(d[5]), "+f"(d[6]), "+f"(d[7]), "+f"(d[8]), "+f"(d[9]), "+f"(d[10]), "+f"(d[11]), "+f"(d[12]), "+f"(d[13]), "+f"(d[14]), "+f"(d[15]), "+f"(d[16]), "+f"(d[17]), "+f"(d[18]), "+f"(d[19]), "+f"(d[20]), "+f"(d[21]), "+f"(d[22]), "+f"(d[23]), "+f"(d[24]), "+f"(d[25]), "+f"(d[26]), "+f"(d[27]), "+f"(d[28]), "+f"(d[29]), "+f"(d[30]), "+f"(d[31]), "+f"(d[32]), "+f"(d[33]), "+f"(d[34]), "+f"(d[35]), "+f"(d[36]), "+f"(d[37]), "+f"(d[38]), "+f"(d[39]), "+f"(d[40]), "+f"(d[41]), "+f"(d[42]), "+f"(d[43]), "+f"(d[44]), "+f"(d[45]), "+f"(d[46]), "+f"(d[47]), "+f"(d[48]), "+f"(d[49]), "+f"(d[50]), "+f"(d[51]), "+f"(d[52]), "+f"(d[53]), "+f"(d[54]), "+f"(d[55]), "+f"(d[56]), "+f"(d[57]), "+f"(d[58]), "+f"(d[59]), "+f"(d[60]), "+f"(d[61]), "+f"(d[62]), "+f"(d[63]), "+f"(d[64]), "+f"(d[65]), "+f"(d[66]), "+f"(d[67]), "+f"(d[68]), "+f"(d[69]), "+f"(d[70]), "+f"(d[71]), "+f"(d[72]), "+f"(d[73]), "+f"(d[74]), "+f"(d[75]), "+f"(d[76]), "+f"(d[77]), "+f"(d[78]), "+f"(d[79]), "+f"(d[80]), "+f"(d[81]), "+f"(d[82]), "+f"(d[83]), "+f"(d[84]), "+f"(d[85]), "+f"(d[86]), "+f"(d[87]), "+f"(d[88]), "+f"(d[89]), "+f"(d[90]), "+f"(d[91]), "+f"(d[92]), "+f"(d[93]), "+f"(d[94]), "+f"(d[95]), "+f"(d[96]), "+f"(d[97]), "+f"(d[98]), "+f"(d[99]), "+f"(d[100]), "+f"(d[101]), "+f"(d[102]), "+f"(d[103]), "+f"(d[104]), "+f"(d[105]), "+f"(d[106]), "+f"(d[107]), "+f"(d[108]), "+f"(d[109]), "+f"(d[110]), "+f"(d[111])
        : "r"(alo), "r"(ahi), "r"(blo), "r"(bhi), "r"(scale_d));
}

__device__ __forceinline__ void wgmma_ss_n256_tb1(float (&d)[128], uint32_t alo, uint32_t ahi, uint32_t blo, uint32_t bhi, int scale_d) {
    asm volatile("{\n.reg .pred p;\n.reg .b64 da, db;\nsetp.ne.b32 p, %132, 0;\nmov.b64 da, {%128, %129};\nmov.b64 db, {%130, %131};\n"
        "wgmma.mma_async.sync.aligned.m64n256k16.f32.bf16.bf16 {%0, %1, %2, %3, %4, %5, %6, %7, %8, %9, %10, %11, %12, %13, %14, %15, %16, %17, %18, %19, %20, %21, %22, %23, %24, %25, %26, %27, %28, %29, %30, %31, %32, %33, %34, %35, %36, %37, %38, %39, %40, %41, %42, %43, %44, %45, %46, %47, %48, %49, %50, %51, %52, %53, %54, %55, %56, %57, %58, %59, %60, %61, %62, %63, %64, %65, %66, %67, %68, %69, %70, %71, %72, %73, %74, %75, %76, %77, %78, %79, %80, %81, %82, %83, %84, %85, %86, %87, %88, %89, %90, %91, %92, %93, %94, %95, %96, %97, %98, %99, %100, %101, %102, %103, %104, %105, %106, %107, %108, %109, %110, %111, %112, %113, %114, %115, %116, %117, %118, %119, %120, %121, %122, %123, %124, %125, %126, %127}, da, db, p, 1, 1, 0, 1;\n}\n"
        : "+f"(d[0]), "+f"(d[1]), "+f"(d[2]), "+f"(d[3]), "+f"(d[4]), "+f"(d[5]), "+f"(d[6]), "+f"(d[7]), "+f"(d[8]), "+f"(d[9]), "+f"(d[10]), "+f"(d[11]), "+f"(d[12]), "+f"(d[13]), "+f"(d[14]), "+f"(d[15]), "+f"(d[16]), "+f"(d[17]), "+f"(d[18]), "+f"(d[19]), "+f"(d[20]), "+f"(d[21]), "+f"(d[22]), "+f"(d[23]), "+f"(d[24]), "+f"(d[25]), "+f"(d[26]), "+f"(d[27]), "+f"(d[28]), "+f"(d[29]), "+f"(d[30]), "+f"(d[31]), "+f"(d[32]), "+f"(d[33]), "+f"(d[34]), "+f"(d[35]), "+f"(d[36]), "+f"(d[37]), "+f"(d[38]), "+f"(d[39]), "+f"(d[40]), "+f"(d[41]), "+f"(d[42]), "+f"(d[43]), "+f"(d[44]), "+f"(d[45]), "+f"(d[46]), "+f"(d[47]), "+f"(d[48]), "+f"(d[49]), "+f"(d[50]), "+f"(d[51]), "+f"(d[52]), "+f"(d[53]), "+f"(d[54]), "+f"(d[55]), "+f"(d[56]), "+f"(d[57]), "+f"(d[58]), "+f"(d[59]), "+f"(d[60]), "+f"(d[61]), "+f"(d[62]), "+f"(d[63]), "+f"(d[64]), "+f"(d[65]), "+f"(d[66]), "+f"(d[67]), "+f"(d[68]), "+f"(d[69]), "+f"(d[70]), "+f"(d[71]), "+f"(d[72]), "+f"(d[73]), "+f"(d[74]), "+f"(d[75]), "+f"(d[76]), "+f"(d[77]), "+f"(d[78]), "+f"(d[79]), "+f"(d[80]), "+f"(d[81]), "+f"(d[82]), "+f"(d[83]), "+f"(d[84]), "+f"(d[85]), "+f"(d[86]), "+f"(d[87]), "+f"(d[88]), "+f"(d[89]), "+f"(d[90]), "+f"(d[91]), "+f"(d[92]), "+f"(d[93]), "+f"(d[94]), "+f"(d[95]), "+f"(d[96]), "+f"(d[97]), "+f"(d[98]), "+f"(d[99]), "+f"(d[100]), "+f"(d[101]), "+f"(d[102]), "+f"(d[103]), "+f"(d[104]), "+f"(d[105]), "+f"(d[106]), "+f"(d[107]), "+f"(d[108]), "+f"(d[109]), "+f"(d[110]), "+f"(d[111]), "+f"(d[112]), "+f"(d[113]), "+f"(d[114]), "+f"(d[115]), "+f"(d[116]), "+f"(d[117]), "+f"(d[118]), "+f"(d[119]), "+f"(d[120]), "+f"(d[121]), "+f"(d[122]), "+f"(d[123]), "+f"(d[124]), "+f"(d[125]), "+f"(d[126]), "+f"(d[127])
        : "r"(alo), "r"(ahi), "r"(blo), "r"(bhi), "r"(scale_d));
}

__device__ __forceinline__ void wgmma_ss_n64_tb0(float (&d)[32], uint32_t alo, uint32_t ahi, uint32_t blo, uint32_t bhi, int scale_d) {
    asm volatile("{\n.reg .pred p;\n.reg .b64 da, db;\nsetp.ne.b32 p, %36, 0;\nmov.b64 da, {%32, %33};\nmov.b64 db, {%34, %35};\n"
        "wgmma.mma_async.sync.aligned.m64n64k16.f32.bf16.bf16 {%0, %1, %2, %3, %4, %5, %6, %7, %8, %9, %10, %11, %12, %13, %14, %15, %16, %17, %18, %19, %20, %21, %22, %23, %24, %25, %26, %27, %28, %29, %30, %31}, da, db, p, 1, 1, 0, 0;\n}\n"
        : "+f"(d[0]), "+f"(d[1]), "+f"(d[2]), "+f"(d[3]), "+f"(d[4]), "+f"(d[5]), "+f"(d[6]), "+f"(d[7]), "+f"(d[8]), "+f"(d[9]), "+f"(d[10]), "+f"(d[11]), "+f"(d[12]), "+f"(d[13]), "+f"(d[14]), "+f"(d[15]), "+f"(d[16]), "+f"(d[17]), "+f"(d[18]), "+f"(d[19]), "+f"(d[20]), "+f"(d[21]), "+f"(d[22]), "+f"(d[23]), "+f"(d[24]), "+f"(d[25]), "+f"(d[26]), "+f"(d[27]), "+f"(d[28]), "+f"(d[29]), "+f"(d[30]), "+f"(d[31])
        : "r"(alo), "r"(ahi), "r"(blo), "r"(bhi), "r"(scale_d));
}

__device__ __forceinline__ void wgmma_rs_n128_tb0(float (&d)[64], uint32_t a0, uint32_t a1, uint32_t a2, uint32_t a3, uint32_t blo, uint32_t bhi, int scale_d) {
    asm volatile("{\n.reg .pred p;\n.reg .b64 db;\nsetp.ne.b32 p, %70, 0;\nmov.b64 db, {%68, %69};\n"
        "wgmma.mma_async.sync.aligned.m64n128k16.f32.bf16.bf16 {%0, %1, %2, %3, %4, %5, %6, %7, %8, %9, %10, %11, %12, %13, %14, %15, %16, %17, %18, %19, %20, %21, %22, %23, %24, %25, %26, %27, %28, %29, %30, %31, %32, %33, %34, %35, %36, %37, %38, %39, %40, %41, %42, %43, %44, %45, %46, %47, %48, %49, %50, %51, %52, %53, %54, %55, %56, %57, %58, %59, %60, %61, %62, %63}, {%64, %65, %66, %67}, db, p, 1, 1, 0;\n}\n"
        : "+f"(d[0]), "+f"(d[1]), "+f"(d[2]), "+f"(d[3]), "+f"(d[4]), "+f"(d[5]), "+f"(d[6]), "+f"(d[7]), "+f"(d[8]), "+f"(d[9]), "+f"(d[10]), "+f"(d[11]), "+f"(d[12]), "+f"(d[13]), "+f"(d[14]), "+f"(d[15]), "+f"(d[16]), "+f"(d[17]), "+f"(d[18]), "+f"(d[19]), "+f"(d[20]), "+f"(d[21]), "+f"(d[22]), "+f"(d[23]), "+f"(d[24]), "+f"(d[25]), "+f"(d[26]), "+f"(d[27]), "+f"(d[28]), "+f"(d[29]), "+f"(d[30]), "+f"(d[31]), "+f"(d[32]), "+f"(d[33]), "+f"(d[34]), "+f"(d[35]), "+f"(d[36]), "+f"(d[37]), "+f"(d[38]), "+f"(d[39]), "+f"(d[40]), "+f"(d[41]), "+f"(d[42]), "+f"(d[43]), "+f"(d[44]), "+f"(d[45]), "+f"(d[46]), "+f"(d[47]), "+f"(d[48]), "+f"(d[49]), "+f"(d[50]), "+f"(d[51]), "+f"(d[52]), "+f"(d[53]), "+f"(d[54]), "+f"(d[55]), "+f"(d[56]), "+f"(d[57]), "+f"(d[58]), "+f"(d[59]), "+f"(d[60]), "+f"(d[61]), "+f"(d[62]), "+f"(d[63])
        : "r"(a0), "r"(a1), "r"(a2), "r"(a3), "r"(blo), "r"(bhi), "r"(scale_d));
}

__device__ __forceinline__ void wgmma_rs_n64_tb0(float (&d)[32], uint32_t a0, uint32_t a1, uint32_t a2, uint32_t a3, uint32_t blo, uint32_t bhi, int scale_d) {
    asm volatile("{\n.reg .pred p;\n.reg .b64 db;\nsetp.ne.b32 p, %38, 0;\nmov.b64 db, {%36, %37};\n"
        "wgmma.mma_async.sync.aligned.m64n64k16.f32.bf16.bf16 {%0, %1, %2, %3, %4, %5, %6, %7, %8, %9, %10, %11, %12, %13, %14, %15, %16, %17, %18, %19, %20, %21, %22, %23, %24, %25, %26, %27, %28, %29, %30, %31}, {%32, %33, %34, %35}, db, p, 1, 1, 0;\n}\n"
        : "+f"(d[0]), "+f"(d[1]), "+f"(d[2]), "+f"(d[3]), "+f"(d[4]), "+f"(d[5]), "+f"(d[6]), "+f"(d[7]), "+f"(d[8]), "+f"(d[9]), "+f"(d[10]), "+f"(d[11]), "+f"(d[12]), "+f"(d[13]), "+f"(d[14]), "+f"(d[15]), "+f"(d[16]), "+f"(d[17]), "+f"(d[18]), "+f"(d[19]), "+f"(d[20]), "+f"(d[21]), "+f"(d[22]), "+f"(d[23]), "+f"(d[24]), "+f"(d[25]), "+f"(d[26]), "+f"(d[27]), "+f"(d[28]), "+f"(d[29]), "+f"(d[30]), "+f"(d[31])
        : "r"(a0), "r"(a1), "r"(a2), "r"(a3), "r"(blo), "r"(bhi), "r"(scale_d));
}

__device__ __forceinline__ void wgmma_rs_n32_tb1(float (&d)[16], uint32_t a0, uint32_t a1, uint32_t a2, uint32_t a3, uint32_t blo, uint32_t bhi, int scale_d) {
    asm volatile("{\n.reg .pred p;\n.reg .b64 db;\nsetp.ne.b32 p, %22, 0;\nmov.b64 db, {%20, %21};\n"
        "wgmma.mma_async.sync.aligned.m64n32k16.f32.bf16.bf16 {%0, %1, %2, %3, %4, %5, %6, %7, %8, %9, %10, %11, %12, %13, %14, %15}, {%16, %17, %18, %19}, db, p, 1, 1, 1;\n}\n"
        : "+f"(d[0]), "+f"(d[1]), "+f"(d[2]), "+f"(d[3]), "+f"(d[4]), "+f"(d[5]), "+f"(d[6]), "+f"(d[7]), "+f"(d[8]), "+f"(d[9]), "+f"(d[10]), "+f"(d[11]), "+f"(d[12]), "+f"(d[13]), "+f"(d[14]), "+f"(d[15])
        : "r"(a0), "r"(a1), "r"(a2), "r"(a3), "r"(blo), "r"(bhi), "r"(scale_d));
}

__device__ __forceinline__ void wgmma_rs_n40_tb1(float (&d)[20], uint32_t a0, uint32_t a1, uint32_t a2, uint32_t a3, uint32_t blo, uint32_t bhi, int scale_d) {
    asm volatile("{\n.reg .pred p;\n.reg .b64 db;\nsetp.ne.b32 p, %26, 0;\nmov.b64 db, {%24, %25};\n"
        "wgmma.mma_async.sync.aligned.m64n40k16.f32.bf16.bf16 {%0, %1, %2, %3, %4, %5, %6, %7, %8, %9, %10, %11, %12, %13, %14, %15, %16, %17, %18, %19}, {%20, %21, %22, %23}, db, p, 1, 1, 1;\n}\n"
        : "+f"(d[0]), "+f"(d[1]), "+f"(d[2]), "+f"(d[3]), "+f"(d[4]), "+f"(d[5]), "+f"(d[6]), "+f"(d[7]), "+f"(d[8]), "+f"(d[9]), "+f"(d[10]), "+f"(d[11]), "+f"(d[12]), "+f"(d[13]), "+f"(d[14]), "+f"(d[15]), "+f"(d[16]), "+f"(d[17]), "+f"(d[18]), "+f"(d[19])
        : "r"(a0), "r"(a1), "r"(a2), "r"(a3), "r"(blo), "r"(bhi), "r"(scale_d));
}

template <int BN>
__device__ __forceinline__ void wgmma_tile(float (&d)[BN / 2], uint32_t da, uint32_t db, int sd) {
    constexpr uint32_t HI = desc_hi(1024, 1);
    if constexpr (BN == 128) wgmma_ss_n128_tb1(d, da, HI, db, HI, sd);
    else if constexpr (BN == 192) wgmma_ss_n192_tb1(d, da, HI, db, HI, sd);
    else if constexpr (BN == 224) wgmma_ss_n224_tb1(d, da, HI, db, HI, sd);
    else wgmma_ss_n256_tb1(d, da, HI, db, HI, sd);
}

__global__ void __launch_bounds__(256) prep_kernel(const bf16* __restrict__ x, const bf16* __restrict__ gate_w,
                                                   const bf16* __restrict__ w1, const bf16* __restrict__ w3) {
    const int tid = threadIdx.x;
    TL_START(0)
    pdl_launch();
    if (blockIdx.x < 256) {
        const int row = blockIdx.x * 8 + (tid >> 5);
        const int lane = tid & 31;
        const uint4* xr = reinterpret_cast<const uint4*>(x + (size_t)row * DM);
        const uint4* gw = reinterpret_cast<const uint4*>(gate_w);
        float v[32];
        float gsum = 0.f, sum = 0.f;
#pragma unroll
        for (int i = 0; i < 4; i++) {
            uint4 a = xr[lane + 32 * i];
            uint4 b = gw[lane + 32 * i];
            const uint32_t aa[4] = {a.x, a.y, a.z, a.w};
            const uint32_t bb[4] = {b.x, b.y, b.z, b.w};
#pragma unroll
            for (int j = 0; j < 4; j++) {
                float x0 = __uint_as_float(aa[j] << 16), x1 = __uint_as_float(aa[j] & 0xFFFF0000u);
                float g0 = __uint_as_float(bb[j] << 16), g1 = __uint_as_float(bb[j] & 0xFFFF0000u);
                v[i * 8 + j * 2] = x0;
                v[i * 8 + j * 2 + 1] = x1;
                sum += x0 + x1;
                gsum += bf16_round(x0 * g0) + bf16_round(x1 * g1);
            }
        }
#pragma unroll
        for (int o = 16; o > 0; o >>= 1) {
            sum += __shfl_xor_sync(0xffffffffu, sum, o);
            gsum += __shfl_xor_sync(0xffffffffu, gsum, o);
        }
        const float mean = sum * (1.0f / DM);
        float m2 = 0.f;
#pragma unroll
        for (int i = 0; i < 32; i++) {
            float d = v[i] - mean;
            m2 += d * d;
        }
#pragma unroll
        for (int o = 16; o > 0; o >>= 1) m2 += __shfl_xor_sync(0xffffffffu, m2, o);
        if (lane == 0) {
            g_mean1[row] = mean;
            g_rstd1[row] = rsqrtf(m2 * (1.0f / DM) + 1e-5f);
            float logit = bf16_round(gsum);
            float g = bf16_round(1.0f / (1.0f + __expf(-logit)));
            g_gate[row] = g;
            g_omg[row] = bf16_round(1.0f - g);
        }
    } else {
        __shared__ float red[32][65];
        const int strip = blockIdx.x - 256;
        const bf16* w;
        float* out;
        int ld, col0;
        if (strip < 16) { w = w1; ld = DM; col0 = strip * 64; out = g_cs1; }
        else { w = w3; ld = FF; col0 = (strip - 16) * 64; out = g_cs3; }
        const int cg = tid & 7;
        const int rg = tid >> 3;
        float acc[8];
#pragma unroll
        for (int j = 0; j < 8; j++) acc[j] = 0.f;
#pragma unroll 8
        for (int r = 0; r < 32; r++) {
            uint4 a = *reinterpret_cast<const uint4*>(w + (size_t)(r * 32 + rg) * ld + col0 + cg * 8);
            const uint32_t aa[4] = {a.x, a.y, a.z, a.w};
#pragma unroll
            for (int j = 0; j < 4; j++) {
                acc[2 * j] += __uint_as_float(aa[j] << 16);
                acc[2 * j + 1] += __uint_as_float(aa[j] & 0xFFFF0000u);
            }
        }
#pragma unroll
        for (int j = 0; j < 8; j++) red[rg][cg * 8 + j] = acc[j];
        __syncthreads();
        if (tid < 64) {
            float s = 0.f;
#pragma unroll
            for (int r = 0; r < 32; r++) s += red[r][tid];
            out[col0 + tid] = s;
        }
    }
    TL_END(0)
}

template <int BN, int STAGES>
struct GemmSmem {
    static constexpr int A_BYTES = 128 * 64 * 2;
    static constexpr int B_BOXES = (BN + 63) / 64;
    static constexpr int B_BYTES = B_BOXES * 64 * 64 * 2;
    static constexpr int STAGE_BYTES = A_BYTES + B_BYTES;
    static constexpr int STG_OFF = STAGES * STAGE_BYTES;
    static constexpr int BAR_OFF = STAGES * STAGE_BYTES + 2 * 16384;
    static constexpr int TOTAL = BAR_OFF + 256 + 1024;
};

template <int MODE, int BN, int STAGES>
__global__ void __launch_bounds__(384, 1)
gemm_kernel(const __grid_constant__ CUtensorMap mA, const __grid_constant__ CUtensorMap mB0,
            const __grid_constant__ CUtensorMap mB1, const __grid_constant__ CUtensorMap mC0,
            const __grid_constant__ CUtensorMap mC1, const bf16* __restrict__ xin, int n_tiles_n, int kblocks) {
    using L = GemmSmem<BN, STAGES>;
    extern __shared__ uint8_t smem_raw[];
    const uint32_t sbase = (smem_u32(smem_raw) + 1023u) & ~1023u;
    const uint32_t bar_full = sbase + L::BAR_OFF;
    const uint32_t bar_empty = bar_full + 8 * STAGES;
    const int wg = threadIdx.x >> 7;
    const int npairs = 8 * n_tiles_n;
    const uint32_t crank = cluster_rank();
    const int cid = blockIdx.x >> 1, ncl = gridDim.x >> 1;
    TL_START(MODE)
    pdl_launch();

    if (threadIdx.x == 0) {
        for (int s = 0; s < STAGES; s++) {
            mbar_init(bar_full + 8 * s, 1);
            mbar_init(bar_empty + 8 * s, 4);
        }
        asm volatile("fence.mbarrier_init.release.cluster;" ::: "memory");
        prefetch_tmap(&mA);
        prefetch_tmap(&mB0);
        if (MODE == 1 || MODE == 5) prefetch_tmap(&mB1);
        prefetch_tmap(&mC0);
    }
    cluster_sync_all();

    if (wg == 0) {
        reg_dealloc<40>();
        if (threadIdx.x == 0) {
            if (MODE != 1) pdl_wait();
            int stage = 0;
            uint32_t phase = 1;
            for (int pr = cid; pr < npairs; pr += ncl) {
                const int m0 = ((pr & 7) * 2 + crank) * 128;
                const int n0 = (pr >> 3) * BN;
                for (int kb = 0; kb < kblocks; kb++) {
                    mbar_wait(bar_empty + 8 * stage, phase);
                    const uint32_t sa = sbase + stage * L::STAGE_BYTES;
                    const uint32_t sb = sa + L::A_BYTES;
                    const uint32_t fb = bar_full + 8 * stage;
                    mbar_expect_tx(fb, L::STAGE_BYTES);
                    int arow = m0;
                    if (MODE == 2) {
                        const int grp = kb >> 2;
                        arow += (grp == 0) ? -1 : (grp == 1) ? 1 : (grp == 2) ? -2 : 2;
                    }
                    tma_load_2d(sa, &mA, kb * 64, arow, fb);
                    const CUtensorMap* mb = &mB0;
                    int bc = n0, br = kb * 64;
                    if (MODE == 1 && n0 >= 3 * DM) { mb = &mB1; bc = n0 - 3 * DM; }
                    if (MODE == 5 && kb >= 16) { mb = &mB1; br = (kb - 16) * 64; }
#pragma unroll
                    for (int b = 0; b < L::B_BOXES / 2; b++) {
                        const int bb = crank * (L::B_BOXES / 2) + b;
                        tma_load_2d_mc(sb + bb * 8192, mb, bc + bb * 64, br, fb, (uint16_t)3);
                    }
                    if (++stage == STAGES) { stage = 0; phase ^= 1; }
                }
            }
        }
    } else {
        reg_alloc<232>();
        const int c = wg - 1;
        const int warp = (threadIdx.x >> 5) & 3;
        const int lane = threadIdx.x & 31;
        const int tid_wg = threadIdx.x & 127;
        const uint32_t stg = sbase + L::STG_OFF + c * 16384;
        int stage = 0;
        uint32_t phase = 0;
        float acc[BN / 2];
        bool first = true;
        for (int pr = cid; pr < npairs; pr += ncl) {
            const int m0 = ((pr & 7) * 2 + crank) * 128;
            const int n0 = (pr >> 3) * BN;
            int prev_stage = 0;
            for (int kb = 0; kb < kblocks; kb++) {
                mbar_wait(bar_full + 8 * stage, phase);
                const uint32_t sa = sbase + stage * L::STAGE_BYTES + c * 8192;
                const uint32_t sb = sbase + stage * L::STAGE_BYTES + L::A_BYTES;
                const uint32_t da = desc_lo(sa, 16);
                const uint32_t db = desc_lo(sb, 8192);
                wgmma_fence();
#pragma unroll
                for (int k = 0; k < 4; k++) wgmma_tile<BN>(acc, da + k * 2, db + k * 128, (kb | k) != 0);
                wgmma_commit();
                if (kb > 0) {
                    wgmma_wait<1>();
                    if (tid_wg < 2) mbar_arrive_cluster(bar_empty + 8 * prev_stage, tid_wg);
                }
                prev_stage = stage;
                if (++stage == STAGES) { stage = 0; phase ^= 1; }
            }
            wgmma_wait<0>();
            if (tid_wg < 2) mbar_arrive_cluster(bar_empty + 8 * prev_stage, tid_wg);
            if (first) { pdl_wait(); first = false; }

            const int r0 = m0 + c * 64 + warp * 16 + (lane >> 2);
            const int r1 = r0 + 8;
            const int cq = (lane & 3) * 2;
            const CUtensorMap* mc = &mC0;
            int out_c0 = n0;
            if (MODE == 1) {
                if (n0 >= 3 * DM) {
                    mc = &mC1;
                    out_c0 = n0 - 3 * DM;
                    const float mu0 = g_mean1[r0], mu1 = g_mean1[r1];
                    const float rs0 = g_rstd1[r0], rs1 = g_rstd1[r1];
#pragma unroll
                    for (int j = 0; j < BN / 8; j++) {
                        const float2 cs = *reinterpret_cast<const float2*>(&g_cs1[out_c0 + 8 * j + cq]);
                        acc[4 * j + 0] = gelu_tanh(rs0 * fmaf(-mu0, cs.x, acc[4 * j + 0]));
                        acc[4 * j + 1] = gelu_tanh(rs0 * fmaf(-mu0, cs.y, acc[4 * j + 1]));
                        acc[4 * j + 2] = gelu_tanh(rs1 * fmaf(-mu1, cs.x, acc[4 * j + 2]));
                        acc[4 * j + 3] = gelu_tanh(rs1 * fmaf(-mu1, cs.y, acc[4 * j + 3]));
                    }
                }
            } else if (MODE == 2) {
                float s0 = 0.f, s1 = 0.f;
#pragma unroll
                for (int j = 0; j < BN / 8; j++) {
                    const uint32_t xa = *reinterpret_cast<const uint32_t*>(xin + (size_t)r0 * DM + n0 + 8 * j + cq);
                    const uint32_t xb = *reinterpret_cast<const uint32_t*>(xin + (size_t)r1 * DM + n0 + 8 * j + cq);
                    acc[4 * j + 0] = bf16_round(bf16_round(acc[4 * j + 0]) + __uint_as_float(xa << 16));
                    acc[4 * j + 1] = bf16_round(bf16_round(acc[4 * j + 1]) + __uint_as_float(xa & 0xFFFF0000u));
                    acc[4 * j + 2] = bf16_round(bf16_round(acc[4 * j + 2]) + __uint_as_float(xb << 16));
                    acc[4 * j + 3] = bf16_round(bf16_round(acc[4 * j + 3]) + __uint_as_float(xb & 0xFFFF0000u));
                    s0 += acc[4 * j + 0] + acc[4 * j + 1];
                    s1 += acc[4 * j + 2] + acc[4 * j + 3];
                }
                s0 += __shfl_xor_sync(0xffffffffu, s0, 1);
                s0 += __shfl_xor_sync(0xffffffffu, s0, 2);
                s1 += __shfl_xor_sync(0xffffffffu, s1, 1);
                s1 += __shfl_xor_sync(0xffffffffu, s1, 2);
                const float mu0 = s0 * (1.0f / BN), mu1 = s1 * (1.0f / BN);
                float q0 = 0.f, q1 = 0.f;
#pragma unroll
                for (int j = 0; j < BN / 8; j++) {
                    float d;
                    d = acc[4 * j + 0] - mu0; q0 += d * d;
                    d = acc[4 * j + 1] - mu0; q0 += d * d;
                    d = acc[4 * j + 2] - mu1; q1 += d * d;
                    d = acc[4 * j + 3] - mu1; q1 += d * d;
                }
                q0 += __shfl_xor_sync(0xffffffffu, q0, 1);
                q0 += __shfl_xor_sync(0xffffffffu, q0, 2);
                q1 += __shfl_xor_sync(0xffffffffu, q1, 1);
                q1 += __shfl_xor_sync(0xffffffffu, q1, 2);
                if ((lane & 3) == 0) {
                    static_assert(MODE != 2 || BN == 128, "stats layout assumes BN=128");
                    g_stat2[r0 * 8 + (n0 >> 7)] = make_float2(s0, q0);
                    g_stat2[r1 * 8 + (n0 >> 7)] = make_float2(s1, q1);
                }
            } else if (MODE == 3) {
                out_c0 = n0 + DM;
                float mu[2], rs[2];
#pragma unroll
                for (int h = 0; h < 2; h++) {
                    const float4* sp = reinterpret_cast<const float4*>(&g_stat2[(h ? r1 : r0) * 8]);
                    float4 p[4];
                    float s = 0.f;
#pragma unroll
                    for (int i = 0; i < 4; i++) { p[i] = sp[i]; s += p[i].x + p[i].z; }
                    const float mean = s * (1.0f / DM);
                    float m2 = 0.f;
#pragma unroll
                    for (int i = 0; i < 4; i++) {
                        float d0 = p[i].x * (1.0f / 128) - mean, d1 = p[i].z * (1.0f / 128) - mean;
                        m2 += p[i].y + p[i].w + 128.0f * (d0 * d0 + d1 * d1);
                    }
                    mu[h] = mean;
                    rs[h] = rsqrtf(m2 * (1.0f / DM) + 1e-5f);
                }
                const float og0 = g_omg[r0], og1 = g_omg[r1];
#pragma unroll
                for (int j = 0; j < BN / 8; j++) {
                    const float2 cs = *reinterpret_cast<const float2*>(&g_cs3[n0 + 8 * j + cq]);
                    acc[4 * j + 0] = og0 * gelu_tanh(rs[0] * fmaf(-mu[0], cs.x, acc[4 * j + 0]));
                    acc[4 * j + 1] = og0 * gelu_tanh(rs[0] * fmaf(-mu[0], cs.y, acc[4 * j + 1]));
                    acc[4 * j + 2] = og1 * gelu_tanh(rs[1] * fmaf(-mu[1], cs.x, acc[4 * j + 2]));
                    acc[4 * j + 3] = og1 * gelu_tanh(rs[1] * fmaf(-mu[1], cs.y, acc[4 * j + 3]));
                }
            } else {
                const float og0 = g_omg[r0], og1 = g_omg[r1];
#pragma unroll
                for (int j = 0; j < BN / 8; j++) {
                    const uint32_t xa = *reinterpret_cast<const uint32_t*>(xin + (size_t)r0 * DM + n0 + 8 * j + cq);
                    const uint32_t xb = *reinterpret_cast<const uint32_t*>(xin + (size_t)r1 * DM + n0 + 8 * j + cq);
                    acc[4 * j + 0] = fmaf(og0, __uint_as_float(xa << 16), acc[4 * j + 0]);
                    acc[4 * j + 1] = fmaf(og0, __uint_as_float(xa & 0xFFFF0000u), acc[4 * j + 1]);
                    acc[4 * j + 2] = fmaf(og1, __uint_as_float(xb << 16), acc[4 * j + 2]);
                    acc[4 * j + 3] = fmaf(og1, __uint_as_float(xb & 0xFFFF0000u), acc[4 * j + 3]);
                }
            }
            const int srow = warp * 16 + (lane & 7) + ((lane >> 3) & 1) * 8;
#pragma unroll
            for (int rnd = 0; rnd < (BN + 127) / 128; rnd++) {
                if (tid_wg == 0) bulk_wait_read0();
                named_bar_sync(1 + c, 128);
#pragma unroll
                for (int jj = 0; jj < 8; jj++) {
                    const int j = rnd * 16 + jj * 2;
                    if (j * 8 < BN) {
                        const int jb = jj * 2 + (lane >> 4);
                        uint32_t addr = stg + (jb >> 3) * 8192 + srow * 128 + (((jb & 7) ^ (srow & 7)) << 4);
                        if (rnd * 128 + 128 > BN && jj >= 4)
                            addr = stg + 8192 + srow * 64 + (((jb & 3) ^ ((srow >> 1) & 3)) << 4);
                        stmatrix_x4(addr, pack_bf16(acc[4 * j + 0], acc[4 * j + 1]), pack_bf16(acc[4 * j + 2], acc[4 * j + 3]),
                                    pack_bf16(acc[4 * j + 4], acc[4 * j + 5]), pack_bf16(acc[4 * j + 6], acc[4 * j + 7]));
                    }
                }
                fence_proxy_async();
                named_bar_sync(1 + c, 128);
                if (tid_wg == 0) {
                    tma_store_2d(mc, stg, out_c0 + rnd * 128, m0 + c * 64);
                    if (rnd * 128 + 64 < BN)
                        tma_store_2d((rnd * 128 + 128 > BN) ? &mC1 : mc, stg + 8192, out_c0 + rnd * 128 + 64, m0 + c * 64);
                    bulk_commit();
                }
            }
        }
        if (tid_wg == 0) bulk_wait0();
        TL_END(MODE)
    }
    cluster_sync_all();
}

#define ATT_SPLIT 4
constexpr int ATT_NTILES = NH * 16;
#define ATT_GRID_N 264
constexpr int ATT_GRID = ATT_GRID_N;
constexpr int ATT_THREADS = 256;
constexpr int ATT_STAGES = 4;
constexpr int ATT_DIST = 2;
constexpr int ATT_Q_OFF = ATT_STAGES * 16384;
constexpr int ATT_ONES_OFF = ATT_Q_OFF + 16384;
constexpr int ATT_BAR_OFF = ATT_ONES_OFF + 4096;
#define ATT_SMEM_BYTES (ATT_BAR_OFF + 256 + 1024)
constexpr int ATT_SMEM = ATT_SMEM_BYTES;

struct AttState {
    float o[20];
    float m0, m1;
    float mp0, mp1;
};

__device__ __forceinline__ void row_max(const float (&s)[32], float& m0, float& m1) {
    float mx0 = fmaxf(s[0], s[1]), mx1 = fmaxf(s[2], s[3]);
#pragma unroll
    for (int i = 1; i < 8; i++) {
        mx0 = fmaxf(mx0, fmaxf(s[4 * i], s[4 * i + 1]));
        mx1 = fmaxf(mx1, fmaxf(s[4 * i + 2], s[4 * i + 3]));
    }
    mx0 = fmaxf(mx0, __shfl_xor_sync(0xffffffffu, mx0, 1));
    mx1 = fmaxf(mx1, __shfl_xor_sync(0xffffffffu, mx1, 1));
    mx0 = fmaxf(mx0, __shfl_xor_sync(0xffffffffu, mx0, 2));
    mx1 = fmaxf(mx1, __shfl_xor_sync(0xffffffffu, mx1, 2));
    m0 = fmaxf(m0, mx0);
    m1 = fmaxf(m1, mx1);
}

__device__ __forceinline__ void attn_step(float (&sc)[32], float (&sn)[32], uint32_t (&p)[16], uint32_t dq,
                                          AttState& st, uint32_t dk_next, uint32_t dv_prev, uint32_t release_bar, int one) {
    const float cs = 0.17677669529663687f * 1.4426950408889634f;
    constexpr uint32_t HI = desc_hi(512, 2);
    wgmma_fence();
    wgmma_ss_n64_tb0(sn, dq, HI, dk_next, HI, 0);
    wgmma_ss_n64_tb0(sn, dq + 2, HI, dk_next + 2, HI, 1);
#pragma unroll
    for (int t = 0; t < 4; t++)
        wgmma_rs_n40_tb1(st.o, p[4 * t], p[4 * t + 1], p[4 * t + 2], p[4 * t + 3], dv_prev + t * 64, HI, 1);
    wgmma_commit();
    const float mc0 = st.m0, mc1 = st.m1;
    const float b0 = mc0 * cs, b1 = mc1 * cs;
    if (one) {
#pragma unroll
        for (int i = 0; i < ATT_SPLIT; i++) {
            sc[4 * i + 0] = ex2(fmaf(sc[4 * i + 0], cs, -b0));
            sc[4 * i + 1] = ex2(fmaf(sc[4 * i + 1], cs, -b0));
            sc[4 * i + 2] = ex2(fmaf(sc[4 * i + 2], cs, -b1));
            sc[4 * i + 3] = ex2(fmaf(sc[4 * i + 3], cs, -b1));
        }
    }
    wgmma_wait<0>();
    if (release_bar != 0 && (threadIdx.x & 127) == 0) mbar_arrive(release_bar);
    if (one) {
        row_max(sn, st.m0, st.m1);
#pragma unroll
        for (int i = ATT_SPLIT; i < 8; i++) {
            sc[4 * i + 0] = ex2(fmaf(sc[4 * i + 0], cs, -b0));
            sc[4 * i + 1] = ex2(fmaf(sc[4 * i + 1], cs, -b0));
            sc[4 * i + 2] = ex2(fmaf(sc[4 * i + 2], cs, -b1));
            sc[4 * i + 3] = ex2(fmaf(sc[4 * i + 3], cs, -b1));
        }
        const float a0 = ex2((st.mp0 - mc0) * cs), a1 = ex2((st.mp1 - mc1) * cs);
#pragma unroll
        for (int i = 0; i < 5; i++) {
            st.o[4 * i + 0] *= a0; st.o[4 * i + 1] *= a0;
            st.o[4 * i + 2] *= a1; st.o[4 * i + 3] *= a1;
        }
        st.mp0 = mc0; st.mp1 = mc1;
#pragma unroll
        for (int i = 0; i < 8; i++) {
            p[2 * i] = pack_bf16(sc[4 * i + 0], sc[4 * i + 1]);
            p[2 * i + 1] = pack_bf16(sc[4 * i + 2], sc[4 * i + 3]);
        }
    }
}

__global__ void __launch_bounds__(256, 2)
attn_kernel(const __grid_constant__ CUtensorMap mKV, int one) {
    extern __shared__ uint8_t smem_raw[];
    const uint32_t sbase = (smem_u32(smem_raw) + 1023u) & ~1023u;
    const uint32_t bar_kfull = sbase + ATT_BAR_OFF;
    const uint32_t bar_vfull = bar_kfull + 8 * ATT_STAGES;
    const uint32_t bar_empty = bar_vfull + 8 * ATT_STAGES;
    const uint32_t bar_q = bar_empty + 8 * ATT_STAGES;
    const int warp_id = threadIdx.x >> 5;
    const int lane = threadIdx.x & 31;
    constexpr int NBLK = S_LEN / 128;
    TL_START(6)
    pdl_launch();
    const int my_tiles = (ATT_NTILES - (int)blockIdx.x + (int)gridDim.x - 1) / (int)gridDim.x;
    const int total_blocks = my_tiles * NBLK;

    auto issue_kv = [&](int g) {
        const int tile = blockIdx.x + (g >> 4) * gridDim.x;
        const int hd = tile >> 4;
        const int sn = g % ATT_STAGES;
        if (g >= ATT_STAGES) mbar_wait(bar_empty + 8 * sn, ((g / ATT_STAGES) - 1) & 1);
        const uint32_t skn = sbase + sn * 16384;
        mbar_expect_tx(bar_kfull + 8 * sn, 8192);
        tma_load_2d(skn, &mKV, DM + hd * DH, (g & 15) * 128, bar_kfull + 8 * sn);
        mbar_expect_tx(bar_vfull + 8 * sn, 8192);
        tma_load_2d(skn + 8192, &mKV, 2 * DM + hd * DH, (g & 15) * 128, bar_vfull + 8 * sn);
    };
    auto issue_q = [&](int it) {
        const int tile = blockIdx.x + it * gridDim.x;
        mbar_expect_tx(bar_q + 8 * (it & 1), 8192);
        tma_load_2d(sbase + ATT_Q_OFF + (it & 1) * 8192, &mKV, (tile >> 4) * DH, (tile & 15) * 128, bar_q + 8 * (it & 1));
    };

    if (threadIdx.x == 0) {
        for (int s = 0; s < ATT_STAGES; s++) {
            mbar_init(bar_kfull + 8 * s, 1);
            mbar_init(bar_vfull + 8 * s, 1);
            mbar_init(bar_empty + 8 * s, 2);
        }
        mbar_init(bar_q, 1);
        mbar_init(bar_q + 8, 1);
        asm volatile("fence.mbarrier_init.release.cluster;" ::: "memory");
        prefetch_tmap(&mKV);
        pdl_wait();
        issue_q(0);
#pragma unroll
        for (int j = 0; j < ATT_DIST; j++) issue_kv(j);
    }
    asm volatile("st.shared.v4.b32 [%0], {%1, %1, %1, %1};" ::"r"(sbase + ATT_ONES_OFF + threadIdx.x * 16), "r"(0x3F803F80u) : "memory");
    fence_proxy_async();
    __syncthreads();
    pdl_wait();

    const int cq = (lane & 3) * 2;
    constexpr uint32_t HI = desc_hi(512, 2);
    const uint32_t dk0 = desc_lo(sbase, 16);
    const uint32_t dv0 = desc_lo(sbase + 8192, ATT_ONES_OFF - 8192);
    int stage = 0;
    uint32_t phase = 0;
#pragma unroll 1
    for (int it = 0; it < my_tiles; it++) {
        const int tile = blockIdx.x + it * gridDim.x;
        const int head = tile >> 4;
        const int row0 = (tile & 15) * 128 + warp_id * 16 + (lane >> 2);
        const uint32_t dq = desc_lo(sbase + ATT_Q_OFF + (it & 1) * 8192 + (threadIdx.x >> 7) * 4096, 16);
        if (threadIdx.x == 0 && it + 1 < my_tiles) issue_q(it + 1);
        AttState st;
#pragma unroll
        for (int i = 0; i < 20; i++) st.o[i] = 0.f;
        st.m0 = -INFINITY; st.m1 = -INFINITY;
        float s0[32], s1[32];
        uint32_t p[16];
#pragma unroll
        for (int i = 0; i < 16; i++) p[i] = 0u;
        mbar_wait(bar_q + 8 * (it & 1), (it >> 1) & 1);
        mbar_wait(bar_kfull + 8 * stage, phase);
        wgmma_fence();
        wgmma_ss_n64_tb0(s0, dq, HI, dk0 + stage * 1024, HI, 0);
        wgmma_ss_n64_tb0(s0, dq + 2, HI, dk0 + stage * 1024 + 2, HI, 1);
        wgmma_commit();
        mbar_wait(bar_vfull + 8 * stage, phase);
        wgmma_wait<0>();
        row_max(s0, st.m0, st.m1);
        st.mp0 = st.m0; st.mp1 = st.m1;
        uint32_t dv_prev = dv0 + stage * 1024 - ((uint32_t)(stage * 1024) << 16);
        int pstage = stage;
#pragma unroll 1
        for (int j = 0; j < NBLK; j++) {
            if (threadIdx.x == 0 && it * NBLK + j + ATT_DIST < total_blocks) issue_kv(it * NBLK + j + ATT_DIST);
            __syncwarp();
            const uint32_t dk = dk0 + stage * 1024;
            const uint32_t dv = dv0 + stage * 1024 - ((uint32_t)(stage * 1024) << 16);
            attn_step(s0, s1, p, dq, st, dk + 256, dv_prev, j > 0 ? bar_empty + 8 * pstage : 0u, one);
            int nstage = stage + 1;
            uint32_t nphase = phase;
            if (nstage == ATT_STAGES) { nstage = 0; nphase ^= 1; }
            uint32_t dkn = dk;
            if (j + 1 < NBLK) {
                mbar_wait(bar_kfull + 8 * nstage, nphase);
                dkn = dk0 + nstage * 1024;
            }
            mbar_wait(bar_vfull + 8 * stage, phase);
            attn_step(s1, s0, p, dq, st, dkn, dv, 0u, one);
            dv_prev = dv + 256 - (256u << 16);
            pstage = stage;
            stage = nstage;
            phase = nphase;
        }
        wgmma_fence();
#pragma unroll
        for (int t = 0; t < 4; t++)
            wgmma_rs_n40_tb1(st.o, p[4 * t], p[4 * t + 1], p[4 * t + 2], p[4 * t + 3], dv_prev + t * 64, HI, 1);
        wgmma_commit();
        wgmma_wait<0>();
        if ((threadIdx.x & 127) == 0) mbar_arrive(bar_empty + 8 * pstage);
        const float f0 = g_gate[row0] / st.o[16], f1 = g_gate[row0 + 8] / st.o[18];
        bf16* op0 = g_a5 + (size_t)row0 * A5W + head * DH + cq;
        bf16* op1 = op0 + 8 * A5W;
#pragma unroll
        for (int i = 0; i < 4; i++) {
            *reinterpret_cast<uint32_t*>(op0 + 8 * i) = pack_bf16(st.o[4 * i] * f0, st.o[4 * i + 1] * f0);
            *reinterpret_cast<uint32_t*>(op1 + 8 * i) = pack_bf16(st.o[4 * i + 2] * f1, st.o[4 * i + 3] * f1);
        }
        __syncthreads();
    }
    TL_END(6)
}

typedef CUresult (*EncodeFn)(CUtensorMap*, CUtensorMapDataType, cuuint32_t, void*, const cuuint64_t*, const cuuint64_t*,
                             const cuuint32_t*, const cuuint32_t*, CUtensorMapInterleave, CUtensorMapSwizzle,
                             CUtensorMapL2promotion, CUtensorMapFloatOOBfill);

static CUtensorMap make_map(EncodeFn fn, const void* ptr, int rows, int cols, int box_cols, int box_rows,
                            CUtensorMapSwizzle swz) {
    CUtensorMap m;
    cuuint64_t dims[2] = {(cuuint64_t)cols, (cuuint64_t)rows};
    cuuint64_t strides[1] = {(cuuint64_t)cols * 2};
    cuuint32_t box[2] = {(cuuint32_t)box_cols, (cuuint32_t)box_rows};
    cuuint32_t es[2] = {1, 1};
    fn(&m, CU_TENSOR_MAP_DATA_TYPE_BFLOAT16, 2, const_cast<void*>(ptr), dims, strides, box, es,
       CU_TENSOR_MAP_INTERLEAVE_NONE, swz, CU_TENSOR_MAP_L2_PROMOTION_L2_256B, CU_TENSOR_MAP_FLOAT_OOB_FILL_NONE);
    return m;
}

template <typename... KArgs, typename... Args>
static void launch_ex(void (*kern)(KArgs...), int grid, int block, int smem, cudaStream_t st, int cluster, Args... args) {
    cudaLaunchConfig_t cfg = {};
    cfg.gridDim = dim3(grid);
    cfg.blockDim = dim3(block);
    cfg.dynamicSmemBytes = smem;
    cfg.stream = st;
    cudaLaunchAttribute at[2];
    at[0].id = cudaLaunchAttributeProgrammaticStreamSerialization;
    at[0].val.programmaticStreamSerializationAllowed = 1;
    at[1].id = cudaLaunchAttributeClusterDimension;
    at[1].val.clusterDim.x = cluster;
    at[1].val.clusterDim.y = 1;
    at[1].val.clusterDim.z = 1;
    cfg.attrs = at;
    cfg.numAttrs = cluster > 1 ? 2 : 1;
    cudaLaunchKernelEx(&cfg, kern, KArgs(args)...);
}

extern "C" void kernel_launch(void* const* d_in, const int* in_sizes, int n_in, void* d_out, int out_size) {
    const bf16* x = (const bf16*)d_in[0];
    const bf16* wqkv = (const bf16*)d_in[1];
    const bf16* wo = (const bf16*)d_in[2];
    const bf16* w1 = (const bf16*)d_in[4];
    const bf16* w2 = (const bf16*)d_in[5];
    const bf16* w3 = (const bf16*)d_in[6];
    const bf16* w4 = (const bf16*)d_in[7];
    const bf16* gate_w = (const bf16*)d_in[8];

    static EncodeFn enc = nullptr;
    static void *p_qkv, *p_h, *p_x1, *p_a5;
    using G1 = GemmSmem<256, 4>;
    using G2 = GemmSmem<128, 5>;
    using G3 = GemmSmem<224, 4>;
    if (!enc) {
        void* fn = nullptr;
        cudaDriverEntryPointQueryResult qres;
        cudaGetDriverEntryPoint("cuTensorMapEncodeTiled", &fn, cudaEnableDefault, &qres);
        enc = (EncodeFn)fn;
        cudaGetSymbolAddress(&p_qkv, g_qkv);
        cudaGetSymbolAddress(&p_h, g_h);
        cudaGetSymbolAddress(&p_x1, g_x1);
        cudaGetSymbolAddress(&p_a5, g_a5);
        cudaFuncSetAttribute(gemm_kernel<1, 256, 4>, cudaFuncAttributeMaxDynamicSharedMemorySize, G1::TOTAL);
        cudaFuncSetAttribute(gemm_kernel<2, 128, 5>, cudaFuncAttributeMaxDynamicSharedMemorySize, G2::TOTAL);
        cudaFuncSetAttribute(gemm_kernel<3, 224, 4>, cudaFuncAttributeMaxDynamicSharedMemorySize, G3::TOTAL);
        cudaFuncSetAttribute(gemm_kernel<5, 128, 5>, cudaFuncAttributeMaxDynamicSharedMemorySize, G2::TOTAL);
        cudaFuncSetAttribute(attn_kernel, cudaFuncAttributeMaxDynamicSharedMemorySize, ATT_SMEM);
    }
    const CUtensorMapSwizzle SW128 = CU_TENSOR_MAP_SWIZZLE_128B, SW64 = CU_TENSOR_MAP_SWIZZLE_64B;
    CUtensorMap mX = make_map(enc, x, S_LEN, DM, 64, 128, SW128);
    CUtensorMap mWqkv = make_map(enc, wqkv, DM, 3 * DM, 64, 64, SW128);
    CUtensorMap mW1 = make_map(enc, w1, DM, DM, 64, 64, SW128);
    CUtensorMap mW2 = make_map(enc, w2, DM, DM, 64, 64, SW128);
    CUtensorMap mW3 = make_map(enc, w3, DM, FF, 64, 64, SW128);
    CUtensorMap mW4 = make_map(enc, w4, FF, DM, 64, 64, SW128);
    CUtensorMap mWo = make_map(enc, wo, DM, DM, 64, 64, SW128);
    CUtensorMap mQKVst = make_map(enc, p_qkv, S_LEN, 3 * DM, 64, 64, SW128);
    CUtensorMap mKV = make_map(enc, p_qkv, S_LEN, 3 * DM, 32, 128, SW64);
    CUtensorMap mHst = make_map(enc, p_h, S_LEN, DM, 64, 64, SW128);
    CUtensorMap mHld = make_map(enc, p_h, S_LEN, DM, 64, 128, SW128);
    CUtensorMap mX1st = make_map(enc, p_x1, S_LEN, DM, 64, 64, SW128);
    CUtensorMap mX1ld = make_map(enc, p_x1, S_LEN, DM, 64, 128, SW128);
    CUtensorMap mA5st = make_map(enc, p_a5, S_LEN, A5W, 64, 64, SW128);
    CUtensorMap mA5st32 = make_map(enc, p_a5, S_LEN, A5W, 32, 64, SW64);
    CUtensorMap mA5ld = make_map(enc, p_a5, S_LEN, A5W, 64, 128, SW128);
    CUtensorMap mOut = make_map(enc, d_out, S_LEN, DM, 64, 64, SW128);

    cudaStream_t st = cudaStreamPerThread;
    prep_kernel<<<256 + 72, 256, 0, st>>>(x, gate_w, w1, w3);
    launch_ex(gemm_kernel<1, 256, 4>, 132, 384, G1::TOTAL, st, 2, mX, mWqkv, mW1, mQKVst, mHst, x, 16, 16);
    launch_ex(attn_kernel, ATT_GRID, ATT_THREADS, ATT_SMEM, st, 1, mKV, 1);
    launch_ex(gemm_kernel<2, 128, 5>, 128, 384, G2::TOTAL, st, 2, mHld, mW2, mW2, mX1st, mX1st, x, 8, 16);
    launch_ex(gemm_kernel<3, 224, 4>, 132, 384, G3::TOTAL, st, 2, mX1ld, mW3, mW3, mA5st, mA5st32, x, 16, 16);
    launch_ex(gemm_kernel<5, 128, 5>, 128, 384, G2::TOTAL, st, 2, mA5ld, mWo, mW4, mOut, mOut, (const bf16*)p_x1, 8, 72);
}
```

```cpp
#include <cuda_runtime.h>
#include <cuda_bf16.h>
#include <cuda.h>
#include <stdint.h>

typedef __nv_bfloat16 bf16;

constexpr int S_LEN = 2048;
constexpr int DM = 1024;
constexpr int FF = 3584;
constexpr int NH = 32;
constexpr int DH = 32;
constexpr int A5W = DM + FF;

__device__ __align__(1024) bf16 g_qkv[S_LEN * 3 * DM];
__device__ __align__(1024) bf16 g_h[S_LEN * DM];
__device__ __align__(1024) bf16 g_x1[S_LEN * DM];
__device__ __align__(1024) bf16 g_a5[S_LEN * A5W];
__device__ __align__(16) float g_mean1[S_LEN];
__device__ __align__(16) float g_rstd1[S_LEN];
__device__ __align__(16) float g_gate[S_LEN];
__device__ __align__(16) float g_omg[S_LEN];
__device__ __align__(16) float g_cs1[DM];
__device__ __align__(16) float g_cs3[FF];
__device__ __align__(16) float2 g_stat2[S_LEN * 8];

#define TL_START(k)
#define TL_END(k)

__device__ __forceinline__ uint32_t smem_u32(const void* p) { return (uint32_t)__cvta_generic_to_shared(p); }

__device__ __forceinline__ void mbar_init(uint32_t bar, uint32_t count) {
    asm volatile("mbarrier.init.shared::cta.b64 [%0], %1;" ::"r"(bar), "r"(count));
}
__device__ __forceinline__ void mbar_expect_tx(uint32_t bar, uint32_t bytes) {
    asm volatile("mbarrier.arrive.expect_tx.shared::cta.b64 _, [%0], %1;" ::"r"(bar), "r"(bytes) : "memory");
}
__device__ __forceinline__ void mbar_arrive(uint32_t bar) {
    asm volatile("mbarrier.arrive.shared::cta.b64 _, [%0];" ::"r"(bar) : "memory");
}
__device__ __forceinline__ bool mbar_try_wait(uint32_t bar, uint32_t parity) {
    uint32_t ok;
    asm volatile(
        "{\n.reg .pred p;\n"
        "mbarrier.try_wait.parity.shared::cta.b64 p, [%1], %2;\n"
        "selp.u32 %0, 1, 0, p;\n}\n"
        : "=r"(ok)
        : "r"(bar), "r"(parity)
        : "memory");
    return ok != 0;
}
__device__ __forceinline__ void mbar_wait(uint32_t bar, uint32_t parity) {
    uint32_t spins = 0;
    while (!mbar_try_wait(bar, parity)) {
        if (++spins > (1u << 24)) __trap();
    }
}
__device__ __forceinline__ void tma_load_2d(uint32_t dst, const CUtensorMap* map, int c0, int c1, uint32_t bar) {
    asm volatile(
        "cp.async.bulk.tensor.2d.shared::cluster.global.mbarrier::complete_tx::bytes [%0], [%1, {%3, %4}], [%2];"
        ::"r"(dst), "l"(map), "r"(bar), "r"(c0), "r"(c1)
        : "memory");
}
__device__ __forceinline__ void tma_store_2d(const CUtensorMap* map, uint32_t src, int c0, int c1) {
    asm volatile("cp.async.bulk.tensor.2d.global.shared::cta.bulk_group [%0, {%2, %3}], [%1];"
                 ::"l"(map), "r"(src), "r"(c0), "r"(c1)
                 : "memory");
}
__device__ __forceinline__ void tma_load_2d_mc(uint32_t dst, const CUtensorMap* map, int c0, int c1, uint32_t bar, uint16_t mask) {
    asm volatile(
        "cp.async.bulk.tensor.2d.shared::cluster.global.mbarrier::complete_tx::bytes.multicast::cluster [%0], [%1, {%3, %4}], [%2], %5;"
        ::"r"(dst), "l"(map), "r"(bar), "r"(c0), "r"(c1), "h"(mask)
        : "memory");
}
__device__ __forceinline__ void mbar_arrive_cluster(uint32_t bar, uint32_t cta) {
    asm volatile(
        "{\n.reg .b32 ra;\nmapa.shared::cluster.u32 ra, %0, %1;\n"
        "mbarrier.arrive.shared::cluster.b64 _, [ra];\n}\n" ::"r"(bar), "r"(cta)
        : "memory");
}
__device__ __forceinline__ void cluster_sync_all() {
    asm volatile("barrier.cluster.arrive.release.aligned;\nbarrier.cluster.wait.acquire.aligned;" ::: "memory");
}
__device__ __forceinline__ uint32_t cluster_rank() { uint32_t r; asm volatile("mov.u32 %0, %%cluster_ctarank;" : "=r"(r)); return r; }
__device__ __forceinline__ void pdl_wait() { asm volatile("griddepcontrol.wait;" ::: "memory"); }
__device__ __forceinline__ void pdl_launch() { asm volatile("griddepcontrol.launch_dependents;" ::: "memory"); }
__device__ __forceinline__ void bulk_commit() { asm volatile("cp.async.bulk.commit_group;" ::: "memory"); }
__device__ __forceinline__ void bulk_wait_read0() { asm volatile("cp.async.bulk.wait_group.read 0;" ::: "memory"); }
__device__ __forceinline__ void bulk_wait0() { asm volatile("cp.async.bulk.wait_group 0;" ::: "memory"); }
__device__ __forceinline__ void fence_proxy_async() { asm volatile("fence.proxy.async.shared::cta;" ::: "memory"); }
__device__ __forceinline__ void named_bar_sync(int id, int n) { asm volatile("bar.sync %0, %1;" ::"r"(id), "r"(n) : "memory"); }
__device__ __forceinline__ void named_bar_arrive(int id, int n) { asm volatile("bar.arrive %0, %1;" ::"r"(id), "r"(n) : "memory"); }
__device__ __forceinline__ void wgmma_fence() { asm volatile("wgmma.fence.sync.aligned;" ::: "memory"); }
__device__ __forceinline__ void wgmma_commit() { asm volatile("wgmma.commit_group.sync.aligned;" ::: "memory"); }
template <int N>
__device__ __forceinline__ void wgmma_wait() { asm volatile("wgmma.wait_group.sync.aligned %0;" ::"n"(N) : "memory"); }
__device__ __forceinline__ void prefetch_tmap(const CUtensorMap* m) {
    asm volatile("prefetch.tensormap [%0];" ::"l"(m) : "memory");
}
template <int R>
__device__ __forceinline__ void reg_alloc() { asm volatile("setmaxnreg.inc.sync.aligned.u32 %0;" ::"n"(R)); }
template <int R>
__device__ __forceinline__ void reg_dealloc() { asm volatile("setmaxnreg.dec.sync.aligned.u32 %0;" ::"n"(R)); }
__device__ __forceinline__ void stmatrix_x4(uint32_t addr, uint32_t r0, uint32_t r1, uint32_t r2, uint32_t r3) {
    asm volatile("stmatrix.sync.aligned.m8n8.x4.shared.b16 [%0], {%1, %2, %3, %4};"
                 ::"r"(addr), "r"(r0), "r"(r1), "r"(r2), "r"(r3)
                 : "memory");
}
__device__ __forceinline__ uint32_t pack_bf16(float lo, float hi) {
    uint32_t r;
    asm("cvt.rn.bf16x2.f32 %0, %1, %2;" : "=r"(r) : "f"(hi), "f"(lo));
    return r;
}
__device__ __forceinline__ float bf16_round(float v) { return __bfloat162float(__float2bfloat16_rn(v)); }
__device__ __forceinline__ float ex2(float x) {
    float y;
    asm volatile("ex2.approx.ftz.f32 %0, %1;" : "=f"(y) : "f"(x));
    return y;
}
__device__ __forceinline__ float tanh_fast(float x) {
    float y;
    asm("tanh.approx.f32 %0, %1;" : "=f"(y) : "f"(x));
    return y;
}
__device__ __forceinline__ float gelu_tanh(float v) {
    float u = 0.7978845608028654f * (v + 0.044715f * v * v * v);
    float hv = 0.5f * v;
    return fmaf(hv, tanh_fast(u), hv);
}
__device__ __forceinline__ uint32_t desc_lo(uint32_t addr, uint32_t lbo_bytes) {
    return ((addr & 0x3FFFF) >> 4) | (((lbo_bytes >> 4) & 0x3FFF) << 16);
}
__host__ __device__ constexpr uint32_t desc_hi(uint32_t sbo_bytes, uint32_t swz) {
    return ((sbo_bytes >> 4) & 0x3FFF) | (swz << 30);
}

__device__ __forceinline__ void wgmma_ss_n128_tb1(float (&d)[64], uint32_t alo, uint32_t ahi, uint32_t blo, uint32_t bhi, int scale_d) {
    asm volatile("{\n.reg .pred p;\n.reg .b64 da, db;\nsetp.ne.b32 p, %68, 0;\nmov.b64 da, {%64, %65};\nmov.b64 db, {%66, %67};\n"
        "wgmma.mma_async.sync.aligned.m64n128k16.f32.bf16.bf16 {%0, %1, %2, %3, %4, %5, %6, %7, %8, %9, %10, %11, %12, %13, %14, %15, %16, %17, %18, %19, %20, %21, %22, %23, %24, %25, %26, %27, %28, %29, %30, %31, %32, %33, %34, %35, %36, %37, %38, %39, %40, %41, %42, %43, %44, %45, %46, %47, %48, %49, %50, %51, %52, %53, %54, %55, %56, %57, %58, %59, %60, %61, %62, %63}, da, db, p, 1, 1, 0, 1;\n}\n"
        : "+f"(d[0]), "+f"(d[1]), "+f"(d[2]), "+f"(d[3]), "+f"(d[4]), "+f"(d[5]), "+f"(d[6]), "+f"(d[7]), "+f"(d[8]), "+f"(d[9]), "+f"(d[10]), "+f"(d[11]), "+f"(d[12]), "+f"(d[13]), "+f"(d[14]), "+f"(d[15]), "+f"(d[16]), "+f"(d[17]), "+f"(d[18]), "+f"(d[19]), "+f"(d[20]), "+f"(d[21]), "+f"(d[22]), "+f"(d[23]), "+f"(d[24]), "+f"(d[25]), "+f"(d[26]), "+f"(d[27]), "+f"(d[28]), "+f"(d[29]), "+f"(d[30]), "+f"(d[31]), "+f"(d[32]), "+f"(d[33]), "+f"(d[34]), "+f"(d[35]), "+f"(d[36]), "+f"(d[37]), "+f"(d[38]), "+f"(d[39]), "+f"(d[40]), "+f"(d[41]), "+f"(d[42]), "+f"(d[43]), "+f"(d[44]), "+f"(d[45]), "+f"(d[46]), "+f"(d[47]), "+f"(d[48]), "+f"(d[49]), "+f"(d[50]), "+f"(d[51]), "+f"(d[52]), "+f"(d[53]), "+f"(d[54]), "+f"(d[55]), "+f"(d[56]), "+f"(d[57]), "+f"(d[58]), "+f"(d[59]), "+f"(d[60]), "+f"(d[61]), "+f"(d[62]), "+f"(d[63])
        : "r"(alo), "r"(ahi), "r"(blo), "r"(bhi), "r"(scale_d));
}

__device__ __forceinline__ void wgmma_ss_n192_tb1(float (&d)[96], uint32_t alo, uint32_t ahi, uint32_t blo, uint32_t bhi, int scale_d) {
    asm volatile("{\n.reg .pred p;\n.reg .b64 da, db;\nsetp.ne.b32 p, %100, 0;\nmov.b64 da, {%96, %97};\nmov.b64 db, {%98, %99};\n"
        "wgmma.mma_async.sync.aligned.m64n192k16.f32.bf16.bf16 {%0, %1, %2, %3, %4, %5, %6, %7, %8, %9, %10, %11, %12, %13, %14, %15, %16, %17, %18, %19, %20, %21, %22, %23, %24, %25, %26, %27, %28, %29, %30, %31, %32, %33, %34, %35, %36, %37, %38, %39, %40, %41, %42, %43, %44, %45, %46, %47, %48, %49, %50, %51, %52, %53, %54, %55, %56, %57, %58, %59, %60, %61, %62, %63, %64, %65, %66, %67, %68, %69, %70, %71, %72, %73, %74, %75, %76, %77, %78, %79, %80, %81, %82, %83, %84, %85, %86, %87, %88, %89, %90, %91, %92, %93, %94, %95}, da, db, p, 1, 1, 0, 1;\n}\n"
        : "+f"(d[0]), "+f"(d[1]), "+f"(d[2]), "+f"(d[3]), "+f"(d[4]), "+f"(d[5]), "+f"(d[6]), "+f"(d[7]), "+f"(d[8]), "+f"(d[9]), "+f"(d[10]), "+f"(d[11]), "+f"(d[12]), "+f"(d[13]), "+f"(d[14]), "+f"(d[15]), "+f"(d[16]), "+f"(d[17]), "+f"(d[18]), "+f"(d[19]), "+f"(d[20]), "+f"(d[21]), "+f"(d[22]), "+f"(d[23]), "+f"(d[24]), "+f"(d[25]), "+f"(d[26]), "+f"(d[27]), "+f"(d[28]), "+f"(d[29]), "+f"(d[30]), "+f"(d[31]), "+f"(d[32]), "+f"(d[33]), "+f"(d[34]), "+f"(d[35]), "+f"(d[36]), "+f"(d[37]), "+f"(d[38]), "+f"(d[39]), "+f"(d[40]), "+f"(d[41]), "+f"(d[42]), "+f"(d[43]), "+f"(d[44]), "+f"(d[45]), "+f"(d[46]), "+f"(d[47]), "+f"(d[48]), "+f"(d[49]), "+f"(d[50]), "+f"(d[51]), "+f"(d[52]), "+f"(d[53]), "+f"(d[54]), "+f"(d[55]), "+f"(d[56]), "+f"(d[57]), "+f"(d[58]), "+f"(d[59]), "+f"(d[60]), "+f"(d[61]), "+f"(d[62]), "+f"(d[63]), "+f"(d[64]), "+f"(d[65]), "+f"(d[66]), "+f"(d[67]), "+f"(d[68]), "+f"(d[69]), "+f"(d[70]), "+f"(d[71]), "+f"(d[72]), "+f"(d[73]), "+f"(d[74]), "+f"(d[75]), "+f"(d[76]), "+f"(d[77]), "+f"(d[78]), "+f"(d[79]), "+f"(d[80]), "+f"(d[81]), "+f"(d[82]), "+f"(d[83]), "+f"(d[84]), "+f"(d[85]), "+f"(d[86]), "+f"(d[87]), "+f"(d[88]), "+f"(d[89]), "+f"(d[90]), "+f"(d[91]), "+f"(d[92]), "+f"(d[93]), "+f"(d[94]), "+f"(d[95])
        : "r"(alo), "r"(ahi), "r"(blo), "r"(bhi), "r"(scale_d));
}

__device__ __forceinline__ void wgmma_ss_n224_tb1(float (&d)[112], uint32_t alo, uint32_t ahi, uint32_t blo, uint32_t bhi, int scale_d) {
    asm volatile("{\n.reg .pred p;\n.reg .b64 da, db;\nsetp.ne.b32 p, %116, 0;\nmov.b64 da, {%112, %113};\nmov.b64 db, {%114, %115};\n"
        "wgmma.mma_async.sync.aligned.m64n224k16.f32.bf16.bf16 {%0, %1, %2, %3, %4, %5, %6, %7, %8, %9, %10, %11, %12, %13, %14, %15, %16, %17, %18, %19, %20, %21, %22, %23, %24, %25, %26, %27, %28, %29, %30, %31, %32, %33, %34, %35, %36, %37, %38, %39, %40, %41, %42, %43, %44, %45, %46, %47, %48, %49, %50, %51, %52, %53, %54, %55, %56, %57, %58, %59, %60, %61, %62, %63, %64, %65, %66, %67, %68, %69, %70, %71, %72, %73, %74, %75, %76, %77, %78, %79, %80, %81, %82, %83, %84, %85, %86, %87, %88, %89, %90, %91, %92, %93, %94, %95, %96, %97, %98, %99, %100, %101, %102, %103, %104, %105, %106, %107, %108, %109, %110, %111}, da, db, p, 1, 1, 0, 1;\n}\n"
        : "+f"(d[0]), "+f"(d[1]), "+f"(d[2]), "+f"(d[3]), "+f"(d[4]), "+f"(d[5]), "+f"(d[6]), "+f"(d[7]), "+f"(d[8]), "+f"(d[9]), "+f"(d[10]), "+f"(d[11]), "+f"(d[12]), "+f"(d[13]), "+f"(d[14]), "+f"(d[15]), "+f"(d[16]), "+f"(d[17]), "+f"(d[18]), "+f"(d[19]), "+f"(d[20]), "+f"(d[21]), "+f"(d[22]), "+f"(d[23]), "+f"(d[24]), "+f"(d[25]), "+f"(d[26]), "+f"(d[27]), "+f"(d[28]), "+f"(d[29]), "+f"(d[30]), "+f"(d[31]), "+f"(d[32]), "+f"(d[33]), "+f"(d[34]), "+f"(d[35]), "+f"(d[36]), "+f"(d[37]), "+f"(d[38]), "+f"(d[39]), "+f"(d[40]), "+f"(d[41]), "+f"(d[42]), "+f"(d[43]), "+f"(d[44]), "+f"(d[45]), "+f"(d[46]), "+f"(d[47]), "+f"(d[48]), "+f"(d[49]), "+f"(d[50]), "+f"(d[51]), "+f"(d[52]), "+f"(d[53]), "+f"(d[54]), "+f"(d[55]), "+f"(d[56]), "+f"(d[57]), "+f"(d[58]), "+f"(d[59]), "+f"(d[60]), "+f"(d[61]), "+f"(d[62]), "+f"(d[63]), "+f"(d[64]), "+f"(d[65]), "+f"(d[66]), "+f"(d[67]), "+f"(d[68]), "+f"(d[69]), "+f"(d[70]), "+f"(d[71]), "+f"(d[72]), "+f"(d[73]), "+f"(d[74]), "+f"(d[75]), "+f"(d[76]), "+f"(d[77]), "+f"(d[78]), "+f"(d[79]), "+f"(d[80]), "+f"(d[81]), "+f"(d[82]), "+f"(d[83]), "+f"(d[84]), "+f"(d[85]), "+f"(d[86]), "+f"(d[87]), "+f"(d[88]), "+f"(d[89]), "+f"(d[90]), "+f"(d[91]), "+f"(d[92]), "+f"(d[93]), "+f"(d[94]), "+f"(d[95]), "+f"(d[96]), "+f"(d[97]), "+f"(d[98]), "+f"(d[99]), "+f"(d[100]), "+f"(d[101]), "+f"(d[102]), "+f"(d[103]), "+f"(d[104]), "+f"(d[105]), "+f"(d[106]), "+f"(d[107]), "+f"(d[108]), "+f"(d[109]), "+f"(d[110]), "+f"(d[111])
        : "r"(alo), "r"(ahi), "r"(blo), "r"(bhi), "r"(scale_d));
}

__device__ __forceinline__ void wgmma_ss_n256_tb1(float (&d)[128], uint32_t alo, uint32_t ahi, uint32_t blo, uint32_t bhi, int scale_d) {
    asm volatile("{\n.reg .pred p;\n.reg .b64 da, db;\nsetp.ne.b32 p, %132, 0;\nmov.b64 da, {%128, %129};\nmov.b64 db, {%130, %131};\n"
        "wgmma.mma_async.sync.aligned.m64n256k16.f32.bf16.bf16 {%0, %1, %2, %3, %4, %5, %6, %7, %8, %9, %10, %11, %12, %13, %14, %15, %16, %17, %18, %19, %20, %21, %22, %23, %24, %25, %26, %27, %28, %29, %30, %31, %32, %33, %34, %35, %36, %37, %38, %39, %40, %41, %42, %43, %44, %45, %46, %47, %48, %49, %50, %51, %52, %53, %54, %55, %56, %57, %58, %59, %60, %61, %62, %63, %64, %65, %66, %67, %68, %69, %70, %71, %72, %73, %74, %75, %76, %77, %78, %79, %80, %81, %82, %83, %84, %85, %86, %87, %88, %89, %90, %91, %92, %93, %94, %95, %96, %97, %98, %99, %100, %101, %102, %103, %104, %105, %106, %107, %108, %109, %110, %111, %112, %113, %114, %115, %116, %117, %118, %119, %120, %121, %122, %123, %124, %125, %126, %127}, da, db, p, 1, 1, 0, 1;\n}\n"
        : "+f"(d[0]), "+f"(d[1]), "+f"(d[2]), "+f"(d[3]), "+f"(d[4]), "+f"(d[5]), "+f"(d[6]), "+f"(d[7]), "+f"(d[8]), "+f"(d[9]), "+f"(d[10]), "+f"(d[11]), "+f"(d[12]), "+f"(d[13]), "+f"(d[14]), "+f"(d[15]), "+f"(d[16]), "+f"(d[17]), "+f"(d[18]), "+f"(d[19]), "+f"(d[20]), "+f"(d[21]), "+f"(d[22]), "+f"(d[23]), "+f"(d[24]), "+f"(d[25]), "+f"(d[26]), "+f"(d[27]), "+f"(d[28]), "+f"(d[29]), "+f"(d[30]), "+f"(d[31]), "+f"(d[32]), "+f"(d[33]), "+f"(d[34]), "+f"(d[35]), "+f"(d[36]), "+f"(d[37]), "+f"(d[38]), "+f"(d[39]), "+f"(d[40]), "+f"(d[41]), "+f"(d[42]), "+f"(d[43]), "+f"(d[44]), "+f"(d[45]), "+f"(d[46]), "+f"(d[47]), "+f"(d[48]), "+f"(d[49]), "+f"(d[50]), "+f"(d[51]), "+f"(d[52]), "+f"(d[53]), "+f"(d[54]), "+f"(d[55]), "+f"(d[56]), "+f"(d[57]), "+f"(d[58]), "+f"(d[59]), "+f"(d[60]), "+f"(d[61]), "+f"(d[62]), "+f"(d[63]), "+f"(d[64]), "+f"(d[65]), "+f"(d[66]), "+f"(d[67]), "+f"(d[68]), "+f"(d[69]), "+f"(d[70]), "+f"(d[71]), "+f"(d[72]), "+f"(d[73]), "+f"(d[74]), "+f"(d[75]), "+f"(d[76]), "+f"(d[77]), "+f"(d[78]), "+f"(d[79]), "+f"(d[80]), "+f"(d[81]), "+f"(d[82]), "+f"(d[83]), "+f"(d[84]), "+f"(d[85]), "+f"(d[86]), "+f"(d[87]), "+f"(d[88]), "+f"(d[89]), "+f"(d[90]), "+f"(d[91]), "+f"(d[92]), "+f"(d[93]), "+f"(d[94]), "+f"(d[95]), "+f"(d[96]), "+f"(d[97]), "+f"(d[98]), "+f"(d[99]), "+f"(d[100]), "+f"(d[101]), "+f"(d[102]), "+f"(d[103]), "+f"(d[104]), "+f"(d[105]), "+f"(d[106]), "+f"(d[107]), "+f"(d[108]), "+f"(d[109]), "+f"(d[110]), "+f"(d[111]), "+f"(d[112]), "+f"(d[113]), "+f"(d[114]), "+f"(d[115]), "+f"(d[116]), "+f"(d[117]), "+f"(d[118]), "+f"(d[119]), "+f"(d[120]), "+f"(d[121]), "+f"(d[122]), "+f"(d[123]), "+f"(d[124]), "+f"(d[125]), "+f"(d[126]), "+f"(d[127])
        : "r"(alo), "r"(ahi), "r"(blo), "r"(bhi), "r"(scale_d));
}

__device__ __forceinline__ void wgmma_ss_n64_tb0(float (&d)[32], uint32_t alo, uint32_t ahi, uint32_t blo, uint32_t bhi, int scale_d) {
    asm volatile("{\n.reg .pred p;\n.reg .b64 da, db;\nsetp.ne.b32 p, %36, 0;\nmov.b64 da, {%32, %33};\nmov.b64 db, {%34, %35};\n"
        "wgmma.mma_async.sync.aligned.m64n64k16.f32.bf16.bf16 {%0, %1, %2, %3, %4, %5, %6, %7, %8, %9, %10, %11, %12, %13, %14, %15, %16, %17, %18, %19, %20, %21, %22, %23, %24, %25, %26, %27, %28, %29, %30, %31}, da, db, p, 1, 1, 0, 0;\n}\n"
        : "+f"(d[0]), "+f"(d[1]), "+f"(d[2]), "+f"(d[3]), "+f"(d[4]), "+f"(d[5]), "+f"(d[6]), "+f"(d[7]), "+f"(d[8]), "+f"(d[9]), "+f"(d[10]), "+f"(d[11]), "+f"(d[12]), "+f"(d[13]), "+f"(d[14]), "+f"(d[15]), "+f"(d[16]), "+f"(d[17]), "+f"(d[18]), "+f"(d[19]), "+f"(d[20]), "+f"(d[21]), "+f"(d[22]), "+f"(d[23]), "+f"(d[24]), "+f"(d[25]), "+f"(d[26]), "+f"(d[27]), "+f"(d[28]), "+f"(d[29]), "+f"(d[30]), "+f"(d[31])
        : "r"(alo), "r"(ahi), "r"(blo), "r"(bhi), "r"(scale_d));
}

__device__ __forceinline__ void wgmma_rs_n128_tb0(float (&d)[64], uint32_t a0, uint32_t a1, uint32_t a2, uint32_t a3, uint32_t blo, uint32_t bhi, int scale_d) {
    asm volatile("{\n.reg .pred p;\n.reg .b64 db;\nsetp.ne.b32 p, %70, 0;\nmov.b64 db, {%68, %69};\n"
        "wgmma.mma_async.sync.aligned.m64n128k16.f32.bf16.bf16 {%0, %1, %2, %3, %4, %5, %6, %7, %8, %9, %10, %11, %12, %13, %14, %15, %16, %17, %18, %19, %20, %21, %22, %23, %24, %25, %26, %27, %28, %29, %30, %31, %32, %33, %34, %35, %36, %37, %38, %39, %40, %41, %42, %43, %44, %45, %46, %47, %48, %49, %50, %51, %52, %53, %54, %55, %56, %57, %58, %59, %60, %61, %62, %63}, {%64, %65, %66, %67}, db, p, 1, 1, 0;\n}\n"
        : "+f"(d[0]), "+f"(d[1]), "+f"(d[2]), "+f"(d[3]), "+f"(d[4]), "+f"(d[5]), "+f"(d[6]), "+f"(d[7]), "+f"(d[8]), "+f"(d[9]), "+f"(d[10]), "+f"(d[11]), "+f"(d[12]), "+f"(d[13]), "+f"(d[14]), "+f"(d[15]), "+f"(d[16]), "+f"(d[17]), "+f"(d[18]), "+f"(d[19]), "+f"(d[20]), "+f"(d[21]), "+f"(d[22]), "+f"(d[23]), "+f"(d[24]), "+f"(d[25]), "+f"(d[26]), "+f"(d[27]), "+f"(d[28]), "+f"(d[29]), "+f"(d[30]), "+f"(d[31]), "+f"(d[32]), "+f"(d[33]), "+f"(d[34]), "+f"(d[35]), "+f"(d[36]), "+f"(d[37]), "+f"(d[38]), "+f"(d[39]), "+f"(d[40]), "+f"(d[41]), "+f"(d[42]), "+f"(d[43]), "+f"(d[44]), "+f"(d[45]), "+f"(d[46]), "+f"(d[47]), "+f"(d[48]), "+f"(d[49]), "+f"(d[50]), "+f"(d[51]), "+f"(d[52]), "+f"(d[53]), "+f"(d[54]), "+f"(d[55]), "+f"(d[56]), "+f"(d[57]), "+f"(d[58]), "+f"(d[59]), "+f"(d[60]), "+f"(d[61]), "+f"(d[62]), "+f"(d[63])
        : "r"(a0), "r"(a1), "r"(a2), "r"(a3), "r"(blo), "r"(bhi), "r"(scale_d));
}

__device__ __forceinline__ void wgmma_rs_n64_tb0(float (&d)[32], uint32_t a0, uint32_t a1, uint32_t a2, uint32_t a3, uint32_t blo, uint32_t bhi, int scale_d) {
    asm volatile("{\n.reg .pred p;\n.reg .b64 db;\nsetp.ne.b32 p, %38, 0;\nmov.b64 db, {%36, %37};\n"
        "wgmma.mma_async.sync.aligned.m64n64k16.f32.bf16.bf16 {%0, %1, %2, %3, %4, %5, %6, %7, %8, %9, %10, %11, %12, %13, %14, %15, %16, %17, %18, %19, %20, %21, %22, %23, %24, %25, %26, %27, %28, %29, %30, %31}, {%32, %33, %34, %35}, db, p, 1, 1, 0;\n}\n"
        : "+f"(d[0]), "+f"(d[1]), "+f"(d[2]), "+f"(d[3]), "+f"(d[4]), "+f"(d[5]), "+f"(d[6]), "+f"(d[7]), "+f"(d[8]), "+f"(d[9]), "+f"(d[10]), "+f"(d[11]), "+f"(d[12]), "+f"(d[13]), "+f"(d[14]), "+f"(d[15]), "+f"(d[16]), "+f"(d[17]), "+f"(d[18]), "+f"(d[19]), "+f"(d[20]), "+f"(d[21]), "+f"(d[22]), "+f"(d[23]), "+f"(d[24]), "+f"(d[25]), "+f"(d[26]), "+f"(d[27]), "+f"(d[28]), "+f"(d[29]), "+f"(d[30]), "+f"(d[31])
        : "r"(a0), "r"(a1), "r"(a2), "r"(a3), "r"(blo), "r"(bhi), "r"(scale_d));
}

__device__ __forceinline__ void wgmma_rs_n32_tb1(float (&d)[16], uint32_t a0, uint32_t a1, uint32_t a2, uint32_t a3, uint32_t blo, uint32_t bhi, int scale_d) {
    asm volatile("{\n.reg .pred p;\n.reg .b64 db;\nsetp.ne.b32 p, %22, 0;\nmov.b64 db, {%20, %21};\n"
        "wgmma.mma_async.sync.aligned.m64n32k16.f32.bf16.bf16 {%0, %1, %2, %3, %4, %5, %6, %7, %8, %9, %10, %11, %12, %13, %14, %15}, {%16, %17, %18, %19}, db, p, 1, 1, 1;\n}\n"
        : "+f"(d[0]), "+f"(d[1]), "+f"(d[2]), "+f"(d[3]), "+f"(d[4]), "+f"(d[5]), "+f"(d[6]), "+f"(d[7]), "+f"(d[8]), "+f"(d[9]), "+f"(d[10]), "+f"(d[11]), "+f"(d[12]), "+f"(d[13]), "+f"(d[14]), "+f"(d[15])
        : "r"(a0), "r"(a1), "r"(a2), "r"(a3), "r"(blo), "r"(bhi), "r"(scale_d));
}

__device__ __forceinline__ void wgmma_rs_n40_tb1(float (&d)[20], uint32_t a0, uint32_t a1, uint32_t a2, uint32_t a3, uint32_t blo, uint32_t bhi, int scale_d) {
    asm volatile("{\n.reg .pred p;\n.reg .b64 db;\nsetp.ne.b32 p, %26, 0;\nmov.b64 db, {%24, %25};\n"
        "wgmma.mma_async.sync.aligned.m64n40k16.f32.bf16.bf16 {%0, %1, %2, %3, %4, %5, %6, %7, %8, %9, %10, %11, %12, %13, %14, %15, %16, %17, %18, %19}, {%20, %21, %22, %23}, db, p, 1, 1, 1;\n}\n"
        : "+f"(d[0]), "+f"(d[1]), "+f"(d[2]), "+f"(d[3]), "+f"(d[4]), "+f"(d[5]), "+f"(d[6]), "+f"(d[7]), "+f"(d[8]), "+f"(d[9]), "+f"(d[10]), "+f"(d[11]), "+f"(d[12]), "+f"(d[13]), "+f"(d[14]), "+f"(d[15]), "+f"(d[16]), "+f"(d[17]), "+f"(d[18]), "+f"(d[19])
        : "r"(a0), "r"(a1), "r"(a2), "r"(a3), "r"(blo), "r"(bhi), "r"(scale_d));
}

template <int BN>
__device__ __forceinline__ void wgmma_tile(float (&d)[BN / 2], uint32_t da, uint32_t db, int sd) {
    constexpr uint32_t HI = desc_hi(1024, 1);
    if constexpr (BN == 128) wgmma_ss_n128_tb1(d, da, HI, db, HI, sd);
    else if constexpr (BN == 192) wgmma_ss_n192_tb1(d, da, HI, db, HI, sd);
    else if constexpr (BN == 224) wgmma_ss_n224_tb1(d, da, HI, db, HI, sd);
    else wgmma_ss_n256_tb1(d, da, HI, db, HI, sd);
}

__global__ void __launch_bounds__(256) prep_kernel(const bf16* __restrict__ x, const bf16* __restrict__ gate_w,
                                                   const bf16* __restrict__ w1, const bf16* __restrict__ w3) {
    const int tid = threadIdx.x;
    TL_START(0)
    pdl_launch();
    if (blockIdx.x < 256) {
        const int row = blockIdx.x * 8 + (tid >> 5);
        const int lane = tid & 31;
        const uint4* xr = reinterpret_cast<const uint4*>(x + (size_t)row * DM);
        const uint4* gw = reinterpret_cast<const uint4*>(gate_w);
        float v[32];
        float gsum = 0.f, sum = 0.f;
#pragma unroll
        for (int i = 0; i < 4; i++) {
            uint4 a = xr[lane + 32 * i];
            uint4 b = gw[lane + 32 * i];
            const uint32_t aa[4] = {a.x, a.y, a.z, a.w};
            const uint32_t bb[4] = {b.x, b.y, b.z, b.w};
#pragma unroll
            for (int j = 0; j < 4; j++) {
                float x0 = __uint_as_float(aa[j] << 16), x1 = __uint_as_float(aa[j] & 0xFFFF0000u);
                float g0 = __uint_as_float(bb[j] << 16), g1 = __uint_as_float(bb[j] & 0xFFFF0000u);
                v[i * 8 + j * 2] = x0;
                v[i * 8 + j * 2 + 1] = x1;
                sum += x0 + x1;
                gsum += bf16_round(x0 * g0) + bf16_round(x1 * g1);
            }
        }
#pragma unroll
        for (int o = 16; o > 0; o >>= 1) {
            sum += __shfl_xor_sync(0xffffffffu, sum, o);
            gsum += __shfl_xor_sync(0xffffffffu, gsum, o);
        }
        const float mean = sum * (1.0f / DM);
        float m2 = 0.f;
#pragma unroll
        for (int i = 0; i < 32; i++) {
            float d = v[i] - mean;
            m2 += d * d;
        }
#pragma unroll
        for (int o = 16; o > 0; o >>= 1) m2 += __shfl_xor_sync(0xffffffffu, m2, o);
        if (lane == 0) {
            g_mean1[row] = mean;
            g_rstd1[row] = rsqrtf(m2 * (1.0f / DM) + 1e-5f);
            float logit = bf16_round(gsum);
            float g = bf16_round(1.0f / (1.0f + __expf(-logit)));
            g_gate[row] = g;
            g_omg[row] = bf16_round(1.0f - g);
        }
    } else {
        __shared__ float red[32][65];
        const int strip = blockIdx.x - 256;
        const bf16* w;
        float* out;
        int ld, col0;
        if (strip < 16) { w = w1; ld = DM; col0 = strip * 64; out = g_cs1; }
        else { w = w3; ld = FF; col0 = (strip - 16) * 64; out = g_cs3; }
        const int cg = tid & 7;
        const int rg = tid >> 3;
        float acc[8];
#pragma unroll
        for (int j = 0; j < 8; j++) acc[j] = 0.f;
#pragma unroll 8
        for (int r = 0; r < 32; r++) {
            uint4 a = *reinterpret_cast<const uint4*>(w + (size_t)(r * 32 + rg) * ld + col0 + cg * 8);
            const uint32_t aa[4] = {a.x, a.y, a.z, a.w};
#pragma unroll
            for (int j = 0; j < 4; j++) {
                acc[2 * j] += __uint_as_float(aa[j] << 16);
                acc[2 * j + 1] += __uint_as_float(aa[j] & 0xFFFF0000u);
            }
        }
#pragma unroll
        for (int j = 0; j < 8; j++) red[rg][cg * 8 + j] = acc[j];
        __syncthreads();
        if (tid < 64) {
            float s = 0.f;
#pragma unroll
            for (int r = 0; r < 32; r++) s += red[r][tid];
            out[col0 + tid] = s;
        }
    }
    TL_END(0)
}

#define RELEASE_STAGE(b) if (tid_wg < 2) mbar_arrive_cluster(b, tid_wg)
template <int BN, int STAGES>
struct GemmSmem {
    static constexpr int A_BYTES = 128 * 64 * 2;
    static constexpr int B_BOXES = (BN + 63) / 64;
    static constexpr int B_BYTES = B_BOXES * 64 * 64 * 2;
    static constexpr int STAGE_BYTES = A_BYTES + B_BYTES;
    static constexpr int STG_OFF = STAGES * STAGE_BYTES;
    static constexpr int BAR_OFF = STAGES * STAGE_BYTES + 2 * 16384;
    static constexpr int TOTAL = BAR_OFF + 256 + 1024;
};

template <int MODE, int BN, int STAGES>
__global__ void __launch_bounds__(384, 1)
gemm_kernel(const __grid_constant__ CUtensorMap mA, const __grid_constant__ CUtensorMap mB0,
            const __grid_constant__ CUtensorMap mB1, const __grid_constant__ CUtensorMap mC0,
            const __grid_constant__ CUtensorMap mC1, const bf16* __restrict__ xin, int n_tiles_n, int kblocks) {
    using L = GemmSmem<BN, STAGES>;
    extern __shared__ uint8_t smem_raw[];
    const uint32_t sbase = (smem_u32(smem_raw) + 1023u) & ~1023u;
    const uint32_t bar_full = sbase + L::BAR_OFF;
    const uint32_t bar_empty = bar_full + 8 * STAGES;
    const int wg = threadIdx.x >> 7;
    const int npairs = 8 * n_tiles_n;
    const uint32_t crank = cluster_rank();
    const int cid = blockIdx.x >> 1, ncl = gridDim.x >> 1;
    TL_START(MODE)
    pdl_launch();

    if (threadIdx.x == 0) {
        for (int s = 0; s < STAGES; s++) {
            mbar_init(bar_full + 8 * s, 1);
            mbar_init(bar_empty + 8 * s, 4);
        }
        asm volatile("fence.mbarrier_init.release.cluster;" ::: "memory");
        prefetch_tmap(&mA);
        prefetch_tmap(&mB0);
        if (MODE == 1 || MODE == 5) prefetch_tmap(&mB1);
        prefetch_tmap(&mC0);
    }
    cluster_sync_all();

    if (wg == 0) {
        reg_dealloc<40>();
        if (threadIdx.x == 0) {
            if (MODE != 1) pdl_wait();
            int stage = 0;
            uint32_t phase = 1;
            for (int pr = cid; pr < npairs; pr += ncl) {
                const int m0 = ((pr & 7) * 2 + crank) * 128;
                const int n0 = (pr >> 3) * BN;
                for (int kb = 0; kb < kblocks; kb++) {
                    mbar_wait(bar_empty + 8 * stage, phase);
                    const uint32_t sa = sbase + stage * L::STAGE_BYTES;
                    const uint32_t sb = sa + L::A_BYTES;
                    const uint32_t fb = bar_full + 8 * stage;
                    mbar_expect_tx(fb, L::STAGE_BYTES);
                    int arow = m0;
                    if (MODE == 2) {
                        const int grp = kb >> 2;
                        arow += (grp == 0) ? -1 : (grp == 1) ? 1 : (grp == 2) ? -2 : 2;
                    }
                    tma_load_2d(sa, &mA, kb * 64, arow, fb);
                    const CUtensorMap* mb = &mB0;
                    int bc = n0, br = kb * 64;
                    if (MODE == 1 && n0 >= 3 * DM) { mb = &mB1; bc = n0 - 3 * DM; }
                    if (MODE == 5 && kb >= 16) { mb = &mB1; br = (kb - 16) * 64; }
#pragma unroll
                    for (int b = 0; b < L::B_BOXES / 2; b++) {
                        const int bb = crank * (L::B_BOXES / 2) + b;
                        tma_load_2d_mc(sb + bb * 8192, mb, bc + bb * 64, br, fb, (uint16_t)3);
                    }
                    if (++stage == STAGES) { stage = 0; phase ^= 1; }
                }
            }
        }
    } else {
        reg_alloc<232>();
        const int c = wg - 1;
        const int warp = (threadIdx.x >> 5) & 3;
        const int lane = threadIdx.x & 31;
        const int tid_wg = threadIdx.x & 127;
        const uint32_t stg = sbase + L::STG_OFF + c * 16384;
        int stage = 0;
        uint32_t phase = 0;
        float acc[BN / 2];
        bool first = true;
        for (int pr = cid; pr < npairs; pr += ncl) {
            const int m0 = ((pr & 7) * 2 + crank) * 128;
            const int n0 = (pr >> 3) * BN;
            int prev_stage = 0;
            for (int kb = 0; kb < kblocks; kb++) {
                mbar_wait(bar_full + 8 * stage, phase);
                const uint32_t sa = sbase + stage * L::STAGE_BYTES + c * 8192;
                const uint32_t sb = sbase + stage * L::STAGE_BYTES + L::A_BYTES;
                const uint32_t da = desc_lo(sa, 16);
                const uint32_t db = desc_lo(sb, 8192);
                wgmma_fence();
#pragma unroll
                for (int k = 0; k < 4; k++) wgmma_tile<BN>(acc, da + k * 2, db + k * 128, (kb | k) != 0);
                wgmma_commit();
                if (kb > 0) {
                    wgmma_wait<1>();
                    RELEASE_STAGE(bar_empty + 8 * prev_stage);
                }
                prev_stage = stage;
                if (++stage == STAGES) { stage = 0; phase ^= 1; }
            }
            wgmma_wait<0>();
            RELEASE_STAGE(bar_empty + 8 * prev_stage);
            if (first) { pdl_wait(); first = false; }

            const int r0 = m0 + c * 64 + warp * 16 + (lane >> 2);
            const int r1 = r0 + 8;
            const int cq = (lane & 3) * 2;
            const CUtensorMap* mc = &mC0;
            int out_c0 = n0;
            if (MODE == 1) {
                if (n0 < DM) {
                    const float qs = 0.17677669529663687f * 1.4426950408889634f;
#pragma unroll
                    for (int j = 0; j < BN / 2; j++) acc[j] *= qs;
                } else if (n0 >= 3 * DM) {
                    mc = &mC1;
                    out_c0 = n0 - 3 * DM;
                    const float mu0 = g_mean1[r0], mu1 = g_mean1[r1];
                    const float rs0 = g_rstd1[r0], rs1 = g_rstd1[r1];
#pragma unroll
                    for (int j = 0; j < BN / 8; j++) {
                        const float2 cs = *reinterpret_cast<const float2*>(&g_cs1[out_c0 + 8 * j + cq]);
                        acc[4 * j + 0] = gelu_tanh(rs0 * fmaf(-mu0, cs.x, acc[4 * j + 0]));
                        acc[4 * j + 1] = gelu_tanh(rs0 * fmaf(-mu0, cs.y, acc[4 * j + 1]));
                        acc[4 * j + 2] = gelu_tanh(rs1 * fmaf(-mu1, cs.x, acc[4 * j + 2]));
                        acc[4 * j + 3] = gelu_tanh(rs1 * fmaf(-mu1, cs.y, acc[4 * j + 3]));
                    }
                }
            } else if (MODE == 2) {
                float s0 = 0.f, s1 = 0.f;
#pragma unroll
                for (int j = 0; j < BN / 8; j++) {
                    const uint32_t xa = *reinterpret_cast<const uint32_t*>(xin + (size_t)r0 * DM + n0 + 8 * j + cq);
                    const uint32_t xb = *reinterpret_cast<const uint32_t*>(xin + (size_t)r1 * DM + n0 + 8 * j + cq);
                    acc[4 * j + 0] = bf16_round(bf16_round(acc[4 * j + 0]) + __uint_as_float(xa << 16));
                    acc[4 * j + 1] = bf16_round(bf16_round(acc[4 * j + 1]) + __uint_as_float(xa & 0xFFFF0000u));
                    acc[4 * j + 2] = bf16_round(bf16_round(acc[4 * j + 2]) + __uint_as_float(xb << 16));
                    acc[4 * j + 3] = bf16_round(bf16_round(acc[4 * j + 3]) + __uint_as_float(xb & 0xFFFF0000u));
                    s0 += acc[4 * j + 0] + acc[4 * j + 1];
                    s1 += acc[4 * j + 2] + acc[4 * j + 3];
                }
                s0 += __shfl_xor_sync(0xffffffffu, s0, 1);
                s0 += __shfl_xor_sync(0xffffffffu, s0, 2);
                s1 += __shfl_xor_sync(0xffffffffu, s1, 1);
                s1 += __shfl_xor_sync(0xffffffffu, s1, 2);
                const float mu0 = s0 * (1.0f / BN), mu1 = s1 * (1.0f / BN);
                float q0 = 0.f, q1 = 0.f;
#pragma unroll
                for (int j = 0; j < BN / 8; j++) {
                    float d;
                    d = acc[4 * j + 0] - mu0; q0 += d * d;
                    d = acc[4 * j + 1] - mu0; q0 += d * d;
                    d = acc[4 * j + 2] - mu1; q1 += d * d;
                    d = acc[4 * j + 3] - mu1; q1 += d * d;
                }
                q0 += __shfl_xor_sync(0xffffffffu, q0, 1);
                q0 += __shfl_xor_sync(0xffffffffu, q0, 2);
                q1 += __shfl_xor_sync(0xffffffffu, q1, 1);
                q1 += __shfl_xor_sync(0xffffffffu, q1, 2);
                if ((lane & 3) == 0) {
                    static_assert(MODE != 2 || BN == 128, "stats layout assumes BN=128");
                    g_stat2[r0 * 8 + (n0 >> 7)] = make_float2(s0, q0);
                    g_stat2[r1 * 8 + (n0 >> 7)] = make_float2(s1, q1);
                }
            } else if (MODE == 3) {
                out_c0 = n0 + DM;
                float mu[2], rs[2];
#pragma unroll
                for (int h = 0; h < 2; h++) {
                    const float4* sp = reinterpret_cast<const float4*>(&g_stat2[(h ? r1 : r0) * 8]);
                    float4 p[4];
                    float s = 0.f;
#pragma unroll
                    for (int i = 0; i < 4; i++) { p[i] = sp[i]; s += p[i].x + p[i].z; }
                    const float mean = s * (1.0f / DM);
                    float m2 = 0.f;
#pragma unroll
                    for (int i = 0; i < 4; i++) {
                        float d0 = p[i].x * (1.0f / 128) - mean, d1 = p[i].z * (1.0f / 128) - mean;
                        m2 += p[i].y + p[i].w + 128.0f * (d0 * d0 + d1 * d1);
                    }
                    mu[h] = mean;
                    rs[h] = rsqrtf(m2 * (1.0f / DM) + 1e-5f);
                }
                const float og0 = g_omg[r0], og1 = g_omg[r1];
#pragma unroll
                for (int j = 0; j < BN / 8; j++) {
                    const float2 cs = *reinterpret_cast<const float2*>(&g_cs3[n0 + 8 * j + cq]);
                    acc[4 * j + 0] = og0 * gelu_tanh(rs[0] * fmaf(-mu[0], cs.x, acc[4 * j + 0]));
                    acc[4 * j + 1] = og0 * gelu_tanh(rs[0] * fmaf(-mu[0], cs.y, acc[4 * j + 1]));
                    acc[4 * j + 2] = og1 * gelu_tanh(rs[1] * fmaf(-mu[1], cs.x, acc[4 * j + 2]));
                    acc[4 * j + 3] = og1 * gelu_tanh(rs[1] * fmaf(-mu[1], cs.y, acc[4 * j + 3]));
                }
            } else {
                const float og0 = g_omg[r0], og1 = g_omg[r1];
#pragma unroll
                for (int j = 0; j < BN / 8; j++) {
                    const uint32_t xa = *reinterpret_cast<const uint32_t*>(xin + (size_t)r0 * DM + n0 + 8 * j + cq);
                    const uint32_t xb = *reinterpret_cast<const uint32_t*>(xin + (size_t)r1 * DM + n0 + 8 * j + cq);
                    acc[4 * j + 0] = fmaf(og0, __uint_as_float(xa << 16), acc[4 * j + 0]);
                    acc[4 * j + 1] = fmaf(og0, __uint_as_float(xa & 0xFFFF0000u), acc[4 * j + 1]);
                    acc[4 * j + 2] = fmaf(og1, __uint_as_float(xb << 16), acc[4 * j + 2]);
                    acc[4 * j + 3] = fmaf(og1, __uint_as_float(xb & 0xFFFF0000u), acc[4 * j + 3]);
                }
            }
            const int srow = warp * 16 + (lane & 7) + ((lane >> 3) & 1) * 8;
#pragma unroll
            for (int rnd = 0; rnd < (BN + 127) / 128; rnd++) {
                if (tid_wg == 0) bulk_wait_read0();
                named_bar_sync(1 + c, 128);
#pragma unroll
                for (int jj = 0; jj < 8; jj++) {
                    const int j = rnd * 16 + jj * 2;
                    if (j * 8 < BN) {
                        const int jb = jj * 2 + (lane >> 4);
                        uint32_t addr = stg + (jb >> 3) * 8192 + srow * 128 + (((jb & 7) ^ (srow & 7)) << 4);
                        if (rnd * 128 + 128 > BN && jj >= 4)
                            addr = stg + 8192 + srow * 64 + (((jb & 3) ^ ((srow >> 1) & 3)) << 4);
                        stmatrix_x4(addr, pack_bf16(acc[4 * j + 0], acc[4 * j + 1]), pack_bf16(acc[4 * j + 2], acc[4 * j + 3]),
                                    pack_bf16(acc[4 * j + 4], acc[4 * j + 5]), pack_bf16(acc[4 * j + 6], acc[4 * j + 7]));
                    }
                }
                fence_proxy_async();
                named_bar_sync(1 + c, 128);
                if (tid_wg == 0) {
                    tma_store_2d(mc, stg, out_c0 + rnd * 128, m0 + c * 64);
                    if (rnd * 128 + 64 < BN)
                        tma_store_2d((rnd * 128 + 128 > BN) ? &mC1 : mc, stg + 8192, out_c0 + rnd * 128 + 64, m0 + c * 64);
                    bulk_commit();
                }
            }
        }
        if (tid_wg == 0) bulk_wait0();
        TL_END(MODE)
    }
    cluster_sync_all();
}

constexpr int ATT_NTILES = NH * 16;
#define ATT_GRID_N 264
constexpr int ATT_GRID = ATT_GRID_N;
constexpr int ATT_THREADS = 256;
constexpr int ATT_STAGES = 4;
constexpr int ATT_DIST = 2;
constexpr int ATT_Q_OFF = ATT_STAGES * 16384;
constexpr int ATT_ONES_OFF = ATT_Q_OFF + 16384;
constexpr int ATT_KEXT_OFF = ATT_ONES_OFF + 4096;
constexpr int ATT_BAR_OFF = ATT_KEXT_OFF + 4096;
constexpr int ATT_SMEM = ATT_BAR_OFF + 256 + 1024;

__device__ __forceinline__ void row_max(const float (&s)[32], float& m0, float& m1) {
    float a0[8], a1[8];
#pragma unroll
    for (int i = 0; i < 8; i++) {
        a0[i] = fmaxf(s[4 * i], s[4 * i + 1]);
        a1[i] = fmaxf(s[4 * i + 2], s[4 * i + 3]);
    }
#pragma unroll
    for (int w = 4; w > 0; w >>= 1)
#pragma unroll
        for (int i = 0; i < w; i++) { a0[i] = fmaxf(a0[i], a0[i + w]); a1[i] = fmaxf(a1[i], a1[i + w]); }
    float mx0 = a0[0], mx1 = a1[0];
    mx0 = fmaxf(mx0, __shfl_xor_sync(0xffffffffu, mx0, 1));
    mx1 = fmaxf(mx1, __shfl_xor_sync(0xffffffffu, mx1, 1));
    mx0 = fmaxf(mx0, __shfl_xor_sync(0xffffffffu, mx0, 2));
    mx1 = fmaxf(mx1, __shfl_xor_sync(0xffffffffu, mx1, 2));
    m0 = fmaxf(m0, mx0);
    m1 = fmaxf(m1, mx1);
}

__device__ __forceinline__ void attn_step(float (&sc)[32], float (&sn)[32], uint32_t (&p)[16], float (&o)[20], uint32_t dq,
                                          uint32_t e0, uint32_t e1, uint32_t dke, uint32_t dk_next, uint32_t dv_prev,
                                          uint32_t release_bar) {
    constexpr uint32_t HI = desc_hi(512, 2);
    wgmma_fence();
    wgmma_ss_n64_tb0(sn, dq, HI, dk_next, HI, 0);
    wgmma_ss_n64_tb0(sn, dq + 2, HI, dk_next + 2, HI, 1);
    wgmma_rs_n64_tb0(sn, e0, e1, 0u, 0u, dke, HI, 1);
#pragma unroll
    for (int t = 0; t < 4; t++)
        wgmma_rs_n40_tb1(o, p[4 * t], p[4 * t + 1], p[4 * t + 2], p[4 * t + 3], dv_prev + t * 64, HI, 1);
    wgmma_commit();
#pragma unroll
    for (int i = 0; i < 32; i++) sc[i] = ex2(sc[i]);
    wgmma_wait<0>();
    if (release_bar != 0 && (threadIdx.x & 127) == 0) mbar_arrive(release_bar);
#pragma unroll
    for (int i = 0; i < 8; i++) {
        p[2 * i] = pack_bf16(sc[4 * i + 0], sc[4 * i + 1]);
        p[2 * i + 1] = pack_bf16(sc[4 * i + 2], sc[4 * i + 3]);
    }
}

__global__ void __launch_bounds__(256, 2)
attn_kernel(const __grid_constant__ CUtensorMap mKV) {
    extern __shared__ uint8_t smem_raw[];
    const uint32_t sbase = (smem_u32(smem_raw) + 1023u) & ~1023u;
    const uint32_t bar_kfull = sbase + ATT_BAR_OFF;
    const uint32_t bar_vfull = bar_kfull + 8 * ATT_STAGES;
    const uint32_t bar_empty = bar_vfull + 8 * ATT_STAGES;
    const uint32_t bar_q = bar_empty + 8 * ATT_STAGES;
    const uint32_t bar_slow = bar_q + 16;
    const int warp_id = threadIdx.x >> 5;
    const int lane = threadIdx.x & 31;
    constexpr int NBLK = S_LEN / 128;
    TL_START(6)
    pdl_launch();
    const int my_tiles = (ATT_NTILES - (int)blockIdx.x + (int)gridDim.x - 1) / (int)gridDim.x;
    const int total_blocks = my_tiles * NBLK;

    auto issue_kv = [&](int g) {
        const int tile = blockIdx.x + (g >> 4) * gridDim.x;
        const int hd = tile >> 4;
        const int sn = g % ATT_STAGES;
        if (g >= ATT_STAGES) mbar_wait(bar_empty + 8 * sn, ((g / ATT_STAGES) - 1) & 1);
        const uint32_t skn = sbase + sn * 16384;
        mbar_expect_tx(bar_kfull + 8 * sn, 8192);
        tma_load_2d(skn, &mKV, DM + hd * DH, (g & 15) * 128, bar_kfull + 8 * sn);
        mbar_expect_tx(bar_vfull + 8 * sn, 8192);
        tma_load_2d(skn + 8192, &mKV, 2 * DM + hd * DH, (g & 15) * 128, bar_vfull + 8 * sn);
    };
    auto issue_q = [&](int it) {
        const int tile = blockIdx.x + it * gridDim.x;
        mbar_expect_tx(bar_q + 8 * (it & 1), 8192);
        tma_load_2d(sbase + ATT_Q_OFF + (it & 1) * 8192, &mKV, (tile >> 4) * DH, (tile & 15) * 128, bar_q + 8 * (it & 1));
    };

    if (threadIdx.x == 0) {
        for (int s = 0; s < ATT_STAGES; s++) {
            mbar_init(bar_kfull + 8 * s, 1);
            mbar_init(bar_vfull + 8 * s, 1);
            mbar_init(bar_empty + 8 * s, 2);
        }
        mbar_init(bar_q, 1);
        mbar_init(bar_q + 8, 1);
        mbar_init(bar_slow, 1);
        asm volatile("fence.mbarrier_init.release.cluster;" ::: "memory");
        prefetch_tmap(&mKV);
        pdl_wait();
        issue_q(0);
#pragma unroll
        for (int j = 0; j < ATT_DIST; j++) issue_kv(j);
    }
    {
        asm volatile("st.shared.v4.b32 [%0], {%1, %1, %1, %1};" ::"r"(sbase + ATT_ONES_OFF + threadIdx.x * 16), "r"(0x3F803F80u) : "memory");
        const int r = threadIdx.x >> 2, ch = threadIdx.x & 3;
        const uint32_t w0 = (ch == ((r >> 1) & 3)) ? 0x00003F80u : 0u;
        asm volatile("st.shared.v4.b32 [%0], {%1, %2, %2, %2};" ::"r"(sbase + ATT_KEXT_OFF + threadIdx.x * 16), "r"(w0), "r"(0u) : "memory");
    }
    fence_proxy_async();
    __syncthreads();
    pdl_wait();

    const int cq = (lane & 3) * 2;
    constexpr uint32_t HI = desc_hi(512, 2);
    const uint32_t dk0 = desc_lo(sbase, 16);
    const uint32_t dv0 = desc_lo(sbase + 8192, ATT_ONES_OFF - 8192);
    const uint32_t dke = desc_lo(sbase + ATT_KEXT_OFF, 16);
    int stage = 0;
    uint32_t phase = 0;
    uint32_t bad_tiles = 0;
#pragma unroll 1
    for (int it = 0; it < my_tiles; it++) {
        const int tile = blockIdx.x + it * gridDim.x;
        const int head = tile >> 4;
        const int row0 = (tile & 15) * 128 + warp_id * 16 + (lane >> 2);
        const uint32_t dq = desc_lo(sbase + ATT_Q_OFF + (it & 1) * 8192 + (threadIdx.x >> 7) * 4096, 16);
        if (threadIdx.x == 0 && it + 1 < my_tiles) issue_q(it + 1);
        float o[20];
#pragma unroll
        for (int i = 0; i < 20; i++) o[i] = 0.f;
        float s0[32], s1[32];
        uint32_t p[16];
#pragma unroll
        for (int i = 0; i < 16; i++) p[i] = 0u;
        mbar_wait(bar_q + 8 * (it & 1), (it >> 1) & 1);
        mbar_wait(bar_kfull + 8 * stage, phase);
        wgmma_fence();
        wgmma_ss_n64_tb0(s0, dq, HI, dk0 + stage * 1024, HI, 0);
        wgmma_ss_n64_tb0(s0, dq + 2, HI, dk0 + stage * 1024 + 2, HI, 1);
        wgmma_commit();
        wgmma_wait<0>();
        float m0 = -INFINITY, m1 = -INFINITY;
        row_max(s0, m0, m1);
        const uint32_t e0 = (lane & 3) == 0 ? (pack_bf16(-m0, 0.f) & 0xFFFFu) : 0u;
        const uint32_t e1 = (lane & 3) == 0 ? (pack_bf16(-m1, 0.f) & 0xFFFFu) : 0u;
        wgmma_fence();
        wgmma_rs_n64_tb0(s0, e0, e1, 0u, 0u, dke, HI, 1);
        wgmma_commit();
        mbar_wait(bar_vfull + 8 * stage, phase);
        wgmma_wait<0>();
        uint32_t dv_prev = dv0 + stage * 1024 - ((uint32_t)(stage * 1024) << 16);
        int pstage = stage;
#pragma unroll 1
        for (int j = 0; j < NBLK; j++) {
            if (threadIdx.x == 0 && it * NBLK + j + ATT_DIST < total_blocks) issue_kv(it * NBLK + j + ATT_DIST);
            __syncwarp();
            const uint32_t dk = dk0 + stage * 1024;
            const uint32_t dv = dv0 + stage * 1024 - ((uint32_t)(stage * 1024) << 16);
            attn_step(s0, s1, p, o, dq, e0, e1, dke, dk + 256, dv_prev, j > 0 ? bar_empty + 8 * pstage : 0u);
            int nstage = stage + 1;
            uint32_t nphase = phase;
            if (nstage == ATT_STAGES) { nstage = 0; nphase ^= 1; }
            uint32_t dkn = dk;
            if (j + 1 < NBLK) {
                mbar_wait(bar_kfull + 8 * nstage, nphase);
                dkn = dk0 + nstage * 1024;
            }
            mbar_wait(bar_vfull + 8 * stage, phase);
            attn_step(s1, s0, p, o, dq, e0, e1, dke, dkn, dv, 0u);
            dv_prev = dv + 256 - (256u << 16);
            pstage = stage;
            stage = nstage;
            phase = nphase;
        }
        wgmma_fence();
#pragma unroll
        for (int t = 0; t < 4; t++)
            wgmma_rs_n40_tb1(o, p[4 * t], p[4 * t + 1], p[4 * t + 2], p[4 * t + 3], dv_prev + t * 64, HI, 1);
        wgmma_commit();
        wgmma_wait<0>();
        if ((threadIdx.x & 127) == 0) mbar_arrive(bar_empty + 8 * pstage);
        bool ok = (o[16] <= 1.8446744e19f) && (o[18] <= 1.8446744e19f);
#pragma unroll
        for (int i = 0; i < 16; i++) ok = ok && (fabsf(o[i]) <= 3.0e38f);
        const float f0 = g_gate[row0] / o[16], f1 = g_gate[row0 + 8] / o[18];
        bf16* op0 = g_a5 + (size_t)row0 * A5W + head * DH + cq;
        bf16* op1 = op0 + 8 * A5W;
#pragma unroll
        for (int i = 0; i < 4; i++) {
            *reinterpret_cast<uint32_t*>(op0 + 8 * i) = pack_bf16(o[4 * i] * f0, o[4 * i + 1] * f0);
            *reinterpret_cast<uint32_t*>(op1 + 8 * i) = pack_bf16(o[4 * i + 2] * f1, o[4 * i + 3] * f1);
        }
        if (__syncthreads_or(!ok)) bad_tiles |= 1u << it;
    }

    if (bad_tiles) {
        uint32_t sphase = 0;
#pragma unroll 1
        for (int it = 0; it < my_tiles; it++) {
            if (!((bad_tiles >> it) & 1)) continue;
            const int tile = blockIdx.x + it * gridDim.x;
            const int head = tile >> 4;
            const int row0 = (tile & 15) * 128 + warp_id * 16 + (lane >> 2);
            const uint32_t dq = desc_lo(sbase + ATT_Q_OFF + (threadIdx.x >> 7) * 4096, 16);
            float o[20];
#pragma unroll
            for (int i = 0; i < 20; i++) o[i] = 0.f;
            float m0 = -INFINITY, m1 = -INFINITY;
#pragma unroll 1
            for (int j = 0; j < NBLK; j++) {
                if (threadIdx.x == 0) {
                    mbar_expect_tx(bar_slow, j == 0 ? 3 * 8192 : 2 * 8192);
                    if (j == 0) tma_load_2d(sbase + ATT_Q_OFF, &mKV, head * DH, (tile & 15) * 128, bar_slow);
                    tma_load_2d(sbase, &mKV, DM + head * DH, j * 128, bar_slow);
                    tma_load_2d(sbase + 8192, &mKV, 2 * DM + head * DH, j * 128, bar_slow);
                }
                __syncwarp();
                mbar_wait(bar_slow, sphase);
                sphase ^= 1;
#pragma unroll 1
                for (int hf = 0; hf < 2; hf++) {
                    float s[32];
                    wgmma_fence();
                    wgmma_ss_n64_tb0(s, dq, HI, dk0 + hf * 256, HI, 0);
                    wgmma_ss_n64_tb0(s, dq + 2, HI, dk0 + hf * 256 + 2, HI, 1);
                    wgmma_commit();
                    wgmma_wait<0>();
                    const float mo0 = m0, mo1 = m1;
                    row_max(s, m0, m1);
                    const float a0 = ex2(mo0 - m0), a1 = ex2(mo1 - m1);
                    uint32_t p[16];
#pragma unroll
                    for (int i = 0; i < 8; i++) {
                        p[2 * i] = pack_bf16(ex2(s[4 * i + 0] - m0), ex2(s[4 * i + 1] - m0));
                        p[2 * i + 1] = pack_bf16(ex2(s[4 * i + 2] - m1), ex2(s[4 * i + 3] - m1));
                    }
#pragma unroll
                    for (int i = 0; i < 5; i++) {
                        o[4 * i + 0] *= a0; o[4 * i + 1] *= a0;
                        o[4 * i + 2] *= a1; o[4 * i + 3] *= a1;
                    }
                    wgmma_fence();
                    const uint32_t dv = dv0 + hf * 256 - ((uint32_t)(hf * 256) << 16);
#pragma unroll
                    for (int t = 0; t < 4; t++)
                        wgmma_rs_n40_tb1(o, p[4 * t], p[4 * t + 1], p[4 * t + 2], p[4 * t + 3], dv + t * 64, HI, 1);
                    wgmma_commit();
                    wgmma_wait<0>();
                }
                __syncthreads();
            }
            const float f0 = g_gate[row0] / o[16], f1 = g_gate[row0 + 8] / o[18];
            bf16* op0 = g_a5 + (size_t)row0 * A5W + head * DH + cq;
            bf16* op1 = op0 + 8 * A5W;
#pragma unroll
            for (int i = 0; i < 4; i++) {
                *reinterpret_cast<uint32_t*>(op0 + 8 * i) = pack_bf16(o[4 * i] * f0, o[4 * i + 1] * f0);
                *reinterpret_cast<uint32_t*>(op1 + 8 * i) = pack_bf16(o[4 * i + 2] * f1, o[4 * i + 3] * f1);
            }
        }
    }
    TL_END(6)
}

typedef CUresult (*EncodeFn)(CUtensorMap*, CUtensorMapDataType, cuuint32_t, void*, const cuuint64_t*, const cuuint64_t*,
                             const cuuint32_t*, const cuuint32_t*, CUtensorMapInterleave, CUtensorMapSwizzle,
                             CUtensorMapL2promotion, CUtensorMapFloatOOBfill);

static CUtensorMap make_map(EncodeFn fn, const void* ptr, int rows, int cols, int box_cols, int box_rows,
                            CUtensorMapSwizzle swz) {
    CUtensorMap m;
    cuuint64_t dims[2] = {(cuuint64_t)cols, (cuuint64_t)rows};
    cuuint64_t strides[1] = {(cuuint64_t)cols * 2};
    cuuint32_t box[2] = {(cuuint32_t)box_cols, (cuuint32_t)box_rows};
    cuuint32_t es[2] = {1, 1};
    fn(&m, CU_TENSOR_MAP_DATA_TYPE_BFLOAT16, 2, const_cast<void*>(ptr), dims, strides, box, es,
       CU_TENSOR_MAP_INTERLEAVE_NONE, swz, CU_TENSOR_MAP_L2_PROMOTION_L2_256B, CU_TENSOR_MAP_FLOAT_OOB_FILL_NONE);
    return m;
}

template <typename... KArgs, typename... Args>
static void launch_ex(void (*kern)(KArgs...), int grid, int block, int smem, cudaStream_t st, int cluster, Args... args) {
    cudaLaunchConfig_t cfg = {};
    cfg.gridDim = dim3(grid);
    cfg.blockDim = dim3(block);
    cfg.dynamicSmemBytes = smem;
    cfg.stream = st;
    cudaLaunchAttribute at[2];
    at[0].id = cudaLaunchAttributeProgrammaticStreamSerialization;
    at[0].val.programmaticStreamSerializationAllowed = 1;
    at[1].id = cudaLaunchAttributeClusterDimension;
    at[1].val.clusterDim.x = cluster;
    at[1].val.clusterDim.y = 1;
    at[1].val.clusterDim.z = 1;
    cfg.attrs = at;
    cfg.numAttrs = cluster > 1 ? 2 : 1;
    cudaLaunchKernelEx(&cfg, kern, KArgs(args)...);
}

extern "C" void kernel_launch(void* const* d_in, const int* in_sizes, int n_in, void* d_out, int out_size) {
    const bf16* x = (const bf16*)d_in[0];
    const bf16* wqkv = (const bf16*)d_in[1];
    const bf16* wo = (const bf16*)d_in[2];
    const bf16* w1 = (const bf16*)d_in[4];
    const bf16* w2 = (const bf16*)d_in[5];
    const bf16* w3 = (const bf16*)d_in[6];
    const bf16* w4 = (const bf16*)d_in[7];
    const bf16* gate_w = (const bf16*)d_in[8];

    static EncodeFn enc = nullptr;
    static void *p_qkv, *p_h, *p_x1, *p_a5;
    using G1 = GemmSmem<256, 4>;
    using G2 = GemmSmem<128, 5>;
    using G3 = GemmSmem<224, 4>;
    if (!enc) {
        void* fn = nullptr;
        cudaDriverEntryPointQueryResult qres;
        cudaGetDriverEntryPoint("cuTensorMapEncodeTiled", &fn, cudaEnableDefault, &qres);
        enc = (EncodeFn)fn;
        cudaGetSymbolAddress(&p_qkv, g_qkv);
        cudaGetSymbolAddress(&p_h, g_h);
        cudaGetSymbolAddress(&p_x1, g_x1);
        cudaGetSymbolAddress(&p_a5, g_a5);
        cudaFuncSetAttribute(gemm_kernel<1, 256, 4>, cudaFuncAttributeMaxDynamicSharedMemorySize, G1::TOTAL);
        cudaFuncSetAttribute(gemm_kernel<2, 128, 5>, cudaFuncAttributeMaxDynamicSharedMemorySize, G2::TOTAL);
        cudaFuncSetAttribute(gemm_kernel<3, 224, 4>, cudaFuncAttributeMaxDynamicSharedMemorySize, G3::TOTAL);
        cudaFuncSetAttribute(gemm_kernel<5, 128, 5>, cudaFuncAttributeMaxDynamicSharedMemorySize, G2::TOTAL);
        cudaFuncSetAttribute(attn_kernel, cudaFuncAttributeMaxDynamicSharedMemorySize, ATT_SMEM);
    }
    const CUtensorMapSwizzle SW128 = CU_TENSOR_MAP_SWIZZLE_128B, SW64 = CU_TENSOR_MAP_SWIZZLE_64B;
    CUtensorMap mX = make_map(enc, x, S_LEN, DM, 64, 128, SW128);
    CUtensorMap mWqkv = make_map(enc, wqkv, DM, 3 * DM, 64, 64, SW128);
    CUtensorMap mW1 = make_map(enc, w1, DM, DM, 64, 64, SW128);
    CUtensorMap mW2 = make_map(enc, w2, DM, DM, 64, 64, SW128);
    CUtensorMap mW3 = make_map(enc, w3, DM, FF, 64, 64, SW128);
    CUtensorMap mW4 = make_map(enc, w4, FF, DM, 64, 64, SW128);
    CUtensorMap mWo = make_map(enc, wo, DM, DM, 64, 64, SW128);
    CUtensorMap mQKVst = make_map(enc, p_qkv, S_LEN, 3 * DM, 64, 64, SW128);
    CUtensorMap mKV = make_map(enc, p_qkv, S_LEN, 3 * DM, 32, 128, SW64);
    CUtensorMap mHst = make_map(enc, p_h, S_LEN, DM, 64, 64, SW128);
    CUtensorMap mHld = make_map(enc, p_h, S_LEN, DM, 64, 128, SW128);
    CUtensorMap mX1st = make_map(enc, p_x1, S_LEN, DM, 64, 64, SW128);
    CUtensorMap mX1ld = make_map(enc, p_x1, S_LEN, DM, 64, 128, SW128);
    CUtensorMap mA5st = make_map(enc, p_a5, S_LEN, A5W, 64, 64, SW128);
    CUtensorMap mA5st32 = make_map(enc, p_a5, S_LEN, A5W, 32, 64, SW64);
    CUtensorMap mA5ld = make_map(enc, p_a5, S_LEN, A5W, 64, 128, SW128);
    CUtensorMap mOut = make_map(enc, d_out, S_LEN, DM, 64, 64, SW128);

    cudaStream_t st = cudaStreamPerThread;
    prep_kernel<<<256 + 72, 256, 0, st>>>(x, gate_w, w1, w3);
    launch_ex(gemm_kernel<1, 256, 4>, 132, 384, G1::TOTAL, st, 2, mX, mWqkv, mW1, mQKVst, mHst, x, 16, 16);
    launch_ex(attn_kernel, ATT_GRID, ATT_THREADS, ATT_SMEM, st, 1, mKV);
    launch_ex(gemm_kernel<2, 128, 5>, 128, 384, G2::TOTAL, st, 2, mHld, mW2, mW2, mX1st, mX1st, x, 8, 16);
    launch_ex(gemm_kernel<3, 224, 4>, 132, 384, G3::TOTAL, st, 2, mX1ld, mW3, mW3, mA5st, mA5st32, x, 16, 16);
    launch_ex(gemm_kernel<5, 128, 5>, 128, 384, G2::TOTAL, st, 2, mA5ld, mWo, mW4, mOut, mOut, (const bf16*)p_x1, 8, 72);
}
```

```cpp
#include <cuda_runtime.h>
#include <cuda_bf16.h>
#include <cuda.h>
#include <stdint.h>

typedef __nv_bfloat16 bf16;

constexpr int S_LEN = 2048;
constexpr int DM = 1024;
constexpr int FF = 3584;
constexpr int NH = 32;
constexpr int DH = 32;
constexpr int A5W = DM + FF;

__device__ __align__(1024) bf16 g_qkv[S_LEN * 3 * DM];
__device__ __align__(1024) bf16 g_h[S_LEN * DM];
__device__ __align__(1024) bf16 g_x1[S_LEN * DM];
__device__ __align__(1024) bf16 g_a5[S_LEN * A5W];
__device__ __align__(16) float g_mean1[S_LEN];
__device__ __align__(16) float g_rstd1[S_LEN];
__device__ __align__(16) float g_gate[S_LEN];
__device__ __align__(16) float g_omg[S_LEN];
__device__ __align__(16) float g_cs1[DM];
__device__ __align__(16) float g_cs3[FF];
__device__ __align__(16) float2 g_stat2[S_LEN * 8];

#define TL_START(k)
#define TL_END(k)

__device__ __forceinline__ uint32_t smem_u32(const void* p) { return (uint32_t)__cvta_generic_to_shared(p); }

__device__ __forceinline__ void mbar_init(uint32_t bar, uint32_t count) {
    asm volatile("mbarrier.init.shared::cta.b64 [%0], %1;" ::"r"(bar), "r"(count));
}
__device__ __forceinline__ void mbar_expect_tx(uint32_t bar, uint32_t bytes) {
    asm volatile("mbarrier.arrive.expect_tx.shared::cta.b64 _, [%0], %1;" ::"r"(bar), "r"(bytes) : "memory");
}
__device__ __forceinline__ void mbar_arrive(uint32_t bar) {
    asm volatile("mbarrier.arrive.shared::cta.b64 _, [%0];" ::"r"(bar) : "memory");
}
__device__ __forceinline__ bool mbar_try_wait(uint32_t bar, uint32_t parity) {
    uint32_t ok;
    asm volatile(
        "{\n.reg .pred p;\n"
        "mbarrier.try_wait.parity.shared::cta.b64 p, [%1], %2;\n"
        "selp.u32 %0, 1, 0, p;\n}\n"
        : "=r"(ok)
        : "r"(bar), "r"(parity)
        : "memory");
    return ok != 0;
}
__device__ __forceinline__ void mbar_wait(uint32_t bar, uint32_t parity) {
    uint32_t spins = 0;
    while (!mbar_try_wait(bar, parity)) {
        if (++spins > (1u << 24)) __trap();
    }
}
__device__ __forceinline__ void tma_load_2d(uint32_t dst, const CUtensorMap* map, int c0, int c1, uint32_t bar) {
    asm volatile(
        "cp.async.bulk.tensor.2d.shared::cluster.global.mbarrier::complete_tx::bytes [%0], [%1, {%3, %4}], [%2];"
        ::"r"(dst), "l"(map), "r"(bar), "r"(c0), "r"(c1)
        : "memory");
}
__device__ __forceinline__ void tma_store_2d(const CUtensorMap* map, uint32_t src, int c0, int c1) {
    asm volatile("cp.async.bulk.tensor.2d.global.shared::cta.bulk_group [%0, {%2, %3}], [%1];"
                 ::"l"(map), "r"(src), "r"(c0), "r"(c1)
                 : "memory");
}
__device__ __forceinline__ void tma_load_2d_mc(uint32_t dst, const CUtensorMap* map, int c0, int c1, uint32_t bar, uint16_t mask) {
    asm volatile(
        "cp.async.bulk.tensor.2d.shared::cluster.global.mbarrier::complete_tx::bytes.multicast::cluster [%0], [%1, {%3, %4}], [%2], %5;"
        ::"r"(dst), "l"(map), "r"(bar), "r"(c0), "r"(c1), "h"(mask)
        : "memory");
}
__device__ __forceinline__ void mbar_arrive_cluster(uint32_t bar, uint32_t cta) {
    asm volatile(
        "{\n.reg .b32 ra;\nmapa.shared::cluster.u32 ra, %0, %1;\n"
        "mbarrier.arrive.shared::cluster.b64 _, [ra];\n}\n" ::"r"(bar), "r"(cta)
        : "memory");
}
__device__ __forceinline__ void cluster_sync_all() {
    asm volatile("barrier.cluster.arrive.release.aligned;\nbarrier.cluster.wait.acquire.aligned;" ::: "memory");
}
__device__ __forceinline__ uint32_t cluster_rank() { uint32_t r; asm volatile("mov.u32 %0, %%cluster_ctarank;" : "=r"(r)); return r; }
__device__ __forceinline__ void pdl_wait() { asm volatile("griddepcontrol.wait;" ::: "memory"); }
__device__ __forceinline__ void pdl_launch() { asm volatile("griddepcontrol.launch_dependents;" ::: "memory"); }
__device__ __forceinline__ void bulk_commit() { asm volatile("cp.async.bulk.commit_group;" ::: "memory"); }
__device__ __forceinline__ void bulk_wait_read0() { asm volatile("cp.async.bulk.wait_group.read 0;" ::: "memory"); }
__device__ __forceinline__ void bulk_wait0() { asm volatile("cp.async.bulk.wait_group 0;" ::: "memory"); }
__device__ __forceinline__ void fence_proxy_async() { asm volatile("fence.proxy.async.shared::cta;" ::: "memory"); }
__device__ __forceinline__ void named_bar_sync(int id, int n) { asm volatile("bar.sync %0, %1;" ::"r"(id), "r"(n) : "memory"); }
__device__ __forceinline__ void named_bar_arrive(int id, int n) { asm volatile("bar.arrive %0, %1;" ::"r"(id), "r"(n) : "memory"); }
__device__ __forceinline__ void wgmma_fence() { asm volatile("wgmma.fence.sync.aligned;" ::: "memory"); }
__device__ __forceinline__ void wgmma_commit() { asm volatile("wgmma.commit_group.sync.aligned;" ::: "memory"); }
template <int N>
__device__ __forceinline__ void wgmma_wait() { asm volatile("wgmma.wait_group.sync.aligned %0;" ::"n"(N) : "memory"); }
__device__ __forceinline__ void prefetch_tmap(const CUtensorMap* m) {
    asm volatile("prefetch.tensormap [%0];" ::"l"(m) : "memory");
}
template <int R>
__device__ __forceinline__ void reg_alloc() { asm volatile("setmaxnreg.inc.sync.aligned.u32 %0;" ::"n"(R)); }
template <int R>
__device__ __forceinline__ void reg_dealloc() { asm volatile("setmaxnreg.dec.sync.aligned.u32 %0;" ::"n"(R)); }
__device__ __forceinline__ void stmatrix_x4(uint32_t addr, uint32_t r0, uint32_t r1, uint32_t r2, uint32_t r3) {
    asm volatile("stmatrix.sync.aligned.m8n8.x4.shared.b16 [%0], {%1, %2, %3, %4};"
                 ::"r"(addr), "r"(r0), "r"(r1), "r"(r2), "r"(r3)
                 : "memory");
}
__device__ __forceinline__ uint32_t pack_bf16(float lo, float hi) {
    uint32_t r;
    asm("cvt.rn.bf16x2.f32 %0, %1, %2;" : "=r"(r) : "f"(hi), "f"(lo));
    return r;
}
__device__ __forceinline__ float bf16_round(float v) { return __bfloat162float(__float2bfloat16_rn(v)); }
__device__ __forceinline__ float ex2(float x) {
    float y;
    asm volatile("ex2.approx.ftz.f32 %0, %1;" : "=f"(y) : "f"(x));
    return y;
}
__device__ __forceinline__ float tanh_fast(float x) {
    float y;
    asm("tanh.approx.f32 %0, %1;" : "=f"(y) : "f"(x));
    return y;
}
__device__ __forceinline__ float gelu_tanh(float v) {
    float u = 0.7978845608028654f * (v + 0.044715f * v * v * v);
    float hv = 0.5f * v;
    return fmaf(hv, tanh_fast(u), hv);
}
__device__ __forceinline__ uint32_t desc_lo(uint32_t addr, uint32_t lbo_bytes) {
    return ((addr & 0x3FFFF) >> 4) | (((lbo_bytes >> 4) & 0x3FFF) << 16);
}
__host__ __device__ constexpr uint32_t desc_hi(uint32_t sbo_bytes, uint32_t swz) {
    return ((sbo_bytes >> 4) & 0x3FFF) | (swz << 30);
}

__device__ __forceinline__ void wgmma_ss_n128_tb1(float (&d)[64], uint32_t alo, uint32_t ahi, uint32_t blo, uint32_t bhi, int scale_d) {
    asm volatile("{\n.reg .pred p;\n.reg .b64 da, db;\nsetp.ne.b32 p, %68, 0;\nmov.b64 da, {%64, %65};\nmov.b64 db, {%66, %67};\n"
        "wgmma.mma_async.sync.aligned.m64n128k16.f32.bf16.bf16 {%0, %1, %2, %3, %4, %5, %6, %7, %8, %9, %10, %11, %12, %13, %14, %15, %16, %17, %18, %19, %20, %21, %22, %23, %24, %25, %26, %27, %28, %29, %30, %31, %32, %33, %34, %35, %36, %37, %38, %39, %40, %41, %42, %43, %44, %45, %46, %47, %48, %49, %50, %51, %52, %53, %54, %55, %56, %57, %58, %59, %60, %61, %62, %63}, da, db, p, 1, 1, 0, 1;\n}\n"
        : "+f"(d[0]), "+f"(d[1]), "+f"(d[2]), "+f"(d[3]), "+f"(d[4]), "+f"(d[5]), "+f"(d[6]), "+f"(d[7]), "+f"(d[8]), "+f"(d[9]), "+f"(d[10]), "+f"(d[11]), "+f"(d[12]), "+f"(d[13]), "+f"(d[14]), "+f"(d[15]), "+f"(d[16]), "+f"(d[17]), "+f"(d[18]), "+f"(d[19]), "+f"(d[20]), "+f"(d[21]), "+f"(d[22]), "+f"(d[23]), "+f"(d[24]), "+f"(d[25]), "+f"(d[26]), "+f"(d[27]), "+f"(d[28]), "+f"(d[29]), "+f"(d[30]), "+f"(d[31]), "+f"(d[32]), "+f"(d[33]), "+f"(d[34]), "+f"(d[35]), "+f"(d[36]), "+f"(d[37]), "+f"(d[38]), "+f"(d[39]), "+f"(d[40]), "+f"(d[41]), "+f"(d[42]), "+f"(d[43]), "+f"(d[44]), "+f"(d[45]), "+f"(d[46]), "+f"(d[47]), "+f"(d[48]), "+f"(d[49]), "+f"(d[50]), "+f"(d[51]), "+f"(d[52]), "+f"(d[53]), "+f"(d[54]), "+f"(d[55]), "+f"(d[56]), "+f"(d[57]), "+f"(d[58]), "+f"(d[59]), "+f"(d[60]), "+f"(d[61]), "+f"(d[62]), "+f"(d[63])
        : "r"(alo), "r"(ahi), "r"(blo), "r"(bhi), "r"(scale_d));
}

__device__ __forceinline__ void wgmma_ss_n192_tb1(float (&d)[96], uint32_t alo, uint32_t ahi, uint32_t blo, uint32_t bhi, int scale_d) {
    asm volatile("{\n.reg .pred p;\n.reg .b64 da, db;\nsetp.ne.b32 p, %100, 0;\nmov.b64 da, {%96, %97};\nmov.b64 db, {%98, %99};\n"
        "wgmma.mma_async.sync.aligned.m64n192k16.f32.bf16.bf16 {%0, %1, %2, %3, %4, %5, %6, %7, %8, %9, %10, %11, %12, %13, %14, %15, %16, %17, %18, %19, %20, %21, %22, %23, %24, %25, %26, %27, %28, %29, %30, %31, %32, %33, %34, %35, %36, %37, %38, %39, %40, %41, %42, %43, %44, %45, %46, %47, %48, %49, %50, %51, %52, %53, %54, %55, %56, %57, %58, %59, %60, %61, %62, %63, %64, %65, %66, %67, %68, %69, %70, %71, %72, %73, %74, %75, %76, %77, %78, %79, %80, %81, %82, %83, %84, %85, %86, %87, %88, %89, %90, %91, %92, %93, %94, %95}, da, db, p, 1, 1, 0, 1;\n}\n"
        : "+f"(d[0]), "+f"(d[1]), "+f"(d[2]), "+f"(d[3]), "+f"(d[4]), "+f"(d[5]), "+f"(d[6]), "+f"(d[7]), "+f"(d[8]), "+f"(d[9]), "+f"(d[10]), "+f"(d[11]), "+f"(d[12]), "+f"(d[13]), "+f"(d[14]), "+f"(d[15]), "+f"(d[16]), "+f"(d[17]), "+f"(d[18]), "+f"(d[19]), "+f"(d[20]), "+f"(d[21]), "+f"(d[22]), "+f"(d[23]), "+f"(d[24]), "+f"(d[25]), "+f"(d[26]), "+f"(d[27]), "+f"(d[28]), "+f"(d[29]), "+f"(d[30]), "+f"(d[31]), "+f"(d[32]), "+f"(d[33]), "+f"(d[34]), "+f"(d[35]), "+f"(d[36]), "+f"(d[37]), "+f"(d[38]), "+f"(d[39]), "+f"(d[40]), "+f"(d[41]), "+f"(d[42]), "+f"(d[43]), "+f"(d[44]), "+f"(d[45]), "+f"(d[46]), "+f"(d[47]), "+f"(d[48]), "+f"(d[49]), "+f"(d[50]), "+f"(d[51]), "+f"(d[52]), "+f"(d[53]), "+f"(d[54]), "+f"(d[55]), "+f"(d[56]), "+f"(d[57]), "+f"(d[58]), "+f"(d[59]), "+f"(d[60]), "+f"(d[61]), "+f"(d[62]), "+f"(d[63]), "+f"(d[64]), "+f"(d[65]), "+f"(d[66]), "+f"(d[67]), "+f"(d[68]), "+f"(d[69]), "+f"(d[70]), "+f"(d[71]), "+f"(d[72]), "+f"(d[73]), "+f"(d[74]), "+f"(d[75]), "+f"(d[76]), "+f"(d[77]), "+f"(d[78]), "+f"(d[79]), "+f"(d[80]), "+f"(d[81]), "+f"(d[82]), "+f"(d[83]), "+f"(d[84]), "+f"(d[85]), "+f"(d[86]), "+f"(d[87]), "+f"(d[88]), "+f"(d[89]), "+f"(d[90]), "+f"(d[91]), "+f"(d[92]), "+f"(d[93]), "+f"(d[94]), "+f"(d[95])
        : "r"(alo), "r"(ahi), "r"(blo), "r"(bhi), "r"(scale_d));
}

__device__ __forceinline__ void wgmma_ss_n224_tb1(float (&d)[112], uint32_t alo, uint32_t ahi, uint32_t blo, uint32_t bhi, int scale_d) {
    asm volatile("{\n.reg .pred p;\n.reg .b64 da, db;\nsetp.ne.b32 p, %116, 0;\nmov.b64 da, {%112, %113};\nmov.b64 db, {%114, %115};\n"
        "wgmma.mma_async.sync.aligned.m64n224k16.f32.bf16.bf16 {%0, %1, %2, %3, %4, %5, %6, %7, %8, %9, %10, %11, %12, %13, %14, %15, %16, %17, %18, %19, %20, %21, %22, %23, %24, %25, %26, %27, %28, %29, %30, %31, %32, %33, %34, %35, %36, %37, %38, %39, %40, %41, %42, %43, %44, %45, %46, %47, %48, %49, %50, %51, %52, %53, %54, %55, %56, %57, %58, %59, %60, %61, %62, %63, %64, %65, %66, %67, %68, %69, %70, %71, %72, %73, %74, %75, %76, %77, %78, %79, %80, %81, %82, %83, %84, %85, %86, %87, %88, %89, %90, %91, %92, %93, %94, %95, %96, %97, %98, %99, %100, %101, %102, %103, %104, %105, %106, %107, %108, %109, %110, %111}, da, db, p, 1, 1, 0, 1;\n}\n"
        : "+f"(d[0]), "+f"(d[1]), "+f"(d[2]), "+f"(d[3]), "+f"(d[4]), "+f"(d[5]), "+f"(d[6]), "+f"(d[7]), "+f"(d[8]), "+f"(d[9]), "+f"(d[10]), "+f"(d[11]), "+f"(d[12]), "+f"(d[13]), "+f"(d[14]), "+f"(d[15]), "+f"(d[16]), "+f"(d[17]), "+f"(d[18]), "+f"(d[19]), "+f"(d[20]), "+f"(d[21]), "+f"(d[22]), "+f"(d[23]), "+f"(d[24]), "+f"(d[25]), "+f"(d[26]), "+f"(d[27]), "+f"(d[28]), "+f"(d[29]), "+f"(d[30]), "+f"(d[31]), "+f"(d[32]), "+f"(d[33]), "+f"(d[34]), "+f"(d[35]), "+f"(d[36]), "+f"(d[37]), "+f"(d[38]), "+f"(d[39]), "+f"(d[40]), "+f"(d[41]), "+f"(d[42]), "+f"(d[43]), "+f"(d[44]), "+f"(d[45]), "+f"(d[46]), "+f"(d[47]), "+f"(d[48]), "+f"(d[49]), "+f"(d[50]), "+f"(d[51]), "+f"(d[52]), "+f"(d[53]), "+f"(d[54]), "+f"(d[55]), "+f"(d[56]), "+f"(d[57]), "+f"(d[58]), "+f"(d[59]), "+f"(d[60]), "+f"(d[61]), "+f"(d[62]), "+f"(d[63]), "+f"(d[64]), "+f"(d[65]), "+f"(d[66]), "+f"(d[67]), "+f"(d[68]), "+f"(d[69]), "+f"(d[70]), "+f"(d[71]), "+f"(d[72]), "+f"(d[73]), "+f"(d[74]), "+f"(d[75]), "+f"(d[76]), "+f"(d[77]), "+f"(d[78]), "+f"(d[79]), "+f"(d[80]), "+f"(d[81]), "+f"(d[82]), "+f"(d[83]), "+f"(d[84]), "+f"(d[85]), "+f"(d[86]), "+f"(d[87]), "+f"(d[88]), "+f"(d[89]), "+f"(d[90]), "+f"(d[91]), "+f"(d[92]), "+f"(d[93]), "+f"(d[94]), "+f"(d[95]), "+f"(d[96]), "+f"(d[97]), "+f"(d[98]), "+f"(d[99]), "+f"(d[100]), "+f"(d[101]), "+f"(d[102]), "+f"(d[103]), "+f"(d[104]), "+f"(d[105]), "+f"(d[106]), "+f"(d[107]), "+f"(d[108]), "+f"(d[109]), "+f"(d[110]), "+f"(d[111])
        : "r"(alo), "r"(ahi), "r"(blo), "r"(bhi), "r"(scale_d));
}

__device__ __forceinline__ void wgmma_ss_n256_tb1(float (&d)[128], uint32_t alo, uint32_t ahi, uint32_t blo, uint32_t bhi, int scale_d) {
    asm volatile("{\n.reg .pred p;\n.reg .b64 da, db;\nsetp.ne.b32 p, %132, 0;\nmov.b64 da, {%128, %129};\nmov.b64 db, {%130, %131};\n"
        "wgmma.mma_async.sync.aligned.m64n256k16.f32.bf16.bf16 {%0, %1, %2, %3, %4, %5, %6, %7, %8, %9, %10, %11, %12, %13, %14, %15, %16, %17, %18, %19, %20, %21, %22, %23, %24, %25, %26, %27, %28, %29, %30, %31, %32, %33, %34, %35, %36, %37, %38, %39, %40, %41, %42, %43, %44, %45, %46, %47, %48, %49, %50, %51, %52, %53, %54, %55, %56, %57, %58, %59, %60, %61, %62, %63, %64, %65, %66, %67, %68, %69, %70, %71, %72, %73, %74, %75, %76, %77, %78, %79, %80, %81, %82, %83, %84, %85, %86, %87, %88, %89, %90, %91, %92, %93, %94, %95, %96, %97, %98, %99, %100, %101, %102, %103, %104, %105, %106, %107, %108, %109, %110, %111, %112, %113, %114, %115, %116, %117, %118, %119, %120, %121, %122, %123, %124, %125, %126, %127}, da, db, p, 1, 1, 0, 1;\n}\n"
        : "+f"(d[0]), "+f"(d[1]), "+f"(d[2]), "+f"(d[3]), "+f"(d[4]), "+f"(d[5]), "+f"(d[6]), "+f"(d[7]), "+f"(d[8]), "+f"(d[9]), "+f"(d[10]), "+f"(d[11]), "+f"(d[12]), "+f"(d[13]), "+f"(d[14]), "+f"(d[15]), "+f"(d[16]), "+f"(d[17]), "+f"(d[18]), "+f"(d[19]), "+f"(d[20]), "+f"(d[21]), "+f"(d[22]), "+f"(d[23]), "+f"(d[24]), "+f"(d[25]), "+f"(d[26]), "+f"(d[27]), "+f"(d[28]), "+f"(d[29]), "+f"(d[30]), "+f"(d[31]), "+f"(d[32]), "+f"(d[33]), "+f"(d[34]), "+f"(d[35]), "+f"(d[36]), "+f"(d[37]), "+f"(d[38]), "+f"(d[39]), "+f"(d[40]), "+f"(d[41]), "+f"(d[42]), "+f"(d[43]), "+f"(d[44]), "+f"(d[45]), "+f"(d[46]), "+f"(d[47]), "+f"(d[48]), "+f"(d[49]), "+f"(d[50]), "+f"(d[51]), "+f"(d[52]), "+f"(d[53]), "+f"(d[54]), "+f"(d[55]), "+f"(d[56]), "+f"(d[57]), "+f"(d[58]), "+f"(d[59]), "+f"(d[60]), "+f"(d[61]), "+f"(d[62]), "+f"(d[63]), "+f"(d[64]), "+f"(d[65]), "+f"(d[66]), "+f"(d[67]), "+f"(d[68]), "+f"(d[69]), "+f"(d[70]), "+f"(d[71]), "+f"(d[72]), "+f"(d[73]), "+f"(d[74]), "+f"(d[75]), "+f"(d[76]), "+f"(d[77]), "+f"(d[78]), "+f"(d[79]), "+f"(d[80]), "+f"(d[81]), "+f"(d[82]), "+f"(d[83]), "+f"(d[84]), "+f"(d[85]), "+f"(d[86]), "+f"(d[87]), "+f"(d[88]), "+f"(d[89]), "+f"(d[90]), "+f"(d[91]), "+f"(d[92]), "+f"(d[93]), "+f"(d[94]), "+f"(d[95]), "+f"(d[96]), "+f"(d[97]), "+f"(d[98]), "+f"(d[99]), "+f"(d[100]), "+f"(d[101]), "+f"(d[102]), "+f"(d[103]), "+f"(d[104]), "+f"(d[105]), "+f"(d[106]), "+f"(d[107]), "+f"(d[108]), "+f"(d[109]), "+f"(d[110]), "+f"(d[111]), "+f"(d[112]), "+f"(d[113]), "+f"(d[114]), "+f"(d[115]), "+f"(d[116]), "+f"(d[117]), "+f"(d[118]), "+f"(d[119]), "+f"(d[120]), "+f"(d[121]), "+f"(d[122]), "+f"(d[123]), "+f"(d[124]), "+f"(d[125]), "+f"(d[126]), "+f"(d[127])
        : "r"(alo), "r"(ahi), "r"(blo), "r"(bhi), "r"(scale_d));
}

__device__ __forceinline__ void wgmma_ss_n64_tb0(float (&d)[32], uint32_t alo, uint32_t ahi, uint32_t blo, uint32_t bhi, int scale_d) {
    asm volatile("{\n.reg .pred p;\n.reg .b64 da, db;\nsetp.ne.b32 p, %36, 0;\nmov.b64 da, {%32, %33};\nmov.b64 db, {%34, %35};\n"
        "wgmma.mma_async.sync.aligned.m64n64k16.f32.bf16.bf16 {%0, %1, %2, %3, %4, %5, %6, %7, %8, %9, %10, %11, %12, %13, %14, %15, %16, %17, %18, %19, %20, %21, %22, %23, %24, %25, %26, %27, %28, %29, %30, %31}, da, db, p, 1, 1, 0, 0;\n}\n"
        : "+f"(d[0]), "+f"(d[1]), "+f"(d[2]), "+f"(d[3]), "+f"(d[4]), "+f"(d[5]), "+f"(d[6]), "+f"(d[7]), "+f"(d[8]), "+f"(d[9]), "+f"(d[10]), "+f"(d[11]), "+f"(d[12]), "+f"(d[13]), "+f"(d[14]), "+f"(d[15]), "+f"(d[16]), "+f"(d[17]), "+f"(d[18]), "+f"(d[19]), "+f"(d[20]), "+f"(d[21]), "+f"(d[22]), "+f"(d[23]), "+f"(d[24]), "+f"(d[25]), "+f"(d[26]), "+f"(d[27]), "+f"(d[28]), "+f"(d[29]), "+f"(d[30]), "+f"(d[31])
        : "r"(alo), "r"(ahi), "r"(blo), "r"(bhi), "r"(scale_d));
}

__device__ __forceinline__ void wgmma_rs_n128_tb0(float (&d)[64], uint32_t a0, uint32_t a1, uint32_t a2, uint32_t a3, uint32_t blo, uint32_t bhi, int scale_d) {
    asm volatile("{\n.reg .pred p;\n.reg .b64 db;\nsetp.ne.b32 p, %70, 0;\nmov.b64 db, {%68, %69};\n"
        "wgmma.mma_async.sync.aligned.m64n128k16.f32.bf16.bf16 {%0, %1, %2, %3, %4, %5, %6, %7, %8, %9, %10, %11, %12, %13, %14, %15, %16, %17, %18, %19, %20, %21, %22, %23, %24, %25, %26, %27, %28, %29, %30, %31, %32, %33, %34, %35, %36, %37, %38, %39, %40, %41, %42, %43, %44, %45, %46, %47, %48, %49, %50, %51, %52, %53, %54, %55, %56, %57, %58, %59, %60, %61, %62, %63}, {%64, %65, %66, %67}, db, p, 1, 1, 0;\n}\n"
        : "+f"(d[0]), "+f"(d[1]), "+f"(d[2]), "+f"(d[3]), "+f"(d[4]), "+f"(d[5]), "+f"(d[6]), "+f"(d[7]), "+f"(d[8]), "+f"(d[9]), "+f"(d[10]), "+f"(d[11]), "+f"(d[12]), "+f"(d[13]), "+f"(d[14]), "+f"(d[15]), "+f"(d[16]), "+f"(d[17]), "+f"(d[18]), "+f"(d[19]), "+f"(d[20]), "+f"(d[21]), "+f"(d[22]), "+f"(d[23]), "+f"(d[24]), "+f"(d[25]), "+f"(d[26]), "+f"(d[27]), "+f"(d[28]), "+f"(d[29]), "+f"(d[30]), "+f"(d[31]), "+f"(d[32]), "+f"(d[33]), "+f"(d[34]), "+f"(d[35]), "+f"(d[36]), "+f"(d[37]), "+f"(d[38]), "+f"(d[39]), "+f"(d[40]), "+f"(d[41]), "+f"(d[42]), "+f"(d[43]), "+f"(d[44]), "+f"(d[45]), "+f"(d[46]), "+f"(d[47]), "+f"(d[48]), "+f"(d[49]), "+f"(d[50]), "+f"(d[51]), "+f"(d[52]), "+f"(d[53]), "+f"(d[54]), "+f"(d[55]), "+f"(d[56]), "+f"(d[57]), "+f"(d[58]), "+f"(d[59]), "+f"(d[60]), "+f"(d[61]), "+f"(d[62]), "+f"(d[63])
        : "r"(a0), "r"(a1), "r"(a2), "r"(a3), "r"(blo), "r"(bhi), "r"(scale_d));
}

__device__ __forceinline__ void wgmma_rs_n64_tb0(float (&d)[32], uint32_t a0, uint32_t a1, uint32_t a2, uint32_t a3, uint32_t blo, uint32_t bhi, int scale_d) {
    asm volatile("{\n.reg .pred p;\n.reg .b64 db;\nsetp.ne.b32 p, %38, 0;\nmov.b64 db, {%36, %37};\n"
        "wgmma.mma_async.sync.aligned.m64n64k16.f32.bf16.bf16 {%0, %1, %2, %3, %4, %5, %6, %7, %8, %9, %10, %11, %12, %13, %14, %15, %16, %17, %18, %19, %20, %21, %22, %23, %24, %25, %26, %27, %28, %29, %30, %31}, {%32, %33, %34, %35}, db, p, 1, 1, 0;\n}\n"
        : "+f"(d[0]), "+f"(d[1]), "+f"(d[2]), "+f"(d[3]), "+f"(d[4]), "+f"(d[5]), "+f"(d[6]), "+f"(d[7]), "+f"(d[8]), "+f"(d[9]), "+f"(d[10]), "+f"(d[11]), "+f"(d[12]), "+f"(d[13]), "+f"(d[14]), "+f"(d[15]), "+f"(d[16]), "+f"(d[17]), "+f"(d[18]), "+f"(d[19]), "+f"(d[20]), "+f"(d[21]), "+f"(d[22]), "+f"(d[23]), "+f"(d[24]), "+f"(d[25]), "+f"(d[26]), "+f"(d[27]), "+f"(d[28]), "+f"(d[29]), "+f"(d[30]), "+f"(d[31])
        : "r"(a0), "r"(a1), "r"(a2), "r"(a3), "r"(blo), "r"(bhi), "r"(scale_d));
}

__device__ __forceinline__ void wgmma_rs_n32_tb1(float (&d)[16], uint32_t a0, uint32_t a1, uint32_t a2, uint32_t a3, uint32_t blo, uint32_t bhi, int scale_d) {
    asm volatile("{\n.reg .pred p;\n.reg .b64 db;\nsetp.ne.b32 p, %22, 0;\nmov.b64 db, {%20, %21};\n"
        "wgmma.mma_async.sync.aligned.m64n32k16.f32.bf16.bf16 {%0, %1, %2, %3, %4, %5, %6, %7, %8, %9, %10, %11, %12, %13, %14, %15}, {%16, %17, %18, %19}, db, p, 1, 1, 1;\n}\n"
        : "+f"(d[0]), "+f"(d[1]), "+f"(d[2]), "+f"(d[3]), "+f"(d[4]), "+f"(d[5]), "+f"(d[6]), "+f"(d[7]), "+f"(d[8]), "+f"(d[9]), "+f"(d[10]), "+f"(d[11]), "+f"(d[12]), "+f"(d[13]), "+f"(d[14]), "+f"(d[15])
        : "r"(a0), "r"(a1), "r"(a2), "r"(a3), "r"(blo), "r"(bhi), "r"(scale_d));
}

__device__ __forceinline__ void wgmma_rs_n40_tb1(float (&d)[20], uint32_t a0, uint32_t a1, uint32_t a2, uint32_t a3, uint32_t blo, uint32_t bhi, int scale_d) {
    asm volatile("{\n.reg .pred p;\n.reg .b64 db;\nsetp.ne.b32 p, %26, 0;\nmov.b64 db, {%24, %25};\n"
        "wgmma.mma_async.sync.aligned.m64n40k16.f32.bf16.bf16 {%0, %1, %2, %3, %4, %5, %6, %7, %8, %9, %10, %11, %12, %13, %14, %15, %16, %17, %18, %19}, {%20, %21, %22, %23}, db, p, 1, 1, 1;\n}\n"
        : "+f"(d[0]), "+f"(d[1]), "+f"(d[2]), "+f"(d[3]), "+f"(d[4]), "+f"(d[5]), "+f"(d[6]), "+f"(d[7]), "+f"(d[8]), "+f"(d[9]), "+f"(d[10]), "+f"(d[11]), "+f"(d[12]), "+f"(d[13]), "+f"(d[14]), "+f"(d[15]), "+f"(d[16]), "+f"(d[17]), "+f"(d[18]), "+f"(d[19])
        : "r"(a0), "r"(a1), "r"(a2), "r"(a3), "r"(blo), "r"(bhi), "r"(scale_d));
}

template <int BN>
__device__ __forceinline__ void wgmma_tile(float (&d)[BN / 2], uint32_t da, uint32_t db, int sd) {
    constexpr uint32_t HI = desc_hi(1024, 1);
    if constexpr (BN == 128) wgmma_ss_n128_tb1(d, da, HI, db, HI, sd);
    else if constexpr (BN == 192) wgmma_ss_n192_tb1(d, da, HI, db, HI, sd);
    else if constexpr (BN == 224) wgmma_ss_n224_tb1(d, da, HI, db, HI, sd);
    else wgmma_ss_n256_tb1(d, da, HI, db, HI, sd);
}

__global__ void __launch_bounds__(256) prep_kernel(const bf16* __restrict__ x, const bf16* __restrict__ gate_w,
                                                   const bf16* __restrict__ w1, const bf16* __restrict__ w3) {
    const int tid = threadIdx.x;
    TL_START(0)
    pdl_launch();
    if (blockIdx.x < 256) {
        const int row = blockIdx.x * 8 + (tid >> 5);
        const int lane = tid & 31;
        const uint4* xr = reinterpret_cast<const uint4*>(x + (size_t)row * DM);
        const uint4* gw = reinterpret_cast<const uint4*>(gate_w);
        float v[32];
        float gsum = 0.f, sum = 0.f;
#pragma unroll
        for (int i = 0; i < 4; i++) {
            uint4 a = xr[lane + 32 * i];
            uint4 b = gw[lane + 32 * i];
            const uint32_t aa[4] = {a.x, a.y, a.z, a.w};
            const uint32_t bb[4] = {b.x, b.y, b.z, b.w};
#pragma unroll
            for (int j = 0; j < 4; j++) {
                float x0 = __uint_as_float(aa[j] << 16), x1 = __uint_as_float(aa[j] & 0xFFFF0000u);
                float g0 = __uint_as_float(bb[j] << 16), g1 = __uint_as_float(bb[j] & 0xFFFF0000u);
                v[i * 8 + j * 2] = x0;
                v[i * 8 + j * 2 + 1] = x1;
                sum += x0 + x1;
                gsum += bf16_round(x0 * g0) + bf16_round(x1 * g1);
            }
        }
#pragma unroll
        for (int o = 16; o > 0; o >>= 1) {
            sum += __shfl_xor_sync(0xffffffffu, sum, o);
            gsum += __shfl_xor_sync(0xffffffffu, gsum, o);
        }
        const float mean = sum * (1.0f / DM);
        float m2 = 0.f;
#pragma unroll
        for (int i = 0; i < 32; i++) {
            float d = v[i] - mean;
            m2 += d * d;
        }
#pragma unroll
        for (int o = 16; o > 0; o >>= 1) m2 += __shfl_xor_sync(0xffffffffu, m2, o);
        if (lane == 0) {
            g_mean1[row] = mean;
            g_rstd1[row] = rsqrtf(m2 * (1.0f / DM) + 1e-5f);
            float logit = bf16_round(gsum);
            float g = bf16_round(1.0f / (1.0f + __expf(-logit)));
            g_gate[row] = g;
            g_omg[row] = bf16_round(1.0f - g);
        }
    } else {
        __shared__ float red[32][65];
        const int strip = blockIdx.x - 256;
        const bf16* w;
        float* out;
        int ld, col0;
        if (strip < 16) { w = w1; ld = DM; col0 = strip * 64; out = g_cs1; }
        else { w = w3; ld = FF; col0 = (strip - 16) * 64; out = g_cs3; }
        const int cg = tid & 7;
        const int rg = tid >> 3;
        float acc[8];
#pragma unroll
        for (int j = 0; j < 8; j++) acc[j] = 0.f;
#pragma unroll 8
        for (int r = 0; r < 32; r++) {
            uint4 a = *reinterpret_cast<const uint4*>(w + (size_t)(r * 32 + rg) * ld + col0 + cg * 8);
            const uint32_t aa[4] = {a.x, a.y, a.z, a.w};
#pragma unroll
            for (int j = 0; j < 4; j++) {
                acc[2 * j] += __uint_as_float(aa[j] << 16);
                acc[2 * j + 1] += __uint_as_float(aa[j] & 0xFFFF0000u);
            }
        }
#pragma unroll
        for (int j = 0; j < 8; j++) red[rg][cg * 8 + j] = acc[j];
        __syncthreads();
        if (tid < 64) {
            float s = 0.f;
#pragma unroll
            for (int r = 0; r < 32; r++) s += red[r][tid];
            out[col0 + tid] = s;
        }
    }
    TL_END(0)
}

#define RELEASE_STAGE(b) if (tid_wg < 2) mbar_arrive_cluster(b, tid_wg)
template <int BN, int STAGES>
struct GemmSmem {
    static constexpr int A_BYTES = 128 * 64 * 2;
    static constexpr int B_BOXES = (BN + 63) / 64;
    static constexpr int B_BYTES = B_BOXES * 64 * 64 * 2;
    static constexpr int STAGE_BYTES = A_BYTES + B_BYTES;
    static constexpr int STG_OFF = STAGES * STAGE_BYTES;
    static constexpr int BAR_OFF = STAGES * STAGE_BYTES + 2 * 16384;
    static constexpr int TOTAL = BAR_OFF + 256 + 1024;
};

template <int MODE, int BN, int STAGES>
__global__ void __launch_bounds__(384, 1)
gemm_kernel(const __grid_constant__ CUtensorMap mA, const __grid_constant__ CUtensorMap mB0,
            const __grid_constant__ CUtensorMap mB1, const __grid_constant__ CUtensorMap mC0,
            const __grid_constant__ CUtensorMap mC1, const bf16* __restrict__ xin, int n_tiles_n, int kblocks) {
    using L = GemmSmem<BN, STAGES>;
    extern __shared__ uint8_t smem_raw[];
    const uint32_t sbase = (smem_u32(smem_raw) + 1023u) & ~1023u;
    const uint32_t bar_full = sbase + L::BAR_OFF;
    const uint32_t bar_empty = bar_full + 8 * STAGES;
    const int wg = threadIdx.x >> 7;
    const int npairs = 8 * n_tiles_n;
    const uint32_t crank = cluster_rank();
    const int cid = blockIdx.x >> 1, ncl = gridDim.x >> 1;
    TL_START(MODE)
    pdl_launch();

    if (threadIdx.x == 0) {
        for (int s = 0; s < STAGES; s++) {
            mbar_init(bar_full + 8 * s, 1);
            mbar_init(bar_empty + 8 * s, 4);
        }
        asm volatile("fence.mbarrier_init.release.cluster;" ::: "memory");
        prefetch_tmap(&mA);
        prefetch_tmap(&mB0);
        if (MODE == 1 || MODE == 5) prefetch_tmap(&mB1);
        prefetch_tmap(&mC0);
    }
    cluster_sync_all();

    if (wg == 0) {
        reg_dealloc<40>();
        if (threadIdx.x == 0) {
            if (MODE != 1) pdl_wait();
            int stage = 0;
            uint32_t phase = 1;
            for (int pr = cid; pr < npairs; pr += ncl) {
                const int m0 = ((pr & 7) * 2 + crank) * 128;
                const int n0 = (pr >> 3) * BN;
                for (int kb = 0; kb < kblocks; kb++) {
                    mbar_wait(bar_empty + 8 * stage, phase);
                    const uint32_t sa = sbase + stage * L::STAGE_BYTES;
                    const uint32_t sb = sa + L::A_BYTES;
                    const uint32_t fb = bar_full + 8 * stage;
                    mbar_expect_tx(fb, L::STAGE_BYTES);
                    int arow = m0;
                    if (MODE == 2) {
                        const int grp = kb >> 2;
                        arow += (grp == 0) ? -1 : (grp == 1) ? 1 : (grp == 2) ? -2 : 2;
                    }
                    tma_load_2d(sa, &mA, kb * 64, arow, fb);
                    const CUtensorMap* mb = &mB0;
                    int bc = n0, br = kb * 64;
                    if (MODE == 1 && n0 >= 3 * DM) { mb = &mB1; bc = n0 - 3 * DM; }
                    if (MODE == 5 && kb >= 16) { mb = &mB1; br = (kb - 16) * 64; }
#pragma unroll
                    for (int b = 0; b < L::B_BOXES / 2; b++) {
                        const int bb = crank * (L::B_BOXES / 2) + b;
                        tma_load_2d_mc(sb + bb * 8192, mb, bc + bb * 64, br, fb, (uint16_t)3);
                    }
                    if (++stage == STAGES) { stage = 0; phase ^= 1; }
                }
            }
        }
    } else {
        reg_alloc<232>();
        const int c = wg - 1;
        const int warp = (threadIdx.x >> 5) & 3;
        const int lane = threadIdx.x & 31;
        const int tid_wg = threadIdx.x & 127;
        const uint32_t stg = sbase + L::STG_OFF + c * 16384;
        int stage = 0;
        uint32_t phase = 0;
        float acc[BN / 2];
        bool first = true;
        for (int pr = cid; pr < npairs; pr += ncl) {
            const int m0 = ((pr & 7) * 2 + crank) * 128;
            const int n0 = (pr >> 3) * BN;
            int prev_stage = 0;
            for (int kb = 0; kb < kblocks; kb++) {
                mbar_wait(bar_full + 8 * stage, phase);
                const uint32_t sa = sbase + stage * L::STAGE_BYTES + c * 8192;
                const uint32_t sb = sbase + stage * L::STAGE_BYTES + L::A_BYTES;
                const uint32_t da = desc_lo(sa, 16);
                const uint32_t db = desc_lo(sb, 8192);
                wgmma_fence();
#pragma unroll
                for (int k = 0; k < 4; k++) wgmma_tile<BN>(acc, da + k * 2, db + k * 128, (kb | k) != 0);
                wgmma_commit();
                if (kb > 0) {
                    wgmma_wait<1>();
                    RELEASE_STAGE(bar_empty + 8 * prev_stage);
                }
                prev_stage = stage;
                if (++stage == STAGES) { stage = 0; phase ^= 1; }
            }
            wgmma_wait<0>();
            RELEASE_STAGE(bar_empty + 8 * prev_stage);
            if (first) { pdl_wait(); first = false; }

            const int r0 = m0 + c * 64 + warp * 16 + (lane >> 2);
            const int r1 = r0 + 8;
            const int cq = (lane & 3) * 2;
            const CUtensorMap* mc = &mC0;
            int out_c0 = n0;
            if (MODE == 1) {
                if (n0 < DM) {
                    const float qs = 0.17677669529663687f * 1.4426950408889634f;
#pragma unroll
                    for (int j = 0; j < BN / 2; j++) acc[j] *= qs;
                } else if (n0 >= 3 * DM) {
                    mc = &mC1;
                    out_c0 = n0 - 3 * DM;
                    const float mu0 = g_mean1[r0], mu1 = g_mean1[r1];
                    const float rs0 = g_rstd1[r0], rs1 = g_rstd1[r1];
#pragma unroll
                    for (int j = 0; j < BN / 8; j++) {
                        const float2 cs = *reinterpret_cast<const float2*>(&g_cs1[out_c0 + 8 * j + cq]);
                        acc[4 * j + 0] = gelu_tanh(rs0 * fmaf(-mu0, cs.x, acc[4 * j + 0]));
                        acc[4 * j + 1] = gelu_tanh(rs0 * fmaf(-mu0, cs.y, acc[4 * j + 1]));
                        acc[4 * j + 2] = gelu_tanh(rs1 * fmaf(-mu1, cs.x, acc[4 * j + 2]));
                        acc[4 * j + 3] = gelu_tanh(rs1 * fmaf(-mu1, cs.y, acc[4 * j + 3]));
                    }
                }
            } else if (MODE == 2) {
                float s0 = 0.f, s1 = 0.f;
#pragma unroll
                for (int j = 0; j < BN / 8; j++) {
                    const uint32_t xa = *reinterpret_cast<const uint32_t*>(xin + (size_t)r0 * DM + n0 + 8 * j + cq);
                    const uint32_t xb = *reinterpret_cast<const uint32_t*>(xin + (size_t)r1 * DM + n0 + 8 * j + cq);
                    acc[4 * j + 0] = bf16_round(bf16_round(acc[4 * j + 0]) + __uint_as_float(xa << 16));
                    acc[4 * j + 1] = bf16_round(bf16_round(acc[4 * j + 1]) + __uint_as_float(xa & 0xFFFF0000u));
                    acc[4 * j + 2] = bf16_round(bf16_round(acc[4 * j + 2]) + __uint_as_float(xb << 16));
                    acc[4 * j + 3] = bf16_round(bf16_round(acc[4 * j + 3]) + __uint_as_float(xb & 0xFFFF0000u));
                    s0 += acc[4 * j + 0] + acc[4 * j + 1];
                    s1 += acc[4 * j + 2] + acc[4 * j + 3];
                }
                s0 += __shfl_xor_sync(0xffffffffu, s0, 1);
                s0 += __shfl_xor_sync(0xffffffffu, s0, 2);
                s1 += __shfl_xor_sync(0xffffffffu, s1, 1);
                s1 += __shfl_xor_sync(0xffffffffu, s1, 2);
                const float mu0 = s0 * (1.0f / BN), mu1 = s1 * (1.0f / BN);
                float q0 = 0.f, q1 = 0.f;
#pragma unroll
                for (int j = 0; j < BN / 8; j++) {
                    float d;
                    d = acc[4 * j + 0] - mu0; q0 += d * d;
                    d = acc[4 * j + 1] - mu0; q0 += d * d;
                    d = acc[4 * j + 2] - mu1; q1 += d * d;
                    d = acc[4 * j + 3] - mu1; q1 += d * d;
                }
                q0 += __shfl_xor_sync(0xffffffffu, q0, 1);
                q0 += __shfl_xor_sync(0xffffffffu, q0, 2);
                q1 += __shfl_xor_sync(0xffffffffu, q1, 1);
                q1 += __shfl_xor_sync(0xffffffffu, q1, 2);
                if ((lane & 3) == 0) {
                    static_assert(MODE != 2 || BN == 128, "stats layout assumes BN=128");
                    g_stat2[r0 * 8 + (n0 >> 7)] = make_float2(s0, q0);
                    g_stat2[r1 * 8 + (n0 >> 7)] = make_float2(s1, q1);
                }
            } else if (MODE == 3) {
                out_c0 = n0 + DM;
                float mu[2], rs[2];
#pragma unroll
                for (int h = 0; h < 2; h++) {
                    const float4* sp = reinterpret_cast<const float4*>(&g_stat2[(h ? r1 : r0) * 8]);
                    float4 p[4];
                    float s = 0.f;
#pragma unroll
                    for (int i = 0; i < 4; i++) { p[i] = sp[i]; s += p[i].x + p[i].z; }
                    const float mean = s * (1.0f / DM);
                    float m2 = 0.f;
#pragma unroll
                    for (int i = 0; i < 4; i++) {
                        float d0 = p[i].x * (1.0f / 128) - mean, d1 = p[i].z * (1.0f / 128) - mean;
                        m2 += p[i].y + p[i].w + 128.0f * (d0 * d0 + d1 * d1);
                    }
                    mu[h] = mean;
                    rs[h] = rsqrtf(m2 * (1.0f / DM) + 1e-5f);
                }
                const float og0 = g_omg[r0], og1 = g_omg[r1];
#pragma unroll
                for (int j = 0; j < BN / 8; j++) {
                    const float2 cs = *reinterpret_cast<const float2*>(&g_cs3[n0 + 8 * j + cq]);
                    acc[4 * j + 0] = og0 * gelu_tanh(rs[0] * fmaf(-mu[0], cs.x, acc[4 * j + 0]));
                    acc[4 * j + 1] = og0 * gelu_tanh(rs[0] * fmaf(-mu[0], cs.y, acc[4 * j + 1]));
                    acc[4 * j + 2] = og1 * gelu_tanh(rs[1] * fmaf(-mu[1], cs.x, acc[4 * j + 2]));
                    acc[4 * j + 3] = og1 * gelu_tanh(rs[1] * fmaf(-mu[1], cs.y, acc[4 * j + 3]));
                }
            } else {
                const float og0 = g_omg[r0], og1 = g_omg[r1];
#pragma unroll
                for (int j = 0; j < BN / 8; j++) {
                    const uint32_t xa = *reinterpret_cast<const uint32_t*>(xin + (size_t)r0 * DM + n0 + 8 * j + cq);
                    const uint32_t xb = *reinterpret_cast<const uint32_t*>(xin + (size_t)r1 * DM + n0 + 8 * j + cq);
                    acc[4 * j + 0] = fmaf(og0, __uint_as_float(xa << 16), acc[4 * j + 0]);
                    acc[4 * j + 1] = fmaf(og0, __uint_as_float(xa & 0xFFFF0000u), acc[4 * j + 1]);
                    acc[4 * j + 2] = fmaf(og1, __uint_as_float(xb << 16), acc[4 * j + 2]);
                    acc[4 * j + 3] = fmaf(og1, __uint_as_float(xb & 0xFFFF0000u), acc[4 * j + 3]);
                }
            }
            const int srow = warp * 16 + (lane & 7) + ((lane >> 3) & 1) * 8;
#pragma unroll
            for (int rnd = 0; rnd < (BN + 127) / 128; rnd++) {
                if (tid_wg == 0) bulk_wait_read0();
                named_bar_sync(1 + c, 128);
#pragma unroll
                for (int jj = 0; jj < 8; jj++) {
                    const int j = rnd * 16 + jj * 2;
                    if (j * 8 < BN) {
                        const int jb = jj * 2 + (lane >> 4);
                        uint32_t addr = stg + (jb >> 3) * 8192 + srow * 128 + (((jb & 7) ^ (srow & 7)) << 4);
                        if (rnd * 128 + 128 > BN && jj >= 4)
                            addr = stg + 8192 + srow * 64 + (((jb & 3) ^ ((srow >> 1) & 3)) << 4);
                        stmatrix_x4(addr, pack_bf16(acc[4 * j + 0], acc[4 * j + 1]), pack_bf16(acc[4 * j + 2], acc[4 * j + 3]),
                                    pack_bf16(acc[4 * j + 4], acc[4 * j + 5]), pack_bf16(acc[4 * j + 6], acc[4 * j + 7]));
                    }
                }
                fence_proxy_async();
                named_bar_sync(1 + c, 128);
                if (tid_wg == 0) {
                    tma_store_2d(mc, stg, out_c0 + rnd * 128, m0 + c * 64);
                    if (rnd * 128 + 64 < BN)
                        tma_store_2d((rnd * 128 + 128 > BN) ? &mC1 : mc, stg + 8192, out_c0 + rnd * 128 + 64, m0 + c * 64);
                    bulk_commit();
                }
            }
        }
        if (tid_wg == 0) bulk_wait0();
        TL_END(MODE)
    }
    cluster_sync_all();
}

constexpr int ATT_NTILES = NH * 16;
#define ATT_GRID_N 264
constexpr int ATT_GRID = ATT_GRID_N;
constexpr int ATT_THREADS = 256;
constexpr int ATT_STAGES = 4;
constexpr int ATT_DIST = 2;
constexpr int ATT_Q_OFF = ATT_STAGES * 16384;
constexpr int ATT_ONES_OFF = ATT_Q_OFF + 16384;
constexpr int ATT_KEXT_OFF = ATT_ONES_OFF + 4096;
constexpr int ATT_BAR_OFF = ATT_KEXT_OFF + 4096;
constexpr int ATT_SMEM = ATT_BAR_OFF + 256 + 1024;

__device__ __forceinline__ void row_max(const float (&s)[32], float& m0, float& m1) {
    float a0[8], a1[8];
#pragma unroll
    for (int i = 0; i < 8; i++) {
        a0[i] = fmaxf(s[4 * i], s[4 * i + 1]);
        a1[i] = fmaxf(s[4 * i + 2], s[4 * i + 3]);
    }
#pragma unroll
    for (int w = 4; w > 0; w >>= 1)
#pragma unroll
        for (int i = 0; i < w; i++) { a0[i] = fmaxf(a0[i], a0[i + w]); a1[i] = fmaxf(a1[i], a1[i + w]); }
    float mx0 = a0[0], mx1 = a1[0];
    mx0 = fmaxf(mx0, __shfl_xor_sync(0xffffffffu, mx0, 1));
    mx1 = fmaxf(mx1, __shfl_xor_sync(0xffffffffu, mx1, 1));
    mx0 = fmaxf(mx0, __shfl_xor_sync(0xffffffffu, mx0, 2));
    mx1 = fmaxf(mx1, __shfl_xor_sync(0xffffffffu, mx1, 2));
    m0 = fmaxf(m0, mx0);
    m1 = fmaxf(m1, mx1);
}

__device__ __forceinline__ void attn_step(float (&sc)[32], float (&sn)[32], uint32_t (&p)[16], float (&o)[20], uint32_t dq,
                                          uint32_t e0, uint32_t e1, uint32_t dke, uint32_t dk_next, uint32_t dv_prev,
                                          uint32_t release_bar) {
    constexpr uint32_t HI = desc_hi(512, 2);
    wgmma_fence();
    wgmma_ss_n64_tb0(sn, dq, HI, dk_next, HI, 0);
    wgmma_ss_n64_tb0(sn, dq + 2, HI, dk_next + 2, HI, 1);
    wgmma_rs_n64_tb0(sn, e0, e1, 0u, 0u, dke, HI, 1);
#pragma unroll
    for (int t = 0; t < 4; t++)
        wgmma_rs_n40_tb1(o, p[4 * t], p[4 * t + 1], p[4 * t + 2], p[4 * t + 3], dv_prev + t * 64, HI, 1);
    wgmma_commit();
#pragma unroll
    for (int i = 0; i < 32; i++) sc[i] = ex2(sc[i]);
    wgmma_wait<0>();
    if (release_bar != 0 && (threadIdx.x & 127) == 0) mbar_arrive(release_bar);
#pragma unroll
    for (int i = 0; i < 8; i++) {
        p[2 * i] = pack_bf16(sc[4 * i + 0], sc[4 * i + 1]);
        p[2 * i + 1] = pack_bf16(sc[4 * i + 2], sc[4 * i + 3]);
    }
}

__device__ __noinline__ void attn_exact(const CUtensorMap* mKV, uint32_t sbase, uint32_t bad_tiles, int my_tiles) {
    constexpr int NBLK = S_LEN / 128;
    constexpr uint32_t HI = desc_hi(512, 2);
    const uint32_t bar_slow = sbase + ATT_BAR_OFF + 24 * ATT_STAGES + 16;
    const int warp_id = threadIdx.x >> 5;
    const int lane = threadIdx.x & 31;
    const int cq = (lane & 3) * 2;
    const uint32_t dk0 = desc_lo(sbase, 16);
    const uint32_t dv0 = desc_lo(sbase + 8192, ATT_ONES_OFF - 8192);
    {
        uint32_t sphase = 0;
#pragma unroll 1
        for (int it = 0; it < my_tiles; it++) {
            if (!((bad_tiles >> it) & 1)) continue;
            const int tile = blockIdx.x + it * gridDim.x;
            const int head = tile >> 4;
            const int row0 = (tile & 15) * 128 + warp_id * 16 + (lane >> 2);
            const uint32_t dq = desc_lo(sbase + ATT_Q_OFF + (threadIdx.x >> 7) * 4096, 16);
            float o[20];
#pragma unroll
            for (int i = 0; i < 20; i++) o[i] = 0.f;
            float m0 = -INFINITY, m1 = -INFINITY;
#pragma unroll 1
            for (int j = 0; j < NBLK; j++) {
                if (threadIdx.x == 0) {
                    mbar_expect_tx(bar_slow, j == 0 ? 3 * 8192 : 2 * 8192);
                    if (j == 0) tma_load_2d(sbase + ATT_Q_OFF, mKV, head * DH, (tile & 15) * 128, bar_slow);
                    tma_load_2d(sbase, mKV, DM + head * DH, j * 128, bar_slow);
                    tma_load_2d(sbase + 8192, mKV, 2 * DM + head * DH, j * 128, bar_slow);
                }
                __syncwarp();
                mbar_wait(bar_slow, sphase);
                sphase ^= 1;
#pragma unroll 1
                for (int hf = 0; hf < 2; hf++) {
                    float s[32];
                    wgmma_fence();
                    wgmma_ss_n64_tb0(s, dq, HI, dk0 + hf * 256, HI, 0);
                    wgmma_ss_n64_tb0(s, dq + 2, HI, dk0 + hf * 256 + 2, HI, 1);
                    wgmma_commit();
                    wgmma_wait<0>();
                    const float mo0 = m0, mo1 = m1;
                    row_max(s, m0, m1);
                    const float a0 = ex2(mo0 - m0), a1 = ex2(mo1 - m1);
                    uint32_t p[16];
#pragma unroll
                    for (int i = 0; i < 8; i++) {
                        p[2 * i] = pack_bf16(ex2(s[4 * i + 0] - m0), ex2(s[4 * i + 1] - m0));
                        p[2 * i + 1] = pack_bf16(ex2(s[4 * i + 2] - m1), ex2(s[4 * i + 3] - m1));
                    }
#pragma unroll
                    for (int i = 0; i < 5; i++) {
                        o[4 * i + 0] *= a0; o[4 * i + 1] *= a0;
                        o[4 * i + 2] *= a1; o[4 * i + 3] *= a1;
                    }
                    wgmma_fence();
                    const uint32_t dv = dv0 + hf * 256 - ((uint32_t)(hf * 256) << 16);
#pragma unroll
                    for (int t = 0; t < 4; t++)
                        wgmma_rs_n40_tb1(o, p[4 * t], p[4 * t + 1], p[4 * t + 2], p[4 * t + 3], dv + t * 64, HI, 1);
                    wgmma_commit();
                    wgmma_wait<0>();
                }
                __syncthreads();
            }
            const float f0 = g_gate[row0] / o[16], f1 = g_gate[row0 + 8] / o[18];
            bf16* op0 = g_a5 + (size_t)row0 * A5W + head * DH + cq;
            bf16* op1 = op0 + 8 * A5W;
#pragma unroll
            for (int i = 0; i < 4; i++) {
                *reinterpret_cast<uint32_t*>(op0 + 8 * i) = pack_bf16(o[4 * i] * f0, o[4 * i + 1] * f0);
                *reinterpret_cast<uint32_t*>(op1 + 8 * i) = pack_bf16(o[4 * i + 2] * f1, o[4 * i + 3] * f1);
            }
        }
    }
}

__global__ void __launch_bounds__(256, 2)
attn_kernel(const __grid_constant__ CUtensorMap mKV) {
    extern __shared__ uint8_t smem_raw[];
    const uint32_t sbase = (smem_u32(smem_raw) + 1023u) & ~1023u;
    const uint32_t bar_kfull = sbase + ATT_BAR_OFF;
    const uint32_t bar_vfull = bar_kfull + 8 * ATT_STAGES;
    const uint32_t bar_empty = bar_vfull + 8 * ATT_STAGES;
    const uint32_t bar_q = bar_empty + 8 * ATT_STAGES;
    const uint32_t bar_slow = bar_q + 16;
    const int warp_id = threadIdx.x >> 5;
    const int lane = threadIdx.x & 31;
    constexpr int NBLK = S_LEN / 128;
    TL_START(6)
    pdl_launch();
    const int my_tiles = (ATT_NTILES - (int)blockIdx.x + (int)gridDim.x - 1) / (int)gridDim.x;
    const int total_blocks = my_tiles * NBLK;

    auto issue_kv = [&](int g) {
        const int tile = blockIdx.x + (g >> 4) * gridDim.x;
        const int hd = tile >> 4;
        const int sn = g % ATT_STAGES;
        if (g >= ATT_STAGES) mbar_wait(bar_empty + 8 * sn, ((g / ATT_STAGES) - 1) & 1);
        const uint32_t skn = sbase + sn * 16384;
        mbar_expect_tx(bar_kfull + 8 * sn, 8192);
        tma_load_2d(skn, &mKV, DM + hd * DH, (g & 15) * 128, bar_kfull + 8 * sn);
        mbar_expect_tx(bar_vfull + 8 * sn, 8192);
        tma_load_2d(skn + 8192, &mKV, 2 * DM + hd * DH, (g & 15) * 128, bar_vfull + 8 * sn);
    };
    auto issue_q = [&](int it) {
        const int tile = blockIdx.x + it * gridDim.x;
        mbar_expect_tx(bar_q + 8 * (it & 1), 8192);
        tma_load_2d(sbase + ATT_Q_OFF + (it & 1) * 8192, &mKV, (tile >> 4) * DH, (tile & 15) * 128, bar_q + 8 * (it & 1));
    };

    if (threadIdx.x == 0) {
        for (int s = 0; s < ATT_STAGES; s++) {
            mbar_init(bar_kfull + 8 * s, 1);
            mbar_init(bar_vfull + 8 * s, 1);
            mbar_init(bar_empty + 8 * s, 2);
        }
        mbar_init(bar_q, 1);
        mbar_init(bar_q + 8, 1);
        mbar_init(bar_slow, 1);
        asm volatile("fence.mbarrier_init.release.cluster;" ::: "memory");
        prefetch_tmap(&mKV);
        pdl_wait();
        issue_q(0);
#pragma unroll
        for (int j = 0; j < ATT_DIST; j++) issue_kv(j);
    }
    {
        asm volatile("st.shared.v4.b32 [%0], {%1, %1, %1, %1};" ::"r"(sbase + ATT_ONES_OFF + threadIdx.x * 16), "r"(0x3F803F80u) : "memory");
        const int r = threadIdx.x >> 2, ch = threadIdx.x & 3;
        const uint32_t w0 = (ch == ((r >> 1) & 3)) ? 0x00003F80u : 0u;
        asm volatile("st.shared.v4.b32 [%0], {%1, %2, %2, %2};" ::"r"(sbase + ATT_KEXT_OFF + threadIdx.x * 16), "r"(w0), "r"(0u) : "memory");
    }
    fence_proxy_async();
    __syncthreads();
    pdl_wait();

    const int cq = (lane & 3) * 2;
    constexpr uint32_t HI = desc_hi(512, 2);
    const uint32_t dk0 = desc_lo(sbase, 16);
    const uint32_t dv0 = desc_lo(sbase + 8192, ATT_ONES_OFF - 8192);
    const uint32_t dke = desc_lo(sbase + ATT_KEXT_OFF, 16);
    int stage = 0;
    uint32_t phase = 0;
    uint32_t bad_tiles = 0;
#pragma unroll 1
    for (int it = 0; it < my_tiles; it++) {
        const int tile = blockIdx.x + it * gridDim.x;
        const int head = tile >> 4;
        const int row0 = (tile & 15) * 128 + warp_id * 16 + (lane >> 2);
        const uint32_t dq = desc_lo(sbase + ATT_Q_OFF + (it & 1) * 8192 + (threadIdx.x >> 7) * 4096, 16);
        if (threadIdx.x == 0 && it + 1 < my_tiles) issue_q(it + 1);
        float o[20];
#pragma unroll
        for (int i = 0; i < 20; i++) o[i] = 0.f;
        float s0[32], s1[32];
        uint32_t p[16];
#pragma unroll
        for (int i = 0; i < 16; i++) p[i] = 0u;
        mbar_wait(bar_q + 8 * (it & 1), (it >> 1) & 1);
        mbar_wait(bar_kfull + 8 * stage, phase);
        wgmma_fence();
        wgmma_ss_n64_tb0(s0, dq, HI, dk0 + stage * 1024, HI, 0);
        wgmma_ss_n64_tb0(s0, dq + 2, HI, dk0 + stage * 1024 + 2, HI, 1);
        wgmma_commit();
        wgmma_wait<0>();
        float m0 = -INFINITY, m1 = -INFINITY;
        row_max(s0, m0, m1);
        const uint32_t e0 = (lane & 3) == 0 ? (pack_bf16(-m0, 0.f) & 0xFFFFu) : 0u;
        const uint32_t e1 = (lane & 3) == 0 ? (pack_bf16(-m1, 0.f) & 0xFFFFu) : 0u;
        wgmma_fence();
        wgmma_rs_n64_tb0(s0, e0, e1, 0u, 0u, dke, HI, 1);
        wgmma_commit();
        mbar_wait(bar_vfull + 8 * stage, phase);
        wgmma_wait<0>();
        uint32_t dv_prev = dv0 + stage * 1024 - ((uint32_t)(stage * 1024) << 16);
        int pstage = stage;
#pragma unroll 1
        for (int j = 0; j < NBLK; j++) {
            if (threadIdx.x == 0 && it * NBLK + j + ATT_DIST < total_blocks) issue_kv(it * NBLK + j + ATT_DIST);
            __syncwarp();
            const uint32_t dk = dk0 + stage * 1024;
            const uint32_t dv = dv0 + stage * 1024 - ((uint32_t)(stage * 1024) << 16);
            attn_step(s0, s1, p, o, dq, e0, e1, dke, dk + 256, dv_prev, j > 0 ? bar_empty + 8 * pstage : 0u);
            int nstage = stage + 1;
            uint32_t nphase = phase;
            if (nstage == ATT_STAGES) { nstage = 0; nphase ^= 1; }
            uint32_t dkn = dk;
            if (j + 1 < NBLK) {
                mbar_wait(bar_kfull + 8 * nstage, nphase);
                dkn = dk0 + nstage * 1024;
            }
            mbar_wait(bar_vfull + 8 * stage, phase);
            attn_step(s1, s0, p, o, dq, e0, e1, dke, dkn, dv, 0u);
            dv_prev = dv + 256 - (256u << 16);
            pstage = stage;
            stage = nstage;
            phase = nphase;
        }
        wgmma_fence();
#pragma unroll
        for (int t = 0; t < 4; t++)
            wgmma_rs_n40_tb1(o, p[4 * t], p[4 * t + 1], p[4 * t + 2], p[4 * t + 3], dv_prev + t * 64, HI, 1);
        wgmma_commit();
        wgmma_wait<0>();
        if ((threadIdx.x & 127) == 0) mbar_arrive(bar_empty + 8 * pstage);
        bool ok = (o[16] <= 1.8446744e19f) && (o[18] <= 1.8446744e19f);
#pragma unroll
        for (int i = 0; i < 16; i++) ok = ok && (fabsf(o[i]) <= 3.0e38f);
        const float f0 = g_gate[row0] / o[16], f1 = g_gate[row0 + 8] / o[18];
        bf16* op0 = g_a5 + (size_t)row0 * A5W + head * DH + cq;
        bf16* op1 = op0 + 8 * A5W;
#pragma unroll
        for (int i = 0; i < 4; i++) {
            *reinterpret_cast<uint32_t*>(op0 + 8 * i) = pack_bf16(o[4 * i] * f0, o[4 * i + 1] * f0);
            *reinterpret_cast<uint32_t*>(op1 + 8 * i) = pack_bf16(o[4 * i + 2] * f1, o[4 * i + 3] * f1);
        }
        if (__syncthreads_or(!ok)) bad_tiles |= 1u << it;
    }

    if (bad_tiles) attn_exact(&mKV, sbase, bad_tiles, my_tiles);
    TL_END(6)
}

typedef CUresult (*EncodeFn)(CUtensorMap*, CUtensorMapDataType, cuuint32_t, void*, const cuuint64_t*, const cuuint64_t*,
                             const cuuint32_t*, const cuuint32_t*, CUtensorMapInterleave, CUtensorMapSwizzle,
                             CUtensorMapL2promotion, CUtensorMapFloatOOBfill);

static CUtensorMap make_map(EncodeFn fn, const void* ptr, int rows, int cols, int box_cols, int box_rows,
                            CUtensorMapSwizzle swz) {
    CUtensorMap m;
    cuuint64_t dims[2] = {(cuuint64_t)cols, (cuuint64_t)rows};
    cuuint64_t strides[1] = {(cuuint64_t)cols * 2};
    cuuint32_t box[2] = {(cuuint32_t)box_cols, (cuuint32_t)box_rows};
    cuuint32_t es[2] = {1, 1};
    fn(&m, CU_TENSOR_MAP_DATA_TYPE_BFLOAT16, 2, const_cast<void*>(ptr), dims, strides, box, es,
       CU_TENSOR_MAP_INTERLEAVE_NONE, swz, CU_TENSOR_MAP_L2_PROMOTION_L2_256B, CU_TENSOR_MAP_FLOAT_OOB_FILL_NONE);
    return m;
}

template <typename... KArgs, typename... Args>
static void launch_ex(void (*kern)(KArgs...), int grid, int block, int smem, cudaStream_t st, int cluster, Args... args) {
    cudaLaunchConfig_t cfg = {};
    cfg.gridDim = dim3(grid);
    cfg.blockDim = dim3(block);
    cfg.dynamicSmemBytes = smem;
    cfg.stream = st;
    cudaLaunchAttribute at[2];
    at[0].id = cudaLaunchAttributeProgrammaticStreamSerialization;
    at[0].val.programmaticStreamSerializationAllowed = 1;
    at[1].id = cudaLaunchAttributeClusterDimension;
    at[1].val.clusterDim.x = cluster;
    at[1].val.clusterDim.y = 1;
    at[1].val.clusterDim.z = 1;
    cfg.attrs = at;
    cfg.numAttrs = cluster > 1 ? 2 : 1;
    cudaLaunchKernelEx(&cfg, kern, KArgs(args)...);
}

extern "C" void kernel_launch(void* const* d_in, const int* in_sizes, int n_in, void* d_out, int out_size) {
    const bf16* x = (const bf16*)d_in[0];
    const bf16* wqkv = (const bf16*)d_in[1];
    const bf16* wo = (const bf16*)d_in[2];
    const bf16* w1 = (const bf16*)d_in[4];
    const bf16* w2 = (const bf16*)d_in[5];
    const bf16* w3 = (const bf16*)d_in[6];
    const bf16* w4 = (const bf16*)d_in[7];
    const bf16* gate_w = (const bf16*)d_in[8];

    static EncodeFn enc = nullptr;
    static void *p_qkv, *p_h, *p_x1, *p_a5;
    using G1 = GemmSmem<256, 4>;
    using G2 = GemmSmem<128, 5>;
    using G3 = GemmSmem<224, 4>;
    if (!enc) {
        void* fn = nullptr;
        cudaDriverEntryPointQueryResult qres;
        cudaGetDriverEntryPoint("cuTensorMapEncodeTiled", &fn, cudaEnableDefault, &qres);
        enc = (EncodeFn)fn;
        cudaGetSymbolAddress(&p_qkv, g_qkv);
        cudaGetSymbolAddress(&p_h, g_h);
        cudaGetSymbolAddress(&p_x1, g_x1);
        cudaGetSymbolAddress(&p_a5, g_a5);
        cudaFuncSetAttribute(gemm_kernel<1, 256, 4>, cudaFuncAttributeMaxDynamicSharedMemorySize, G1::TOTAL);
        cudaFuncSetAttribute(gemm_kernel<2, 128, 5>, cudaFuncAttributeMaxDynamicSharedMemorySize, G2::TOTAL);
        cudaFuncSetAttribute(gemm_kernel<3, 224, 4>, cudaFuncAttributeMaxDynamicSharedMemorySize, G3::TOTAL);
        cudaFuncSetAttribute(gemm_kernel<5, 128, 5>, cudaFuncAttributeMaxDynamicSharedMemorySize, G2::TOTAL);
        cudaFuncSetAttribute(attn_kernel, cudaFuncAttributeMaxDynamicSharedMemorySize, ATT_SMEM);
    }
    const CUtensorMapSwizzle SW128 = CU_TENSOR_MAP_SWIZZLE_128B, SW64 = CU_TENSOR_MAP_SWIZZLE_64B;
    CUtensorMap mX = make_map(enc, x, S_LEN, DM, 64, 128, SW128);
    CUtensorMap mWqkv = make_map(enc, wqkv, DM, 3 * DM, 64, 64, SW128);
    CUtensorMap mW1 = make_map(enc, w1, DM, DM, 64, 64, SW128);
    CUtensorMap mW2 = make_map(enc, w2, DM, DM, 64, 64, SW128);
    CUtensorMap mW3 = make_map(enc, w3, DM, FF, 64, 64, SW128);
    CUtensorMap mW4 = make_map(enc, w4, FF, DM, 64, 64, SW128);
    CUtensorMap mWo = make_map(enc, wo, DM, DM, 64, 64, SW128);
    CUtensorMap mQKVst = make_map(enc, p_qkv, S_LEN, 3 * DM, 64, 64, SW128);
    CUtensorMap mKV = make_map(enc, p_qkv, S_LEN, 3 * DM, 32, 128, SW64);
    CUtensorMap mHst = make_map(enc, p_h, S_LEN, DM, 64, 64, SW128);
    CUtensorMap mHld = make_map(enc, p_h, S_LEN, DM, 64, 128, SW128);
    CUtensorMap mX1st = make_map(enc, p_x1, S_LEN, DM, 64, 64, SW128);
    CUtensorMap mX1ld = make_map(enc, p_x1, S_LEN, DM, 64, 128, SW128);
    CUtensorMap mA5st = make_map(enc, p_a5, S_LEN, A5W, 64, 64, SW128);
    CUtensorMap mA5st32 = make_map(enc, p_a5, S_LEN, A5W, 32, 64, SW64);
    CUtensorMap mA5ld = make_map(enc, p_a5, S_LEN, A5W, 64, 128, SW128);
    CUtensorMap mOut = make_map(enc, d_out, S_LEN, DM, 64, 64, SW128);

    cudaStream_t st = cudaStreamPerThread;
    prep_kernel<<<256 + 72, 256, 0, st>>>(x, gate_w, w1, w3);
    launch_ex(gemm_kernel<1, 256, 4>, 132, 384, G1::TOTAL, st, 2, mX, mWqkv, mW1, mQKVst, mHst, x, 16, 16);
    launch_ex(attn_kernel, ATT_GRID, ATT_THREADS, ATT_SMEM, st, 1, mKV);
    launch_ex(gemm_kernel<2, 128, 5>, 128, 384, G2::TOTAL, st, 2, mHld, mW2, mW2, mX1st, mX1st, x, 8, 16);
    launch_ex(gemm_kernel<3, 224, 4>, 132, 384, G3::TOTAL, st, 2, mX1ld, mW3, mW3, mA5st, mA5st32, x, 16, 16);
    launch_ex(gemm_kernel<5, 128, 5>, 128, 384, G2::TOTAL, st, 2, mA5ld, mWo, mW4, mOut, mOut, (const bf16*)p_x1, 8, 72);
}
```

```cpp
#include <cuda_runtime.h>
#include <cuda_bf16.h>
#include <cuda.h>
#include <stdint.h>

typedef __nv_bfloat16 bf16;

constexpr int S_LEN = 2048;
constexpr int DM = 1024;
constexpr int FF = 3584;
constexpr int NH = 32;
constexpr int DH = 32;
constexpr int A5W = DM + FF;

__device__ __align__(1024) bf16 g_qkv[S_LEN * 3 * DM];
__device__ __align__(1024) bf16 g_h[S_LEN * DM];
__device__ __align__(1024) bf16 g_x1[S_LEN * DM];
__device__ __align__(1024) bf16 g_a5[S_LEN * A5W];
__device__ __align__(16) float g_mean1[S_LEN];
__device__ __align__(16) float g_rstd1[S_LEN];
__device__ __align__(16) float g_gate[S_LEN];
__device__ __align__(16) float g_omg[S_LEN];
__device__ __align__(16) float g_cs1[DM];
__device__ __align__(16) float g_cs3[FF];
__device__ __align__(16) float2 g_stat2[S_LEN * 8];
__device__ int g_bad[NH * 16];

#define TL_START(k)
#define TL_END(k)

__device__ __forceinline__ uint32_t smem_u32(const void* p) { return (uint32_t)__cvta_generic_to_shared(p); }

__device__ __forceinline__ void mbar_init(uint32_t bar, uint32_t count) {
    asm volatile("mbarrier.init.shared::cta.b64 [%0], %1;" ::"r"(bar), "r"(count));
}
__device__ __forceinline__ void mbar_expect_tx(uint32_t bar, uint32_t bytes) {
    asm volatile("mbarrier.arrive.expect_tx.shared::cta.b64 _, [%0], %1;" ::"r"(bar), "r"(bytes) : "memory");
}
__device__ __forceinline__ void mbar_arrive(uint32_t bar) {
    asm volatile("mbarrier.arrive.shared::cta.b64 _, [%0];" ::"r"(bar) : "memory");
}
__device__ __forceinline__ bool mbar_try_wait(uint32_t bar, uint32_t parity) {
    uint32_t ok;
    asm volatile(
        "{\n.reg .pred p;\n"
        "mbarrier.try_wait.parity.shared::cta.b64 p, [%1], %2;\n"
        "selp.u32 %0, 1, 0, p;\n}\n"
        : "=r"(ok)
        : "r"(bar), "r"(parity)
        : "memory");
    return ok != 0;
}
__device__ __forceinline__ void mbar_wait(uint32_t bar, uint32_t parity) {
    uint32_t spins = 0;
    while (!mbar_try_wait(bar, parity)) {
        if (++spins > (1u << 24)) __trap();
    }
}
__device__ __forceinline__ void tma_load_2d(uint32_t dst, const CUtensorMap* map, int c0, int c1, uint32_t bar) {
    asm volatile(
        "cp.async.bulk.tensor.2d.shared::cluster.global.mbarrier::complete_tx::bytes [%0], [%1, {%3, %4}], [%2];"
        ::"r"(dst), "l"(map), "r"(bar), "r"(c0), "r"(c1)
        : "memory");
}
__device__ __forceinline__ void tma_store_2d(const CUtensorMap* map, uint32_t src, int c0, int c1) {
    asm volatile("cp.async.bulk.tensor.2d.global.shared::cta.bulk_group [%0, {%2, %3}], [%1];"
                 ::"l"(map), "r"(src), "r"(c0), "r"(c1)
                 : "memory");
}
__device__ __forceinline__ void tma_load_2d_mc(uint32_t dst, const CUtensorMap* map, int c0, int c1, uint32_t bar, uint16_t mask) {
    asm volatile(
        "cp.async.bulk.tensor.2d.shared::cluster.global.mbarrier::complete_tx::bytes.multicast::cluster [%0], [%1, {%3, %4}], [%2], %5;"
        ::"r"(dst), "l"(map), "r"(bar), "r"(c0), "r"(c1), "h"(mask)
        : "memory");
}
__device__ __forceinline__ void mbar_arrive_cluster(uint32_t bar, uint32_t cta) {
    asm volatile(
        "{\n.reg .b32 ra;\nmapa.shared::cluster.u32 ra, %0, %1;\n"
        "mbarrier.arrive.shared::cluster.b64 _, [ra];\n}\n" ::"r"(bar), "r"(cta)
        : "memory");
}
__device__ __forceinline__ void cluster_sync_all() {
    asm volatile("barrier.cluster.arrive.release.aligned;\nbarrier.cluster.wait.acquire.aligned;" ::: "memory");
}
__device__ __forceinline__ uint32_t cluster_rank() { uint32_t r; asm volatile("mov.u32 %0, %%cluster_ctarank;" : "=r"(r)); return r; }
__device__ __forceinline__ void pdl_wait() { asm volatile("griddepcontrol.wait;" ::: "memory"); }
__device__ __forceinline__ void pdl_launch() { asm volatile("griddepcontrol.launch_dependents;" ::: "memory"); }
__device__ __forceinline__ void bulk_commit() { asm volatile("cp.async.bulk.commit_group;" ::: "memory"); }
__device__ __forceinline__ void bulk_wait_read0() { asm volatile("cp.async.bulk.wait_group.read 0;" ::: "memory"); }
__device__ __forceinline__ void bulk_wait0() { asm volatile("cp.async.bulk.wait_group 0;" ::: "memory"); }
__device__ __forceinline__ void fence_proxy_async() { asm volatile("fence.proxy.async.shared::cta;" ::: "memory"); }
__device__ __forceinline__ void named_bar_sync(int id, int n) { asm volatile("bar.sync %0, %1;" ::"r"(id), "r"(n) : "memory"); }
__device__ __forceinline__ void named_bar_arrive(int id, int n) { asm volatile("bar.arrive %0, %1;" ::"r"(id), "r"(n) : "memory"); }
__device__ __forceinline__ void wgmma_fence() { asm volatile("wgmma.fence.sync.aligned;" ::: "memory"); }
__device__ __forceinline__ void wgmma_commit() { asm volatile("wgmma.commit_group.sync.aligned;" ::: "memory"); }
template <int N>
__device__ __forceinline__ void wgmma_wait() { asm volatile("wgmma.wait_group.sync.aligned %0;" ::"n"(N) : "memory"); }
__device__ __forceinline__ void prefetch_tmap(const CUtensorMap* m) {
    asm volatile("prefetch.tensormap [%0];" ::"l"(m) : "memory");
}
template <int R>
__device__ __forceinline__ void reg_alloc() { asm volatile("setmaxnreg.inc.sync.aligned.u32 %0;" ::"n"(R)); }
template <int R>
__device__ __forceinline__ void reg_dealloc() { asm volatile("setmaxnreg.dec.sync.aligned.u32 %0;" ::"n"(R)); }
__device__ __forceinline__ void stmatrix_x4(uint32_t addr, uint32_t r0, uint32_t r1, uint32_t r2, uint32_t r3) {
    asm volatile("stmatrix.sync.aligned.m8n8.x4.shared.b16 [%0], {%1, %2, %3, %4};"
                 ::"r"(addr), "r"(r0), "r"(r1), "r"(r2), "r"(r3)
                 : "memory");
}
__device__ __forceinline__ uint32_t pack_bf16(float lo, float hi) {
    uint32_t r;
    asm("cvt.rn.bf16x2.f32 %0, %1, %2;" : "=r"(r) : "f"(hi), "f"(lo));
    return r;
}
__device__ __forceinline__ float bf16_round(float v) { return __bfloat162float(__float2bfloat16_rn(v)); }
__device__ __forceinline__ float ex2(float x) {
    float y;
    asm volatile("ex2.approx.ftz.f32 %0, %1;" : "=f"(y) : "f"(x));
    return y;
}
__device__ __forceinline__ float tanh_fast(float x) {
    float y;
    asm("tanh.approx.f32 %0, %1;" : "=f"(y) : "f"(x));
    return y;
}
__device__ __forceinline__ float gelu_tanh(float v) {
    float u = 0.7978845608028654f * (v + 0.044715f * v * v * v);
    float hv = 0.5f * v;
    return fmaf(hv, tanh_fast(u), hv);
}
__device__ __forceinline__ uint32_t desc_lo(uint32_t addr, uint32_t lbo_bytes) {
    return ((addr & 0x3FFFF) >> 4) | (((lbo_bytes >> 4) & 0x3FFF) << 16);
}
__host__ __device__ constexpr uint32_t desc_hi(uint32_t sbo_bytes, uint32_t swz) {
    return ((sbo_bytes >> 4) & 0x3FFF) | (swz << 30);
}

__device__ __forceinline__ void wgmma_ss_n128_tb1(float (&d)[64], uint32_t alo, uint32_t ahi, uint32_t blo, uint32_t bhi, int scale_d) {
    asm volatile("{\n.reg .pred p;\n.reg .b64 da, db;\nsetp.ne.b32 p, %68, 0;\nmov.b64 da, {%64, %65};\nmov.b64 db, {%66, %67};\n"
        "wgmma.mma_async.sync.aligned.m64n128k16.f32.bf16.bf16 {%0, %1, %2, %3, %4, %5, %6, %7, %8, %9, %10, %11, %12, %13, %14, %15, %16, %17, %18, %19, %20, %21, %22, %23, %24, %25, %26, %27, %28, %29, %30, %31, %32, %33, %34, %35, %36, %37, %38, %39, %40, %41, %42, %43, %44, %45, %46, %47, %48, %49, %50, %51, %52, %53, %54, %55, %56, %57, %58, %59, %60, %61, %62, %63}, da, db, p, 1, 1, 0, 1;\n}\n"
        : "+f"(d[0]), "+f"(d[1]), "+f"(d[2]), "+f"(d[3]), "+f"(d[4]), "+f"(d[5]), "+f"(d[6]), "+f"(d[7]), "+f"(d[8]), "+f"(d[9]), "+f"(d[10]), "+f"(d[11]), "+f"(d[12]), "+f"(d[13]), "+f"(d[14]), "+f"(d[15]), "+f"(d[16]), "+f"(d[17]), "+f"(d[18]), "+f"(d[19]), "+f"(d[20]), "+f"(d[21]), "+f"(d[22]), "+f"(d[23]), "+f"(d[24]), "+f"(d[25]), "+f"(d[26]), "+f"(d[27]), "+f"(d[28]), "+f"(d[29]), "+f"(d[30]), "+f"(d[31]), "+f"(d[32]), "+f"(d[33]), "+f"(d[34]), "+f"(d[35]), "+f"(d[36]), "+f"(d[37]), "+f"(d[38]), "+f"(d[39]), "+f"(d[40]), "+f"(d[41]), "+f"(d[42]), "+f"(d[43]), "+f"(d[44]), "+f"(d[45]), "+f"(d[46]), "+f"(d[47]), "+f"(d[48]), "+f"(d[49]), "+f"(d[50]), "+f"(d[51]), "+f"(d[52]), "+f"(d[53]), "+f"(d[54]), "+f"(d[55]), "+f"(d[56]), "+f"(d[57]), "+f"(d[58]), "+f"(d[59]), "+f"(d[60]), "+f"(d[61]), "+f"(d[62]), "+f"(d[63])
        : "r"(alo), "r"(ahi), "r"(blo), "r"(bhi), "r"(scale_d));
}

__device__ __forceinline__ void wgmma_ss_n192_tb1(float (&d)[96], uint32_t alo, uint32_t ahi, uint32_t blo, uint32_t bhi, int scale_d) {
    asm volatile("{\n.reg .pred p;\n.reg .b64 da, db;\nsetp.ne.b32 p, %100, 0;\nmov.b64 da, {%96, %97};\nmov.b64 db, {%98, %99};\n"
        "wgmma.mma_async.sync.aligned.m64n192k16.f32.bf16.bf16 {%0, %1, %2, %3, %4, %5, %6, %7, %8, %9, %10, %11, %12, %13, %14, %15, %16, %17, %18, %19, %20, %21, %22, %23, %24, %25, %26, %27, %28, %29, %30, %31, %32, %33, %34, %35, %36, %37, %38, %39, %40, %41, %42, %43, %44, %45, %46, %47, %48, %49, %50, %51, %52, %53, %54, %55, %56, %57, %58, %59, %60, %61, %62, %63, %64, %65, %66, %67, %68, %69, %70, %71, %72, %73, %74, %75, %76, %77, %78, %79, %80, %81, %82, %83, %84, %85, %86, %87, %88, %89, %90, %91, %92, %93, %94, %95}, da, db, p, 1, 1, 0, 1;\n}\n"
        : "+f"(d[0]), "+f"(d[1]), "+f"(d[2]), "+f"(d[3]), "+f"(d[4]), "+f"(d[5]), "+f"(d[6]), "+f"(d[7]), "+f"(d[8]), "+f"(d[9]), "+f"(d[10]), "+f"(d[11]), "+f"(d[12]), "+f"(d[13]), "+f"(d[14]), "+f"(d[15]), "+f"(d[16]), "+f"(d[17]), "+f"(d[18]), "+f"(d[19]), "+f"(d[20]), "+f"(d[21]), "+f"(d[22]), "+f"(d[23]), "+f"(d[24]), "+f"(d[25]), "+f"(d[26]), "+f"(d[27]), "+f"(d[28]), "+f"(d[29]), "+f"(d[30]), "+f"(d[31]), "+f"(d[32]), "+f"(d[33]), "+f"(d[34]), "+f"(d[35]), "+f"(d[36]), "+f"(d[37]), "+f"(d[38]), "+f"(d[39]), "+f"(d[40]), "+f"(d[41]), "+f"(d[42]), "+f"(d[43]), "+f"(d[44]), "+f"(d[45]), "+f"(d[46]), "+f"(d[47]), "+f"(d[48]), "+f"(d[49]), "+f"(d[50]), "+f"(d[51]), "+f"(d[52]), "+f"(d[53]), "+f"(d[54]), "+f"(d[55]), "+f"(d[56]), "+f"(d[57]), "+f"(d[58]), "+f"(d[59]), "+f"(d[60]), "+f"(d[61]), "+f"(d[62]), "+f"(d[63]), "+f"(d[64]), "+f"(d[65]), "+f"(d[66]), "+f"(d[67]), "+f"(d[68]), "+f"(d[69]), "+f"(d[70]), "+f"(d[71]), "+f"(d[72]), "+f"(d[73]), "+f"(d[74]), "+f"(d[75]), "+f"(d[76]), "+f"(d[77]), "+f"(d[78]), "+f"(d[79]), "+f"(d[80]), "+f"(d[81]), "+f"(d[82]), "+f"(d[83]), "+f"(d[84]), "+f"(d[85]), "+f"(d[86]), "+f"(d[87]), "+f"(d[88]), "+f"(d[89]), "+f"(d[90]), "+f"(d[91]), "+f"(d[92]), "+f"(d[93]), "+f"(d[94]), "+f"(d[95])
        : "r"(alo), "r"(ahi), "r"(blo), "r"(bhi), "r"(scale_d));
}

__device__ __forceinline__ void wgmma_ss_n224_tb1(float (&d)[112], uint32_t alo, uint32_t ahi, uint32_t blo, uint32_t bhi, int scale_d) {
    asm volatile("{\n.reg .pred p;\n.reg .b64 da, db;\nsetp.ne.b32 p, %116, 0;\nmov.b64 da, {%112, %113};\nmov.b64 db, {%114, %115};\n"
        "wgmma.mma_async.sync.aligned.m64n224k16.f32.bf16.bf16 {%0, %1, %2, %3, %4, %5, %6, %7, %8, %9, %10, %11, %12, %13, %14, %15, %16, %17, %18, %19, %20, %21, %22, %23, %24, %25, %26, %27, %28, %29, %30, %31, %32, %33, %34, %35, %36, %37, %38, %39, %40, %41, %42, %43, %44, %45, %46, %47, %48, %49, %50, %51, %52, %53, %54, %55, %56, %57, %58, %59, %60, %61, %62, %63, %64, %65, %66, %67, %68, %69, %70, %71, %72, %73, %74, %75, %76, %77, %78, %79, %80, %81, %82, %83, %84, %85, %86, %87, %88, %89, %90, %91, %92, %93, %94, %95, %96, %97, %98, %99, %100, %101, %102, %103, %104, %105, %106, %107, %108, %109, %110, %111}, da, db, p, 1, 1, 0, 1;\n}\n"
        : "+f"(d[0]), "+f"(d[1]), "+f"(d[2]), "+f"(d[3]), "+f"(d[4]), "+f"(d[5]), "+f"(d[6]), "+f"(d[7]), "+f"(d[8]), "+f"(d[9]), "+f"(d[10]), "+f"(d[11]), "+f"(d[12]), "+f"(d[13]), "+f"(d[14]), "+f"(d[15]), "+f"(d[16]), "+f"(d[17]), "+f"(d[18]), "+f"(d[19]), "+f"(d[20]), "+f"(d[21]), "+f"(d[22]), "+f"(d[23]), "+f"(d[24]), "+f"(d[25]), "+f"(d[26]), "+f"(d[27]), "+f"(d[28]), "+f"(d[29]), "+f"(d[30]), "+f"(d[31]), "+f"(d[32]), "+f"(d[33]), "+f"(d[34]), "+f"(d[35]), "+f"(d[36]), "+f"(d[37]), "+f"(d[38]), "+f"(d[39]), "+f"(d[40]), "+f"(d[41]), "+f"(d[42]), "+f"(d[43]), "+f"(d[44]), "+f"(d[45]), "+f"(d[46]), "+f"(d[47]), "+f"(d[48]), "+f"(d[49]), "+f"(d[50]), "+f"(d[51]), "+f"(d[52]), "+f"(d[53]), "+f"(d[54]), "+f"(d[55]), "+f"(d[56]), "+f"(d[57]), "+f"(d[58]), "+f"(d[59]), "+f"(d[60]), "+f"(d[61]), "+f"(d[62]), "+f"(d[63]), "+f"(d[64]), "+f"(d[65]), "+f"(d[66]), "+f"(d[67]), "+f"(d[68]), "+f"(d[69]), "+f"(d[70]), "+f"(d[71]), "+f"(d[72]), "+f"(d[73]), "+f"(d[74]), "+f"(d[75]), "+f"(d[76]), "+f"(d[77]), "+f"(d[78]), "+f"(d[79]), "+f"(d[80]), "+f"(d[81]), "+f"(d[82]), "+f"(d[83]), "+f"(d[84]), "+f"(d[85]), "+f"(d[86]), "+f"(d[87]), "+f"(d[88]), "+f"(d[89]), "+f"(d[90]), "+f"(d[91]), "+f"(d[92]), "+f"(d[93]), "+f"(d[94]), "+f"(d[95]), "+f"(d[96]), "+f"(d[97]), "+f"(d[98]), "+f"(d[99]), "+f"(d[100]), "+f"(d[101]), "+f"(d[102]), "+f"(d[103]), "+f"(d[104]), "+f"(d[105]), "+f"(d[106]), "+f"(d[107]), "+f"(d[108]), "+f"(d[109]), "+f"(d[110]), "+f"(d[111])
        : "r"(alo), "r"(ahi), "r"(blo), "r"(bhi), "r"(scale_d));
}

__device__ __forceinline__ void wgmma_ss_n256_tb1(float (&d)[128], uint32_t alo, uint32_t ahi, uint32_t blo, uint32_t bhi, int scale_d) {
    asm volatile("{\n.reg .pred p;\n.reg .b64 da, db;\nsetp.ne.b32 p, %132, 0;\nmov.b64 da, {%128, %129};\nmov.b64 db, {%130, %131};\n"
        "wgmma.mma_async.sync.aligned.m64n256k16.f32.bf16.bf16 {%0, %1, %2, %3, %4, %5, %6, %7, %8, %9, %10, %11, %12, %13, %14, %15, %16, %17, %18, %19, %20, %21, %22, %23, %24, %25, %26, %27, %28, %29, %30, %31, %32, %33, %34, %35, %36, %37, %38, %39, %40, %41, %42, %43, %44, %45, %46, %47, %48, %49, %50, %51, %52, %53, %54, %55, %56, %57, %58, %59, %60, %61, %62, %63, %64, %65, %66, %67, %68, %69, %70, %71, %72, %73, %74, %75, %76, %77, %78, %79, %80, %81, %82, %83, %84, %85, %86, %87, %88, %89, %90, %91, %92, %93, %94, %95, %96, %97, %98, %99, %100, %101, %102, %103, %104, %105, %106, %107, %108, %109, %110, %111, %112, %113, %114, %115, %116, %117, %118, %119, %120, %121, %122, %123, %124, %125, %126, %127}, da, db, p, 1, 1, 0, 1;\n}\n"
        : "+f"(d[0]), "+f"(d[1]), "+f"(d[2]), "+f"(d[3]), "+f"(d[4]), "+f"(d[5]), "+f"(d[6]), "+f"(d[7]), "+f"(d[8]), "+f"(d[9]), "+f"(d[10]), "+f"(d[11]), "+f"(d[12]), "+f"(d[13]), "+f"(d[14]), "+f"(d[15]), "+f"(d[16]), "+f"(d[17]), "+f"(d[18]), "+f"(d[19]), "+f"(d[20]), "+f"(d[21]), "+f"(d[22]), "+f"(d[23]), "+f"(d[24]), "+f"(d[25]), "+f"(d[26]), "+f"(d[27]), "+f"(d[28]), "+f"(d[29]), "+f"(d[30]), "+f"(d[31]), "+f"(d[32]), "+f"(d[33]), "+f"(d[34]), "+f"(d[35]), "+f"(d[36]), "+f"(d[37]), "+f"(d[38]), "+f"(d[39]), "+f"(d[40]), "+f"(d[41]), "+f"(d[42]), "+f"(d[43]), "+f"(d[44]), "+f"(d[45]), "+f"(d[46]), "+f"(d[47]), "+f"(d[48]), "+f"(d[49]), "+f"(d[50]), "+f"(d[51]), "+f"(d[52]), "+f"(d[53]), "+f"(d[54]), "+f"(d[55]), "+f"(d[56]), "+f"(d[57]), "+f"(d[58]), "+f"(d[59]), "+f"(d[60]), "+f"(d[61]), "+f"(d[62]), "+f"(d[63]), "+f"(d[64]), "+f"(d[65]), "+f"(d[66]), "+f"(d[67]), "+f"(d[68]), "+f"(d[69]), "+f"(d[70]), "+f"(d[71]), "+f"(d[72]), "+f"(d[73]), "+f"(d[74]), "+f"(d[75]), "+f"(d[76]), "+f"(d[77]), "+f"(d[78]), "+f"(d[79]), "+f"(d[80]), "+f"(d[81]), "+f"(d[82]), "+f"(d[83]), "+f"(d[84]), "+f"(d[85]), "+f"(d[86]), "+f"(d[87]), "+f"(d[88]), "+f"(d[89]), "+f"(d[90]), "+f"(d[91]), "+f"(d[92]), "+f"(d[93]), "+f"(d[94]), "+f"(d[95]), "+f"(d[96]), "+f"(d[97]), "+f"(d[98]), "+f"(d[99]), "+f"(d[100]), "+f"(d[101]), "+f"(d[102]), "+f"(d[103]), "+f"(d[104]), "+f"(d[105]), "+f"(d[106]), "+f"(d[107]), "+f"(d[108]), "+f"(d[109]), "+f"(d[110]), "+f"(d[111]), "+f"(d[112]), "+f"(d[113]), "+f"(d[114]), "+f"(d[115]), "+f"(d[116]), "+f"(d[117]), "+f"(d[118]), "+f"(d[119]), "+f"(d[120]), "+f"(d[121]), "+f"(d[122]), "+f"(d[123]), "+f"(d[124]), "+f"(d[125]), "+f"(d[126]), "+f"(d[127])
        : "r"(alo), "r"(ahi), "r"(blo), "r"(bhi), "r"(scale_d));
}

__device__ __forceinline__ void wgmma_ss_n64_tb0(float (&d)[32], uint32_t alo, uint32_t ahi, uint32_t blo, uint32_t bhi, int scale_d) {
    asm volatile("{\n.reg .pred p;\n.reg .b64 da, db;\nsetp.ne.b32 p, %36, 0;\nmov.b64 da, {%32, %33};\nmov.b64 db, {%34, %35};\n"
        "wgmma.mma_async.sync.aligned.m64n64k16.f32.bf16.bf16 {%0, %1, %2, %3, %4, %5, %6, %7, %8, %9, %10, %11, %12, %13, %14, %15, %16, %17, %18, %19, %20, %21, %22, %23, %24, %25, %26, %27, %28, %29, %30, %31}, da, db, p, 1, 1, 0, 0;\n}\n"
        : "+f"(d[0]), "+f"(d[1]), "+f"(d[2]), "+f"(d[3]), "+f"(d[4]), "+f"(d[5]), "+f"(d[6]), "+f"(d[7]), "+f"(d[8]), "+f"(d[9]), "+f"(d[10]), "+f"(d[11]), "+f"(d[12]), "+f"(d[13]), "+f"(d[14]), "+f"(d[15]), "+f"(d[16]), "+f"(d[17]), "+f"(d[18]), "+f"(d[19]), "+f"(d[20]), "+f"(d[21]), "+f"(d[22]), "+f"(d[23]), "+f"(d[24]), "+f"(d[25]), "+f"(d[26]), "+f"(d[27]), "+f"(d[28]), "+f"(d[29]), "+f"(d[30]), "+f"(d[31])
        : "r"(alo), "r"(ahi), "r"(blo), "r"(bhi), "r"(scale_d));
}

__device__ __forceinline__ void wgmma_rs_n128_tb0(float (&d)[64], uint32_t a0, uint32_t a1, uint32_t a2, uint32_t a3, uint32_t blo, uint32_t bhi, int scale_d) {
    asm volatile("{\n.reg .pred p;\n.reg .b64 db;\nsetp.ne.b32 p, %70, 0;\nmov.b64 db, {%68, %69};\n"
        "wgmma.mma_async.sync.aligned.m64n128k16.f32.bf16.bf16 {%0, %1, %2, %3, %4, %5, %6, %7, %8, %9, %10, %11, %12, %13, %14, %15, %16, %17, %18, %19, %20, %21, %22, %23, %24, %25, %26, %27, %28, %29, %30, %31, %32, %33, %34, %35, %36, %37, %38, %39, %40, %41, %42, %43, %44, %45, %46, %47, %48, %49, %50, %51, %52, %53, %54, %55, %56, %57, %58, %59, %60, %61, %62, %63}, {%64, %65, %66, %67}, db, p, 1, 1, 0;\n}\n"
        : "+f"(d[0]), "+f"(d[1]), "+f"(d[2]), "+f"(d[3]), "+f"(d[4]), "+f"(d[5]), "+f"(d[6]), "+f"(d[7]), "+f"(d[8]), "+f"(d[9]), "+f"(d[10]), "+f"(d[11]), "+f"(d[12]), "+f"(d[13]), "+f"(d[14]), "+f"(d[15]), "+f"(d[16]), "+f"(d[17]), "+f"(d[18]), "+f"(d[19]), "+f"(d[20]), "+f"(d[21]), "+f"(d[22]), "+f"(d[23]), "+f"(d[24]), "+f"(d[25]), "+f"(d[26]), "+f"(d[27]), "+f"(d[28]), "+f"(d[29]), "+f"(d[30]), "+f"(d[31]), "+f"(d[32]), "+f"(d[33]), "+f"(d[34]), "+f"(d[35]), "+f"(d[36]), "+f"(d[37]), "+f"(d[38]), "+f"(d[39]), "+f"(d[40]), "+f"(d[41]), "+f"(d[42]), "+f"(d[43]), "+f"(d[44]), "+f"(d[45]), "+f"(d[46]), "+f"(d[47]), "+f"(d[48]), "+f"(d[49]), "+f"(d[50]), "+f"(d[51]), "+f"(d[52]), "+f"(d[53]), "+f"(d[54]), "+f"(d[55]), "+f"(d[56]), "+f"(d[57]), "+f"(d[58]), "+f"(d[59]), "+f"(d[60]), "+f"(d[61]), "+f"(d[62]), "+f"(d[63])
        : "r"(a0), "r"(a1), "r"(a2), "r"(a3), "r"(blo), "r"(bhi), "r"(scale_d));
}

__device__ __forceinline__ void wgmma_rs_n64_tb0(float (&d)[32], uint32_t a0, uint32_t a1, uint32_t a2, uint32_t a3, uint32_t blo, uint32_t bhi, int scale_d) {
    asm volatile("{\n.reg .pred p;\n.reg .b64 db;\nsetp.ne.b32 p, %38, 0;\nmov.b64 db, {%36, %37};\n"
        "wgmma.mma_async.sync.aligned.m64n64k16.f32.bf16.bf16 {%0, %1, %2, %3, %4, %5, %6, %7, %8, %9, %10, %11, %12, %13, %14, %15, %16, %17, %18, %19, %20, %21, %22, %23, %24, %25, %26, %27, %28, %29, %30, %31}, {%32, %33, %34, %35}, db, p, 1, 1, 0;\n}\n"
        : "+f"(d[0]), "+f"(d[1]), "+f"(d[2]), "+f"(d[3]), "+f"(d[4]), "+f"(d[5]), "+f"(d[6]), "+f"(d[7]), "+f"(d[8]), "+f"(d[9]), "+f"(d[10]), "+f"(d[11]), "+f"(d[12]), "+f"(d[13]), "+f"(d[14]), "+f"(d[15]), "+f"(d[16]), "+f"(d[17]), "+f"(d[18]), "+f"(d[19]), "+f"(d[20]), "+f"(d[21]), "+f"(d[22]), "+f"(d[23]), "+f"(d[24]), "+f"(d[25]), "+f"(d[26]), "+f"(d[27]), "+f"(d[28]), "+f"(d[29]), "+f"(d[30]), "+f"(d[31])
        : "r"(a0), "r"(a1), "r"(a2), "r"(a3), "r"(blo), "r"(bhi), "r"(scale_d));
}

__device__ __forceinline__ void wgmma_rs_n32_tb1(float (&d)[16], uint32_t a0, uint32_t a1, uint32_t a2, uint32_t a3, uint32_t blo, uint32_t bhi, int scale_d) {
    asm volatile("{\n.reg .pred p;\n.reg .b64 db;\nsetp.ne.b32 p, %22, 0;\nmov.b64 db, {%20, %21};\n"
        "wgmma.mma_async.sync.aligned.m64n32k16.f32.bf16.bf16 {%0, %1, %2, %3, %4, %5, %6, %7, %8, %9, %10, %11, %12, %13, %14, %15}, {%16, %17, %18, %19}, db, p, 1, 1, 1;\n}\n"
        : "+f"(d[0]), "+f"(d[1]), "+f"(d[2]), "+f"(d[3]), "+f"(d[4]), "+f"(d[5]), "+f"(d[6]), "+f"(d[7]), "+f"(d[8]), "+f"(d[9]), "+f"(d[10]), "+f"(d[11]), "+f"(d[12]), "+f"(d[13]), "+f"(d[14]), "+f"(d[15])
        : "r"(a0), "r"(a1), "r"(a2), "r"(a3), "r"(blo), "r"(bhi), "r"(scale_d));
}

__device__ __forceinline__ void wgmma_rs_n40_tb1(float (&d)[20], uint32_t a0, uint32_t a1, uint32_t a2, uint32_t a3, uint32_t blo, uint32_t bhi, int scale_d) {
    asm volatile("{\n.reg .pred p;\n.reg .b64 db;\nsetp.ne.b32 p, %26, 0;\nmov.b64 db, {%24, %25};\n"
        "wgmma.mma_async.sync.aligned.m64n40k16.f32.bf16.bf16 {%0, %1, %2, %3, %4, %5, %6, %7, %8, %9, %10, %11, %12, %13, %14, %15, %16, %17, %18, %19}, {%20, %21, %22, %23}, db, p, 1, 1, 1;\n}\n"
        : "+f"(d[0]), "+f"(d[1]), "+f"(d[2]), "+f"(d[3]), "+f"(d[4]), "+f"(d[5]), "+f"(d[6]), "+f"(d[7]), "+f"(d[8]), "+f"(d[9]), "+f"(d[10]), "+f"(d[11]), "+f"(d[12]), "+f"(d[13]), "+f"(d[14]), "+f"(d[15]), "+f"(d[16]), "+f"(d[17]), "+f"(d[18]), "+f"(d[19])
        : "r"(a0), "r"(a1), "r"(a2), "r"(a3), "r"(blo), "r"(bhi), "r"(scale_d));
}

template <int BN>
__device__ __forceinline__ void wgmma_tile(float (&d)[BN / 2], uint32_t da, uint32_t db, int sd) {
    constexpr uint32_t HI = desc_hi(1024, 1);
    if constexpr (BN == 128) wgmma_ss_n128_tb1(d, da, HI, db, HI, sd);
    else if constexpr (BN == 192) wgmma_ss_n192_tb1(d, da, HI, db, HI, sd);
    else if constexpr (BN == 224) wgmma_ss_n224_tb1(d, da, HI, db, HI, sd);
    else wgmma_ss_n256_tb1(d, da, HI, db, HI, sd);
}

__global__ void __launch_bounds__(256) prep_kernel(const bf16* __restrict__ x, const bf16* __restrict__ gate_w,
                                                   const bf16* __restrict__ w1, const bf16* __restrict__ w3) {
    const int tid = threadIdx.x;
    TL_START(0)
    pdl_launch();
    if (blockIdx.x < 256) {
        const int row = blockIdx.x * 8 + (tid >> 5);
        const int lane = tid & 31;
        const uint4* xr = reinterpret_cast<const uint4*>(x + (size_t)row * DM);
        const uint4* gw = reinterpret_cast<const uint4*>(gate_w);
        float v[32];
        float gsum = 0.f, sum = 0.f;
#pragma unroll
        for (int i = 0; i < 4; i++) {
            uint4 a = xr[lane + 32 * i];
            uint4 b = gw[lane + 32 * i];
            const uint32_t aa[4] = {a.x, a.y, a.z, a.w};
            const uint32_t bb[4] = {b.x, b.y, b.z, b.w};
#pragma unroll
            for (int j = 0; j < 4; j++) {
                float x0 = __uint_as_float(aa[j] << 16), x1 = __uint_as_float(aa[j] & 0xFFFF0000u);
                float g0 = __uint_as_float(bb[j] << 16), g1 = __uint_as_float(bb[j] & 0xFFFF0000u);
                v[i * 8 + j * 2] = x0;
                v[i * 8 + j * 2 + 1] = x1;
                sum += x0 + x1;
                gsum += bf16_round(x0 * g0) + bf16_round(x1 * g1);
            }
        }
#pragma unroll
        for (int o = 16; o > 0; o >>= 1) {
            sum += __shfl_xor_sync(0xffffffffu, sum, o);
            gsum += __shfl_xor_sync(0xffffffffu, gsum, o);
        }
        const float mean = sum * (1.0f / DM);
        float m2 = 0.f;
#pragma unroll
        for (int i = 0; i < 32; i++) {
            float d = v[i] - mean;
            m2 += d * d;
        }
#pragma unroll
        for (int o = 16; o > 0; o >>= 1) m2 += __shfl_xor_sync(0xffffffffu, m2, o);
        if (lane == 0) {
            g_mean1[row] = mean;
            g_rstd1[row] = rsqrtf(m2 * (1.0f / DM) + 1e-5f);
            float logit = bf16_round(gsum);
            float g = bf16_round(1.0f / (1.0f + __expf(-logit)));
            g_gate[row] = g;
            g_omg[row] = bf16_round(1.0f - g);
        }
    } else {
        __shared__ float red[32][65];
        const int strip = blockIdx.x - 256;
        const bf16* w;
        float* out;
        int ld, col0;
        if (strip < 16) { w = w1; ld = DM; col0 = strip * 64; out = g_cs1; }
        else { w = w3; ld = FF; col0 = (strip - 16) * 64; out = g_cs3; }
        const int cg = tid & 7;
        const int rg = tid >> 3;
        float acc[8];
#pragma unroll
        for (int j = 0; j < 8; j++) acc[j] = 0.f;
#pragma unroll 8
        for (int r = 0; r < 32; r++) {
            uint4 a = *reinterpret_cast<const uint4*>(w + (size_t)(r * 32 + rg) * ld + col0 + cg * 8);
            const uint32_t aa[4] = {a.x, a.y, a.z, a.w};
#pragma unroll
            for (int j = 0; j < 4; j++) {
                acc[2 * j] += __uint_as_float(aa[j] << 16);
                acc[2 * j + 1] += __uint_as_float(aa[j] & 0xFFFF0000u);
            }
        }
#pragma unroll
        for (int j = 0; j < 8; j++) red[rg][cg * 8 + j] = acc[j];
        __syncthreads();
        if (tid < 64) {
            float s = 0.f;
#pragma unroll
            for (int r = 0; r < 32; r++) s += red[r][tid];
            out[col0 + tid] = s;
        }
    }
    TL_END(0)
}

#define RELEASE_STAGE(b) if (tid_wg < 2) mbar_arrive_cluster(b, tid_wg)
template <int BN, int STAGES>
struct GemmSmem {
    static constexpr int A_BYTES = 128 * 64 * 2;
    static constexpr int B_BOXES = (BN + 63) / 64;
    static constexpr int B_BYTES = B_BOXES * 64 * 64 * 2;
    static constexpr int STAGE_BYTES = A_BYTES + B_BYTES;
    static constexpr int STG_OFF = STAGES * STAGE_BYTES;
    static constexpr int BAR_OFF = STAGES * STAGE_BYTES + 2 * 16384;
    static constexpr int TOTAL = BAR_OFF + 256 + 1024;
};

template <int MODE, int BN, int STAGES>
__global__ void __launch_bounds__(384, 1)
gemm_kernel(const __grid_constant__ CUtensorMap mA, const __grid_constant__ CUtensorMap mB0,
            const __grid_constant__ CUtensorMap mB1, const __grid_constant__ CUtensorMap mC0,
            const __grid_constant__ CUtensorMap mC1, const bf16* __restrict__ xin, int n_tiles_n, int kblocks) {
    using L = GemmSmem<BN, STAGES>;
    extern __shared__ uint8_t smem_raw[];
    const uint32_t sbase = (smem_u32(smem_raw) + 1023u) & ~1023u;
    const uint32_t bar_full = sbase + L::BAR_OFF;
    const uint32_t bar_empty = bar_full + 8 * STAGES;
    const int wg = threadIdx.x >> 7;
    const int npairs = 8 * n_tiles_n;
    const uint32_t crank = cluster_rank();
    const int cid = blockIdx.x >> 1, ncl = gridDim.x >> 1;
    TL_START(MODE)
    pdl_launch();

    if (threadIdx.x == 0) {
        for (int s = 0; s < STAGES; s++) {
            mbar_init(bar_full + 8 * s, 1);
            mbar_init(bar_empty + 8 * s, 4);
        }
        asm volatile("fence.mbarrier_init.release.cluster;" ::: "memory");
        prefetch_tmap(&mA);
        prefetch_tmap(&mB0);
        if (MODE == 1 || MODE == 5) prefetch_tmap(&mB1);
        prefetch_tmap(&mC0);
    }
    cluster_sync_all();

    if (wg == 0) {
        reg_dealloc<40>();
        if (threadIdx.x == 0) {
            if (MODE != 1) pdl_wait();
            int stage = 0;
            uint32_t phase = 1;
            for (int pr = cid; pr < npairs; pr += ncl) {
                const int m0 = ((pr & 7) * 2 + crank) * 128;
                const int n0 = (pr >> 3) * BN;
                for (int kb = 0; kb < kblocks; kb++) {
                    mbar_wait(bar_empty + 8 * stage, phase);
                    const uint32_t sa = sbase + stage * L::STAGE_BYTES;
                    const uint32_t sb = sa + L::A_BYTES;
                    const uint32_t fb = bar_full + 8 * stage;
                    mbar_expect_tx(fb, L::STAGE_BYTES);
                    int arow = m0;
                    if (MODE == 2) {
                        const int grp = kb >> 2;
                        arow += (grp == 0) ? -1 : (grp == 1) ? 1 : (grp == 2) ? -2 : 2;
                    }
                    tma_load_2d(sa, &mA, kb * 64, arow, fb);
                    const CUtensorMap* mb = &mB0;
                    int bc = n0, br = kb * 64;
                    if (MODE == 1 && n0 >= 3 * DM) { mb = &mB1; bc = n0 - 3 * DM; }
                    if (MODE == 5 && kb >= 16) { mb = &mB1; br = (kb - 16) * 64; }
#pragma unroll
                    for (int b = 0; b < L::B_BOXES / 2; b++) {
                        const int bb = crank * (L::B_BOXES / 2) + b;
                        tma_load_2d_mc(sb + bb * 8192, mb, bc + bb * 64, br, fb, (uint16_t)3);
                    }
                    if (++stage == STAGES) { stage = 0; phase ^= 1; }
                }
            }
        }
    } else {
        reg_alloc<232>();
        const int c = wg - 1;
        const int warp = (threadIdx.x >> 5) & 3;
        const int lane = threadIdx.x & 31;
        const int tid_wg = threadIdx.x & 127;
        const uint32_t stg = sbase + L::STG_OFF + c * 16384;
        int stage = 0;
        uint32_t phase = 0;
        float acc[BN / 2];
        bool first = true;
        for (int pr = cid; pr < npairs; pr += ncl) {
            const int m0 = ((pr & 7) * 2 + crank) * 128;
            const int n0 = (pr >> 3) * BN;
            int prev_stage = 0;
            for (int kb = 0; kb < kblocks; kb++) {
                mbar_wait(bar_full + 8 * stage, phase);
                const uint32_t sa = sbase + stage * L::STAGE_BYTES + c * 8192;
                const uint32_t sb = sbase + stage * L::STAGE_BYTES + L::A_BYTES;
                const uint32_t da = desc_lo(sa, 16);
                const uint32_t db = desc_lo(sb, 8192);
                wgmma_fence();
#pragma unroll
                for (int k = 0; k < 4; k++) wgmma_tile<BN>(acc, da + k * 2, db + k * 128, (kb | k) != 0);
                wgmma_commit();
                if (kb > 0) {
                    wgmma_wait<1>();
                    RELEASE_STAGE(bar_empty + 8 * prev_stage);
                }
                prev_stage = stage;
                if (++stage == STAGES) { stage = 0; phase ^= 1; }
            }
            wgmma_wait<0>();
            RELEASE_STAGE(bar_empty + 8 * prev_stage);
            if (first) { pdl_wait(); first = false; }

            const int r0 = m0 + c * 64 + warp * 16 + (lane >> 2);
            const int r1 = r0 + 8;
            const int cq = (lane & 3) * 2;
            const CUtensorMap* mc = &mC0;
            int out_c0 = n0;
            if (MODE == 1) {
                if (n0 < DM) {
                    const float qs = 0.17677669529663687f * 1.4426950408889634f;
#pragma unroll
                    for (int j = 0; j < BN / 2; j++) acc[j] *= qs;
                } else if (n0 >= 3 * DM) {
                    mc = &mC1;
                    out_c0 = n0 - 3 * DM;
                    const float mu0 = g_mean1[r0], mu1 = g_mean1[r1];
                    const float rs0 = g_rstd1[r0], rs1 = g_rstd1[r1];
#pragma unroll
                    for (int j = 0; j < BN / 8; j++) {
                        const float2 cs = *reinterpret_cast<const float2*>(&g_cs1[out_c0 + 8 * j + cq]);
                        acc[4 * j + 0] = gelu_tanh(rs0 * fmaf(-mu0, cs.x, acc[4 * j + 0]));
                        acc[4 * j + 1] = gelu_tanh(rs0 * fmaf(-mu0, cs.y, acc[4 * j + 1]));
                        acc[4 * j + 2] = gelu_tanh(rs1 * fmaf(-mu1, cs.x, acc[4 * j + 2]));
                        acc[4 * j + 3] = gelu_tanh(rs1 * fmaf(-mu1, cs.y, acc[4 * j + 3]));
                    }
                }
            } else if (MODE == 2) {
                float s0 = 0.f, s1 = 0.f;
#pragma unroll
                for (int j = 0; j < BN / 8; j++) {
                    const uint32_t xa = *reinterpret_cast<const uint32_t*>(xin + (size_t)r0 * DM + n0 + 8 * j + cq);
                    const uint32_t xb = *reinterpret_cast<const uint32_t*>(xin + (size_t)r1 * DM + n0 + 8 * j + cq);
                    acc[4 * j + 0] = bf16_round(bf16_round(acc[4 * j + 0]) + __uint_as_float(xa << 16));
                    acc[4 * j + 1] = bf16_round(bf16_round(acc[4 * j + 1]) + __uint_as_float(xa & 0xFFFF0000u));
                    acc[4 * j + 2] = bf16_round(bf16_round(acc[4 * j + 2]) + __uint_as_float(xb << 16));
                    acc[4 * j + 3] = bf16_round(bf16_round(acc[4 * j + 3]) + __uint_as_float(xb & 0xFFFF0000u));
                    s0 += acc[4 * j + 0] + acc[4 * j + 1];
                    s1 += acc[4 * j + 2] + acc[4 * j + 3];
                }
                s0 += __shfl_xor_sync(0xffffffffu, s0, 1);
                s0 += __shfl_xor_sync(0xffffffffu, s0, 2);
                s1 += __shfl_xor_sync(0xffffffffu, s1, 1);
                s1 += __shfl_xor_sync(0xffffffffu, s1, 2);
                const float mu0 = s0 * (1.0f / BN), mu1 = s1 * (1.0f / BN);
                float q0 = 0.f, q1 = 0.f;
#pragma unroll
                for (int j = 0; j < BN / 8; j++) {
                    float d;
                    d = acc[4 * j + 0] - mu0; q0 += d * d;
                    d = acc[4 * j + 1] - mu0; q0 += d * d;
                    d = acc[4 * j + 2] - mu1; q1 += d * d;
                    d = acc[4 * j + 3] - mu1; q1 += d * d;
                }
                q0 += __shfl_xor_sync(0xffffffffu, q0, 1);
                q0 += __shfl_xor_sync(0xffffffffu, q0, 2);
                q1 += __shfl_xor_sync(0xffffffffu, q1, 1);
                q1 += __shfl_xor_sync(0xffffffffu, q1, 2);
                if ((lane & 3) == 0) {
                    static_assert(MODE != 2 || BN == 128, "stats layout assumes BN=128");
                    g_stat2[r0 * 8 + (n0 >> 7)] = make_float2(s0, q0);
                    g_stat2[r1 * 8 + (n0 >> 7)] = make_float2(s1, q1);
                }
            } else if (MODE == 3) {
                out_c0 = n0 + DM;
                float mu[2], rs[2];
#pragma unroll
                for (int h = 0; h < 2; h++) {
                    const float4* sp = reinterpret_cast<const float4*>(&g_stat2[(h ? r1 : r0) * 8]);
                    float4 p[4];
                    float s = 0.f;
#pragma unroll
                    for (int i = 0; i < 4; i++) { p[i] = sp[i]; s += p[i].x + p[i].z; }
                    const float mean = s * (1.0f / DM);
                    float m2 = 0.f;
#pragma unroll
                    for (int i = 0; i < 4; i++) {
                        float d0 = p[i].x * (1.0f / 128) - mean, d1 = p[i].z * (1.0f / 128) - mean;
                        m2 += p[i].y + p[i].w + 128.0f * (d0 * d0 + d1 * d1);
                    }
                    mu[h] = mean;
                    rs[h] = rsqrtf(m2 * (1.0f / DM) + 1e-5f);
                }
                const float og0 = g_omg[r0], og1 = g_omg[r1];
#pragma unroll
                for (int j = 0; j < BN / 8; j++) {
                    const float2 cs = *reinterpret_cast<const float2*>(&g_cs3[n0 + 8 * j + cq]);
                    acc[4 * j + 0] = og0 * gelu_tanh(rs[0] * fmaf(-mu[0], cs.x, acc[4 * j + 0]));
                    acc[4 * j + 1] = og0 * gelu_tanh(rs[0] * fmaf(-mu[0], cs.y, acc[4 * j + 1]));
                    acc[4 * j + 2] = og1 * gelu_tanh(rs[1] * fmaf(-mu[1], cs.x, acc[4 * j + 2]));
                    acc[4 * j + 3] = og1 * gelu_tanh(rs[1] * fmaf(-mu[1], cs.y, acc[4 * j + 3]));
                }
            } else {
                const float og0 = g_omg[r0], og1 = g_omg[r1];
#pragma unroll
                for (int j = 0; j < BN / 8; j++) {
                    const uint32_t xa = *reinterpret_cast<const uint32_t*>(xin + (size_t)r0 * DM + n0 + 8 * j + cq);
                    const uint32_t xb = *reinterpret_cast<const uint32_t*>(xin + (size_t)r1 * DM + n0 + 8 * j + cq);
                    acc[4 * j + 0] = fmaf(og0, __uint_as_float(xa << 16), acc[4 * j + 0]);
                    acc[4 * j + 1] = fmaf(og0, __uint_as_float(xa & 0xFFFF0000u), acc[4 * j + 1]);
                    acc[4 * j + 2] = fmaf(og1, __uint_as_float(xb << 16), acc[4 * j + 2]);
                    acc[4 * j + 3] = fmaf(og1, __uint_as_float(xb & 0xFFFF0000u), acc[4 * j + 3]);
                }
            }
            const int srow = warp * 16 + (lane & 7) + ((lane >> 3) & 1) * 8;
#pragma unroll
            for (int rnd = 0; rnd < (BN + 127) / 128; rnd++) {
                if (tid_wg == 0) bulk_wait_read0();
                named_bar_sync(1 + c, 128);
#pragma unroll
                for (int jj = 0; jj < 8; jj++) {
                    const int j = rnd * 16 + jj * 2;
                    if (j * 8 < BN) {
                        const int jb = jj * 2 + (lane >> 4);
                        uint32_t addr = stg + (jb >> 3) * 8192 + srow * 128 + (((jb & 7) ^ (srow & 7)) << 4);
                        if (rnd * 128 + 128 > BN && jj >= 4)
                            addr = stg + 8192 + srow * 64 + (((jb & 3) ^ ((srow >> 1) & 3)) << 4);
                        stmatrix_x4(addr, pack_bf16(acc[4 * j + 0], acc[4 * j + 1]), pack_bf16(acc[4 * j + 2], acc[4 * j + 3]),
                                    pack_bf16(acc[4 * j + 4], acc[4 * j + 5]), pack_bf16(acc[4 * j + 6], acc[4 * j + 7]));
                    }
                }
                fence_proxy_async();
                named_bar_sync(1 + c, 128);
                if (tid_wg == 0) {
                    tma_store_2d(mc, stg, out_c0 + rnd * 128, m0 + c * 64);
                    if (rnd * 128 + 64 < BN)
                        tma_store_2d((rnd * 128 + 128 > BN) ? &mC1 : mc, stg + 8192, out_c0 + rnd * 128 + 64, m0 + c * 64);
                    bulk_commit();
                }
            }
        }
        if (tid_wg == 0) bulk_wait0();
        TL_END(MODE)
    }
    cluster_sync_all();
}

constexpr int ATT_NTILES = NH * 16;
#define ATT_GRID_N 264
constexpr int ATT_GRID = ATT_GRID_N;
constexpr int ATT_THREADS = 256;
constexpr int ATT_STAGES = 4;
constexpr int ATT_DIST = 2;
constexpr int ATT_Q_OFF = ATT_STAGES * 16384;
constexpr int ATT_ONES_OFF = ATT_Q_OFF + 16384;
constexpr int ATT_KEXT_OFF = ATT_ONES_OFF + 4096;
constexpr int ATT_BAR_OFF = ATT_KEXT_OFF + 4096;
constexpr int ATT_SMEM = ATT_BAR_OFF + 256 + 1024;

__device__ __forceinline__ void row_max(const float (&s)[32], float& m0, float& m1) {
    float a0[8], a1[8];
#pragma unroll
    for (int i = 0; i < 8; i++) {
        a0[i] = fmaxf(s[4 * i], s[4 * i + 1]);
        a1[i] = fmaxf(s[4 * i + 2], s[4 * i + 3]);
    }
#pragma unroll
    for (int w = 4; w > 0; w >>= 1)
#pragma unroll
        for (int i = 0; i < w; i++) { a0[i] = fmaxf(a0[i], a0[i + w]); a1[i] = fmaxf(a1[i], a1[i + w]); }
    float mx0 = a0[0], mx1 = a1[0];
    mx0 = fmaxf(mx0, __shfl_xor_sync(0xffffffffu, mx0, 1));
    mx1 = fmaxf(mx1, __shfl_xor_sync(0xffffffffu, mx1, 1));
    mx0 = fmaxf(mx0, __shfl_xor_sync(0xffffffffu, mx0, 2));
    mx1 = fmaxf(mx1, __shfl_xor_sync(0xffffffffu, mx1, 2));
    m0 = fmaxf(m0, mx0);
    m1 = fmaxf(m1, mx1);
}

__device__ __forceinline__ void attn_step(float (&sc)[32], float (&sn)[32], uint32_t (&p)[16], float (&o)[20], uint32_t dq,
                                          uint32_t e0, uint32_t e1, uint32_t dke, uint32_t dk_next, uint32_t dv_prev,
                                          uint32_t release_bar) {
    constexpr uint32_t HI = desc_hi(512, 2);
    wgmma_fence();
    wgmma_ss_n64_tb0(sn, dq, HI, dk_next, HI, 0);
    wgmma_ss_n64_tb0(sn, dq + 2, HI, dk_next + 2, HI, 1);
    wgmma_rs_n64_tb0(sn, e0, e1, 0u, 0u, dke, HI, 1);
#pragma unroll
    for (int t = 0; t < 4; t++)
        wgmma_rs_n40_tb1(o, p[4 * t], p[4 * t + 1], p[4 * t + 2], p[4 * t + 3], dv_prev + t * 64, HI, 1);
    wgmma_commit();
#pragma unroll
    for (int i = 0; i < 32; i++) sc[i] = ex2(sc[i]);
    wgmma_wait<0>();
    if (release_bar != 0 && (threadIdx.x & 127) == 0) mbar_arrive(release_bar);
#pragma unroll
    for (int i = 0; i < 8; i++) {
        p[2 * i] = pack_bf16(sc[4 * i + 0], sc[4 * i + 1]);
        p[2 * i + 1] = pack_bf16(sc[4 * i + 2], sc[4 * i + 3]);
    }
}

__global__ void __launch_bounds__(256, 1)
attn_exact_kernel(const __grid_constant__ CUtensorMap mKV) {
    extern __shared__ uint8_t smem_raw[];
    pdl_launch();
    pdl_wait();
    const int tile = blockIdx.x;
    if (g_bad[tile] == 0) return;
    constexpr int NBLK = S_LEN / 128;
    constexpr uint32_t HI = desc_hi(512, 2);
    const uint32_t sbase = (smem_u32(smem_raw) + 1023u) & ~1023u;
    const uint32_t bar = sbase + ATT_BAR_OFF;
    const int warp_id = threadIdx.x >> 5;
    const int lane = threadIdx.x & 31;
    const int cq = (lane & 3) * 2;
    const uint32_t dk0 = desc_lo(sbase, 16);
    const uint32_t dv0 = desc_lo(sbase + 8192, ATT_ONES_OFF - 8192);
    if (threadIdx.x == 0) {
        mbar_init(bar, 1);
        asm volatile("fence.mbarrier_init.release.cluster;" ::: "memory");
    }
    asm volatile("st.shared.v4.b32 [%0], {%1, %1, %1, %1};" ::"r"(sbase + ATT_ONES_OFF + threadIdx.x * 16), "r"(0x3F803F80u) : "memory");
    fence_proxy_async();
    __syncthreads();
    const int head = tile >> 4;
    const int row0 = (tile & 15) * 128 + warp_id * 16 + (lane >> 2);
    const uint32_t dq = desc_lo(sbase + ATT_Q_OFF + (threadIdx.x >> 7) * 4096, 16);
    float o[20];
#pragma unroll
    for (int i = 0; i < 20; i++) o[i] = 0.f;
    float m0 = -INFINITY, m1 = -INFINITY;
#pragma unroll 1
    for (int j = 0; j < NBLK; j++) {
        if (threadIdx.x == 0) {
            mbar_expect_tx(bar, j == 0 ? 3 * 8192 : 2 * 8192);
            if (j == 0) tma_load_2d(sbase + ATT_Q_OFF, &mKV, head * DH, (tile & 15) * 128, bar);
            tma_load_2d(sbase, &mKV, DM + head * DH, j * 128, bar);
            tma_load_2d(sbase + 8192, &mKV, 2 * DM + head * DH, j * 128, bar);
        }
        __syncwarp();
        mbar_wait(bar, j & 1);
#pragma unroll 1
        for (int hf = 0; hf < 2; hf++) {
            float s[32];
            wgmma_fence();
            wgmma_ss_n64_tb0(s, dq, HI, dk0 + hf * 256, HI, 0);
            wgmma_ss_n64_tb0(s, dq + 2, HI, dk0 + hf * 256 + 2, HI, 1);
            wgmma_commit();
            wgmma_wait<0>();
            const float mo0 = m0, mo1 = m1;
            row_max(s, m0, m1);
            const float a0 = ex2(mo0 - m0), a1 = ex2(mo1 - m1);
            uint32_t p[16];
#pragma unroll
            for (int i = 0; i < 8; i++) {
                p[2 * i] = pack_bf16(ex2(s[4 * i + 0] - m0), ex2(s[4 * i + 1] - m0));
                p[2 * i + 1] = pack_bf16(ex2(s[4 * i + 2] - m1), ex2(s[4 * i + 3] - m1));
            }
#pragma unroll
            for (int i = 0; i < 5; i++) {
                o[4 * i + 0] *= a0; o[4 * i + 1] *= a0;
                o[4 * i + 2] *= a1; o[4 * i + 3] *= a1;
            }
            wgmma_fence();
            const uint32_t dv = dv0 + hf * 256 - ((uint32_t)(hf * 256) << 16);
#pragma unroll
            for (int t = 0; t < 4; t++)
                wgmma_rs_n40_tb1(o, p[4 * t], p[4 * t + 1], p[4 * t + 2], p[4 * t + 3], dv + t * 64, HI, 1);
            wgmma_commit();
            wgmma_wait<0>();
        }
        __syncthreads();
    }
    const float f0 = g_gate[row0] / o[16], f1 = g_gate[row0 + 8] / o[18];
    bf16* op0 = g_a5 + (size_t)row0 * A5W + head * DH + cq;
    bf16* op1 = op0 + 8 * A5W;
#pragma unroll
    for (int i = 0; i < 4; i++) {
        *reinterpret_cast<uint32_t*>(op0 + 8 * i) = pack_bf16(o[4 * i] * f0, o[4 * i + 1] * f0);
        *reinterpret_cast<uint32_t*>(op1 + 8 * i) = pack_bf16(o[4 * i + 2] * f1, o[4 * i + 3] * f1);
    }
}

__global__ void __launch_bounds__(256, 2)
attn_kernel(const __grid_constant__ CUtensorMap mKV) {
    extern __shared__ uint8_t smem_raw[];
    const uint32_t sbase = (smem_u32(smem_raw) + 1023u) & ~1023u;
    const uint32_t bar_kfull = sbase + ATT_BAR_OFF;
    const uint32_t bar_vfull = bar_kfull + 8 * ATT_STAGES;
    const uint32_t bar_empty = bar_vfull + 8 * ATT_STAGES;
    const uint32_t bar_q = bar_empty + 8 * ATT_STAGES;
    const int warp_id = threadIdx.x >> 5;
    const int lane = threadIdx.x & 31;
    constexpr int NBLK = S_LEN / 128;
    TL_START(6)
    pdl_launch();
    const int my_tiles = (ATT_NTILES - (int)blockIdx.x + (int)gridDim.x - 1) / (int)gridDim.x;
    const int total_blocks = my_tiles * NBLK;

    auto issue_kv = [&](int g) {
        const int tile = blockIdx.x + (g >> 4) * gridDim.x;
        const int hd = tile >> 4;
        const int sn = g % ATT_STAGES;
        if (g >= ATT_STAGES) mbar_wait(bar_empty + 8 * sn, ((g / ATT_STAGES) - 1) & 1);
        const uint32_t skn = sbase + sn * 16384;
        mbar_expect_tx(bar_kfull + 8 * sn, 8192);
        tma_load_2d(skn, &mKV, DM + hd * DH, (g & 15) * 128, bar_kfull + 8 * sn);
        mbar_expect_tx(bar_vfull + 8 * sn, 8192);
        tma_load_2d(skn + 8192, &mKV, 2 * DM + hd * DH, (g & 15) * 128, bar_vfull + 8 * sn);
    };
    auto issue_q = [&](int it) {
        const int tile = blockIdx.x + it * gridDim.x;
        mbar_expect_tx(bar_q + 8 * (it & 1), 8192);
        tma_load_2d(sbase + ATT_Q_OFF + (it & 1) * 8192, &mKV, (tile >> 4) * DH, (tile & 15) * 128, bar_q + 8 * (it & 1));
    };

    if (threadIdx.x == 0) {
        for (int s = 0; s < ATT_STAGES; s++) {
            mbar_init(bar_kfull + 8 * s, 1);
            mbar_init(bar_vfull + 8 * s, 1);
            mbar_init(bar_empty + 8 * s, 2);
        }
        mbar_init(bar_q, 1);
        mbar_init(bar_q + 8, 1);
        asm volatile("fence.mbarrier_init.release.cluster;" ::: "memory");
        prefetch_tmap(&mKV);
        pdl_wait();
        issue_q(0);
#pragma unroll
        for (int j = 0; j < ATT_DIST; j++) issue_kv(j);
    }
    {
        asm volatile("st.shared.v4.b32 [%0], {%1, %1, %1, %1};" ::"r"(sbase + ATT_ONES_OFF + threadIdx.x * 16), "r"(0x3F803F80u) : "memory");
        const int r = threadIdx.x >> 2, ch = threadIdx.x & 3;
        const uint32_t w0 = (ch == ((r >> 1) & 3)) ? 0x00003F80u : 0u;
        asm volatile("st.shared.v4.b32 [%0], {%1, %2, %2, %2};" ::"r"(sbase + ATT_KEXT_OFF + threadIdx.x * 16), "r"(w0), "r"(0u) : "memory");
    }
    fence_proxy_async();
    __syncthreads();
    pdl_wait();

    const int cq = (lane & 3) * 2;
    constexpr uint32_t HI = desc_hi(512, 2);
    const uint32_t dk0 = desc_lo(sbase, 16);
    const uint32_t dv0 = desc_lo(sbase + 8192, ATT_ONES_OFF - 8192);
    const uint32_t dke = desc_lo(sbase + ATT_KEXT_OFF, 16);
    int stage = 0;
    uint32_t phase = 0;
#pragma unroll 1
    for (int it = 0; it < my_tiles; it++) {
        const int tile = blockIdx.x + it * gridDim.x;
        const int head = tile >> 4;
        const int row0 = (tile & 15) * 128 + warp_id * 16 + (lane >> 2);
        const uint32_t dq = desc_lo(sbase + ATT_Q_OFF + (it & 1) * 8192 + (threadIdx.x >> 7) * 4096, 16);
        if (threadIdx.x == 0 && it + 1 < my_tiles) issue_q(it + 1);
        float o[20];
#pragma unroll
        for (int i = 0; i < 20; i++) o[i] = 0.f;
        float s0[32], s1[32];
        uint32_t p[16];
#pragma unroll
        for (int i = 0; i < 16; i++) p[i] = 0u;
        mbar_wait(bar_q + 8 * (it & 1), (it >> 1) & 1);
        mbar_wait(bar_kfull + 8 * stage, phase);
        wgmma_fence();
        wgmma_ss_n64_tb0(s0, dq, HI, dk0 + stage * 1024, HI, 0);
        wgmma_ss_n64_tb0(s0, dq + 2, HI, dk0 + stage * 1024 + 2, HI, 1);
        wgmma_commit();
        wgmma_wait<0>();
        float m0 = -INFINITY, m1 = -INFINITY;
        row_max(s0, m0, m1);
        const uint32_t e0 = (lane & 3) == 0 ? (pack_bf16(-m0, 0.f) & 0xFFFFu) : 0u;
        const uint32_t e1 = (lane & 3) == 0 ? (pack_bf16(-m1, 0.f) & 0xFFFFu) : 0u;
        wgmma_fence();
        wgmma_rs_n64_tb0(s0, e0, e1, 0u, 0u, dke, HI, 1);
        wgmma_commit();
        mbar_wait(bar_vfull + 8 * stage, phase);
        wgmma_wait<0>();
        uint32_t dv_prev = dv0 + stage * 1024 - ((uint32_t)(stage * 1024) << 16);
        int pstage = stage;
#pragma unroll 1
        for (int j = 0; j < NBLK; j++) {
            if (threadIdx.x == 0 && it * NBLK + j + ATT_DIST < total_blocks) issue_kv(it * NBLK + j + ATT_DIST);
            __syncwarp();
            const uint32_t dk = dk0 + stage * 1024;
            const uint32_t dv = dv0 + stage * 1024 - ((uint32_t)(stage * 1024) << 16);
            attn_step(s0, s1, p, o, dq, e0, e1, dke, dk + 256, dv_prev, j > 0 ? bar_empty + 8 * pstage : 0u);
            int nstage = stage + 1;
            uint32_t nphase = phase;
            if (nstage == ATT_STAGES) { nstage = 0; nphase ^= 1; }
            uint32_t dkn = dk;
            if (j + 1 < NBLK) {
                mbar_wait(bar_kfull + 8 * nstage, nphase);
                dkn = dk0 + nstage * 1024;
            }
            mbar_wait(bar_vfull + 8 * stage, phase);
            attn_step(s1, s0, p, o, dq, e0, e1, dke, dkn, dv, 0u);
            dv_prev = dv + 256 - (256u << 16);
            pstage = stage;
            stage = nstage;
            phase = nphase;
        }
        wgmma_fence();
#pragma unroll
        for (int t = 0; t < 4; t++)
            wgmma_rs_n40_tb1(o, p[4 * t], p[4 * t + 1], p[4 * t + 2], p[4 * t + 3], dv_prev + t * 64, HI, 1);
        wgmma_commit();
        wgmma_wait<0>();
        if ((threadIdx.x & 127) == 0) mbar_arrive(bar_empty + 8 * pstage);
        bool ok = (o[16] <= 1.8446744e19f) && (o[18] <= 1.8446744e19f);
#pragma unroll
        for (int i = 0; i < 16; i++) ok = ok && (fabsf(o[i]) <= 3.0e38f);
        const float f0 = g_gate[row0] / o[16], f1 = g_gate[row0 + 8] / o[18];
        bf16* op0 = g_a5 + (size_t)row0 * A5W + head * DH + cq;
        bf16* op1 = op0 + 8 * A5W;
#pragma unroll
        for (int i = 0; i < 4; i++) {
            *reinterpret_cast<uint32_t*>(op0 + 8 * i) = pack_bf16(o[4 * i] * f0, o[4 * i + 1] * f0);
            *reinterpret_cast<uint32_t*>(op1 + 8 * i) = pack_bf16(o[4 * i + 2] * f1, o[4 * i + 3] * f1);
        }
        const int bad = __syncthreads_or(!ok);
        if (threadIdx.x == 0) g_bad[tile] = bad;
    }

    TL_END(6)
}

typedef CUresult (*EncodeFn)(CUtensorMap*, CUtensorMapDataType, cuuint32_t, void*, const cuuint64_t*, const cuuint64_t*,
                             const cuuint32_t*, const cuuint32_t*, CUtensorMapInterleave, CUtensorMapSwizzle,
                             CUtensorMapL2promotion, CUtensorMapFloatOOBfill);

static CUtensorMap make_map(EncodeFn fn, const void* ptr, int rows, int cols, int box_cols, int box_rows,
                            CUtensorMapSwizzle swz) {
    CUtensorMap m;
    cuuint64_t dims[2] = {(cuuint64_t)cols, (cuuint64_t)rows};
    cuuint64_t strides[1] = {(cuuint64_t)cols * 2};
    cuuint32_t box[2] = {(cuuint32_t)box_cols, (cuuint32_t)box_rows};
    cuuint32_t es[2] = {1, 1};
    fn(&m, CU_TENSOR_MAP_DATA_TYPE_BFLOAT16, 2, const_cast<void*>(ptr), dims, strides, box, es,
       CU_TENSOR_MAP_INTERLEAVE_NONE, swz, CU_TENSOR_MAP_L2_PROMOTION_L2_256B, CU_TENSOR_MAP_FLOAT_OOB_FILL_NONE);
    return m;
}

template <typename... KArgs, typename... Args>
static void launch_ex(void (*kern)(KArgs...), int grid, int block, int smem, cudaStream_t st, int cluster, Args... args) {
    cudaLaunchConfig_t cfg = {};
    cfg.gridDim = dim3(grid);
    cfg.blockDim = dim3(block);
    cfg.dynamicSmemBytes = smem;
    cfg.stream = st;
    cudaLaunchAttribute at[2];
    at[0].id = cudaLaunchAttributeProgrammaticStreamSerialization;
    at[0].val.programmaticStreamSerializationAllowed = 1;
    at[1].id = cudaLaunchAttributeClusterDimension;
    at[1].val.clusterDim.x = cluster;
    at[1].val.clusterDim.y = 1;
    at[1].val.clusterDim.z = 1;
    cfg.attrs = at;
    cfg.numAttrs = cluster > 1 ? 2 : 1;
    cudaLaunchKernelEx(&cfg, kern, KArgs(args)...);
}

extern "C" void kernel_launch(void* const* d_in, const int* in_sizes, int n_in, void* d_out, int out_size) {
    const bf16* x = (const bf16*)d_in[0];
    const bf16* wqkv = (const bf16*)d_in[1];
    const bf16* wo = (const bf16*)d_in[2];
    const bf16* w1 = (const bf16*)d_in[4];
    const bf16* w2 = (const bf16*)d_in[5];
    const bf16* w3 = (const bf16*)d_in[6];
    const bf16* w4 = (const bf16*)d_in[7];
    const bf16* gate_w = (const bf16*)d_in[8];

    static EncodeFn enc = nullptr;
    static void *p_qkv, *p_h, *p_x1, *p_a5;
    using G1 = GemmSmem<256, 4>;
    using G2 = GemmSmem<128, 5>;
    using G3 = GemmSmem<224, 4>;
    if (!enc) {
        void* fn = nullptr;
        cudaDriverEntryPointQueryResult qres;
        cudaGetDriverEntryPoint("cuTensorMapEncodeTiled", &fn, cudaEnableDefault, &qres);
        enc = (EncodeFn)fn;
        cudaGetSymbolAddress(&p_qkv, g_qkv);
        cudaGetSymbolAddress(&p_h, g_h);
        cudaGetSymbolAddress(&p_x1, g_x1);
        cudaGetSymbolAddress(&p_a5, g_a5);
        cudaFuncSetAttribute(gemm_kernel<1, 256, 4>, cudaFuncAttributeMaxDynamicSharedMemorySize, G1::TOTAL);
        cudaFuncSetAttribute(gemm_kernel<2, 128, 5>, cudaFuncAttributeMaxDynamicSharedMemorySize, G2::TOTAL);
        cudaFuncSetAttribute(gemm_kernel<3, 224, 4>, cudaFuncAttributeMaxDynamicSharedMemorySize, G3::TOTAL);
        cudaFuncSetAttribute(gemm_kernel<5, 128, 5>, cudaFuncAttributeMaxDynamicSharedMemorySize, G2::TOTAL);
        cudaFuncSetAttribute(attn_kernel, cudaFuncAttributeMaxDynamicSharedMemorySize, ATT_SMEM);
        cudaFuncSetAttribute(attn_exact_kernel, cudaFuncAttributeMaxDynamicSharedMemorySize, ATT_SMEM);
    }
    const CUtensorMapSwizzle SW128 = CU_TENSOR_MAP_SWIZZLE_128B, SW64 = CU_TENSOR_MAP_SWIZZLE_64B;
    CUtensorMap mX = make_map(enc, x, S_LEN, DM, 64, 128, SW128);
    CUtensorMap mWqkv = make_map(enc, wqkv, DM, 3 * DM, 64, 64, SW128);
    CUtensorMap mW1 = make_map(enc, w1, DM, DM, 64, 64, SW128);
    CUtensorMap mW2 = make_map(enc, w2, DM, DM, 64, 64, SW128);
    CUtensorMap mW3 = make_map(enc, w3, DM, FF, 64, 64, SW128);
    CUtensorMap mW4 = make_map(enc, w4, FF, DM, 64, 64, SW128);
    CUtensorMap mWo = make_map(enc, wo, DM, DM, 64, 64, SW128);
    CUtensorMap mQKVst = make_map(enc, p_qkv, S_LEN, 3 * DM, 64, 64, SW128);
    CUtensorMap mKV = make_map(enc, p_qkv, S_LEN, 3 * DM, 32, 128, SW64);
    CUtensorMap mHst = make_map(enc, p_h, S_LEN, DM, 64, 64, SW128);
    CUtensorMap mHld = make_map(enc, p_h, S_LEN, DM, 64, 128, SW128);
    CUtensorMap mX1st = make_map(enc, p_x1, S_LEN, DM, 64, 64, SW128);
    CUtensorMap mX1ld = make_map(enc, p_x1, S_LEN, DM, 64, 128, SW128);
    CUtensorMap mA5st = make_map(enc, p_a5, S_LEN, A5W, 64, 64, SW128);
    CUtensorMap mA5st32 = make_map(enc, p_a5, S_LEN, A5W, 32, 64, SW64);
    CUtensorMap mA5ld = make_map(enc, p_a5, S_LEN, A5W, 64, 128, SW128);
    CUtensorMap mOut = make_map(enc, d_out, S_LEN, DM, 64, 64, SW128);

    cudaStream_t st = cudaStreamPerThread;
    prep_kernel<<<256 + 72, 256, 0, st>>>(x, gate_w, w1, w3);
    launch_ex(gemm_kernel<1, 256, 4>, 132, 384, G1::TOTAL, st, 2, mX, mWqkv, mW1, mQKVst, mHst, x, 16, 16);
    launch_ex(attn_kernel, ATT_GRID, ATT_THREADS, ATT_SMEM, st, 1, mKV);
    launch_ex(attn_exact_kernel, ATT_NTILES, ATT_THREADS, ATT_SMEM, st, 1, mKV);
    launch_ex(gemm_kernel<2, 128, 5>, 128, 384, G2::TOTAL, st, 2, mHld, mW2, mW2, mX1st, mX1st, x, 8, 16);
    launch_ex(gemm_kernel<3, 224, 4>, 132, 384, G3::TOTAL, st, 2, mX1ld, mW3, mW3, mA5st, mA5st32, x, 16, 16);
    launch_ex(gemm_kernel<5, 128, 5>, 128, 384, G2::TOTAL, st, 2, mA5ld, mWo, mW4, mOut, mOut, (const bf16*)p_x1, 8, 72);
}
```

```cpp
#include <cuda_runtime.h>
#include <cuda_bf16.h>
#include <cuda.h>
#include <stdint.h>

typedef __nv_bfloat16 bf16;

constexpr int S_LEN = 2048;
constexpr int DM = 1024;
constexpr int FF = 3584;
constexpr int NH = 32;
constexpr int DH = 32;
constexpr int A5W = DM + FF;

__device__ __align__(1024) bf16 g_qkv[S_LEN * 3 * DM];
__device__ __align__(1024) bf16 g_h[S_LEN * DM];
__device__ __align__(1024) bf16 g_x1[S_LEN * DM];
__device__ __align__(1024) bf16 g_a5[S_LEN * A5W];
__device__ __align__(16) float g_mean1[S_LEN];
__device__ __align__(16) float g_rstd1[S_LEN];
__device__ __align__(16) float g_gate[S_LEN];
__device__ __align__(16) float g_omg[S_LEN];
__device__ __align__(16) float g_cs1[DM];
__device__ __align__(16) float g_cs3[FF];
__device__ __align__(16) float2 g_stat2[S_LEN * 8];
__device__ int g_bad[NH * 16];

#define TL_START(k)
#define TL_END(k)

__device__ __forceinline__ uint32_t smem_u32(const void* p) { return (uint32_t)__cvta_generic_to_shared(p); }

__device__ __forceinline__ void mbar_init(uint32_t bar, uint32_t count) {
    asm volatile("mbarrier.init.shared::cta.b64 [%0], %1;" ::"r"(bar), "r"(count));
}
__device__ __forceinline__ void mbar_expect_tx(uint32_t bar, uint32_t bytes) {
    asm volatile("mbarrier.arrive.expect_tx.shared::cta.b64 _, [%0], %1;" ::"r"(bar), "r"(bytes) : "memory");
}
__device__ __forceinline__ void mbar_arrive(uint32_t bar) {
    asm volatile("mbarrier.arrive.shared::cta.b64 _, [%0];" ::"r"(bar) : "memory");
}
__device__ __forceinline__ bool mbar_try_wait(uint32_t bar, uint32_t parity) {
    uint32_t ok;
    asm volatile(
        "{\n.reg .pred p;\n"
        "mbarrier.try_wait.parity.shared::cta.b64 p, [%1], %2;\n"
        "selp.u32 %0, 1, 0, p;\n}\n"
        : "=r"(ok)
        : "r"(bar), "r"(parity)
        : "memory");
    return ok != 0;
}
__device__ __forceinline__ void mbar_wait(uint32_t bar, uint32_t parity) {
    uint32_t spins = 0;
    while (!mbar_try_wait(bar, parity)) {
        if (++spins > (1u << 24)) __trap();
    }
}
__device__ __forceinline__ void tma_load_2d(uint32_t dst, const CUtensorMap* map, int c0, int c1, uint32_t bar) {
    asm volatile(
        "cp.async.bulk.tensor.2d.shared::cluster.global.mbarrier::complete_tx::bytes [%0], [%1, {%3, %4}], [%2];"
        ::"r"(dst), "l"(map), "r"(bar), "r"(c0), "r"(c1)
        : "memory");
}
__device__ __forceinline__ void tma_store_2d(const CUtensorMap* map, uint32_t src, int c0, int c1) {
    asm volatile("cp.async.bulk.tensor.2d.global.shared::cta.bulk_group [%0, {%2, %3}], [%1];"
                 ::"l"(map), "r"(src), "r"(c0), "r"(c1)
                 : "memory");
}
__device__ __forceinline__ void tma_load_2d_mc(uint32_t dst, const CUtensorMap* map, int c0, int c1, uint32_t bar, uint16_t mask) {
    asm volatile(
        "cp.async.bulk.tensor.2d.shared::cluster.global.mbarrier::complete_tx::bytes.multicast::cluster [%0], [%1, {%3, %4}], [%2], %5;"
        ::"r"(dst), "l"(map), "r"(bar), "r"(c0), "r"(c1), "h"(mask)
        : "memory");
}
__device__ __forceinline__ void mbar_arrive_cluster(uint32_t bar, uint32_t cta) {
    asm volatile(
        "{\n.reg .b32 ra;\nmapa.shared::cluster.u32 ra, %0, %1;\n"
        "mbarrier.arrive.shared::cluster.b64 _, [ra];\n}\n" ::"r"(bar), "r"(cta)
        : "memory");
}
__device__ __forceinline__ void cluster_sync_all() {
    asm volatile("barrier.cluster.arrive.release.aligned;\nbarrier.cluster.wait.acquire.aligned;" ::: "memory");
}
__device__ __forceinline__ uint32_t cluster_rank() { uint32_t r; asm volatile("mov.u32 %0, %%cluster_ctarank;" : "=r"(r)); return r; }
__device__ __forceinline__ void pdl_wait() { asm volatile("griddepcontrol.wait;" ::: "memory"); }
__device__ __forceinline__ void pdl_launch() { asm volatile("griddepcontrol.launch_dependents;" ::: "memory"); }
__device__ __forceinline__ void bulk_commit() { asm volatile("cp.async.bulk.commit_group;" ::: "memory"); }
__device__ __forceinline__ void bulk_wait_read0() { asm volatile("cp.async.bulk.wait_group.read 0;" ::: "memory"); }
__device__ __forceinline__ void bulk_wait0() { asm volatile("cp.async.bulk.wait_group 0;" ::: "memory"); }
__device__ __forceinline__ void fence_proxy_async() { asm volatile("fence.proxy.async.shared::cta;" ::: "memory"); }
__device__ __forceinline__ void named_bar_sync(int id, int n) { asm volatile("bar.sync %0, %1;" ::"r"(id), "r"(n) : "memory"); }
__device__ __forceinline__ void named_bar_arrive(int id, int n) { asm volatile("bar.arrive %0, %1;" ::"r"(id), "r"(n) : "memory"); }
__device__ __forceinline__ void wgmma_fence() { asm volatile("wgmma.fence.sync.aligned;" ::: "memory"); }
__device__ __forceinline__ void wgmma_commit() { asm volatile("wgmma.commit_group.sync.aligned;" ::: "memory"); }
template <int N>
__device__ __forceinline__ void wgmma_wait() { asm volatile("wgmma.wait_group.sync.aligned %0;" ::"n"(N) : "memory"); }
__device__ __forceinline__ void prefetch_tmap(const CUtensorMap* m) {
    asm volatile("prefetch.tensormap [%0];" ::"l"(m) : "memory");
}
template <int R>
__device__ __forceinline__ void reg_alloc() { asm volatile("setmaxnreg.inc.sync.aligned.u32 %0;" ::"n"(R)); }
template <int R>
__device__ __forceinline__ void reg_dealloc() { asm volatile("setmaxnreg.dec.sync.aligned.u32 %0;" ::"n"(R)); }
__device__ __forceinline__ void stmatrix_x4(uint32_t addr, uint32_t r0, uint32_t r1, uint32_t r2, uint32_t r3) {
    asm volatile("stmatrix.sync.aligned.m8n8.x4.shared.b16 [%0], {%1, %2, %3, %4};"
                 ::"r"(addr), "r"(r0), "r"(r1), "r"(r2), "r"(r3)
                 : "memory");
}
__device__ __forceinline__ uint32_t pack_bf16(float lo, float hi) {
    uint32_t r;
    asm("cvt.rn.bf16x2.f32 %0, %1, %2;" : "=r"(r) : "f"(hi), "f"(lo));
    return r;
}
__device__ __forceinline__ float bf16_round(float v) { return __bfloat162float(__float2bfloat16_rn(v)); }
__device__ __forceinline__ float ex2(float x) {
    float y;
    asm volatile("ex2.approx.ftz.f32 %0, %1;" : "=f"(y) : "f"(x));
    return y;
}
__device__ __forceinline__ float tanh_fast(float x) {
    float y;
    asm("tanh.approx.f32 %0, %1;" : "=f"(y) : "f"(x));
    return y;
}
__device__ __forceinline__ float gelu_tanh(float v) {
    float u = 0.7978845608028654f * (v + 0.044715f * v * v * v);
    float hv = 0.5f * v;
    return fmaf(hv, tanh_fast(u), hv);
}
__device__ __forceinline__ uint32_t desc_lo(uint32_t addr, uint32_t lbo_bytes) {
    return ((addr & 0x3FFFF) >> 4) | (((lbo_bytes >> 4) & 0x3FFF) << 16);
}
__host__ __device__ constexpr uint32_t desc_hi(uint32_t sbo_bytes, uint32_t swz) {
    return ((sbo_bytes >> 4) & 0x3FFF) | (swz << 30);
}

__device__ __forceinline__ void wgmma_ss_n128_tb1(float (&d)[64], uint32_t alo, uint32_t ahi, uint32_t blo, uint32_t bhi, int scale_d) {
    asm volatile("{\n.reg .pred p;\n.reg .b64 da, db;\nsetp.ne.b32 p, %68, 0;\nmov.b64 da, {%64, %65};\nmov.b64 db, {%66, %67};\n"
        "wgmma.mma_async.sync.aligned.m64n128k16.f32.bf16.bf16 {%0, %1, %2, %3, %4, %5, %6, %7, %8, %9, %10, %11, %12, %13, %14, %15, %16, %17, %18, %19, %20, %21, %22, %23, %24, %25, %26, %27, %28, %29, %30, %31, %32, %33, %34, %35, %36, %37, %38, %39, %40, %41, %42, %43, %44, %45, %46, %47, %48, %49, %50, %51, %52, %53, %54, %55, %56, %57, %58, %59, %60, %61, %62, %63}, da, db, p, 1, 1, 0, 1;\n}\n"
        : "+f"(d[0]), "+f"(d[1]), "+f"(d[2]), "+f"(d[3]), "+f"(d[4]), "+f"(d[5]), "+f"(d[6]), "+f"(d[7]), "+f"(d[8]), "+f"(d[9]), "+f"(d[10]), "+f"(d[11]), "+f"(d[12]), "+f"(d[13]), "+f"(d[14]), "+f"(d[15]), "+f"(d[16]), "+f"(d[17]), "+f"(d[18]), "+f"(d[19]), "+f"(d[20]), "+f"(d[21]), "+f"(d[22]), "+f"(d[23]), "+f"(d[24]), "+f"(d[25]), "+f"(d[26]), "+f"(d[27]), "+f"(d[28]), "+f"(d[29]), "+f"(d[30]), "+f"(d[31]), "+f"(d[32]), "+f"(d[33]), "+f"(d[34]), "+f"(d[35]), "+f"(d[36]), "+f"(d[37]), "+f"(d[38]), "+f"(d[39]), "+f"(d[40]), "+f"(d[41]), "+f"(d[42]), "+f"(d[43]), "+f"(d[44]), "+f"(d[45]), "+f"(d[46]), "+f"(d[47]), "+f"(d[48]), "+f"(d[49]), "+f"(d[50]), "+f"(d[51]), "+f"(d[52]), "+f"(d[53]), "+f"(d[54]), "+f"(d[55]), "+f"(d[56]), "+f"(d[57]), "+f"(d[58]), "+f"(d[59]), "+f"(d[60]), "+f"(d[61]), "+f"(d[62]), "+f"(d[63])
        : "r"(alo), "r"(ahi), "r"(blo), "r"(bhi), "r"(scale_d));
}

__device__ __forceinline__ void wgmma_ss_n192_tb1(float (&d)[96], uint32_t alo, uint32_t ahi, uint32_t blo, uint32_t bhi, int scale_d) {
    asm volatile("{\n.reg .pred p;\n.reg .b64 da, db;\nsetp.ne.b32 p, %100, 0;\nmov.b64 da, {%96, %97};\nmov.b64 db, {%98, %99};\n"
        "wgmma.mma_async.sync.aligned.m64n192k16.f32.bf16.bf16 {%0, %1, %2, %3, %4, %5, %6, %7, %8, %9, %10, %11, %12, %13, %14, %15, %16, %17, %18, %19, %20, %21, %22, %23, %24, %25, %26, %27, %28, %29, %30, %31, %32, %33, %34, %35, %36, %37, %38, %39, %40, %41, %42, %43, %44, %45, %46, %47, %48, %49, %50, %51, %52, %53, %54, %55, %56, %57, %58, %59, %60, %61, %62, %63, %64, %65, %66, %67, %68, %69, %70, %71, %72, %73, %74, %75, %76, %77, %78, %79, %80, %81, %82, %83, %84, %85, %86, %87, %88, %89, %90, %91, %92, %93, %94, %95}, da, db, p, 1, 1, 0, 1;\n}\n"
        : "+f"(d[0]), "+f"(d[1]), "+f"(d[2]), "+f"(d[3]), "+f"(d[4]), "+f"(d[5]), "+f"(d[6]), "+f"(d[7]), "+f"(d[8]), "+f"(d[9]), "+f"(d[10]), "+f"(d[11]), "+f"(d[12]), "+f"(d[13]), "+f"(d[14]), "+f"(d[15]), "+f"(d[16]), "+f"(d[17]), "+f"(d[18]), "+f"(d[19]), "+f"(d[20]), "+f"(d[21]), "+f"(d[22]), "+f"(d[23]), "+f"(d[24]), "+f"(d[25]), "+f"(d[26]), "+f"(d[27]), "+f"(d[28]), "+f"(d[29]), "+f"(d[30]), "+f"(d[31]), "+f"(d[32]), "+f"(d[33]), "+f"(d[34]), "+f"(d[35]), "+f"(d[36]), "+f"(d[37]), "+f"(d[38]), "+f"(d[39]), "+f"(d[40]), "+f"(d[41]), "+f"(d[42]), "+f"(d[43]), "+f"(d[44]), "+f"(d[45]), "+f"(d[46]), "+f"(d[47]), "+f"(d[48]), "+f"(d[49]), "+f"(d[50]), "+f"(d[51]), "+f"(d[52]), "+f"(d[53]), "+f"(d[54]), "+f"(d[55]), "+f"(d[56]), "+f"(d[57]), "+f"(d[58]), "+f"(d[59]), "+f"(d[60]), "+f"(d[61]), "+f"(d[62]), "+f"(d[63]), "+f"(d[64]), "+f"(d[65]), "+f"(d[66]), "+f"(d[67]), "+f"(d[68]), "+f"(d[69]), "+f"(d[70]), "+f"(d[71]), "+f"(d[72]), "+f"(d[73]), "+f"(d[74]), "+f"(d[75]), "+f"(d[76]), "+f"(d[77]), "+f"(d[78]), "+f"(d[79]), "+f"(d[80]), "+f"(d[81]), "+f"(d[82]), "+f"(d[83]), "+f"(d[84]), "+f"(d[85]), "+f"(d[86]), "+f"(d[87]), "+f"(d[88]), "+f"(d[89]), "+f"(d[90]), "+f"(d[91]), "+f"(d[92]), "+f"(d[93]), "+f"(d[94]), "+f"(d[95])
        : "r"(alo), "r"(ahi), "r"(blo), "r"(bhi), "r"(scale_d));
}

__device__ __forceinline__ void wgmma_ss_n224_tb1(float (&d)[112], uint32_t alo, uint32_t ahi, uint32_t blo, uint32_t bhi, int scale_d) {
    asm volatile("{\n.reg .pred p;\n.reg .b64 da, db;\nsetp.ne.b32 p, %116, 0;\nmov.b64 da, {%112, %113};\nmov.b64 db, {%114, %115};\n"
        "wgmma.mma_async.sync.aligned.m64n224k16.f32.bf16.bf16 {%0, %1, %2, %3, %4, %5, %6, %7, %8, %9, %10, %11, %12, %13, %14, %15, %16, %17, %18, %19, %20, %21, %22, %23, %24, %25, %26, %27, %28, %29, %30, %31, %32, %33, %34, %35, %36, %37, %38, %39, %40, %41, %42, %43, %44, %45, %46, %47, %48, %49, %50, %51, %52, %53, %54, %55, %56, %57, %58, %59, %60, %61, %62, %63, %64, %65, %66, %67, %68, %69, %70, %71, %72, %73, %74, %75, %76, %77, %78, %79, %80, %81, %82, %83, %84, %85, %86, %87, %88, %89, %90, %91, %92, %93, %94, %95, %96, %97, %98, %99, %100, %101, %102, %103, %104, %105, %106, %107, %108, %109, %110, %111}, da, db, p, 1, 1, 0, 1;\n}\n"
        : "+f"(d[0]), "+f"(d[1]), "+f"(d[2]), "+f"(d[3]), "+f"(d[4]), "+f"(d[5]), "+f"(d[6]), "+f"(d[7]), "+f"(d[8]), "+f"(d[9]), "+f"(d[10]), "+f"(d[11]), "+f"(d[12]), "+f"(d[13]), "+f"(d[14]), "+f"(d[15]), "+f"(d[16]), "+f"(d[17]), "+f"(d[18]), "+f"(d[19]), "+f"(d[20]), "+f"(d[21]), "+f"(d[22]), "+f"(d[23]), "+f"(d[24]), "+f"(d[25]), "+f"(d[26]), "+f"(d[27]), "+f"(d[28]), "+f"(d[29]), "+f"(d[30]), "+f"(d[31]), "+f"(d[32]), "+f"(d[33]), "+f"(d[34]), "+f"(d[35]), "+f"(d[36]), "+f"(d[37]), "+f"(d[38]), "+f"(d[39]), "+f"(d[40]), "+f"(d[41]), "+f"(d[42]), "+f"(d[43]), "+f"(d[44]), "+f"(d[45]), "+f"(d[46]), "+f"(d[47]), "+f"(d[48]), "+f"(d[49]), "+f"(d[50]), "+f"(d[51]), "+f"(d[52]), "+f"(d[53]), "+f"(d[54]), "+f"(d[55]), "+f"(d[56]), "+f"(d[57]), "+f"(d[58]), "+f"(d[59]), "+f"(d[60]), "+f"(d[61]), "+f"(d[62]), "+f"(d[63]), "+f"(d[64]), "+f"(d[65]), "+f"(d[66]), "+f"(d[67]), "+f"(d[68]), "+f"(d[69]), "+f"(d[70]), "+f"(d[71]), "+f"(d[72]), "+f"(d[73]), "+f"(d[74]), "+f"(d[75]), "+f"(d[76]), "+f"(d[77]), "+f"(d[78]), "+f"(d[79]), "+f"(d[80]), "+f"(d[81]), "+f"(d[82]), "+f"(d[83]), "+f"(d[84]), "+f"(d[85]), "+f"(d[86]), "+f"(d[87]), "+f"(d[88]), "+f"(d[89]), "+f"(d[90]), "+f"(d[91]), "+f"(d[92]), "+f"(d[93]), "+f"(d[94]), "+f"(d[95]), "+f"(d[96]), "+f"(d[97]), "+f"(d[98]), "+f"(d[99]), "+f"(d[100]), "+f"(d[101]), "+f"(d[102]), "+f"(d[103]), "+f"(d[104]), "+f"(d[105]), "+f"(d[106]), "+f"(d[107]), "+f"(d[108]), "+f"(d[109]), "+f"(d[110]), "+f"(d[111])
        : "r"(alo), "r"(ahi), "r"(blo), "r"(bhi), "r"(scale_d));
}

__device__ __forceinline__ void wgmma_ss_n256_tb1(float (&d)[128], uint32_t alo, uint32_t ahi, uint32_t blo, uint32_t bhi, int scale_d) {
    asm volatile("{\n.reg .pred p;\n.reg .b64 da, db;\nsetp.ne.b32 p, %132, 0;\nmov.b64 da, {%128, %129};\nmov.b64 db, {%130, %131};\n"
        "wgmma.mma_async.sync.aligned.m64n256k16.f32.bf16.bf16 {%0, %1, %2, %3, %4, %5, %6, %7, %8, %9, %10, %11, %12, %13, %14, %15, %16, %17, %18, %19, %20, %21, %22, %23, %24, %25, %26, %27, %28, %29, %30, %31, %32, %33, %34, %35, %36, %37, %38, %39, %40, %41, %42, %43, %44, %45, %46, %47, %48, %49, %50, %51, %52, %53, %54, %55, %56, %57, %58, %59, %60, %61, %62, %63, %64, %65, %66, %67, %68, %69, %70, %71, %72, %73, %74, %75, %76, %77, %78, %79, %80, %81, %82, %83, %84, %85, %86, %87, %88, %89, %90, %91, %92, %93, %94, %95, %96, %97, %98, %99, %100, %101, %102, %103, %104, %105, %106, %107, %108, %109, %110, %111, %112, %113, %114, %115, %116, %117, %118, %119, %120, %121, %122, %123, %124, %125, %126, %127}, da, db, p, 1, 1, 0, 1;\n}\n"
        : "+f"(d[0]), "+f"(d[1]), "+f"(d[2]), "+f"(d[3]), "+f"(d[4]), "+f"(d[5]), "+f"(d[6]), "+f"(d[7]), "+f"(d[8]), "+f"(d[9]), "+f"(d[10]), "+f"(d[11]), "+f"(d[12]), "+f"(d[13]), "+f"(d[14]), "+f"(d[15]), "+f"(d[16]), "+f"(d[17]), "+f"(d[18]), "+f"(d[19]), "+f"(d[20]), "+f"(d[21]), "+f"(d[22]), "+f"(d[23]), "+f"(d[24]), "+f"(d[25]), "+f"(d[26]), "+f"(d[27]), "+f"(d[28]), "+f"(d[29]), "+f"(d[30]), "+f"(d[31]), "+f"(d[32]), "+f"(d[33]), "+f"(d[34]), "+f"(d[35]), "+f"(d[36]), "+f"(d[37]), "+f"(d[38]), "+f"(d[39]), "+f"(d[40]), "+f"(d[41]), "+f"(d[42]), "+f"(d[43]), "+f"(d[44]), "+f"(d[45]), "+f"(d[46]), "+f"(d[47]), "+f"(d[48]), "+f"(d[49]), "+f"(d[50]), "+f"(d[51]), "+f"(d[52]), "+f"(d[53]), "+f"(d[54]), "+f"(d[55]), "+f"(d[56]), "+f"(d[57]), "+f"(d[58]), "+f"(d[59]), "+f"(d[60]), "+f"(d[61]), "+f"(d[62]), "+f"(d[63]), "+f"(d[64]), "+f"(d[65]), "+f"(d[66]), "+f"(d[67]), "+f"(d[68]), "+f"(d[69]), "+f"(d[70]), "+f"(d[71]), "+f"(d[72]), "+f"(d[73]), "+f"(d[74]), "+f"(d[75]), "+f"(d[76]), "+f"(d[77]), "+f"(d[78]), "+f"(d[79]), "+f"(d[80]), "+f"(d[81]), "+f"(d[82]), "+f"(d[83]), "+f"(d[84]), "+f"(d[85]), "+f"(d[86]), "+f"(d[87]), "+f"(d[88]), "+f"(d[89]), "+f"(d[90]), "+f"(d[91]), "+f"(d[92]), "+f"(d[93]), "+f"(d[94]), "+f"(d[95]), "+f"(d[96]), "+f"(d[97]), "+f"(d[98]), "+f"(d[99]), "+f"(d[100]), "+f"(d[101]), "+f"(d[102]), "+f"(d[103]), "+f"(d[104]), "+f"(d[105]), "+f"(d[106]), "+f"(d[107]), "+f"(d[108]), "+f"(d[109]), "+f"(d[110]), "+f"(d[111]), "+f"(d[112]), "+f"(d[113]), "+f"(d[114]), "+f"(d[115]), "+f"(d[116]), "+f"(d[117]), "+f"(d[118]), "+f"(d[119]), "+f"(d[120]), "+f"(d[121]), "+f"(d[122]), "+f"(d[123]), "+f"(d[124]), "+f"(d[125]), "+f"(d[126]), "+f"(d[127])
        : "r"(alo), "r"(ahi), "r"(blo), "r"(bhi), "r"(scale_d));
}

__device__ __forceinline__ void wgmma_ss_n64_tb0(float (&d)[32], uint32_t alo, uint32_t ahi, uint32_t blo, uint32_t bhi, int scale_d) {
    asm volatile("{\n.reg .pred p;\n.reg .b64 da, db;\nsetp.ne.b32 p, %36, 0;\nmov.b64 da, {%32, %33};\nmov.b64 db, {%34, %35};\n"
        "wgmma.mma_async.sync.aligned.m64n64k16.f32.bf16.bf16 {%0, %1, %2, %3, %4, %5, %6, %7, %8, %9, %10, %11, %12, %13, %14, %15, %16, %17, %18, %19, %20, %21, %22, %23, %24, %25, %26, %27, %28, %29, %30, %31}, da, db, p, 1, 1, 0, 0;\n}\n"
        : "+f"(d[0]), "+f"(d[1]), "+f"(d[2]), "+f"(d[3]), "+f"(d[4]), "+f"(d[5]), "+f"(d[6]), "+f"(d[7]), "+f"(d[8]), "+f"(d[9]), "+f"(d[10]), "+f"(d[11]), "+f"(d[12]), "+f"(d[13]), "+f"(d[14]), "+f"(d[15]), "+f"(d[16]), "+f"(d[17]), "+f"(d[18]), "+f"(d[19]), "+f"(d[20]), "+f"(d[21]), "+f"(d[22]), "+f"(d[23]), "+f"(d[24]), "+f"(d[25]), "+f"(d[26]), "+f"(d[27]), "+f"(d[28]), "+f"(d[29]), "+f"(d[30]), "+f"(d[31])
        : "r"(alo), "r"(ahi), "r"(blo), "r"(bhi), "r"(scale_d));
}

__device__ __forceinline__ void wgmma_rs_n128_tb0(float (&d)[64], uint32_t a0, uint32_t a1, uint32_t a2, uint32_t a3, uint32_t blo, uint32_t bhi, int scale_d) {
    asm volatile("{\n.reg .pred p;\n.reg .b64 db;\nsetp.ne.b32 p, %70, 0;\nmov.b64 db, {%68, %69};\n"
        "wgmma.mma_async.sync.aligned.m64n128k16.f32.bf16.bf16 {%0, %1, %2, %3, %4, %5, %6, %7, %8, %9, %10, %11, %12, %13, %14, %15, %16, %17, %18, %19, %20, %21, %22, %23, %24, %25, %26, %27, %28, %29, %30, %31, %32, %33, %34, %35, %36, %37, %38, %39, %40, %41, %42, %43, %44, %45, %46, %47, %48, %49, %50, %51, %52, %53, %54, %55, %56, %57, %58, %59, %60, %61, %62, %63}, {%64, %65, %66, %67}, db, p, 1, 1, 0;\n}\n"
        : "+f"(d[0]), "+f"(d[1]), "+f"(d[2]), "+f"(d[3]), "+f"(d[4]), "+f"(d[5]), "+f"(d[6]), "+f"(d[7]), "+f"(d[8]), "+f"(d[9]), "+f"(d[10]), "+f"(d[11]), "+f"(d[12]), "+f"(d[13]), "+f"(d[14]), "+f"(d[15]), "+f"(d[16]), "+f"(d[17]), "+f"(d[18]), "+f"(d[19]), "+f"(d[20]), "+f"(d[21]), "+f"(d[22]), "+f"(d[23]), "+f"(d[24]), "+f"(d[25]), "+f"(d[26]), "+f"(d[27]), "+f"(d[28]), "+f"(d[29]), "+f"(d[30]), "+f"(d[31]), "+f"(d[32]), "+f"(d[33]), "+f"(d[34]), "+f"(d[35]), "+f"(d[36]), "+f"(d[37]), "+f"(d[38]), "+f"(d[39]), "+f"(d[40]), "+f"(d[41]), "+f"(d[42]), "+f"(d[43]), "+f"(d[44]), "+f"(d[45]), "+f"(d[46]), "+f"(d[47]), "+f"(d[48]), "+f"(d[49]), "+f"(d[50]), "+f"(d[51]), "+f"(d[52]), "+f"(d[53]), "+f"(d[54]), "+f"(d[55]), "+f"(d[56]), "+f"(d[57]), "+f"(d[58]), "+f"(d[59]), "+f"(d[60]), "+f"(d[61]), "+f"(d[62]), "+f"(d[63])
        : "r"(a0), "r"(a1), "r"(a2), "r"(a3), "r"(blo), "r"(bhi), "r"(scale_d));
}

__device__ __forceinline__ void wgmma_rs_n64_tb0(float (&d)[32], uint32_t a0, uint32_t a1, uint32_t a2, uint32_t a3, uint32_t blo, uint32_t bhi, int scale_d) {
    asm volatile("{\n.reg .pred p;\n.reg .b64 db;\nsetp.ne.b32 p, %38, 0;\nmov.b64 db, {%36, %37};\n"
        "wgmma.mma_async.sync.aligned.m64n64k16.f32.bf16.bf16 {%0, %1, %2, %3, %4, %5, %6, %7, %8, %9, %10, %11, %12, %13, %14, %15, %16, %17, %18, %19, %20, %21, %22, %23, %24, %25, %26, %27, %28, %29, %30, %31}, {%32, %33, %34, %35}, db, p, 1, 1, 0;\n}\n"
        : "+f"(d[0]), "+f"(d[1]), "+f"(d[2]), "+f"(d[3]), "+f"(d[4]), "+f"(d[5]), "+f"(d[6]), "+f"(d[7]), "+f"(d[8]), "+f"(d[9]), "+f"(d[10]), "+f"(d[11]), "+f"(d[12]), "+f"(d[13]), "+f"(d[14]), "+f"(d[15]), "+f"(d[16]), "+f"(d[17]), "+f"(d[18]), "+f"(d[19]), "+f"(d[20]), "+f"(d[21]), "+f"(d[22]), "+f"(d[23]), "+f"(d[24]), "+f"(d[25]), "+f"(d[26]), "+f"(d[27]), "+f"(d[28]), "+f"(d[29]), "+f"(d[30]), "+f"(d[31])
        : "r"(a0), "r"(a1), "r"(a2), "r"(a3), "r"(blo), "r"(bhi), "r"(scale_d));
}

__device__ __forceinline__ void wgmma_rs_n32_tb1(float (&d)[16], uint32_t a0, uint32_t a1, uint32_t a2, uint32_t a3, uint32_t blo, uint32_t bhi, int scale_d) {
    asm volatile("{\n.reg .pred p;\n.reg .b64 db;\nsetp.ne.b32 p, %22, 0;\nmov.b64 db, {%20, %21};\n"
        "wgmma.mma_async.sync.aligned.m64n32k16.f32.bf16.bf16 {%0, %1, %2, %3, %4, %5, %6, %7, %8, %9, %10, %11, %12, %13, %14, %15}, {%16, %17, %18, %19}, db, p, 1, 1, 1;\n}\n"
        : "+f"(d[0]), "+f"(d[1]), "+f"(d[2]), "+f"(d[3]), "+f"(d[4]), "+f"(d[5]), "+f"(d[6]), "+f"(d[7]), "+f"(d[8]), "+f"(d[9]), "+f"(d[10]), "+f"(d[11]), "+f"(d[12]), "+f"(d[13]), "+f"(d[14]), "+f"(d[15])
        : "r"(a0), "r"(a1), "r"(a2), "r"(a3), "r"(blo), "r"(bhi), "r"(scale_d));
}

__device__ __forceinline__ void wgmma_rs_n40_tb1(float (&d)[20], uint32_t a0, uint32_t a1, uint32_t a2, uint32_t a3, uint32_t blo, uint32_t bhi, int scale_d) {
    asm volatile("{\n.reg .pred p;\n.reg .b64 db;\nsetp.ne.b32 p, %26, 0;\nmov.b64 db, {%24, %25};\n"
        "wgmma.mma_async.sync.aligned.m64n40k16.f32.bf16.bf16 {%0, %1, %2, %3, %4, %5, %6, %7, %8, %9, %10, %11, %12, %13, %14, %15, %16, %17, %18, %19}, {%20, %21, %22, %23}, db, p, 1, 1, 1;\n}\n"
        : "+f"(d[0]), "+f"(d[1]), "+f"(d[2]), "+f"(d[3]), "+f"(d[4]), "+f"(d[5]), "+f"(d[6]), "+f"(d[7]), "+f"(d[8]), "+f"(d[9]), "+f"(d[10]), "+f"(d[11]), "+f"(d[12]), "+f"(d[13]), "+f"(d[14]), "+f"(d[15]), "+f"(d[16]), "+f"(d[17]), "+f"(d[18]), "+f"(d[19])
        : "r"(a0), "r"(a1), "r"(a2), "r"(a3), "r"(blo), "r"(bhi), "r"(scale_d));
}

template <int BN>
__device__ __forceinline__ void wgmma_tile(float (&d)[BN / 2], uint32_t da, uint32_t db, int sd) {
    constexpr uint32_t HI = desc_hi(1024, 1);
    if constexpr (BN == 128) wgmma_ss_n128_tb1(d, da, HI, db, HI, sd);
    else if constexpr (BN == 192) wgmma_ss_n192_tb1(d, da, HI, db, HI, sd);
    else if constexpr (BN == 224) wgmma_ss_n224_tb1(d, da, HI, db, HI, sd);
    else wgmma_ss_n256_tb1(d, da, HI, db, HI, sd);
}

__global__ void __launch_bounds__(256) prep_kernel(const bf16* __restrict__ x, const bf16* __restrict__ gate_w,
                                                   const bf16* __restrict__ w1, const bf16* __restrict__ w3) {
    const int tid = threadIdx.x;
    TL_START(0)
    pdl_launch();
    if (blockIdx.x < 256) {
        const int row = blockIdx.x * 8 + (tid >> 5);
        const int lane = tid & 31;
        const uint4* xr = reinterpret_cast<const uint4*>(x + (size_t)row * DM);
        const uint4* gw = reinterpret_cast<const uint4*>(gate_w);
        float v[32];
        float gsum = 0.f, sum = 0.f;
#pragma unroll
        for (int i = 0; i < 4; i++) {
            uint4 a = xr[lane + 32 * i];
            uint4 b = gw[lane + 32 * i];
            const uint32_t aa[4] = {a.x, a.y, a.z, a.w};
            const uint32_t bb[4] = {b.x, b.y, b.z, b.w};
#pragma unroll
            for (int j = 0; j < 4; j++) {
                float x0 = __uint_as_float(aa[j] << 16), x1 = __uint_as_float(aa[j] & 0xFFFF0000u);
                float g0 = __uint_as_float(bb[j] << 16), g1 = __uint_as_float(bb[j] & 0xFFFF0000u);
                v[i * 8 + j * 2] = x0;
                v[i * 8 + j * 2 + 1] = x1;
                sum += x0 + x1;
                gsum += bf16_round(x0 * g0) + bf16_round(x1 * g1);
            }
        }
#pragma unroll
        for (int o = 16; o > 0; o >>= 1) {
            sum += __shfl_xor_sync(0xffffffffu, sum, o);
            gsum += __shfl_xor_sync(0xffffffffu, gsum, o);
        }
        const float mean = sum * (1.0f / DM);
        float m2 = 0.f;
#pragma unroll
        for (int i = 0; i < 32; i++) {
            float d = v[i] - mean;
            m2 += d * d;
        }
#pragma unroll
        for (int o = 16; o > 0; o >>= 1) m2 += __shfl_xor_sync(0xffffffffu, m2, o);
        if (lane == 0) {
            g_mean1[row] = mean;
            g_rstd1[row] = rsqrtf(m2 * (1.0f / DM) + 1e-5f);
            float logit = bf16_round(gsum);
            float g = bf16_round(1.0f / (1.0f + __expf(-logit)));
            g_gate[row] = g;
            g_omg[row] = bf16_round(1.0f - g);
        }
    } else {
        __shared__ float red[32][65];
        const int strip = blockIdx.x - 256;
        const bf16* w;
        float* out;
        int ld, col0;
        if (strip < 16) { w = w1; ld = DM; col0 = strip * 64; out = g_cs1; }
        else { w = w3; ld = FF; col0 = (strip - 16) * 64; out = g_cs3; }
        const int cg = tid & 7;
        const int rg = tid >> 3;
        float acc[8];
#pragma unroll
        for (int j = 0; j < 8; j++) acc[j] = 0.f;
#pragma unroll 8
        for (int r = 0; r < 32; r++) {
            uint4 a = *reinterpret_cast<const uint4*>(w + (size_t)(r * 32 + rg) * ld + col0 + cg * 8);
            const uint32_t aa[4] = {a.x, a.y, a.z, a.w};
#pragma unroll
            for (int j = 0; j < 4; j++) {
                acc[2 * j] += __uint_as_float(aa[j] << 16);
                acc[2 * j + 1] += __uint_as_float(aa[j] & 0xFFFF0000u);
            }
        }
#pragma unroll
        for (int j = 0; j < 8; j++) red[rg][cg * 8 + j] = acc[j];
        __syncthreads();
        if (tid < 64) {
            float s = 0.f;
#pragma unroll
            for (int r = 0; r < 32; r++) s += red[r][tid];
            out[col0 + tid] = s;
        }
    }
    TL_END(0)
}

#define RELEASE_STAGE(b) if (tid_wg < 2) mbar_arrive_cluster(b, tid_wg)
template <int BN, int STAGES>
struct GemmSmem {
    static constexpr int A_BYTES = 128 * 64 * 2;
    static constexpr int B_BOXES = (BN + 63) / 64;
    static constexpr int B_BYTES = B_BOXES * 64 * 64 * 2;
    static constexpr int STAGE_BYTES = A_BYTES + B_BYTES;
    static constexpr int STG_OFF = STAGES * STAGE_BYTES;
    static constexpr int BAR_OFF = STAGES * STAGE_BYTES + 2 * 16384;
    static constexpr int TOTAL = BAR_OFF + 256 + 1024;
};

template <int MODE, int BN, int STAGES>
__global__ void __launch_bounds__(384, 1)
gemm_kernel(const __grid_constant__ CUtensorMap mA, const __grid_constant__ CUtensorMap mB0,
            const __grid_constant__ CUtensorMap mB1, const __grid_constant__ CUtensorMap mC0,
            const __grid_constant__ CUtensorMap mC1, const bf16* __restrict__ xin, int n_tiles_n, int kblocks) {
    using L = GemmSmem<BN, STAGES>;
    extern __shared__ uint8_t smem_raw[];
    const uint32_t sbase = (smem_u32(smem_raw) + 1023u) & ~1023u;
    const uint32_t bar_full = sbase + L::BAR_OFF;
    const uint32_t bar_empty = bar_full + 8 * STAGES;
    const int wg = threadIdx.x >> 7;
    const int npairs = 8 * n_tiles_n;
    const uint32_t crank = cluster_rank();
    const int cid = blockIdx.x >> 1, ncl = gridDim.x >> 1;
    TL_START(MODE)
    pdl_launch();

    if (threadIdx.x == 0) {
        for (int s = 0; s < STAGES; s++) {
            mbar_init(bar_full + 8 * s, 1);
            mbar_init(bar_empty + 8 * s, 4);
        }
        asm volatile("fence.mbarrier_init.release.cluster;" ::: "memory");
        prefetch_tmap(&mA);
        prefetch_tmap(&mB0);
        if (MODE == 1 || MODE == 5) prefetch_tmap(&mB1);
        prefetch_tmap(&mC0);
    }
    cluster_sync_all();

    if (wg == 0) {
        reg_dealloc<40>();
        if (threadIdx.x == 0) {
            if (MODE != 1) pdl_wait();
            int stage = 0;
            uint32_t phase = 1;
            for (int pr = cid; pr < npairs; pr += ncl) {
                const int m0 = ((pr & 7) * 2 + crank) * 128;
                const int n0 = (pr >> 3) * BN;
                for (int kb = 0; kb < kblocks; kb++) {
                    mbar_wait(bar_empty + 8 * stage, phase);
                    const uint32_t sa = sbase + stage * L::STAGE_BYTES;
                    const uint32_t sb = sa + L::A_BYTES;
                    const uint32_t fb = bar_full + 8 * stage;
                    mbar_expect_tx(fb, L::STAGE_BYTES);
                    int arow = m0;
                    if (MODE == 2) {
                        const int grp = kb >> 2;
                        arow += (grp == 0) ? -1 : (grp == 1) ? 1 : (grp == 2) ? -2 : 2;
                    }
                    tma_load_2d(sa, &mA, kb * 64, arow, fb);
                    const CUtensorMap* mb = &mB0;
                    int bc = n0, br = kb * 64;
                    if (MODE == 1 && n0 >= 3 * DM) { mb = &mB1; bc = n0 - 3 * DM; }
                    if (MODE == 5 && kb >= 16) { mb = &mB1; br = (kb - 16) * 64; }
#pragma unroll
                    for (int b = 0; b < L::B_BOXES / 2; b++) {
                        const int bb = crank * (L::B_BOXES / 2) + b;
                        tma_load_2d_mc(sb + bb * 8192, mb, bc + bb * 64, br, fb, (uint16_t)3);
                    }
                    if (++stage == STAGES) { stage = 0; phase ^= 1; }
                }
            }
        }
    } else {
        reg_alloc<232>();
        const int c = wg - 1;
        const int warp = (threadIdx.x >> 5) & 3;
        const int lane = threadIdx.x & 31;
        const int tid_wg = threadIdx.x & 127;
        const uint32_t stg = sbase + L::STG_OFF + c * 16384;
        int stage = 0;
        uint32_t phase = 0;
        float acc[BN / 2];
        bool first = true;
        for (int pr = cid; pr < npairs; pr += ncl) {
            const int m0 = ((pr & 7) * 2 + crank) * 128;
            const int n0 = (pr >> 3) * BN;
            int prev_stage = 0;
            for (int kb = 0; kb < kblocks; kb++) {
                mbar_wait(bar_full + 8 * stage, phase);
                const uint32_t sa = sbase + stage * L::STAGE_BYTES + c * 8192;
                const uint32_t sb = sbase + stage * L::STAGE_BYTES + L::A_BYTES;
                const uint32_t da = desc_lo(sa, 16);
                const uint32_t db = desc_lo(sb, 8192);
                wgmma_fence();
#pragma unroll
                for (int k = 0; k < 4; k++) wgmma_tile<BN>(acc, da + k * 2, db + k * 128, (kb | k) != 0);
                wgmma_commit();
                if (kb > 0) {
                    wgmma_wait<1>();
                    RELEASE_STAGE(bar_empty + 8 * prev_stage);
                }
                prev_stage = stage;
                if (++stage == STAGES) { stage = 0; phase ^= 1; }
            }
            wgmma_wait<0>();
            RELEASE_STAGE(bar_empty + 8 * prev_stage);
            if (first) { pdl_wait(); first = false; }

            const int r0 = m0 + c * 64 + warp * 16 + (lane >> 2);
            const int r1 = r0 + 8;
            const int cq = (lane & 3) * 2;
            const CUtensorMap* mc = &mC0;
            int out_c0 = n0;
            if (MODE == 1) {
                if (n0 < DM) {
                    const float qs = 0.17677669529663687f * 1.4426950408889634f;
#pragma unroll
                    for (int j = 0; j < BN / 2; j++) acc[j] *= qs;
                } else if (n0 >= 3 * DM) {
                    mc = &mC1;
                    out_c0 = n0 - 3 * DM;
                    const float mu0 = g_mean1[r0], mu1 = g_mean1[r1];
                    const float rs0 = g_rstd1[r0], rs1 = g_rstd1[r1];
#pragma unroll
                    for (int j = 0; j < BN / 8; j++) {
                        const float2 cs = *reinterpret_cast<const float2*>(&g_cs1[out_c0 + 8 * j + cq]);
                        acc[4 * j + 0] = gelu_tanh(rs0 * fmaf(-mu0, cs.x, acc[4 * j + 0]));
                        acc[4 * j + 1] = gelu_tanh(rs0 * fmaf(-mu0, cs.y, acc[4 * j + 1]));
                        acc[4 * j + 2] = gelu_tanh(rs1 * fmaf(-mu1, cs.x, acc[4 * j + 2]));
                        acc[4 * j + 3] = gelu_tanh(rs1 * fmaf(-mu1, cs.y, acc[4 * j + 3]));
                    }
                }
            } else if (MODE == 2) {
                float s0 = 0.f, s1 = 0.f;
#pragma unroll
                for (int j = 0; j < BN / 8; j++) {
                    const uint32_t xa = *reinterpret_cast<const uint32_t*>(xin + (size_t)r0 * DM + n0 + 8 * j + cq);
                    const uint32_t xb = *reinterpret_cast<const uint32_t*>(xin + (size_t)r1 * DM + n0 + 8 * j + cq);
                    acc[4 * j + 0] = bf16_round(bf16_round(acc[4 * j + 0]) + __uint_as_float(xa << 16));
                    acc[4 * j + 1] = bf16_round(bf16_round(acc[4 * j + 1]) + __uint_as_float(xa & 0xFFFF0000u));
                    acc[4 * j + 2] = bf16_round(bf16_round(acc[4 * j + 2]) + __uint_as_float(xb << 16));
                    acc[4 * j + 3] = bf16_round(bf16_round(acc[4 * j + 3]) + __uint_as_float(xb & 0xFFFF0000u));
                    s0 += acc[4 * j + 0] + acc[4 * j + 1];
                    s1 += acc[4 * j + 2] + acc[4 * j + 3];
                }
                s0 += __shfl_xor_sync(0xffffffffu, s0, 1);
                s0 += __shfl_xor_sync(0xffffffffu, s0, 2);
                s1 += __shfl_xor_sync(0xffffffffu, s1, 1);
                s1 += __shfl_xor_sync(0xffffffffu, s1, 2);
                const float mu0 = s0 * (1.0f / BN), mu1 = s1 * (1.0f / BN);
                float q0 = 0.f, q1 = 0.f;
#pragma unroll
                for (int j = 0; j < BN / 8; j++) {
                    float d;
                    d = acc[4 * j + 0] - mu0; q0 += d * d;
                    d = acc[4 * j + 1] - mu0; q0 += d * d;
                    d = acc[4 * j + 2] - mu1; q1 += d * d;
                    d = acc[4 * j + 3] - mu1; q1 += d * d;
                }
                q0 += __shfl_xor_sync(0xffffffffu, q0, 1);
                q0 += __shfl_xor_sync(0xffffffffu, q0, 2);
                q1 += __shfl_xor_sync(0xffffffffu, q1, 1);
                q1 += __shfl_xor_sync(0xffffffffu, q1, 2);
                if ((lane & 3) == 0) {
                    static_assert(MODE != 2 || BN == 128, "stats layout assumes BN=128");
                    g_stat2[r0 * 8 + (n0 >> 7)] = make_float2(s0, q0);
                    g_stat2[r1 * 8 + (n0 >> 7)] = make_float2(s1, q1);
                }
            } else if (MODE == 3) {
                out_c0 = n0 + DM;
                float mu[2], rs[2];
#pragma unroll
                for (int h = 0; h < 2; h++) {
                    const float4* sp = reinterpret_cast<const float4*>(&g_stat2[(h ? r1 : r0) * 8]);
                    float4 p[4];
                    float s = 0.f;
#pragma unroll
                    for (int i = 0; i < 4; i++) { p[i] = sp[i]; s += p[i].x + p[i].z; }
                    const float mean = s * (1.0f / DM);
                    float m2 = 0.f;
#pragma unroll
                    for (int i = 0; i < 4; i++) {
                        float d0 = p[i].x * (1.0f / 128) - mean, d1 = p[i].z * (1.0f / 128) - mean;
                        m2 += p[i].y + p[i].w + 128.0f * (d0 * d0 + d1 * d1);
                    }
                    mu[h] = mean;
                    rs[h] = rsqrtf(m2 * (1.0f / DM) + 1e-5f);
                }
                const float og0 = g_omg[r0], og1 = g_omg[r1];
#pragma unroll
                for (int j = 0; j < BN / 8; j++) {
                    const float2 cs = *reinterpret_cast<const float2*>(&g_cs3[n0 + 8 * j + cq]);
                    acc[4 * j + 0] = og0 * gelu_tanh(rs[0] * fmaf(-mu[0], cs.x, acc[4 * j + 0]));
                    acc[4 * j + 1] = og0 * gelu_tanh(rs[0] * fmaf(-mu[0], cs.y, acc[4 * j + 1]));
                    acc[4 * j + 2] = og1 * gelu_tanh(rs[1] * fmaf(-mu[1], cs.x, acc[4 * j + 2]));
                    acc[4 * j + 3] = og1 * gelu_tanh(rs[1] * fmaf(-mu[1], cs.y, acc[4 * j + 3]));
                }
            } else {
                const float og0 = g_omg[r0], og1 = g_omg[r1];
#pragma unroll
                for (int j = 0; j < BN / 8; j++) {
                    const uint32_t xa = *reinterpret_cast<const uint32_t*>(xin + (size_t)r0 * DM + n0 + 8 * j + cq);
                    const uint32_t xb = *reinterpret_cast<const uint32_t*>(xin + (size_t)r1 * DM + n0 + 8 * j + cq);
                    acc[4 * j + 0] = fmaf(og0, __uint_as_float(xa << 16), acc[4 * j + 0]);
                    acc[4 * j + 1] = fmaf(og0, __uint_as_float(xa & 0xFFFF0000u), acc[4 * j + 1]);
                    acc[4 * j + 2] = fmaf(og1, __uint_as_float(xb << 16), acc[4 * j + 2]);
                    acc[4 * j + 3] = fmaf(og1, __uint_as_float(xb & 0xFFFF0000u), acc[4 * j + 3]);
                }
            }
            const int srow = warp * 16 + (lane & 7) + ((lane >> 3) & 1) * 8;
#pragma unroll
            for (int rnd = 0; rnd < (BN + 127) / 128; rnd++) {
                if (tid_wg == 0) bulk_wait_read0();
                named_bar_sync(1 + c, 128);
#pragma unroll
                for (int jj = 0; jj < 8; jj++) {
                    const int j = rnd * 16 + jj * 2;
                    if (j * 8 < BN) {
                        const int jb = jj * 2 + (lane >> 4);
                        uint32_t addr = stg + (jb >> 3) * 8192 + srow * 128 + (((jb & 7) ^ (srow & 7)) << 4);
                        if (rnd * 128 + 128 > BN && jj >= 4)
                            addr = stg + 8192 + srow * 64 + (((jb & 3) ^ ((srow >> 1) & 3)) << 4);
                        stmatrix_x4(addr, pack_bf16(acc[4 * j + 0], acc[4 * j + 1]), pack_bf16(acc[4 * j + 2], acc[4 * j + 3]),
                                    pack_bf16(acc[4 * j + 4], acc[4 * j + 5]), pack_bf16(acc[4 * j + 6], acc[4 * j + 7]));
                    }
                }
                fence_proxy_async();
                named_bar_sync(1 + c, 128);
                if (tid_wg == 0) {
                    tma_store_2d(mc, stg, out_c0 + rnd * 128, m0 + c * 64);
                    if (rnd * 128 + 64 < BN)
                        tma_store_2d((rnd * 128 + 128 > BN) ? &mC1 : mc, stg + 8192, out_c0 + rnd * 128 + 64, m0 + c * 64);
                    bulk_commit();
                }
            }
        }
        if (tid_wg == 0) bulk_wait0();
        TL_END(MODE)
    }
    cluster_sync_all();
}

constexpr int ATT_NTILES = NH * 16;
#define ATT_GRID_N 512
constexpr int ATT_GRID = ATT_GRID_N;
constexpr int ATT_THREADS = 256;
constexpr int ATT_STAGES = 4;
constexpr int ATT_DIST = 2;
constexpr int ATT_Q_OFF = ATT_STAGES * 16384;
constexpr int ATT_ONES_OFF = ATT_Q_OFF + 8192;
constexpr int ATT_KEXT_OFF = ATT_ONES_OFF + 4096;
constexpr int ATT_BAR_OFF = ATT_KEXT_OFF + 4096;
constexpr int ATT_SMEM = ATT_BAR_OFF + 256 + 1024;

__device__ __forceinline__ void row_max(const float (&s)[32], float& m0, float& m1) {
    float a0[8], a1[8];
#pragma unroll
    for (int i = 0; i < 8; i++) {
        a0[i] = fmaxf(s[4 * i], s[4 * i + 1]);
        a1[i] = fmaxf(s[4 * i + 2], s[4 * i + 3]);
    }
#pragma unroll
    for (int w = 4; w > 0; w >>= 1)
#pragma unroll
        for (int i = 0; i < w; i++) { a0[i] = fmaxf(a0[i], a0[i + w]); a1[i] = fmaxf(a1[i], a1[i + w]); }
    float mx0 = a0[0], mx1 = a1[0];
    mx0 = fmaxf(mx0, __shfl_xor_sync(0xffffffffu, mx0, 1));
    mx1 = fmaxf(mx1, __shfl_xor_sync(0xffffffffu, mx1, 1));
    mx0 = fmaxf(mx0, __shfl_xor_sync(0xffffffffu, mx0, 2));
    mx1 = fmaxf(mx1, __shfl_xor_sync(0xffffffffu, mx1, 2));
    m0 = fmaxf(m0, mx0);
    m1 = fmaxf(m1, mx1);
}

__device__ __forceinline__ void attn_step(float (&sc)[32], float (&sn)[32], uint32_t (&p)[16], float (&o)[20], uint32_t dq,
                                          uint32_t e0, uint32_t e1, uint32_t dke, uint32_t dk_next, uint32_t dv_prev,
                                          uint32_t release_bar) {
    constexpr uint32_t HI = desc_hi(512, 2);
    wgmma_fence();
    wgmma_ss_n64_tb0(sn, dq, HI, dk_next, HI, 0);
    wgmma_ss_n64_tb0(sn, dq + 2, HI, dk_next + 2, HI, 1);
    wgmma_rs_n64_tb0(sn, e0, e1, 0u, 0u, dke, HI, 1);
#pragma unroll
    for (int t = 0; t < 4; t++)
        wgmma_rs_n40_tb1(o, p[4 * t], p[4 * t + 1], p[4 * t + 2], p[4 * t + 3], dv_prev + t * 64, HI, 1);
    wgmma_commit();
#pragma unroll
    for (int i = 0; i < 32; i++) sc[i] = ex2(sc[i]);
    wgmma_wait<0>();
    if (release_bar != 0 && (threadIdx.x & 127) == 0) mbar_arrive(release_bar);
#pragma unroll
    for (int i = 0; i < 8; i++) {
        p[2 * i] = pack_bf16(sc[4 * i + 0], sc[4 * i + 1]);
        p[2 * i + 1] = pack_bf16(sc[4 * i + 2], sc[4 * i + 3]);
    }
}

__global__ void __launch_bounds__(256, 1)
attn_exact_kernel(const __grid_constant__ CUtensorMap mKV) {
    extern __shared__ uint8_t smem_raw[];
    pdl_launch();
    pdl_wait();
    const int tile = blockIdx.x;
    if (g_bad[tile] == 0) return;
    constexpr int NBLK = S_LEN / 128;
    constexpr uint32_t HI = desc_hi(512, 2);
    const uint32_t sbase = (smem_u32(smem_raw) + 1023u) & ~1023u;
    const uint32_t bar = sbase + ATT_BAR_OFF;
    const int warp_id = threadIdx.x >> 5;
    const int lane = threadIdx.x & 31;
    const int cq = (lane & 3) * 2;
    const uint32_t dk0 = desc_lo(sbase, 16);
    const uint32_t dv0 = desc_lo(sbase + 8192, ATT_ONES_OFF - 8192);
    if (threadIdx.x == 0) {
        mbar_init(bar, 1);
        asm volatile("fence.mbarrier_init.release.cluster;" ::: "memory");
    }
    asm volatile("st.shared.v4.b32 [%0], {%1, %1, %1, %1};" ::"r"(sbase + ATT_ONES_OFF + threadIdx.x * 16), "r"(0x3F803F80u) : "memory");
    fence_proxy_async();
    __syncthreads();
    const int head = tile >> 4;
    const int row0 = (tile & 15) * 128 + warp_id * 16 + (lane >> 2);
    const uint32_t dq = desc_lo(sbase + ATT_Q_OFF + (threadIdx.x >> 7) * 4096, 16);
    float o[20];
#pragma unroll
    for (int i = 0; i < 20; i++) o[i] = 0.f;
    float m0 = -INFINITY, m1 = -INFINITY;
#pragma unroll 1
    for (int j = 0; j < NBLK; j++) {
        if (threadIdx.x == 0) {
            mbar_expect_tx(bar, j == 0 ? 3 * 8192 : 2 * 8192);
            if (j == 0) tma_load_2d(sbase + ATT_Q_OFF, &mKV, head * DH, (tile & 15) * 128, bar);
            tma_load_2d(sbase, &mKV, DM + head * DH, j * 128, bar);
            tma_load_2d(sbase + 8192, &mKV, 2 * DM + head * DH, j * 128, bar);
        }
        __syncwarp();
        mbar_wait(bar, j & 1);
#pragma unroll 1
        for (int hf = 0; hf < 2; hf++) {
            float s[32];
            wgmma_fence();
            wgmma_ss_n64_tb0(s, dq, HI, dk0 + hf * 256, HI, 0);
            wgmma_ss_n64_tb0(s, dq + 2, HI, dk0 + hf * 256 + 2, HI, 1);
            wgmma_commit();
            wgmma_wait<0>();
            const float mo0 = m0, mo1 = m1;
            row_max(s, m0, m1);
            const float a0 = ex2(mo0 - m0), a1 = ex2(mo1 - m1);
            uint32_t p[16];
#pragma unroll
            for (int i = 0; i < 8; i++) {
                p[2 * i] = pack_bf16(ex2(s[4 * i + 0] - m0), ex2(s[4 * i + 1] - m0));
                p[2 * i + 1] = pack_bf16(ex2(s[4 * i + 2] - m1), ex2(s[4 * i + 3] - m1));
            }
#pragma unroll
            for (int i = 0; i < 5; i++) {
                o[4 * i + 0] *= a0; o[4 * i + 1] *= a0;
                o[4 * i + 2] *= a1; o[4 * i + 3] *= a1;
            }
            wgmma_fence();
            const uint32_t dv = dv0 + hf * 256 - ((uint32_t)(hf * 256) << 16);
#pragma unroll
            for (int t = 0; t < 4; t++)
                wgmma_rs_n40_tb1(o, p[4 * t], p[4 * t + 1], p[4 * t + 2], p[4 * t + 3], dv + t * 64, HI, 1);
            wgmma_commit();
            wgmma_wait<0>();
        }
        __syncthreads();
    }
    const float f0 = g_gate[row0] / o[16], f1 = g_gate[row0 + 8] / o[18];
    bf16* op0 = g_a5 + (size_t)row0 * A5W + head * DH + cq;
    bf16* op1 = op0 + 8 * A5W;
#pragma unroll
    for (int i = 0; i < 4; i++) {
        *reinterpret_cast<uint32_t*>(op0 + 8 * i) = pack_bf16(o[4 * i] * f0, o[4 * i + 1] * f0);
        *reinterpret_cast<uint32_t*>(op1 + 8 * i) = pack_bf16(o[4 * i + 2] * f1, o[4 * i + 3] * f1);
    }
}

__global__ void __launch_bounds__(256, 2)
attn_kernel(const __grid_constant__ CUtensorMap mKV) {
    extern __shared__ uint8_t smem_raw[];
    const uint32_t sbase = (smem_u32(smem_raw) + 1023u) & ~1023u;
    const uint32_t bar_kfull = sbase + ATT_BAR_OFF;
    const uint32_t bar_vfull = bar_kfull + 8 * ATT_STAGES;
    const uint32_t bar_empty = bar_vfull + 8 * ATT_STAGES;
    const int tile = blockIdx.x;
    const int head = tile >> 4;
    const int lane = threadIdx.x & 31;
    constexpr int NBLK = S_LEN / 128;
    TL_START(6)
    pdl_launch();

    auto issue_kv = [&](int g) {
        const int sn = g % ATT_STAGES;
        if (g >= ATT_STAGES) mbar_wait(bar_empty + 8 * sn, ((g / ATT_STAGES) - 1) & 1);
        const uint32_t skn = sbase + sn * 16384;
        mbar_expect_tx(bar_kfull + 8 * sn, g == 0 ? 16384 : 8192);
        if (g == 0) tma_load_2d(sbase + ATT_Q_OFF, &mKV, head * DH, (tile & 15) * 128, bar_kfull);
        tma_load_2d(skn, &mKV, DM + head * DH, g * 128, bar_kfull + 8 * sn);
        mbar_expect_tx(bar_vfull + 8 * sn, 8192);
        tma_load_2d(skn + 8192, &mKV, 2 * DM + head * DH, g * 128, bar_vfull + 8 * sn);
    };

    if (threadIdx.x == 0) {
        for (int s = 0; s < ATT_STAGES; s++) {
            mbar_init(bar_kfull + 8 * s, 1);
            mbar_init(bar_vfull + 8 * s, 1);
            mbar_init(bar_empty + 8 * s, 2);
        }
        asm volatile("fence.mbarrier_init.release.cluster;" ::: "memory");
        prefetch_tmap(&mKV);
        pdl_wait();
#pragma unroll
        for (int j = 0; j < ATT_DIST; j++) issue_kv(j);
    }
    {
        asm volatile("st.shared.v4.b32 [%0], {%1, %1, %1, %1};" ::"r"(sbase + ATT_ONES_OFF + threadIdx.x * 16), "r"(0x3F803F80u) : "memory");
        const int r = threadIdx.x >> 2, ch = threadIdx.x & 3;
        const uint32_t w0 = (ch == ((r >> 1) & 3)) ? 0x00003F80u : 0u;
        asm volatile("st.shared.v4.b32 [%0], {%1, %2, %2, %2};" ::"r"(sbase + ATT_KEXT_OFF + threadIdx.x * 16), "r"(w0), "r"(0u) : "memory");
    }
    fence_proxy_async();
    __syncthreads();

    constexpr uint32_t HI = desc_hi(512, 2);
    const uint32_t dk0 = desc_lo(sbase, 16);
    const uint32_t dv0 = desc_lo(sbase + 8192, ATT_ONES_OFF - 8192);
    const uint32_t dke = dk0 + (ATT_KEXT_OFF >> 4);
    const uint32_t dq = dk0 + ((ATT_Q_OFF + (threadIdx.x >> 7) * 4096) >> 4);
    float o[20];
#pragma unroll
    for (int i = 0; i < 20; i++) o[i] = 0.f;
    float s0[32], s1[32];
    uint32_t p[16];
#pragma unroll
    for (int i = 0; i < 16; i++) p[i] = 0u;
    mbar_wait(bar_kfull, 0);
    wgmma_fence();
    wgmma_ss_n64_tb0(s0, dq, HI, dk0, HI, 0);
    wgmma_ss_n64_tb0(s0, dq + 2, HI, dk0 + 2, HI, 1);
    wgmma_commit();
    wgmma_wait<0>();
    float m0 = -INFINITY, m1 = -INFINITY;
    row_max(s0, m0, m1);
    const uint32_t e0 = (lane & 3) == 0 ? (pack_bf16(-m0, 0.f) & 0xFFFFu) : 0u;
    const uint32_t e1 = (lane & 3) == 0 ? (pack_bf16(-m1, 0.f) & 0xFFFFu) : 0u;
    wgmma_fence();
    wgmma_rs_n64_tb0(s0, e0, e1, 0u, 0u, dke, HI, 1);
    wgmma_commit();
    mbar_wait(bar_vfull, 0);
    wgmma_wait<0>();
    uint32_t dv_prev = dv0;
#pragma unroll 1
    for (int j = 0; j < NBLK; j++) {
        if (threadIdx.x == 0 && j + ATT_DIST < NBLK) issue_kv(j + ATT_DIST);
        __syncwarp();
        const uint32_t stage = j & (ATT_STAGES - 1), nstage = (j + 1) & (ATT_STAGES - 1);
        const uint32_t dk = dk0 + stage * 1024;
        const uint32_t dv = dv0 + stage * 1024 - (stage << 26);
        attn_step(s0, s1, p, o, dq, e0, e1, dke, dk + 256, dv_prev,
                  j > 0 ? bar_empty + 8 * ((j - 1) & (ATT_STAGES - 1)) : 0u);
        uint32_t dkn = dk;
        if (j + 1 < NBLK) {
            mbar_wait(bar_kfull + 8 * nstage, ((j + 1) / ATT_STAGES) & 1);
            dkn = dk0 + nstage * 1024;
        }
        mbar_wait(bar_vfull + 8 * stage, (j / ATT_STAGES) & 1);
        attn_step(s1, s0, p, o, dq, e0, e1, dke, dkn, dv, 0u);
        dv_prev = dv + 256 - (256u << 16);
    }
    wgmma_fence();
#pragma unroll
    for (int t = 0; t < 4; t++)
        wgmma_rs_n40_tb1(o, p[4 * t], p[4 * t + 1], p[4 * t + 2], p[4 * t + 3], dv_prev + t * 64, HI, 1);
    wgmma_commit();
    wgmma_wait<0>();
    bool ok = (o[16] <= 1.8446744e19f) && (o[18] <= 1.8446744e19f);
#pragma unroll
    for (int i = 0; i < 16; i++) ok = ok && (fabsf(o[i]) <= 3.0e38f);
    const int row0 = (tile & 15) * 128 + (threadIdx.x >> 5) * 16 + (lane >> 2);
    const float f0 = g_gate[row0] / o[16], f1 = g_gate[row0 + 8] / o[18];
    bf16* op0 = g_a5 + (size_t)row0 * A5W + head * DH + (lane & 3) * 2;
    bf16* op1 = op0 + 8 * A5W;
#pragma unroll
    for (int i = 0; i < 4; i++) {
        *reinterpret_cast<uint32_t*>(op0 + 8 * i) = pack_bf16(o[4 * i] * f0, o[4 * i + 1] * f0);
        *reinterpret_cast<uint32_t*>(op1 + 8 * i) = pack_bf16(o[4 * i + 2] * f1, o[4 * i + 3] * f1);
    }
    const int bad = __syncthreads_or(!ok);
    if (threadIdx.x == 0) g_bad[tile] = bad;
    TL_END(6)
}

typedef CUresult (*EncodeFn)(CUtensorMap*, CUtensorMapDataType, cuuint32_t, void*, const cuuint64_t*, const cuuint64_t*,
                             const cuuint32_t*, const cuuint32_t*, CUtensorMapInterleave, CUtensorMapSwizzle,
                             CUtensorMapL2promotion, CUtensorMapFloatOOBfill);

static CUtensorMap make_map(EncodeFn fn, const void* ptr, int rows, int cols, int box_cols, int box_rows,
                            CUtensorMapSwizzle swz) {
    CUtensorMap m;
    cuuint64_t dims[2] = {(cuuint64_t)cols, (cuuint64_t)rows};
    cuuint64_t strides[1] = {(cuuint64_t)cols * 2};
    cuuint32_t box[2] = {(cuuint32_t)box_cols, (cuuint32_t)box_rows};
    cuuint32_t es[2] = {1, 1};
    fn(&m, CU_TENSOR_MAP_DATA_TYPE_BFLOAT16, 2, const_cast<void*>(ptr), dims, strides, box, es,
       CU_TENSOR_MAP_INTERLEAVE_NONE, swz, CU_TENSOR_MAP_L2_PROMOTION_L2_256B, CU_TENSOR_MAP_FLOAT_OOB_FILL_NONE);
    return m;
}

template <typename... KArgs, typename... Args>
static void launch_ex(void (*kern)(KArgs...), int grid, int block, int smem, cudaStream_t st, int cluster, Args... args) {
    cudaLaunchConfig_t cfg = {};
    cfg.gridDim = dim3(grid);
    cfg.blockDim = dim3(block);
    cfg.dynamicSmemBytes = smem;
    cfg.stream = st;
    cudaLaunchAttribute at[2];
    at[0].id = cudaLaunchAttributeProgrammaticStreamSerialization;
    at[0].val.programmaticStreamSerializationAllowed = 1;
    at[1].id = cudaLaunchAttributeClusterDimension;
    at[1].val.clusterDim.x = cluster;
    at[1].val.clusterDim.y = 1;
    at[1].val.clusterDim.z = 1;
    cfg.attrs = at;
    cfg.numAttrs = cluster > 1 ? 2 : 1;
    cudaLaunchKernelEx(&cfg, kern, KArgs(args)...);
}

extern "C" void kernel_launch(void* const* d_in, const int* in_sizes, int n_in, void* d_out, int out_size) {
    const bf16* x = (const bf16*)d_in[0];
    const bf16* wqkv = (const bf16*)d_in[1];
    const bf16* wo = (const bf16*)d_in[2];
    const bf16* w1 = (const bf16*)d_in[4];
    const bf16* w2 = (const bf16*)d_in[5];
    const bf16* w3 = (const bf16*)d_in[6];
    const bf16* w4 = (const bf16*)d_in[7];
    const bf16* gate_w = (const bf16*)d_in[8];

    static EncodeFn enc = nullptr;
    static void *p_qkv, *p_h, *p_x1, *p_a5;
    using G1 = GemmSmem<256, 4>;
    using G2 = GemmSmem<128, 5>;
    using G3 = GemmSmem<224, 4>;
    if (!enc) {
        void* fn = nullptr;
        cudaDriverEntryPointQueryResult qres;
        cudaGetDriverEntryPoint("cuTensorMapEncodeTiled", &fn, cudaEnableDefault, &qres);
        enc = (EncodeFn)fn;
        cudaGetSymbolAddress(&p_qkv, g_qkv);
        cudaGetSymbolAddress(&p_h, g_h);
        cudaGetSymbolAddress(&p_x1, g_x1);
        cudaGetSymbolAddress(&p_a5, g_a5);
        cudaFuncSetAttribute(gemm_kernel<1, 256, 4>, cudaFuncAttributeMaxDynamicSharedMemorySize, G1::TOTAL);
        cudaFuncSetAttribute(gemm_kernel<2, 128, 5>, cudaFuncAttributeMaxDynamicSharedMemorySize, G2::TOTAL);
        cudaFuncSetAttribute(gemm_kernel<3, 224, 4>, cudaFuncAttributeMaxDynamicSharedMemorySize, G3::TOTAL);
        cudaFuncSetAttribute(gemm_kernel<5, 128, 5>, cudaFuncAttributeMaxDynamicSharedMemorySize, G2::TOTAL);
        cudaFuncSetAttribute(attn_kernel, cudaFuncAttributeMaxDynamicSharedMemorySize, ATT_SMEM);
        cudaFuncSetAttribute(attn_exact_kernel, cudaFuncAttributeMaxDynamicSharedMemorySize, ATT_SMEM);
    }
    const CUtensorMapSwizzle SW128 = CU_TENSOR_MAP_SWIZZLE_128B, SW64 = CU_TENSOR_MAP_SWIZZLE_64B;
    CUtensorMap mX = make_map(enc, x, S_LEN, DM, 64, 128, SW128);
    CUtensorMap mWqkv = make_map(enc, wqkv, DM, 3 * DM, 64, 64, SW128);
    CUtensorMap mW1 = make_map(enc, w1, DM, DM, 64, 64, SW128);
    CUtensorMap mW2 = make_map(enc, w2, DM, DM, 64, 64, SW128);
    CUtensorMap mW3 = make_map(enc, w3, DM, FF, 64, 64, SW128);
    CUtensorMap mW4 = make_map(enc, w4, FF, DM, 64, 64, SW128);
    CUtensorMap mWo = make_map(enc, wo, DM, DM, 64, 64, SW128);
    CUtensorMap mQKVst = make_map(enc, p_qkv, S_LEN, 3 * DM, 64, 64, SW128);
    CUtensorMap mKV = make_map(enc, p_qkv, S_LEN, 3 * DM, 32, 128, SW64);
    CUtensorMap mHst = make_map(enc, p_h, S_LEN, DM, 64, 64, SW128);
    CUtensorMap mHld = make_map(enc, p_h, S_LEN, DM, 64, 128, SW128);
    CUtensorMap mX1st = make_map(enc, p_x1, S_LEN, DM, 64, 64, SW128);
    CUtensorMap mX1ld = make_map(enc, p_x1, S_LEN, DM, 64, 128, SW128);
    CUtensorMap mA5st = make_map(enc, p_a5, S_LEN, A5W, 64, 64, SW128);
    CUtensorMap mA5st32 = make_map(enc, p_a5, S_LEN, A5W, 32, 64, SW64);
    CUtensorMap mA5ld = make_map(enc, p_a5, S_LEN, A5W, 64, 128, SW128);
    CUtensorMap mOut = make_map(enc, d_out, S_LEN, DM, 64, 64, SW128);

    cudaStream_t st = cudaStreamPerThread;
    prep_kernel<<<256 + 72, 256, 0, st>>>(x, gate_w, w1, w3);
    launch_ex(gemm_kernel<1, 256, 4>, 132, 384, G1::TOTAL, st, 2, mX, mWqkv, mW1, mQKVst, mHst, x, 16, 16);
    launch_ex(attn_kernel, ATT_GRID, ATT_THREADS, ATT_SMEM, st, 1, mKV);
    launch_ex(attn_exact_kernel, ATT_NTILES, ATT_THREADS, ATT_SMEM, st, 1, mKV);
    launch_ex(gemm_kernel<2, 128, 5>, 128, 384, G2::TOTAL, st, 2, mHld, mW2, mW2, mX1st, mX1st, x, 8, 16);
    launch_ex(gemm_kernel<3, 224, 4>, 132, 384, G3::TOTAL, st, 2, mX1ld, mW3, mW3, mA5st, mA5st32, x, 16, 16);
    launch_ex(gemm_kernel<5, 128, 5>, 128, 384, G2::TOTAL, st, 2, mA5ld, mWo, mW4, mOut, mOut, (const bf16*)p_x1, 8, 72);
}
```

```cpp
#include <cuda_runtime.h>
#include <cuda_bf16.h>
#include <cuda.h>
#include <stdint.h>

typedef __nv_bfloat16 bf16;

constexpr int S_LEN = 2048;
constexpr int DM = 1024;
constexpr int FF = 3584;
constexpr int NH = 32;
constexpr int DH = 32;
constexpr int A5W = DM + FF;

__device__ __align__(1024) bf16 g_qkv[S_LEN * 3 * DM];
__device__ __align__(1024) bf16 g_h[S_LEN * DM];
__device__ __align__(1024) bf16 g_x1[S_LEN * DM];
__device__ __align__(1024) bf16 g_a5[S_LEN * A5W];
__device__ __align__(16) float g_mean1[S_LEN];
__device__ __align__(16) float g_rstd1[S_LEN];
__device__ __align__(16) float g_gate[S_LEN];
__device__ __align__(16) float g_omg[S_LEN];
__device__ __align__(16) float g_cs1[DM];
__device__ __align__(16) float g_cs3[FF];
__device__ __align__(16) float2 g_stat2[S_LEN * 8];
__device__ int g_bad[NH * 16];

#define TL_START(k)
#define TL_END(k)

__device__ __forceinline__ uint32_t smem_u32(const void* p) { return (uint32_t)__cvta_generic_to_shared(p); }

__device__ __forceinline__ void mbar_init(uint32_t bar, uint32_t count) {
    asm volatile("mbarrier.init.shared::cta.b64 [%0], %1;" ::"r"(bar), "r"(count));
}
__device__ __forceinline__ void mbar_expect_tx(uint32_t bar, uint32_t bytes) {
    asm volatile("mbarrier.arrive.expect_tx.shared::cta.b64 _, [%0], %1;" ::"r"(bar), "r"(bytes) : "memory");
}
__device__ __forceinline__ void mbar_arrive(uint32_t bar) {
    asm volatile("mbarrier.arrive.shared::cta.b64 _, [%0];" ::"r"(bar) : "memory");
}
__device__ __forceinline__ bool mbar_try_wait(uint32_t bar, uint32_t parity) {
    uint32_t ok;
    asm volatile(
        "{\n.reg .pred p;\n"
        "mbarrier.try_wait.parity.shared::cta.b64 p, [%1], %2;\n"
        "selp.u32 %0, 1, 0, p;\n}\n"
        : "=r"(ok)
        : "r"(bar), "r"(parity)
        : "memory");
    return ok != 0;
}
__device__ __forceinline__ void mbar_wait(uint32_t bar, uint32_t parity) {
    uint32_t spins = 0;
    while (!mbar_try_wait(bar, parity)) {
        if (++spins > (1u << 24)) __trap();
    }
}
__device__ __forceinline__ void tma_load_2d(uint32_t dst, const CUtensorMap* map, int c0, int c1, uint32_t bar) {
    asm volatile(
        "cp.async.bulk.tensor.2d.shared::cluster.global.mbarrier::complete_tx::bytes [%0], [%1, {%3, %4}], [%2];"
        ::"r"(dst), "l"(map), "r"(bar), "r"(c0), "r"(c1)
        : "memory");
}
__device__ __forceinline__ void tma_store_2d(const CUtensorMap* map, uint32_t src, int c0, int c1) {
    asm volatile("cp.async.bulk.tensor.2d.global.shared::cta.bulk_group [%0, {%2, %3}], [%1];"
                 ::"l"(map), "r"(src), "r"(c0), "r"(c1)
                 : "memory");
}
__device__ __forceinline__ void tma_load_2d_mc(uint32_t dst, const CUtensorMap* map, int c0, int c1, uint32_t bar, uint16_t mask) {
    asm volatile(
        "cp.async.bulk.tensor.2d.shared::cluster.global.mbarrier::complete_tx::bytes.multicast::cluster [%0], [%1, {%3, %4}], [%2], %5;"
        ::"r"(dst), "l"(map), "r"(bar), "r"(c0), "r"(c1), "h"(mask)
        : "memory");
}
__device__ __forceinline__ void mbar_arrive_cluster(uint32_t bar, uint32_t cta) {
    asm volatile(
        "{\n.reg .b32 ra;\nmapa.shared::cluster.u32 ra, %0, %1;\n"
        "mbarrier.arrive.shared::cluster.b64 _, [ra];\n}\n" ::"r"(bar), "r"(cta)
        : "memory");
}
__device__ __forceinline__ void cluster_sync_all() {
    asm volatile("barrier.cluster.arrive.release.aligned;\nbarrier.cluster.wait.acquire.aligned;" ::: "memory");
}
__device__ __forceinline__ uint32_t cluster_rank() { uint32_t r; asm volatile("mov.u32 %0, %%cluster_ctarank;" : "=r"(r)); return r; }
__device__ __forceinline__ void pdl_wait() { asm volatile("griddepcontrol.wait;" ::: "memory"); }
__device__ __forceinline__ void pdl_launch() { asm volatile("griddepcontrol.launch_dependents;" ::: "memory"); }
__device__ __forceinline__ void bulk_commit() { asm volatile("cp.async.bulk.commit_group;" ::: "memory"); }
__device__ __forceinline__ void bulk_wait_read0() { asm volatile("cp.async.bulk.wait_group.read 0;" ::: "memory"); }
__device__ __forceinline__ void bulk_wait0() { asm volatile("cp.async.bulk.wait_group 0;" ::: "memory"); }
__device__ __forceinline__ void fence_proxy_async() { asm volatile("fence.proxy.async.shared::cta;" ::: "memory"); }
__device__ __forceinline__ void named_bar_sync(int id, int n) { asm volatile("bar.sync %0, %1;" ::"r"(id), "r"(n) : "memory"); }
__device__ __forceinline__ void named_bar_arrive(int id, int n) { asm volatile("bar.arrive %0, %1;" ::"r"(id), "r"(n) : "memory"); }
__device__ __forceinline__ void wgmma_fence() { asm volatile("wgmma.fence.sync.aligned;" ::: "memory"); }
__device__ __forceinline__ void wgmma_commit() { asm volatile("wgmma.commit_group.sync.aligned;" ::: "memory"); }
template <int N>
__device__ __forceinline__ void wgmma_wait() { asm volatile("wgmma.wait_group.sync.aligned %0;" ::"n"(N) : "memory"); }
__device__ __forceinline__ void prefetch_tmap(const CUtensorMap* m) {
    asm volatile("prefetch.tensormap [%0];" ::"l"(m) : "memory");
}
template <int R>
__device__ __forceinline__ void reg_alloc() { asm volatile("setmaxnreg.inc.sync.aligned.u32 %0;" ::"n"(R)); }
template <int R>
__device__ __forceinline__ void reg_dealloc() { asm volatile("setmaxnreg.dec.sync.aligned.u32 %0;" ::"n"(R)); }
__device__ __forceinline__ void stmatrix_x4(uint32_t addr, uint32_t r0, uint32_t r1, uint32_t r2, uint32_t r3) {
    asm volatile("stmatrix.sync.aligned.m8n8.x4.shared.b16 [%0], {%1, %2, %3, %4};"
                 ::"r"(addr), "r"(r0), "r"(r1), "r"(r2), "r"(r3)
                 : "memory");
}
__device__ __forceinline__ uint32_t pack_bf16(float lo, float hi) {
    uint32_t r;
    asm("cvt.rn.bf16x2.f32 %0, %1, %2;" : "=r"(r) : "f"(hi), "f"(lo));
    return r;
}
__device__ __forceinline__ float bf16_round(float v) { return __bfloat162float(__float2bfloat16_rn(v)); }
__device__ __forceinline__ float ex2(float x) {
    float y;
    asm volatile("ex2.approx.ftz.f32 %0, %1;" : "=f"(y) : "f"(x));
    return y;
}
__device__ __forceinline__ float tanh_fast(float x) {
    float y;
    asm("tanh.approx.f32 %0, %1;" : "=f"(y) : "f"(x));
    return y;
}
__device__ __forceinline__ float gelu_tanh(float v) {
    float u = 0.7978845608028654f * (v + 0.044715f * v * v * v);
    float hv = 0.5f * v;
    return fmaf(hv, tanh_fast(u), hv);
}
__device__ __forceinline__ uint32_t desc_lo(uint32_t addr, uint32_t lbo_bytes) {
    return ((addr & 0x3FFFF) >> 4) | (((lbo_bytes >> 4) & 0x3FFF) << 16);
}
__host__ __device__ constexpr uint32_t desc_hi(uint32_t sbo_bytes, uint32_t swz) {
    return ((sbo_bytes >> 4) & 0x3FFF) | (swz << 30);
}

__device__ __forceinline__ void wgmma_ss_n128_tb1(float (&d)[64], uint32_t alo, uint32_t ahi, uint32_t blo, uint32_t bhi, int scale_d) {
    asm volatile("{\n.reg .pred p;\n.reg .b64 da, db;\nsetp.ne.b32 p, %68, 0;\nmov.b64 da, {%64, %65};\nmov.b64 db, {%66, %67};\n"
        "wgmma.mma_async.sync.aligned.m64n128k16.f32.bf16.bf16 {%0, %1, %2, %3, %4, %5, %6, %7, %8, %9, %10, %11, %12, %13, %14, %15, %16, %17, %18, %19, %20, %21, %22, %23, %24, %25, %26, %27, %28, %29, %30, %31, %32, %33, %34, %35, %36, %37, %38, %39, %40, %41, %42, %43, %44, %45, %46, %47, %48, %49, %50, %51, %52, %53, %54, %55, %56, %57, %58, %59, %60, %61, %62, %63}, da, db, p, 1, 1, 0, 1;\n}\n"
        : "+f"(d[0]), "+f"(d[1]), "+f"(d[2]), "+f"(d[3]), "+f"(d[4]), "+f"(d[5]), "+f"(d[6]), "+f"(d[7]), "+f"(d[8]), "+f"(d[9]), "+f"(d[10]), "+f"(d[11]), "+f"(d[12]), "+f"(d[13]), "+f"(d[14]), "+f"(d[15]), "+f"(d[16]), "+f"(d[17]), "+f"(d[18]), "+f"(d[19]), "+f"(d[20]), "+f"(d[21]), "+f"(d[22]), "+f"(d[23]), "+f"(d[24]), "+f"(d[25]), "+f"(d[26]), "+f"(d[27]), "+f"(d[28]), "+f"(d[29]), "+f"(d[30]), "+f"(d[31]), "+f"(d[32]), "+f"(d[33]), "+f"(d[34]), "+f"(d[35]), "+f"(d[36]), "+f"(d[37]), "+f"(d[38]), "+f"(d[39]), "+f"(d[40]), "+f"(d[41]), "+f"(d[42]), "+f"(d[43]), "+f"(d[44]), "+f"(d[45]), "+f"(d[46]), "+f"(d[47]), "+f"(d[48]), "+f"(d[49]), "+f"(d[50]), "+f"(d[51]), "+f"(d[52]), "+f"(d[53]), "+f"(d[54]), "+f"(d[55]), "+f"(d[56]), "+f"(d[57]), "+f"(d[58]), "+f"(d[59]), "+f"(d[60]), "+f"(d[61]), "+f"(d[62]), "+f"(d[63])
        : "r"(alo), "r"(ahi), "r"(blo), "r"(bhi), "r"(scale_d));
}

__device__ __forceinline__ void wgmma_ss_n192_tb1(float (&d)[96], uint32_t alo, uint32_t ahi, uint32_t blo, uint32_t bhi, int scale_d) {
    asm volatile("{\n.reg .pred p;\n.reg .b64 da, db;\nsetp.ne.b32 p, %100, 0;\nmov.b64 da, {%96, %97};\nmov.b64 db, {%98, %99};\n"
        "wgmma.mma_async.sync.aligned.m64n192k16.f32.bf16.bf16 {%0, %1, %2, %3, %4, %5, %6, %7, %8, %9, %10, %11, %12, %13, %14, %15, %16, %17, %18, %19, %20, %21, %22, %23, %24, %25, %26, %27, %28, %29, %30, %31, %32, %33, %34, %35, %36, %37, %38, %39, %40, %41, %42, %43, %44, %45, %46, %47, %48, %49, %50, %51, %52, %53, %54, %55, %56, %57, %58, %59, %60, %61, %62, %63, %64, %65, %66, %67, %68, %69, %70, %71, %72, %73, %74, %75, %76, %77, %78, %79, %80, %81, %82, %83, %84, %85, %86, %87, %88, %89, %90, %91, %92, %93, %94, %95}, da, db, p, 1, 1, 0, 1;\n}\n"
        : "+f"(d[0]), "+f"(d[1]), "+f"(d[2]), "+f"(d[3]), "+f"(d[4]), "+f"(d[5]), "+f"(d[6]), "+f"(d[7]), "+f"(d[8]), "+f"(d[9]), "+f"(d[10]), "+f"(d[11]), "+f"(d[12]), "+f"(d[13]), "+f"(d[14]), "+f"(d[15]), "+f"(d[16]), "+f"(d[17]), "+f"(d[18]), "+f"(d[19]), "+f"(d[20]), "+f"(d[21]), "+f"(d[22]), "+f"(d[23]), "+f"(d[24]), "+f"(d[25]), "+f"(d[26]), "+f"(d[27]), "+f"(d[28]), "+f"(d[29]), "+f"(d[30]), "+f"(d[31]), "+f"(d[32]), "+f"(d[33]), "+f"(d[34]), "+f"(d[35]), "+f"(d[36]), "+f"(d[37]), "+f"(d[38]), "+f"(d[39]), "+f"(d[40]), "+f"(d[41]), "+f"(d[42]), "+f"(d[43]), "+f"(d[44]), "+f"(d[45]), "+f"(d[46]), "+f"(d[47]), "+f"(d[48]), "+f"(d[49]), "+f"(d[50]), "+f"(d[51]), "+f"(d[52]), "+f"(d[53]), "+f"(d[54]), "+f"(d[55]), "+f"(d[56]), "+f"(d[57]), "+f"(d[58]), "+f"(d[59]), "+f"(d[60]), "+f"(d[61]), "+f"(d[62]), "+f"(d[63]), "+f"(d[64]), "+f"(d[65]), "+f"(d[66]), "+f"(d[67]), "+f"(d[68]), "+f"(d[69]), "+f"(d[70]), "+f"(d[71]), "+f"(d[72]), "+f"(d[73]), "+f"(d[74]), "+f"(d[75]), "+f"(d[76]), "+f"(d[77]), "+f"(d[78]), "+f"(d[79]), "+f"(d[80]), "+f"(d[81]), "+f"(d[82]), "+f"(d[83]), "+f"(d[84]), "+f"(d[85]), "+f"(d[86]), "+f"(d[87]), "+f"(d[88]), "+f"(d[89]), "+f"(d[90]), "+f"(d[91]), "+f"(d[92]), "+f"(d[93]), "+f"(d[94]), "+f"(d[95])
        : "r"(alo), "r"(ahi), "r"(blo), "r"(bhi), "r"(scale_d));
}

__device__ __forceinline__ void wgmma_ss_n224_tb1(float (&d)[112], uint32_t alo, uint32_t ahi, uint32_t blo, uint32_t bhi, int scale_d) {
    asm volatile("{\n.reg .pred p;\n.reg .b64 da, db;\nsetp.ne.b32 p, %116, 0;\nmov.b64 da, {%112, %113};\nmov.b64 db, {%114, %115};\n"
        "wgmma.mma_async.sync.aligned.m64n224k16.f32.bf16.bf16 {%0, %1, %2, %3, %4, %5, %6, %7, %8, %9, %10, %11, %12, %13, %14, %15, %16, %17, %18, %19, %20, %21, %22, %23, %24, %25, %26, %27, %28, %29, %30, %31, %32, %33, %34, %35, %36, %37, %38, %39, %40, %41, %42, %43, %44, %45, %46, %47, %48, %49, %50, %51, %52, %53, %54, %55, %56, %57, %58, %59, %60, %61, %62, %63, %64, %65, %66, %67, %68, %69, %70, %71, %72, %73, %74, %75, %76, %77, %78, %79, %80, %81, %82, %83, %84, %85, %86, %87, %88, %89, %90, %91, %92, %93, %94, %95, %96, %97, %98, %99, %100, %101, %102, %103, %104, %105, %106, %107, %108, %109, %110, %111}, da, db, p, 1, 1, 0, 1;\n}\n"
        : "+f"(d[0]), "+f"(d[1]), "+f"(d[2]), "+f"(d[3]), "+f"(d[4]), "+f"(d[5]), "+f"(d[6]), "+f"(d[7]), "+f"(d[8]), "+f"(d[9]), "+f"(d[10]), "+f"(d[11]), "+f"(d[12]), "+f"(d[13]), "+f"(d[14]), "+f"(d[15]), "+f"(d[16]), "+f"(d[17]), "+f"(d[18]), "+f"(d[19]), "+f"(d[20]), "+f"(d[21]), "+f"(d[22]), "+f"(d[23]), "+f"(d[24]), "+f"(d[25]), "+f"(d[26]), "+f"(d[27]), "+f"(d[28]), "+f"(d[29]), "+f"(d[30]), "+f"(d[31]), "+f"(d[32]), "+f"(d[33]), "+f"(d[34]), "+f"(d[35]), "+f"(d[36]), "+f"(d[37]), "+f"(d[38]), "+f"(d[39]), "+f"(d[40]), "+f"(d[41]), "+f"(d[42]), "+f"(d[43]), "+f"(d[44]), "+f"(d[45]), "+f"(d[46]), "+f"(d[47]), "+f"(d[48]), "+f"(d[49]), "+f"(d[50]), "+f"(d[51]), "+f"(d[52]), "+f"(d[53]), "+f"(d[54]), "+f"(d[55]), "+f"(d[56]), "+f"(d[57]), "+f"(d[58]), "+f"(d[59]), "+f"(d[60]), "+f"(d[61]), "+f"(d[62]), "+f"(d[63]), "+f"(d[64]), "+f"(d[65]), "+f"(d[66]), "+f"(d[67]), "+f"(d[68]), "+f"(d[69]), "+f"(d[70]), "+f"(d[71]), "+f"(d[72]), "+f"(d[73]), "+f"(d[74]), "+f"(d[75]), "+f"(d[76]), "+f"(d[77]), "+f"(d[78]), "+f"(d[79]), "+f"(d[80]), "+f"(d[81]), "+f"(d[82]), "+f"(d[83]), "+f"(d[84]), "+f"(d[85]), "+f"(d[86]), "+f"(d[87]), "+f"(d[88]), "+f"(d[89]), "+f"(d[90]), "+f"(d[91]), "+f"(d[92]), "+f"(d[93]), "+f"(d[94]), "+f"(d[95]), "+f"(d[96]), "+f"(d[97]), "+f"(d[98]), "+f"(d[99]), "+f"(d[100]), "+f"(d[101]), "+f"(d[102]), "+f"(d[103]), "+f"(d[104]), "+f"(d[105]), "+f"(d[106]), "+f"(d[107]), "+f"(d[108]), "+f"(d[109]), "+f"(d[110]), "+f"(d[111])
        : "r"(alo), "r"(ahi), "r"(blo), "r"(bhi), "r"(scale_d));
}

__device__ __forceinline__ void wgmma_ss_n256_tb1(float (&d)[128], uint32_t alo, uint32_t ahi, uint32_t blo, uint32_t bhi, int scale_d) {
    asm volatile("{\n.reg .pred p;\n.reg .b64 da, db;\nsetp.ne.b32 p, %132, 0;\nmov.b64 da, {%128, %129};\nmov.b64 db, {%130, %131};\n"
        "wgmma.mma_async.sync.aligned.m64n256k16.f32.bf16.bf16 {%0, %1, %2, %3, %4, %5, %6, %7, %8, %9, %10, %11, %12, %13, %14, %15, %16, %17, %18, %19, %20, %21, %22, %23, %24, %25, %26, %27, %28, %29, %30, %31, %32, %33, %34, %35, %36, %37, %38, %39, %40, %41, %42, %43, %44, %45, %46, %47, %48, %49, %50, %51, %52, %53, %54, %55, %56, %57, %58, %59, %60, %61, %62, %63, %64, %65, %66, %67, %68, %69, %70, %71, %72, %73, %74, %75, %76, %77, %78, %79, %80, %81, %82, %83, %84, %85, %86, %87, %88, %89, %90, %91, %92, %93, %94, %95, %96, %97, %98, %99, %100, %101, %102, %103, %104, %105, %106, %107, %108, %109, %110, %111, %112, %113, %114, %115, %116, %117, %118, %119, %120, %121, %122, %123, %124, %125, %126, %127}, da, db, p, 1, 1, 0, 1;\n}\n"
        : "+f"(d[0]), "+f"(d[1]), "+f"(d[2]), "+f"(d[3]), "+f"(d[4]), "+f"(d[5]), "+f"(d[6]), "+f"(d[7]), "+f"(d[8]), "+f"(d[9]), "+f"(d[10]), "+f"(d[11]), "+f"(d[12]), "+f"(d[13]), "+f"(d[14]), "+f"(d[15]), "+f"(d[16]), "+f"(d[17]), "+f"(d[18]), "+f"(d[19]), "+f"(d[20]), "+f"(d[21]), "+f"(d[22]), "+f"(d[23]), "+f"(d[24]), "+f"(d[25]), "+f"(d[26]), "+f"(d[27]), "+f"(d[28]), "+f"(d[29]), "+f"(d[30]), "+f"(d[31]), "+f"(d[32]), "+f"(d[33]), "+f"(d[34]), "+f"(d[35]), "+f"(d[36]), "+f"(d[37]), "+f"(d[38]), "+f"(d[39]), "+f"(d[40]), "+f"(d[41]), "+f"(d[42]), "+f"(d[43]), "+f"(d[44]), "+f"(d[45]), "+f"(d[46]), "+f"(d[47]), "+f"(d[48]), "+f"(d[49]), "+f"(d[50]), "+f"(d[51]), "+f"(d[52]), "+f"(d[53]), "+f"(d[54]), "+f"(d[55]), "+f"(d[56]), "+f"(d[57]), "+f"(d[58]), "+f"(d[59]), "+f"(d[60]), "+f"(d[61]), "+f"(d[62]), "+f"(d[63]), "+f"(d[64]), "+f"(d[65]), "+f"(d[66]), "+f"(d[67]), "+f"(d[68]), "+f"(d[69]), "+f"(d[70]), "+f"(d[71]), "+f"(d[72]), "+f"(d[73]), "+f"(d[74]), "+f"(d[75]), "+f"(d[76]), "+f"(d[77]), "+f"(d[78]), "+f"(d[79]), "+f"(d[80]), "+f"(d[81]), "+f"(d[82]), "+f"(d[83]), "+f"(d[84]), "+f"(d[85]), "+f"(d[86]), "+f"(d[87]), "+f"(d[88]), "+f"(d[89]), "+f"(d[90]), "+f"(d[91]), "+f"(d[92]), "+f"(d[93]), "+f"(d[94]), "+f"(d[95]), "+f"(d[96]), "+f"(d[97]), "+f"(d[98]), "+f"(d[99]), "+f"(d[100]), "+f"(d[101]), "+f"(d[102]), "+f"(d[103]), "+f"(d[104]), "+f"(d[105]), "+f"(d[106]), "+f"(d[107]), "+f"(d[108]), "+f"(d[109]), "+f"(d[110]), "+f"(d[111]), "+f"(d[112]), "+f"(d[113]), "+f"(d[114]), "+f"(d[115]), "+f"(d[116]), "+f"(d[117]), "+f"(d[118]), "+f"(d[119]), "+f"(d[120]), "+f"(d[121]), "+f"(d[122]), "+f"(d[123]), "+f"(d[124]), "+f"(d[125]), "+f"(d[126]), "+f"(d[127])
        : "r"(alo), "r"(ahi), "r"(blo), "r"(bhi), "r"(scale_d));
}

__device__ __forceinline__ void wgmma_ss_n64_tb0(float (&d)[32], uint32_t alo, uint32_t ahi, uint32_t blo, uint32_t bhi, int scale_d) {
    asm volatile("{\n.reg .pred p;\n.reg .b64 da, db;\nsetp.ne.b32 p, %36, 0;\nmov.b64 da, {%32, %33};\nmov.b64 db, {%34, %35};\n"
        "wgmma.mma_async.sync.aligned.m64n64k16.f32.bf16.bf16 {%0, %1, %2, %3, %4, %5, %6, %7, %8, %9, %10, %11, %12, %13, %14, %15, %16, %17, %18, %19, %20, %21, %22, %23, %24, %25, %26, %27, %28, %29, %30, %31}, da, db, p, 1, 1, 0, 0;\n}\n"
        : "+f"(d[0]), "+f"(d[1]), "+f"(d[2]), "+f"(d[3]), "+f"(d[4]), "+f"(d[5]), "+f"(d[6]), "+f"(d[7]), "+f"(d[8]), "+f"(d[9]), "+f"(d[10]), "+f"(d[11]), "+f"(d[12]), "+f"(d[13]), "+f"(d[14]), "+f"(d[15]), "+f"(d[16]), "+f"(d[17]), "+f"(d[18]), "+f"(d[19]), "+f"(d[20]), "+f"(d[21]), "+f"(d[22]), "+f"(d[23]), "+f"(d[24]), "+f"(d[25]), "+f"(d[26]), "+f"(d[27]), "+f"(d[28]), "+f"(d[29]), "+f"(d[30]), "+f"(d[31])
        : "r"(alo), "r"(ahi), "r"(blo), "r"(bhi), "r"(scale_d));
}

__device__ __forceinline__ void wgmma_rs_n128_tb0(float (&d)[64], uint32_t a0, uint32_t a1, uint32_t a2, uint32_t a3, uint32_t blo, uint32_t bhi, int scale_d) {
    asm volatile("{\n.reg .pred p;\n.reg .b64 db;\nsetp.ne.b32 p, %70, 0;\nmov.b64 db, {%68, %69};\n"
        "wgmma.mma_async.sync.aligned.m64n128k16.f32.bf16.bf16 {%0, %1, %2, %3, %4, %5, %6, %7, %8, %9, %10, %11, %12, %13, %14, %15, %16, %17, %18, %19, %20, %21, %22, %23, %24, %25, %26, %27, %28, %29, %30, %31, %32, %33, %34, %35, %36, %37, %38, %39, %40, %41, %42, %43, %44, %45, %46, %47, %48, %49, %50, %51, %52, %53, %54, %55, %56, %57, %58, %59, %60, %61, %62, %63}, {%64, %65, %66, %67}, db, p, 1, 1, 0;\n}\n"
        : "+f"(d[0]), "+f"(d[1]), "+f"(d[2]), "+f"(d[3]), "+f"(d[4]), "+f"(d[5]), "+f"(d[6]), "+f"(d[7]), "+f"(d[8]), "+f"(d[9]), "+f"(d[10]), "+f"(d[11]), "+f"(d[12]), "+f"(d[13]), "+f"(d[14]), "+f"(d[15]), "+f"(d[16]), "+f"(d[17]), "+f"(d[18]), "+f"(d[19]), "+f"(d[20]), "+f"(d[21]), "+f"(d[22]), "+f"(d[23]), "+f"(d[24]), "+f"(d[25]), "+f"(d[26]), "+f"(d[27]), "+f"(d[28]), "+f"(d[29]), "+f"(d[30]), "+f"(d[31]), "+f"(d[32]), "+f"(d[33]), "+f"(d[34]), "+f"(d[35]), "+f"(d[36]), "+f"(d[37]), "+f"(d[38]), "+f"(d[39]), "+f"(d[40]), "+f"(d[41]), "+f"(d[42]), "+f"(d[43]), "+f"(d[44]), "+f"(d[45]), "+f"(d[46]), "+f"(d[47]), "+f"(d[48]), "+f"(d[49]), "+f"(d[50]), "+f"(d[51]), "+f"(d[52]), "+f"(d[53]), "+f"(d[54]), "+f"(d[55]), "+f"(d[56]), "+f"(d[57]), "+f"(d[58]), "+f"(d[59]), "+f"(d[60]), "+f"(d[61]), "+f"(d[62]), "+f"(d[63])
        : "r"(a0), "r"(a1), "r"(a2), "r"(a3), "r"(blo), "r"(bhi), "r"(scale_d));
}

__device__ __forceinline__ void wgmma_rs_n64_tb0(float (&d)[32], uint32_t a0, uint32_t a1, uint32_t a2, uint32_t a3, uint32_t blo, uint32_t bhi, int scale_d) {
    asm volatile("{\n.reg .pred p;\n.reg .b64 db;\nsetp.ne.b32 p, %38, 0;\nmov.b64 db, {%36, %37};\n"
        "wgmma.mma_async.sync.aligned.m64n64k16.f32.bf16.bf16 {%0, %1, %2, %3, %4, %5, %6, %7, %8, %9, %10, %11, %12, %13, %14, %15, %16, %17, %18, %19, %20, %21, %22, %23, %24, %25, %26, %27, %28, %29, %30, %31}, {%32, %33, %34, %35}, db, p, 1, 1, 0;\n}\n"
        : "+f"(d[0]), "+f"(d[1]), "+f"(d[2]), "+f"(d[3]), "+f"(d[4]), "+f"(d[5]), "+f"(d[6]), "+f"(d[7]), "+f"(d[8]), "+f"(d[9]), "+f"(d[10]), "+f"(d[11]), "+f"(d[12]), "+f"(d[13]), "+f"(d[14]), "+f"(d[15]), "+f"(d[16]), "+f"(d[17]), "+f"(d[18]), "+f"(d[19]), "+f"(d[20]), "+f"(d[21]), "+f"(d[22]), "+f"(d[23]), "+f"(d[24]), "+f"(d[25]), "+f"(d[26]), "+f"(d[27]), "+f"(d[28]), "+f"(d[29]), "+f"(d[30]), "+f"(d[31])
        : "r"(a0), "r"(a1), "r"(a2), "r"(a3), "r"(blo), "r"(bhi), "r"(scale_d));
}

__device__ __forceinline__ void wgmma_rs_n32_tb1(float (&d)[16], uint32_t a0, uint32_t a1, uint32_t a2, uint32_t a3, uint32_t blo, uint32_t bhi, int scale_d) {
    asm volatile("{\n.reg .pred p;\n.reg .b64 db;\nsetp.ne.b32 p, %22, 0;\nmov.b64 db, {%20, %21};\n"
        "wgmma.mma_async.sync.aligned.m64n32k16.f32.bf16.bf16 {%0, %1, %2, %3, %4, %5, %6, %7, %8, %9, %10, %11, %12, %13, %14, %15}, {%16, %17, %18, %19}, db, p, 1, 1, 1;\n}\n"
        : "+f"(d[0]), "+f"(d[1]), "+f"(d[2]), "+f"(d[3]), "+f"(d[4]), "+f"(d[5]), "+f"(d[6]), "+f"(d[7]), "+f"(d[8]), "+f"(d[9]), "+f"(d[10]), "+f"(d[11]), "+f"(d[12]), "+f"(d[13]), "+f"(d[14]), "+f"(d[15])
        : "r"(a0), "r"(a1), "r"(a2), "r"(a3), "r"(blo), "r"(bhi), "r"(scale_d));
}

__device__ __forceinline__ void wgmma_rs_n40_tb1(float (&d)[20], uint32_t a0, uint32_t a1, uint32_t a2, uint32_t a3, uint32_t blo, uint32_t bhi, int scale_d) {
    asm volatile("{\n.reg .pred p;\n.reg .b64 db;\nsetp.ne.b32 p, %26, 0;\nmov.b64 db, {%24, %25};\n"
        "wgmma.mma_async.sync.aligned.m64n40k16.f32.bf16.bf16 {%0, %1, %2, %3, %4, %5, %6, %7, %8, %9, %10, %11, %12, %13, %14, %15, %16, %17, %18, %19}, {%20, %21, %22, %23}, db, p, 1, 1, 1;\n}\n"
        : "+f"(d[0]), "+f"(d[1]), "+f"(d[2]), "+f"(d[3]), "+f"(d[4]), "+f"(d[5]), "+f"(d[6]), "+f"(d[7]), "+f"(d[8]), "+f"(d[9]), "+f"(d[10]), "+f"(d[11]), "+f"(d[12]), "+f"(d[13]), "+f"(d[14]), "+f"(d[15]), "+f"(d[16]), "+f"(d[17]), "+f"(d[18]), "+f"(d[19])
        : "r"(a0), "r"(a1), "r"(a2), "r"(a3), "r"(blo), "r"(bhi), "r"(scale_d));
}

template <int BN>
__device__ __forceinline__ void wgmma_tile(float (&d)[BN / 2], uint32_t da, uint32_t db, int sd) {
    constexpr uint32_t HI = desc_hi(1024, 1);
    if constexpr (BN == 128) wgmma_ss_n128_tb1(d, da, HI, db, HI, sd);
    else if constexpr (BN == 192) wgmma_ss_n192_tb1(d, da, HI, db, HI, sd);
    else if constexpr (BN == 224) wgmma_ss_n224_tb1(d, da, HI, db, HI, sd);
    else wgmma_ss_n256_tb1(d, da, HI, db, HI, sd);
}

__global__ void __launch_bounds__(256) prep_kernel(const bf16* __restrict__ x, const bf16* __restrict__ gate_w,
                                                   const bf16* __restrict__ w1, const bf16* __restrict__ w3) {
    const int tid = threadIdx.x;
    TL_START(0)
    pdl_launch();
    if (blockIdx.x < 256) {
        const int row = blockIdx.x * 8 + (tid >> 5);
        const int lane = tid & 31;
        const uint4* xr = reinterpret_cast<const uint4*>(x + (size_t)row * DM);
        const uint4* gw = reinterpret_cast<const uint4*>(gate_w);
        float v[32];
        float gsum = 0.f, sum = 0.f;
#pragma unroll
        for (int i = 0; i < 4; i++) {
            uint4 a = xr[lane + 32 * i];
            uint4 b = gw[lane + 32 * i];
            const uint32_t aa[4] = {a.x, a.y, a.z, a.w};
            const uint32_t bb[4] = {b.x, b.y, b.z, b.w};
#pragma unroll
            for (int j = 0; j < 4; j++) {
                float x0 = __uint_as_float(aa[j] << 16), x1 = __uint_as_float(aa[j] & 0xFFFF0000u);
                float g0 = __uint_as_float(bb[j] << 16), g1 = __uint_as_float(bb[j] & 0xFFFF0000u);
                v[i * 8 + j * 2] = x0;
                v[i * 8 + j * 2 + 1] = x1;
                sum += x0 + x1;
                gsum += bf16_round(x0 * g0) + bf16_round(x1 * g1);
            }
        }
#pragma unroll
        for (int o = 16; o > 0; o >>= 1) {
            sum += __shfl_xor_sync(0xffffffffu, sum, o);
            gsum += __shfl_xor_sync(0xffffffffu, gsum, o);
        }
        const float mean = sum * (1.0f / DM);
        float m2 = 0.f;
#pragma unroll
        for (int i = 0; i < 32; i++) {
            float d = v[i] - mean;
            m2 += d * d;
        }
#pragma unroll
        for (int o = 16; o > 0; o >>= 1) m2 += __shfl_xor_sync(0xffffffffu, m2, o);
        if (lane == 0) {
            g_mean1[row] = mean;
            g_rstd1[row] = rsqrtf(m2 * (1.0f / DM) + 1e-5f);
            float logit = bf16_round(gsum);
            float g = bf16_round(1.0f / (1.0f + __expf(-logit)));
            g_gate[row] = g;
            g_omg[row] = bf16_round(1.0f - g);
        }
    } else {
        __shared__ float red[32][65];
        const int strip = blockIdx.x - 256;
        const bf16* w;
        float* out;
        int ld, col0;
        if (strip < 16) { w = w1; ld = DM; col0 = strip * 64; out = g_cs1; }
        else { w = w3; ld = FF; col0 = (strip - 16) * 64; out = g_cs3; }
        const int cg = tid & 7;
        const int rg = tid >> 3;
        float acc[8];
#pragma unroll
        for (int j = 0; j < 8; j++) acc[j] = 0.f;
#pragma unroll 8
        for (int r = 0; r < 32; r++) {
            uint4 a = *reinterpret_cast<const uint4*>(w + (size_t)(r * 32 + rg) * ld + col0 + cg * 8);
            const uint32_t aa[4] = {a.x, a.y, a.z, a.w};
#pragma unroll
            for (int j = 0; j < 4; j++) {
                acc[2 * j] += __uint_as_float(aa[j] << 16);
                acc[2 * j + 1] += __uint_as_float(aa[j] & 0xFFFF0000u);
            }
        }
#pragma unroll
        for (int j = 0; j < 8; j++) red[rg][cg * 8 + j] = acc[j];
        __syncthreads();
        if (tid < 64) {
            float s = 0.f;
#pragma unroll
            for (int r = 0; r < 32; r++) s += red[r][tid];
            out[col0 + tid] = s;
        }
    }
    TL_END(0)
}

#define RELEASE_STAGE(b) if (tid_wg < 2) mbar_arrive_cluster(b, tid_wg)
template <int BN, int STAGES>
struct GemmSmem {
    static constexpr int A_BYTES = 128 * 64 * 2;
    static constexpr int B_BOXES = (BN + 63) / 64;
    static constexpr int B_BYTES = B_BOXES * 64 * 64 * 2;
    static constexpr int STAGE_BYTES = A_BYTES + B_BYTES;
    static constexpr int STG_OFF = STAGES * STAGE_BYTES;
    static constexpr int BAR_OFF = STAGES * STAGE_BYTES + 2 * 16384;
    static constexpr int TOTAL = BAR_OFF + 256 + 1024;
};

template <int MODE, int BN, int STAGES>
__global__ void __launch_bounds__(384, 1)
gemm_kernel(const __grid_constant__ CUtensorMap mA, const __grid_constant__ CUtensorMap mB0,
            const __grid_constant__ CUtensorMap mB1, const __grid_constant__ CUtensorMap mC0,
            const __grid_constant__ CUtensorMap mC1, const bf16* __restrict__ xin, int n_tiles_n, int kblocks) {
    using L = GemmSmem<BN, STAGES>;
    extern __shared__ uint8_t smem_raw[];
    const uint32_t sbase = (smem_u32(smem_raw) + 1023u) & ~1023u;
    const uint32_t bar_full = sbase + L::BAR_OFF;
    const uint32_t bar_empty = bar_full + 8 * STAGES;
    const int wg = threadIdx.x >> 7;
    const int npairs = 8 * n_tiles_n;
    const uint32_t crank = cluster_rank();
    const int cid = blockIdx.x >> 1, ncl = gridDim.x >> 1;
    TL_START(MODE)
    pdl_launch();

    if (threadIdx.x == 0) {
        for (int s = 0; s < STAGES; s++) {
            mbar_init(bar_full + 8 * s, 1);
            mbar_init(bar_empty + 8 * s, 4);
        }
        asm volatile("fence.mbarrier_init.release.cluster;" ::: "memory");
        prefetch_tmap(&mA);
        prefetch_tmap(&mB0);
        if (MODE == 1 || MODE == 5) prefetch_tmap(&mB1);
        prefetch_tmap(&mC0);
    }
    cluster_sync_all();

    if (wg == 0) {
        reg_dealloc<40>();
        if (threadIdx.x == 0) {
            if (MODE != 1) pdl_wait();
            int stage = 0;
            uint32_t phase = 1;
            for (int pr = cid; pr < npairs; pr += ncl) {
                const int m0 = ((pr & 7) * 2 + crank) * 128;
                const int n0 = (pr >> 3) * BN;
                for (int kb = 0; kb < kblocks; kb++) {
                    mbar_wait(bar_empty + 8 * stage, phase);
                    const uint32_t sa = sbase + stage * L::STAGE_BYTES;
                    const uint32_t sb = sa + L::A_BYTES;
                    const uint32_t fb = bar_full + 8 * stage;
                    mbar_expect_tx(fb, L::STAGE_BYTES);
                    int arow = m0;
                    if (MODE == 2) {
                        const int grp = kb >> 2;
                        arow += (grp == 0) ? -1 : (grp == 1) ? 1 : (grp == 2) ? -2 : 2;
                    }
                    tma_load_2d(sa, &mA, kb * 64, arow, fb);
                    const CUtensorMap* mb = &mB0;
                    int bc = n0, br = kb * 64;
                    if (MODE == 1 && n0 >= 3 * DM) { mb = &mB1; bc = n0 - 3 * DM; }
                    if (MODE == 5 && kb >= 16) { mb = &mB1; br = (kb - 16) * 64; }
#pragma unroll
                    for (int b = 0; b < L::B_BOXES / 2; b++) {
                        const int bb = crank * (L::B_BOXES / 2) + b;
                        tma_load_2d_mc(sb + bb * 8192, mb, bc + bb * 64, br, fb, (uint16_t)3);
                    }
                    if (++stage == STAGES) { stage = 0; phase ^= 1; }
                }
            }
        }
    } else {
        reg_alloc<232>();
        const int c = wg - 1;
        const int warp = (threadIdx.x >> 5) & 3;
        const int lane = threadIdx.x & 31;
        const int tid_wg = threadIdx.x & 127;
        const uint32_t stg = sbase + L::STG_OFF + c * 16384;
        int stage = 0;
        uint32_t phase = 0;
        float acc[BN / 2];
        bool first = true;
        for (int pr = cid; pr < npairs; pr += ncl) {
            const int m0 = ((pr & 7) * 2 + crank) * 128;
            const int n0 = (pr >> 3) * BN;
            int prev_stage = 0;
            for (int kb = 0; kb < kblocks; kb++) {
                mbar_wait(bar_full + 8 * stage, phase);
                const uint32_t sa = sbase + stage * L::STAGE_BYTES + c * 8192;
                const uint32_t sb = sbase + stage * L::STAGE_BYTES + L::A_BYTES;
                const uint32_t da = desc_lo(sa, 16);
                const uint32_t db = desc_lo(sb, 8192);
                wgmma_fence();
#pragma unroll
                for (int k = 0; k < 4; k++) wgmma_tile<BN>(acc, da + k * 2, db + k * 128, (kb | k) != 0);
                wgmma_commit();
                if (kb > 0) {
                    wgmma_wait<1>();
                    RELEASE_STAGE(bar_empty + 8 * prev_stage);
                }
                prev_stage = stage;
                if (++stage == STAGES) { stage = 0; phase ^= 1; }
            }
            wgmma_wait<0>();
            RELEASE_STAGE(bar_empty + 8 * prev_stage);
            if (first) { pdl_wait(); first = false; }

            const int r0 = m0 + c * 64 + warp * 16 + (lane >> 2);
            const int r1 = r0 + 8;
            const int cq = (lane & 3) * 2;
            const CUtensorMap* mc = &mC0;
            int out_c0 = n0;
            if (MODE == 1) {
                if (n0 < DM) {
                    const float qs = 0.17677669529663687f * 1.4426950408889634f;
#pragma unroll
                    for (int j = 0; j < BN / 2; j++) acc[j] *= qs;
                } else if (n0 >= 3 * DM) {
                    mc = &mC1;
                    out_c0 = n0 - 3 * DM;
                    const float mu0 = g_mean1[r0], mu1 = g_mean1[r1];
                    const float rs0 = g_rstd1[r0], rs1 = g_rstd1[r1];
#pragma unroll
                    for (int j = 0; j < BN / 8; j++) {
                        const float2 cs = *reinterpret_cast<const float2*>(&g_cs1[out_c0 + 8 * j + cq]);
                        acc[4 * j + 0] = gelu_tanh(rs0 * fmaf(-mu0, cs.x, acc[4 * j + 0]));
                        acc[4 * j + 1] = gelu_tanh(rs0 * fmaf(-mu0, cs.y, acc[4 * j + 1]));
                        acc[4 * j + 2] = gelu_tanh(rs1 * fmaf(-mu1, cs.x, acc[4 * j + 2]));
                        acc[4 * j + 3] = gelu_tanh(rs1 * fmaf(-mu1, cs.y, acc[4 * j + 3]));
                    }
                }
            } else if (MODE == 2) {
                float s0 = 0.f, s1 = 0.f;
#pragma unroll
                for (int j = 0; j < BN / 8; j++) {
                    const uint32_t xa = *reinterpret_cast<const uint32_t*>(xin + (size_t)r0 * DM + n0 + 8 * j + cq);
                    const uint32_t xb = *reinterpret_cast<const uint32_t*>(xin + (size_t)r1 * DM + n0 + 8 * j + cq);
                    acc[4 * j + 0] = bf16_round(bf16_round(acc[4 * j + 0]) + __uint_as_float(xa << 16));
                    acc[4 * j + 1] = bf16_round(bf16_round(acc[4 * j + 1]) + __uint_as_float(xa & 0xFFFF0000u));
                    acc[4 * j + 2] = bf16_round(bf16_round(acc[4 * j + 2]) + __uint_as_float(xb << 16));
                    acc[4 * j + 3] = bf16_round(bf16_round(acc[4 * j + 3]) + __uint_as_float(xb & 0xFFFF0000u));
                    s0 += acc[4 * j + 0] + acc[4 * j + 1];
                    s1 += acc[4 * j + 2] + acc[4 * j + 3];
                }
                s0 += __shfl_xor_sync(0xffffffffu, s0, 1);
                s0 += __shfl_xor_sync(0xffffffffu, s0, 2);
                s1 += __shfl_xor_sync(0xffffffffu, s1, 1);
                s1 += __shfl_xor_sync(0xffffffffu, s1, 2);
                const float mu0 = s0 * (1.0f / BN), mu1 = s1 * (1.0f / BN);
                float q0 = 0.f, q1 = 0.f;
#pragma unroll
                for (int j = 0; j < BN / 8; j++) {
                    float d;
                    d = acc[4 * j + 0] - mu0; q0 += d * d;
                    d = acc[4 * j + 1] - mu0; q0 += d * d;
                    d = acc[4 * j + 2] - mu1; q1 += d * d;
                    d = acc[4 * j + 3] - mu1; q1 += d * d;
                }
                q0 += __shfl_xor_sync(0xffffffffu, q0, 1);
                q0 += __shfl_xor_sync(0xffffffffu, q0, 2);
                q1 += __shfl_xor_sync(0xffffffffu, q1, 1);
                q1 += __shfl_xor_sync(0xffffffffu, q1, 2);
                if ((lane & 3) == 0) {
                    static_assert(MODE != 2 || BN == 128, "stats layout assumes BN=128");
                    g_stat2[r0 * 8 + (n0 >> 7)] = make_float2(s0, q0);
                    g_stat2[r1 * 8 + (n0 >> 7)] = make_float2(s1, q1);
                }
            } else if (MODE == 3) {
                out_c0 = n0 + DM;
                float mu[2], rs[2];
#pragma unroll
                for (int h = 0; h < 2; h++) {
                    const float4* sp = reinterpret_cast<const float4*>(&g_stat2[(h ? r1 : r0) * 8]);
                    float4 p[4];
                    float s = 0.f;
#pragma unroll
                    for (int i = 0; i < 4; i++) { p[i] = sp[i]; s += p[i].x + p[i].z; }
                    const float mean = s * (1.0f / DM);
                    float m2 = 0.f;
#pragma unroll
                    for (int i = 0; i < 4; i++) {
                        float d0 = p[i].x * (1.0f / 128) - mean, d1 = p[i].z * (1.0f / 128) - mean;
                        m2 += p[i].y + p[i].w + 128.0f * (d0 * d0 + d1 * d1);
                    }
                    mu[h] = mean;
                    rs[h] = rsqrtf(m2 * (1.0f / DM) + 1e-5f);
                }
                const float og0 = g_omg[r0], og1 = g_omg[r1];
#pragma unroll
                for (int j = 0; j < BN / 8; j++) {
                    const float2 cs = *reinterpret_cast<const float2*>(&g_cs3[n0 + 8 * j + cq]);
                    acc[4 * j + 0] = og0 * gelu_tanh(rs[0] * fmaf(-mu[0], cs.x, acc[4 * j + 0]));
                    acc[4 * j + 1] = og0 * gelu_tanh(rs[0] * fmaf(-mu[0], cs.y, acc[4 * j + 1]));
                    acc[4 * j + 2] = og1 * gelu_tanh(rs[1] * fmaf(-mu[1], cs.x, acc[4 * j + 2]));
                    acc[4 * j + 3] = og1 * gelu_tanh(rs[1] * fmaf(-mu[1], cs.y, acc[4 * j + 3]));
                }
            } else {
                const float og0 = g_omg[r0], og1 = g_omg[r1];
#pragma unroll
                for (int j = 0; j < BN / 8; j++) {
                    const uint32_t xa = *reinterpret_cast<const uint32_t*>(xin + (size_t)r0 * DM + n0 + 8 * j + cq);
                    const uint32_t xb = *reinterpret_cast<const uint32_t*>(xin + (size_t)r1 * DM + n0 + 8 * j + cq);
                    acc[4 * j + 0] = fmaf(og0, __uint_as_float(xa << 16), acc[4 * j + 0]);
                    acc[4 * j + 1] = fmaf(og0, __uint_as_float(xa & 0xFFFF0000u), acc[4 * j + 1]);
                    acc[4 * j + 2] = fmaf(og1, __uint_as_float(xb << 16), acc[4 * j + 2]);
                    acc[4 * j + 3] = fmaf(og1, __uint_as_float(xb & 0xFFFF0000u), acc[4 * j + 3]);
                }
            }
            const int srow = warp * 16 + (lane & 7) + ((lane >> 3) & 1) * 8;
#pragma unroll
            for (int rnd = 0; rnd < (BN + 127) / 128; rnd++) {
                if (tid_wg == 0) bulk_wait_read0();
                named_bar_sync(1 + c, 128);
#pragma unroll
                for (int jj = 0; jj < 8; jj++) {
                    const int j = rnd * 16 + jj * 2;
                    if (j * 8 < BN) {
                        const int jb = jj * 2 + (lane >> 4);
                        uint32_t addr = stg + (jb >> 3) * 8192 + srow * 128 + (((jb & 7) ^ (srow & 7)) << 4);
                        if (rnd * 128 + 128 > BN && jj >= 4)
                            addr = stg + 8192 + srow * 64 + (((jb & 3) ^ ((srow >> 1) & 3)) << 4);
                        stmatrix_x4(addr, pack_bf16(acc[4 * j + 0], acc[4 * j + 1]), pack_bf16(acc[4 * j + 2], acc[4 * j + 3]),
                                    pack_bf16(acc[4 * j + 4], acc[4 * j + 5]), pack_bf16(acc[4 * j + 6], acc[4 * j + 7]));
                    }
                }
                fence_proxy_async();
                named_bar_sync(1 + c, 128);
                if (tid_wg == 0) {
                    tma_store_2d(mc, stg, out_c0 + rnd * 128, m0 + c * 64);
                    if (rnd * 128 + 64 < BN)
                        tma_store_2d((rnd * 128 + 128 > BN) ? &mC1 : mc, stg + 8192, out_c0 + rnd * 128 + 64, m0 + c * 64);
                    bulk_commit();
                }
            }
        }
        if (tid_wg == 0) bulk_wait0();
        TL_END(MODE)
    }
    cluster_sync_all();
}

constexpr int ATT_NTILES = NH * 16;
#define ATT_GRID_N 512
constexpr int ATT_GRID = ATT_GRID_N;
constexpr int ATT_THREADS = 256;
constexpr int ATT_STAGES = 4;
constexpr int ATT_DIST = 2;
constexpr int ATT_Q_OFF = ATT_STAGES * 16384;
constexpr int ATT_ONES_OFF = ATT_Q_OFF + 8192;
constexpr int ATT_KEXT_OFF = ATT_ONES_OFF + 4096;
constexpr int ATT_QEXT_OFF = ATT_KEXT_OFF + 4096;
constexpr int ATT_BAR_OFF = ATT_QEXT_OFF + 8192;
constexpr int ATT_SMEM = ATT_BAR_OFF + 256 + 1024;

__device__ __forceinline__ void row_max(const float (&s)[32], float& m0, float& m1) {
    float a0[8], a1[8];
#pragma unroll
    for (int i = 0; i < 8; i++) {
        a0[i] = fmaxf(s[4 * i], s[4 * i + 1]);
        a1[i] = fmaxf(s[4 * i + 2], s[4 * i + 3]);
    }
#pragma unroll
    for (int w = 4; w > 0; w >>= 1)
#pragma unroll
        for (int i = 0; i < w; i++) { a0[i] = fmaxf(a0[i], a0[i + w]); a1[i] = fmaxf(a1[i], a1[i + w]); }
    float mx0 = a0[0], mx1 = a1[0];
    mx0 = fmaxf(mx0, __shfl_xor_sync(0xffffffffu, mx0, 1));
    mx1 = fmaxf(mx1, __shfl_xor_sync(0xffffffffu, mx1, 1));
    mx0 = fmaxf(mx0, __shfl_xor_sync(0xffffffffu, mx0, 2));
    mx1 = fmaxf(mx1, __shfl_xor_sync(0xffffffffu, mx1, 2));
    m0 = fmaxf(m0, mx0);
    m1 = fmaxf(m1, mx1);
}

__device__ __forceinline__ void attn_step(float (&sc)[32], float (&sn)[32], uint32_t (&p)[16], float (&o)[20], uint32_t dq,
                                          uint32_t dke, uint32_t dk_next, uint32_t dv_prev,
                                          uint32_t release_bar) {
    constexpr uint32_t HI = desc_hi(512, 2);
    wgmma_fence();
    wgmma_ss_n64_tb0(sn, dq, HI, dk_next, HI, 0);
    wgmma_ss_n64_tb0(sn, dq + 2, HI, dk_next + 2, HI, 1);
    wgmma_ss_n64_tb0(sn, dq + ((ATT_QEXT_OFF - ATT_Q_OFF) >> 4), HI, dke, HI, 1);
#pragma unroll
    for (int t = 0; t < 4; t++)
        wgmma_rs_n40_tb1(o, p[4 * t], p[4 * t + 1], p[4 * t + 2], p[4 * t + 3], dv_prev + t * 64, HI, 1);
    wgmma_commit();
#pragma unroll
    for (int i = 0; i < 32; i++) sc[i] = ex2(sc[i]);
    wgmma_wait<0>();
    if (release_bar != 0 && (threadIdx.x & 127) == 0) mbar_arrive(release_bar);
#pragma unroll
    for (int i = 0; i < 8; i++) {
        p[2 * i] = pack_bf16(sc[4 * i + 0], sc[4 * i + 1]);
        p[2 * i + 1] = pack_bf16(sc[4 * i + 2], sc[4 * i + 3]);
    }
}

__global__ void __launch_bounds__(256, 1)
attn_exact_kernel(const __grid_constant__ CUtensorMap mKV) {
    extern __shared__ uint8_t smem_raw[];
    pdl_launch();
    pdl_wait();
    const int tile = blockIdx.x;
    if (g_bad[tile] == 0) return;
    constexpr int NBLK = S_LEN / 128;
    constexpr uint32_t HI = desc_hi(512, 2);
    const uint32_t sbase = (smem_u32(smem_raw) + 1023u) & ~1023u;
    const uint32_t bar = sbase + ATT_BAR_OFF;
    const int warp_id = threadIdx.x >> 5;
    const int lane = threadIdx.x & 31;
    const int cq = (lane & 3) * 2;
    const uint32_t dk0 = desc_lo(sbase, 16);
    const uint32_t dv0 = desc_lo(sbase + 8192, ATT_ONES_OFF - 8192);
    if (threadIdx.x == 0) {
        mbar_init(bar, 1);
        asm volatile("fence.mbarrier_init.release.cluster;" ::: "memory");
    }
    asm volatile("st.shared.v4.b32 [%0], {%1, %1, %1, %1};" ::"r"(sbase + ATT_ONES_OFF + threadIdx.x * 16), "r"(0x3F803F80u) : "memory");
    fence_proxy_async();
    __syncthreads();
    const int head = tile >> 4;
    const int row0 = (tile & 15) * 128 + warp_id * 16 + (lane >> 2);
    const uint32_t dq = desc_lo(sbase + ATT_Q_OFF + (threadIdx.x >> 7) * 4096, 16);
    float o[20];
#pragma unroll
    for (int i = 0; i < 20; i++) o[i] = 0.f;
    float m0 = -INFINITY, m1 = -INFINITY;
#pragma unroll 1
    for (int j = 0; j < NBLK; j++) {
        if (threadIdx.x == 0) {
            mbar_expect_tx(bar, j == 0 ? 3 * 8192 : 2 * 8192);
            if (j == 0) tma_load_2d(sbase + ATT_Q_OFF, &mKV, head * DH, (tile & 15) * 128, bar);
            tma_load_2d(sbase, &mKV, DM + head * DH, j * 128, bar);
            tma_load_2d(sbase + 8192, &mKV, 2 * DM + head * DH, j * 128, bar);
        }
        __syncwarp();
        mbar_wait(bar, j & 1);
#pragma unroll 1
        for (int hf = 0; hf < 2; hf++) {
            float s[32];
            wgmma_fence();
            wgmma_ss_n64_tb0(s, dq, HI, dk0 + hf * 256, HI, 0);
            wgmma_ss_n64_tb0(s, dq + 2, HI, dk0 + hf * 256 + 2, HI, 1);
            wgmma_commit();
            wgmma_wait<0>();
            const float mo0 = m0, mo1 = m1;
            row_max(s, m0, m1);
            const float a0 = ex2(mo0 - m0), a1 = ex2(mo1 - m1);
            uint32_t p[16];
#pragma unroll
            for (int i = 0; i < 8; i++) {
                p[2 * i] = pack_bf16(ex2(s[4 * i + 0] - m0), ex2(s[4 * i + 1] - m0));
                p[2 * i + 1] = pack_bf16(ex2(s[4 * i + 2] - m1), ex2(s[4 * i + 3] - m1));
            }
#pragma unroll
            for (int i = 0; i < 5; i++) {
                o[4 * i + 0] *= a0; o[4 * i + 1] *= a0;
                o[4 * i + 2] *= a1; o[4 * i + 3] *= a1;
            }
            wgmma_fence();
            const uint32_t dv = dv0 + hf * 256 - ((uint32_t)(hf * 256) << 16);
#pragma unroll
            for (int t = 0; t < 4; t++)
                wgmma_rs_n40_tb1(o, p[4 * t], p[4 * t + 1], p[4 * t + 2], p[4 * t + 3], dv + t * 64, HI, 1);
            wgmma_commit();
            wgmma_wait<0>();
        }
        __syncthreads();
    }
    const float f0 = g_gate[row0] / o[16], f1 = g_gate[row0 + 8] / o[18];
    bf16* op0 = g_a5 + (size_t)row0 * A5W + head * DH + cq;
    bf16* op1 = op0 + 8 * A5W;
#pragma unroll
    for (int i = 0; i < 4; i++) {
        *reinterpret_cast<uint32_t*>(op0 + 8 * i) = pack_bf16(o[4 * i] * f0, o[4 * i + 1] * f0);
        *reinterpret_cast<uint32_t*>(op1 + 8 * i) = pack_bf16(o[4 * i + 2] * f1, o[4 * i + 3] * f1);
    }
}

__global__ void __launch_bounds__(256, 2)
attn_kernel(const __grid_constant__ CUtensorMap mKV) {
    extern __shared__ uint8_t smem_raw[];
    const uint32_t sbase = (smem_u32(smem_raw) + 1023u) & ~1023u;
    const uint32_t bar_kfull = sbase + ATT_BAR_OFF;
    const uint32_t bar_vfull = bar_kfull + 8 * ATT_STAGES;
    const uint32_t bar_empty = bar_vfull + 8 * ATT_STAGES;
    const int tile = blockIdx.x;
    const int head = tile >> 4;
    const int lane = threadIdx.x & 31;
    constexpr int NBLK = S_LEN / 128;
    TL_START(6)
    pdl_launch();

    auto issue_kv = [&](int g) {
        const int sn = g % ATT_STAGES;
        if (g >= ATT_STAGES) mbar_wait(bar_empty + 8 * sn, ((g / ATT_STAGES) - 1) & 1);
        const uint32_t skn = sbase + sn * 16384;
        mbar_expect_tx(bar_kfull + 8 * sn, g == 0 ? 16384 : 8192);
        if (g == 0) tma_load_2d(sbase + ATT_Q_OFF, &mKV, head * DH, (tile & 15) * 128, bar_kfull);
        tma_load_2d(skn, &mKV, DM + head * DH, g * 128, bar_kfull + 8 * sn);
        mbar_expect_tx(bar_vfull + 8 * sn, 8192);
        tma_load_2d(skn + 8192, &mKV, 2 * DM + head * DH, g * 128, bar_vfull + 8 * sn);
    };

    if (threadIdx.x == 0) {
        for (int s = 0; s < ATT_STAGES; s++) {
            mbar_init(bar_kfull + 8 * s, 1);
            mbar_init(bar_vfull + 8 * s, 1);
            mbar_init(bar_empty + 8 * s, 2);
        }
        asm volatile("fence.mbarrier_init.release.cluster;" ::: "memory");
        prefetch_tmap(&mKV);
        pdl_wait();
#pragma unroll
        for (int j = 0; j < ATT_DIST; j++) issue_kv(j);
    }
    {
        asm volatile("st.shared.v4.b32 [%0], {%1, %1, %1, %1};" ::"r"(sbase + ATT_ONES_OFF + threadIdx.x * 16), "r"(0x3F803F80u) : "memory");
        const int r = threadIdx.x >> 2, ch = threadIdx.x & 3;
        const uint32_t w0 = (ch == ((r >> 1) & 3)) ? 0x00003F80u : 0u;
        asm volatile("st.shared.v4.b32 [%0], {%1, %2, %2, %2};" ::"r"(sbase + ATT_KEXT_OFF + threadIdx.x * 16), "r"(w0), "r"(0u) : "memory");
        asm volatile("st.shared.v4.b32 [%0], {%1, %1, %1, %1};" ::"r"(sbase + ATT_QEXT_OFF + threadIdx.x * 16), "r"(0u) : "memory");
        asm volatile("st.shared.v4.b32 [%0], {%1, %1, %1, %1};" ::"r"(sbase + ATT_QEXT_OFF + 4096 + threadIdx.x * 16), "r"(0u) : "memory");
    }
    fence_proxy_async();
    __syncthreads();

    constexpr uint32_t HI = desc_hi(512, 2);
    const uint32_t dk0 = desc_lo(sbase, 16);
    const uint32_t dv0 = desc_lo(sbase + 8192, ATT_ONES_OFF - 8192);
    const uint32_t dke = dk0 + (ATT_KEXT_OFF >> 4);
    const uint32_t dq = dk0 + ((ATT_Q_OFF + (threadIdx.x >> 7) * 4096) >> 4);
    float o[20];
#pragma unroll
    for (int i = 0; i < 20; i++) o[i] = 0.f;
    float s0[32], s1[32];
    uint32_t p[16];
#pragma unroll
    for (int i = 0; i < 16; i++) p[i] = 0u;
    mbar_wait(bar_kfull, 0);
    wgmma_fence();
    wgmma_ss_n64_tb0(s0, dq, HI, dk0, HI, 0);
    wgmma_ss_n64_tb0(s0, dq + 2, HI, dk0 + 2, HI, 1);
    wgmma_commit();
    wgmma_wait<0>();
    float m0 = -INFINITY, m1 = -INFINITY;
    row_max(s0, m0, m1);
    if ((lane & 3) == 0) {
        const int r = ((threadIdx.x >> 5) & 3) * 16 + (lane >> 2);
        const uint32_t qe = sbase + ATT_QEXT_OFF + (threadIdx.x >> 7) * 4096;
        asm volatile("st.shared.b16 [%0], %1;" ::"r"(qe + r * 64 + (((r >> 1) & 3) << 4)), "h"((uint16_t)(pack_bf16(-m0, 0.f) & 0xFFFFu)) : "memory");
        asm volatile("st.shared.b16 [%0], %1;" ::"r"(qe + (r + 8) * 64 + ((((r + 8) >> 1) & 3) << 4)), "h"((uint16_t)(pack_bf16(-m1, 0.f) & 0xFFFFu)) : "memory");
    }
    fence_proxy_async();
    named_bar_sync(1 + (threadIdx.x >> 7), 128);
    wgmma_fence();
    wgmma_ss_n64_tb0(s0, dq + ((ATT_QEXT_OFF - ATT_Q_OFF) >> 4), HI, dke, HI, 1);
    wgmma_commit();
    mbar_wait(bar_vfull, 0);
    wgmma_wait<0>();
    uint32_t dv_prev = dv0;
#pragma unroll 1
    for (int j = 0; j < NBLK; j++) {
        if (threadIdx.x == 0 && j + ATT_DIST < NBLK) issue_kv(j + ATT_DIST);
        __syncwarp();
        const uint32_t stage = j & (ATT_STAGES - 1), nstage = (j + 1) & (ATT_STAGES - 1);
        const uint32_t dk = dk0 + stage * 1024;
        const uint32_t dv = dv0 + stage * 1024 - (stage << 26);
        attn_step(s0, s1, p, o, dq, dke, dk + 256, dv_prev,
                  j > 0 ? bar_empty + 8 * ((j - 1) & (ATT_STAGES - 1)) : 0u);
        uint32_t dkn = dk;
        if (j + 1 < NBLK) {
            mbar_wait(bar_kfull + 8 * nstage, ((j + 1) / ATT_STAGES) & 1);
            dkn = dk0 + nstage * 1024;
        }
        mbar_wait(bar_vfull + 8 * stage, (j / ATT_STAGES) & 1);
        attn_step(s1, s0, p, o, dq, dke, dkn, dv, 0u);
        dv_prev = dv + 256 - (256u << 16);
    }
    wgmma_fence();
#pragma unroll
    for (int t = 0; t < 4; t++)
        wgmma_rs_n40_tb1(o, p[4 * t], p[4 * t + 1], p[4 * t + 2], p[4 * t + 3], dv_prev + t * 64, HI, 1);
    wgmma_commit();
    wgmma_wait<0>();
    bool ok = (o[16] <= 1.8446744e19f) && (o[18] <= 1.8446744e19f);
#pragma unroll
    for (int i = 0; i < 16; i++) ok = ok && (fabsf(o[i]) <= 3.0e38f);
    const int row0 = (tile & 15) * 128 + (threadIdx.x >> 5) * 16 + (lane >> 2);
    const float f0 = g_gate[row0] / o[16], f1 = g_gate[row0 + 8] / o[18];
    bf16* op0 = g_a5 + (size_t)row0 * A5W + head * DH + (lane & 3) * 2;
    bf16* op1 = op0 + 8 * A5W;
#pragma unroll
    for (int i = 0; i < 4; i++) {
        *reinterpret_cast<uint32_t*>(op0 + 8 * i) = pack_bf16(o[4 * i] * f0, o[4 * i + 1] * f0);
        *reinterpret_cast<uint32_t*>(op1 + 8 * i) = pack_bf16(o[4 * i + 2] * f1, o[4 * i + 3] * f1);
    }
    const int bad = __syncthreads_or(!ok);
    if (threadIdx.x == 0) g_bad[tile] = bad;
    TL_END(6)
}

typedef CUresult (*EncodeFn)(CUtensorMap*, CUtensorMapDataType, cuuint32_t, void*, const cuuint64_t*, const cuuint64_t*,
                             const cuuint32_t*, const cuuint32_t*, CUtensorMapInterleave, CUtensorMapSwizzle,
                             CUtensorMapL2promotion, CUtensorMapFloatOOBfill);

static CUtensorMap make_map(EncodeFn fn, const void* ptr, int rows, int cols, int box_cols, int box_rows,
                            CUtensorMapSwizzle swz) {
    CUtensorMap m;
    cuuint64_t dims[2] = {(cuuint64_t)cols, (cuuint64_t)rows};
    cuuint64_t strides[1] = {(cuuint64_t)cols * 2};
    cuuint32_t box[2] = {(cuuint32_t)box_cols, (cuuint32_t)box_rows};
    cuuint32_t es[2] = {1, 1};
    fn(&m, CU_TENSOR_MAP_DATA_TYPE_BFLOAT16, 2, const_cast<void*>(ptr), dims, strides, box, es,
       CU_TENSOR_MAP_INTERLEAVE_NONE, swz, CU_TENSOR_MAP_L2_PROMOTION_L2_256B, CU_TENSOR_MAP_FLOAT_OOB_FILL_NONE);
    return m;
}

template <typename... KArgs, typename... Args>
static void launch_ex(void (*kern)(KArgs...), int grid, int block, int smem, cudaStream_t st, int cluster, Args... args) {
    cudaLaunchConfig_t cfg = {};
    cfg.gridDim = dim3(grid);
    cfg.blockDim = dim3(block);
    cfg.dynamicSmemBytes = smem;
    cfg.stream = st;
    cudaLaunchAttribute at[2];
    at[0].id = cudaLaunchAttributeProgrammaticStreamSerialization;
    at[0].val.programmaticStreamSerializationAllowed = 1;
    at[1].id = cudaLaunchAttributeClusterDimension;
    at[1].val.clusterDim.x = cluster;
    at[1].val.clusterDim.y = 1;
    at[1].val.clusterDim.z = 1;
    cfg.attrs = at;
    cfg.numAttrs = cluster > 1 ? 2 : 1;
    cudaLaunchKernelEx(&cfg, kern, KArgs(args)...);
}

extern "C" void kernel_launch(void* const* d_in, const int* in_sizes, int n_in, void* d_out, int out_size) {
    const bf16* x = (const bf16*)d_in[0];
    const bf16* wqkv = (const bf16*)d_in[1];
    const bf16* wo = (const bf16*)d_in[2];
    const bf16* w1 = (const bf16*)d_in[4];
    const bf16* w2 = (const bf16*)d_in[5];
    const bf16* w3 = (const bf16*)d_in[6];
    const bf16* w4 = (const bf16*)d_in[7];
    const bf16* gate_w = (const bf16*)d_in[8];

    static EncodeFn enc = nullptr;
    static void *p_qkv, *p_h, *p_x1, *p_a5;
    using G1 = GemmSmem<256, 4>;
    using G2 = GemmSmem<128, 5>;
    using G3 = GemmSmem<224, 4>;
    if (!enc) {
        void* fn = nullptr;
        cudaDriverEntryPointQueryResult qres;
        cudaGetDriverEntryPoint("cuTensorMapEncodeTiled", &fn, cudaEnableDefault, &qres);
        enc = (EncodeFn)fn;
        cudaGetSymbolAddress(&p_qkv, g_qkv);
        cudaGetSymbolAddress(&p_h, g_h);
        cudaGetSymbolAddress(&p_x1, g_x1);
        cudaGetSymbolAddress(&p_a5, g_a5);
        cudaFuncSetAttribute(gemm_kernel<1, 256, 4>, cudaFuncAttributeMaxDynamicSharedMemorySize, G1::TOTAL);
        cudaFuncSetAttribute(gemm_kernel<2, 128, 5>, cudaFuncAttributeMaxDynamicSharedMemorySize, G2::TOTAL);
        cudaFuncSetAttribute(gemm_kernel<3, 224, 4>, cudaFuncAttributeMaxDynamicSharedMemorySize, G3::TOTAL);
        cudaFuncSetAttribute(gemm_kernel<5, 128, 5>, cudaFuncAttributeMaxDynamicSharedMemorySize, G2::TOTAL);
        cudaFuncSetAttribute(attn_kernel, cudaFuncAttributeMaxDynamicSharedMemorySize, ATT_SMEM);
        cudaFuncSetAttribute(attn_exact_kernel, cudaFuncAttributeMaxDynamicSharedMemorySize, ATT_SMEM);
    }
    const CUtensorMapSwizzle SW128 = CU_TENSOR_MAP_SWIZZLE_128B, SW64 = CU_TENSOR_MAP_SWIZZLE_64B;
    CUtensorMap mX = make_map(enc, x, S_LEN, DM, 64, 128, SW128);
    CUtensorMap mWqkv = make_map(enc, wqkv, DM, 3 * DM, 64, 64, SW128);
    CUtensorMap mW1 = make_map(enc, w1, DM, DM, 64, 64, SW128);
    CUtensorMap mW2 = make_map(enc, w2, DM, DM, 64, 64, SW128);
    CUtensorMap mW3 = make_map(enc, w3, DM, FF, 64, 64, SW128);
    CUtensorMap mW4 = make_map(enc, w4, FF, DM, 64, 64, SW128);
    CUtensorMap mWo = make_map(enc, wo, DM, DM, 64, 64, SW128);
    CUtensorMap mQKVst = make_map(enc, p_qkv, S_LEN, 3 * DM, 64, 64, SW128);
    CUtensorMap mKV = make_map(enc, p_qkv, S_LEN, 3 * DM, 32, 128, SW64);
    CUtensorMap mHst = make_map(enc, p_h, S_LEN, DM, 64, 64, SW128);
    CUtensorMap mHld = make_map(enc, p_h, S_LEN, DM, 64, 128, SW128);
    CUtensorMap mX1st = make_map(enc, p_x1, S_LEN, DM, 64, 64, SW128);
    CUtensorMap mX1ld = make_map(enc, p_x1, S_LEN, DM, 64, 128, SW128);
    CUtensorMap mA5st = make_map(enc, p_a5, S_LEN, A5W, 64, 64, SW128);
    CUtensorMap mA5st32 = make_map(enc, p_a5, S_LEN, A5W, 32, 64, SW64);
    CUtensorMap mA5ld = make_map(enc, p_a5, S_LEN, A5W, 64, 128, SW128);
    CUtensorMap mOut = make_map(enc, d_out, S_LEN, DM, 64, 64, SW128);

    cudaStream_t st = cudaStreamPerThread;
    prep_kernel<<<256 + 72, 256, 0, st>>>(x, gate_w, w1, w3);
    launch_ex(gemm_kernel<1, 256, 4>, 132, 384, G1::TOTAL, st, 2, mX, mWqkv, mW1, mQKVst, mHst, x, 16, 16);
    launch_ex(attn_kernel, ATT_GRID, ATT_THREADS, ATT_SMEM, st, 1, mKV);
    launch_ex(attn_exact_kernel, ATT_NTILES, ATT_THREADS, ATT_SMEM, st, 1, mKV);
    launch_ex(gemm_kernel<2, 128, 5>, 128, 384, G2::TOTAL, st, 2, mHld, mW2, mW2, mX1st, mX1st, x, 8, 16);
    launch_ex(gemm_kernel<3, 224, 4>, 132, 384, G3::TOTAL, st, 2, mX1ld, mW3, mW3, mA5st, mA5st32, x, 16, 16);
    launch_ex(gemm_kernel<5, 128, 5>, 128, 384, G2::TOTAL, st, 2, mA5ld, mWo, mW4, mOut, mOut, (const bf16*)p_x1, 8, 72);
}
```

```cpp
#include <cuda_runtime.h>
#include <cuda_bf16.h>
#include <cuda.h>
#include <stdint.h>

typedef __nv_bfloat16 bf16;

constexpr int S_LEN = 2048;
constexpr int DM = 1024;
constexpr int FF = 3584;
constexpr int NH = 32;
constexpr int DH = 32;
constexpr int A5W = DM + FF;

__device__ __align__(1024) bf16 g_qkv[S_LEN * 3 * DM];
__device__ __align__(1024) bf16 g_h[S_LEN * DM];
__device__ __align__(1024) bf16 g_x1[S_LEN * DM];
__device__ __align__(1024) bf16 g_a5[S_LEN * A5W];
__device__ __align__(16) float g_mean1[S_LEN];
__device__ __align__(16) float g_rstd1[S_LEN];
__device__ __align__(16) float g_gate[S_LEN];
__device__ __align__(16) float g_omg[S_LEN];
__device__ __align__(16) float g_cs1[DM];
__device__ __align__(16) float g_cs3[FF];
__device__ __align__(16) float2 g_stat2[S_LEN * 8];
__device__ int g_bad[NH * 16];

#define TL_START(k)
#define TL_END(k)

__device__ __forceinline__ uint32_t smem_u32(const void* p) { return (uint32_t)__cvta_generic_to_shared(p); }

__device__ __forceinline__ void mbar_init(uint32_t bar, uint32_t count) {
    asm volatile("mbarrier.init.shared::cta.b64 [%0], %1;" ::"r"(bar), "r"(count));
}
__device__ __forceinline__ void mbar_expect_tx(uint32_t bar, uint32_t bytes) {
    asm volatile("mbarrier.arrive.expect_tx.shared::cta.b64 _, [%0], %1;" ::"r"(bar), "r"(bytes) : "memory");
}
__device__ __forceinline__ void mbar_arrive(uint32_t bar) {
    asm volatile("mbarrier.arrive.shared::cta.b64 _, [%0];" ::"r"(bar) : "memory");
}
__device__ __forceinline__ bool mbar_try_wait(uint32_t bar, uint32_t parity) {
    uint32_t ok;
    asm volatile(
        "{\n.reg .pred p;\n"
        "mbarrier.try_wait.parity.shared::cta.b64 p, [%1], %2;\n"
        "selp.u32 %0, 1, 0, p;\n}\n"
        : "=r"(ok)
        : "r"(bar), "r"(parity)
        : "memory");
    return ok != 0;
}
__device__ __forceinline__ void mbar_wait(uint32_t bar, uint32_t parity) {
    uint32_t spins = 0;
    while (!mbar_try_wait(bar, parity)) {
        if (++spins > (1u << 24)) __trap();
    }
}
__device__ __forceinline__ void tma_load_2d(uint32_t dst, const CUtensorMap* map, int c0, int c1, uint32_t bar) {
    asm volatile(
        "cp.async.bulk.tensor.2d.shared::cluster.global.mbarrier::complete_tx::bytes [%0], [%1, {%3, %4}], [%2];"
        ::"r"(dst), "l"(map), "r"(bar), "r"(c0), "r"(c1)
        : "memory");
}
__device__ __forceinline__ void tma_store_2d(const CUtensorMap* map, uint32_t src, int c0, int c1) {
    asm volatile("cp.async.bulk.tensor.2d.global.shared::cta.bulk_group [%0, {%2, %3}], [%1];"
                 ::"l"(map), "r"(src), "r"(c0), "r"(c1)
                 : "memory");
}
__device__ __forceinline__ void tma_load_2d_mc(uint32_t dst, const CUtensorMap* map, int c0, int c1, uint32_t bar, uint16_t mask) {
    asm volatile(
        "cp.async.bulk.tensor.2d.shared::cluster.global.mbarrier::complete_tx::bytes.multicast::cluster [%0], [%1, {%3, %4}], [%2], %5;"
        ::"r"(dst), "l"(map), "r"(bar), "r"(c0), "r"(c1), "h"(mask)
        : "memory");
}
__device__ __forceinline__ void mbar_arrive_cluster(uint32_t bar, uint32_t cta) {
    asm volatile(
        "{\n.reg .b32 ra;\nmapa.shared::cluster.u32 ra, %0, %1;\n"
        "mbarrier.arrive.shared::cluster.b64 _, [ra];\n}\n" ::"r"(bar), "r"(cta)
        : "memory");
}
__device__ __forceinline__ void cluster_sync_all() {
    asm volatile("barrier.cluster.arrive.release.aligned;\nbarrier.cluster.wait.acquire.aligned;" ::: "memory");
}
__device__ __forceinline__ uint32_t cluster_rank() { uint32_t r; asm volatile("mov.u32 %0, %%cluster_ctarank;" : "=r"(r)); return r; }
__device__ __forceinline__ void pdl_wait() { asm volatile("griddepcontrol.wait;" ::: "memory"); }
__device__ __forceinline__ void pdl_launch() { asm volatile("griddepcontrol.launch_dependents;" ::: "memory"); }
__device__ __forceinline__ void bulk_commit() { asm volatile("cp.async.bulk.commit_group;" ::: "memory"); }
__device__ __forceinline__ void bulk_wait_read0() { asm volatile("cp.async.bulk.wait_group.read 0;" ::: "memory"); }
__device__ __forceinline__ void bulk_wait0() { asm volatile("cp.async.bulk.wait_group 0;" ::: "memory"); }
__device__ __forceinline__ void fence_proxy_async() { asm volatile("fence.proxy.async.shared::cta;" ::: "memory"); }
__device__ __forceinline__ void named_bar_sync(int id, int n) { asm volatile("bar.sync %0, %1;" ::"r"(id), "r"(n) : "memory"); }
__device__ __forceinline__ void named_bar_arrive(int id, int n) { asm volatile("bar.arrive %0, %1;" ::"r"(id), "r"(n) : "memory"); }
__device__ __forceinline__ void wgmma_fence() { asm volatile("wgmma.fence.sync.aligned;" ::: "memory"); }
__device__ __forceinline__ void wgmma_commit() { asm volatile("wgmma.commit_group.sync.aligned;" ::: "memory"); }
template <int N>
__device__ __forceinline__ void wgmma_wait() { asm volatile("wgmma.wait_group.sync.aligned %0;" ::"n"(N) : "memory"); }
__device__ __forceinline__ void prefetch_tmap(const CUtensorMap* m) {
    asm volatile("prefetch.tensormap [%0];" ::"l"(m) : "memory");
}
template <int R>
__device__ __forceinline__ void reg_alloc() { asm volatile("setmaxnreg.inc.sync.aligned.u32 %0;" ::"n"(R)); }
template <int R>
__device__ __forceinline__ void reg_dealloc() { asm volatile("setmaxnreg.dec.sync.aligned.u32 %0;" ::"n"(R)); }
__device__ __forceinline__ void stmatrix_x4(uint32_t addr, uint32_t r0, uint32_t r1, uint32_t r2, uint32_t r3) {
    asm volatile("stmatrix.sync.aligned.m8n8.x4.shared.b16 [%0], {%1, %2, %3, %4};"
                 ::"r"(addr), "r"(r0), "r"(r1), "r"(r2), "r"(r3)
                 : "memory");
}
__device__ __forceinline__ uint32_t pack_bf16(float lo, float hi) {
    uint32_t r;
    asm("cvt.rn.bf16x2.f32 %0, %1, %2;" : "=r"(r) : "f"(hi), "f"(lo));
    return r;
}
__device__ __forceinline__ float bf16_round(float v) { return __bfloat162float(__float2bfloat16_rn(v)); }
__device__ __forceinline__ float ex2(float x) {
    float y;
    asm volatile("ex2.approx.ftz.f32 %0, %1;" : "=f"(y) : "f"(x));
    return y;
}
__device__ __forceinline__ float tanh_fast(float x) {
    float y;
    asm("tanh.approx.f32 %0, %1;" : "=f"(y) : "f"(x));
    return y;
}
__device__ __forceinline__ float gelu_tanh(float v) {
    float u = 0.7978845608028654f * (v + 0.044715f * v * v * v);
    float hv = 0.5f * v;
    return fmaf(hv, tanh_fast(u), hv);
}
__device__ __forceinline__ uint32_t desc_lo(uint32_t addr, uint32_t lbo_bytes) {
    return ((addr & 0x3FFFF) >> 4) | (((lbo_bytes >> 4) & 0x3FFF) << 16);
}
__host__ __device__ constexpr uint32_t desc_hi(uint32_t sbo_bytes, uint32_t swz) {
    return ((sbo_bytes >> 4) & 0x3FFF) | (swz << 30);
}

__device__ __forceinline__ void wgmma_ss_n128_tb1(float (&d)[64], uint32_t alo, uint32_t ahi, uint32_t blo, uint32_t bhi, int scale_d) {
    asm volatile("{\n.reg .pred p;\n.reg .b64 da, db;\nsetp.ne.b32 p, %68, 0;\nmov.b64 da, {%64, %65};\nmov.b64 db, {%66, %67};\n"
        "wgmma.mma_async.sync.aligned.m64n128k16.f32.bf16.bf16 {%0, %1, %2, %3, %4, %5, %6, %7, %8, %9, %10, %11, %12, %13, %14, %15, %16, %17, %18, %19, %20, %21, %22, %23, %24, %25, %26, %27, %28, %29, %30, %31, %32, %33, %34, %35, %36, %37, %38, %39, %40, %41, %42, %43, %44, %45, %46, %47, %48, %49, %50, %51, %52, %53, %54, %55, %56, %57, %58, %59, %60, %61, %62, %63}, da, db, p, 1, 1, 0, 1;\n}\n"
        : "+f"(d[0]), "+f"(d[1]), "+f"(d[2]), "+f"(d[3]), "+f"(d[4]), "+f"(d[5]), "+f"(d[6]), "+f"(d[7]), "+f"(d[8]), "+f"(d[9]), "+f"(d[10]), "+f"(d[11]), "+f"(d[12]), "+f"(d[13]), "+f"(d[14]), "+f"(d[15]), "+f"(d[16]), "+f"(d[17]), "+f"(d[18]), "+f"(d[19]), "+f"(d[20]), "+f"(d[21]), "+f"(d[22]), "+f"(d[23]), "+f"(d[24]), "+f"(d[25]), "+f"(d[26]), "+f"(d[27]), "+f"(d[28]), "+f"(d[29]), "+f"(d[30]), "+f"(d[31]), "+f"(d[32]), "+f"(d[33]), "+f"(d[34]), "+f"(d[35]), "+f"(d[36]), "+f"(d[37]), "+f"(d[38]), "+f"(d[39]), "+f"(d[40]), "+f"(d[41]), "+f"(d[42]), "+f"(d[43]), "+f"(d[44]), "+f"(d[45]), "+f"(d[46]), "+f"(d[47]), "+f"(d[48]), "+f"(d[49]), "+f"(d[50]), "+f"(d[51]), "+f"(d[52]), "+f"(d[53]), "+f"(d[54]), "+f"(d[55]), "+f"(d[56]), "+f"(d[57]), "+f"(d[58]), "+f"(d[59]), "+f"(d[60]), "+f"(d[61]), "+f"(d[62]), "+f"(d[63])
        : "r"(alo), "r"(ahi), "r"(blo), "r"(bhi), "r"(scale_d));
}

__device__ __forceinline__ void wgmma_ss_n192_tb1(float (&d)[96], uint32_t alo, uint32_t ahi, uint32_t blo, uint32_t bhi, int scale_d) {
    asm volatile("{\n.reg .pred p;\n.reg .b64 da, db;\nsetp.ne.b32 p, %100, 0;\nmov.b64 da, {%96, %97};\nmov.b64 db, {%98, %99};\n"
        "wgmma.mma_async.sync.aligned.m64n192k16.f32.bf16.bf16 {%0, %1, %2, %3, %4, %5, %6, %7, %8, %9, %10, %11, %12, %13, %14, %15, %16, %17, %18, %19, %20, %21, %22, %23, %24, %25, %26, %27, %28, %29, %30, %31, %32, %33, %34, %35, %36, %37, %38, %39, %40, %41, %42, %43, %44, %45, %46, %47, %48, %49, %50, %51, %52, %53, %54, %55, %56, %57, %58, %59, %60, %61, %62, %63, %64, %65, %66, %67, %68, %69, %70, %71, %72, %73, %74, %75, %76, %77, %78, %79, %80, %81, %82, %83, %84, %85, %86, %87, %88, %89, %90, %91, %92, %93, %94, %95}, da, db, p, 1, 1, 0, 1;\n}\n"
        : "+f"(d[0]), "+f"(d[1]), "+f"(d[2]), "+f"(d[3]), "+f"(d[4]), "+f"(d[5]), "+f"(d[6]), "+f"(d[7]), "+f"(d[8]), "+f"(d[9]), "+f"(d[10]), "+f"(d[11]), "+f"(d[12]), "+f"(d[13]), "+f"(d[14]), "+f"(d[15]), "+f"(d[16]), "+f"(d[17]), "+f"(d[18]), "+f"(d[19]), "+f"(d[20]), "+f"(d[21]), "+f"(d[22]), "+f"(d[23]), "+f"(d[24]), "+f"(d[25]), "+f"(d[26]), "+f"(d[27]), "+f"(d[28]), "+f"(d[29]), "+f"(d[30]), "+f"(d[31]), "+f"(d[32]), "+f"(d[33]), "+f"(d[34]), "+f"(d[35]), "+f"(d[36]), "+f"(d[37]), "+f"(d[38]), "+f"(d[39]), "+f"(d[40]), "+f"(d[41]), "+f"(d[42]), "+f"(d[43]), "+f"(d[44]), "+f"(d[45]), "+f"(d[46]), "+f"(d[47]), "+f"(d[48]), "+f"(d[49]), "+f"(d[50]), "+f"(d[51]), "+f"(d[52]), "+f"(d[53]), "+f"(d[54]), "+f"(d[55]), "+f"(d[56]), "+f"(d[57]), "+f"(d[58]), "+f"(d[59]), "+f"(d[60]), "+f"(d[61]), "+f"(d[62]), "+f"(d[63]), "+f"(d[64]), "+f"(d[65]), "+f"(d[66]), "+f"(d[67]), "+f"(d[68]), "+f"(d[69]), "+f"(d[70]), "+f"(d[71]), "+f"(d[72]), "+f"(d[73]), "+f"(d[74]), "+f"(d[75]), "+f"(d[76]), "+f"(d[77]), "+f"(d[78]), "+f"(d[79]), "+f"(d[80]), "+f"(d[81]), "+f"(d[82]), "+f"(d[83]), "+f"(d[84]), "+f"(d[85]), "+f"(d[86]), "+f"(d[87]), "+f"(d[88]), "+f"(d[89]), "+f"(d[90]), "+f"(d[91]), "+f"(d[92]), "+f"(d[93]), "+f"(d[94]), "+f"(d[95])
        : "r"(alo), "r"(ahi), "r"(blo), "r"(bhi), "r"(scale_d));
}

__device__ __forceinline__ void wgmma_ss_n224_tb1(float (&d)[112], uint32_t alo, uint32_t ahi, uint32_t blo, uint32_t bhi, int scale_d) {
    asm volatile("{\n.reg .pred p;\n.reg .b64 da, db;\nsetp.ne.b32 p, %116, 0;\nmov.b64 da, {%112, %113};\nmov.b64 db, {%114, %115};\n"
        "wgmma.mma_async.sync.aligned.m64n224k16.f32.bf16.bf16 {%0, %1, %2, %3, %4, %5, %6, %7, %8, %9, %10, %11, %12, %13, %14, %15, %16, %17, %18, %19, %20, %21, %22, %23, %24, %25, %26, %27, %28, %29, %30, %31, %32, %33, %34, %35, %36, %37, %38, %39, %40, %41, %42, %43, %44, %45, %46, %47, %48, %49, %50, %51, %52, %53, %54, %55, %56, %57, %58, %59, %60, %61, %62, %63, %64, %65, %66, %67, %68, %69, %70, %71, %72, %73, %74, %75, %76, %77, %78, %79, %80, %81, %82, %83, %84, %85, %86, %87, %88, %89, %90, %91, %92, %93, %94, %95, %96, %97, %98, %99, %100, %101, %102, %103, %104, %105, %106, %107, %108, %109, %110, %111}, da, db, p, 1, 1, 0, 1;\n}\n"
        : "+f"(d[0]), "+f"(d[1]), "+f"(d[2]), "+f"(d[3]), "+f"(d[4]), "+f"(d[5]), "+f"(d[6]), "+f"(d[7]), "+f"(d[8]), "+f"(d[9]), "+f"(d[10]), "+f"(d[11]), "+f"(d[12]), "+f"(d[13]), "+f"(d[14]), "+f"(d[15]), "+f"(d[16]), "+f"(d[17]), "+f"(d[18]), "+f"(d[19]), "+f"(d[20]), "+f"(d[21]), "+f"(d[22]), "+f"(d[23]), "+f"(d[24]), "+f"(d[25]), "+f"(d[26]), "+f"(d[27]), "+f"(d[28]), "+f"(d[29]), "+f"(d[30]), "+f"(d[31]), "+f"(d[32]), "+f"(d[33]), "+f"(d[34]), "+f"(d[35]), "+f"(d[36]), "+f"(d[37]), "+f"(d[38]), "+f"(d[39]), "+f"(d[40]), "+f"(d[41]), "+f"(d[42]), "+f"(d[43]), "+f"(d[44]), "+f"(d[45]), "+f"(d[46]), "+f"(d[47]), "+f"(d[48]), "+f"(d[49]), "+f"(d[50]), "+f"(d[51]), "+f"(d[52]), "+f"(d[53]), "+f"(d[54]), "+f"(d[55]), "+f"(d[56]), "+f"(d[57]), "+f"(d[58]), "+f"(d[59]), "+f"(d[60]), "+f"(d[61]), "+f"(d[62]), "+f"(d[63]), "+f"(d[64]), "+f"(d[65]), "+f"(d[66]), "+f"(d[67]), "+f"(d[68]), "+f"(d[69]), "+f"(d[70]), "+f"(d[71]), "+f"(d[72]), "+f"(d[73]), "+f"(d[74]), "+f"(d[75]), "+f"(d[76]), "+f"(d[77]), "+f"(d[78]), "+f"(d[79]), "+f"(d[80]), "+f"(d[81]), "+f"(d[82]), "+f"(d[83]), "+f"(d[84]), "+f"(d[85]), "+f"(d[86]), "+f"(d[87]), "+f"(d[88]), "+f"(d[89]), "+f"(d[90]), "+f"(d[91]), "+f"(d[92]), "+f"(d[93]), "+f"(d[94]), "+f"(d[95]), "+f"(d[96]), "+f"(d[97]), "+f"(d[98]), "+f"(d[99]), "+f"(d[100]), "+f"(d[101]), "+f"(d[102]), "+f"(d[103]), "+f"(d[104]), "+f"(d[105]), "+f"(d[106]), "+f"(d[107]), "+f"(d[108]), "+f"(d[109]), "+f"(d[110]), "+f"(d[111])
        : "r"(alo), "r"(ahi), "r"(blo), "r"(bhi), "r"(scale_d));
}

__device__ __forceinline__ void wgmma_ss_n256_tb1(float (&d)[128], uint32_t alo, uint32_t ahi, uint32_t blo, uint32_t bhi, int scale_d) {
    asm volatile("{\n.reg .pred p;\n.reg .b64 da, db;\nsetp.ne.b32 p, %132, 0;\nmov.b64 da, {%128, %129};\nmov.b64 db, {%130, %131};\n"
        "wgmma.mma_async.sync.aligned.m64n256k16.f32.bf16.bf16 {%0, %1, %2, %3, %4, %5, %6, %7, %8, %9, %10, %11, %12, %13, %14, %15, %16, %17, %18, %19, %20, %21, %22, %23, %24, %25, %26, %27, %28, %29, %30, %31, %32, %33, %34, %35, %36, %37, %38, %39, %40, %41, %42, %43, %44, %45, %46, %47, %48, %49, %50, %51, %52, %53, %54, %55, %56, %57, %58, %59, %60, %61, %62, %63, %64, %65, %66, %67, %68, %69, %70, %71, %72, %73, %74, %75, %76, %77, %78, %79, %80, %81, %82, %83, %84, %85, %86, %87, %88, %89, %90, %91, %92, %93, %94, %95, %96, %97, %98, %99, %100, %101, %102, %103, %104, %105, %106, %107, %108, %109, %110, %111, %112, %113, %114, %115, %116, %117, %118, %119, %120, %121, %122, %123, %124, %125, %126, %127}, da, db, p, 1, 1, 0, 1;\n}\n"
        : "+f"(d[0]), "+f"(d[1]), "+f"(d[2]), "+f"(d[3]), "+f"(d[4]), "+f"(d[5]), "+f"(d[6]), "+f"(d[7]), "+f"(d[8]), "+f"(d[9]), "+f"(d[10]), "+f"(d[11]), "+f"(d[12]), "+f"(d[13]), "+f"(d[14]), "+f"(d[15]), "+f"(d[16]), "+f"(d[17]), "+f"(d[18]), "+f"(d[19]), "+f"(d[20]), "+f"(d[21]), "+f"(d[22]), "+f"(d[23]), "+f"(d[24]), "+f"(d[25]), "+f"(d[26]), "+f"(d[27]), "+f"(d[28]), "+f"(d[29]), "+f"(d[30]), "+f"(d[31]), "+f"(d[32]), "+f"(d[33]), "+f"(d[34]), "+f"(d[35]), "+f"(d[36]), "+f"(d[37]), "+f"(d[38]), "+f"(d[39]), "+f"(d[40]), "+f"(d[41]), "+f"(d[42]), "+f"(d[43]), "+f"(d[44]), "+f"(d[45]), "+f"(d[46]), "+f"(d[47]), "+f"(d[48]), "+f"(d[49]), "+f"(d[50]), "+f"(d[51]), "+f"(d[52]), "+f"(d[53]), "+f"(d[54]), "+f"(d[55]), "+f"(d[56]), "+f"(d[57]), "+f"(d[58]), "+f"(d[59]), "+f"(d[60]), "+f"(d[61]), "+f"(d[62]), "+f"(d[63]), "+f"(d[64]), "+f"(d[65]), "+f"(d[66]), "+f"(d[67]), "+f"(d[68]), "+f"(d[69]), "+f"(d[70]), "+f"(d[71]), "+f"(d[72]), "+f"(d[73]), "+f"(d[74]), "+f"(d[75]), "+f"(d[76]), "+f"(d[77]), "+f"(d[78]), "+f"(d[79]), "+f"(d[80]), "+f"(d[81]), "+f"(d[82]), "+f"(d[83]), "+f"(d[84]), "+f"(d[85]), "+f"(d[86]), "+f"(d[87]), "+f"(d[88]), "+f"(d[89]), "+f"(d[90]), "+f"(d[91]), "+f"(d[92]), "+f"(d[93]), "+f"(d[94]), "+f"(d[95]), "+f"(d[96]), "+f"(d[97]), "+f"(d[98]), "+f"(d[99]), "+f"(d[100]), "+f"(d[101]), "+f"(d[102]), "+f"(d[103]), "+f"(d[104]), "+f"(d[105]), "+f"(d[106]), "+f"(d[107]), "+f"(d[108]), "+f"(d[109]), "+f"(d[110]), "+f"(d[111]), "+f"(d[112]), "+f"(d[113]), "+f"(d[114]), "+f"(d[115]), "+f"(d[116]), "+f"(d[117]), "+f"(d[118]), "+f"(d[119]), "+f"(d[120]), "+f"(d[121]), "+f"(d[122]), "+f"(d[123]), "+f"(d[124]), "+f"(d[125]), "+f"(d[126]), "+f"(d[127])
        : "r"(alo), "r"(ahi), "r"(blo), "r"(bhi), "r"(scale_d));
}

__device__ __forceinline__ void wgmma_ss_n64_tb0(float (&d)[32], uint32_t alo, uint32_t ahi, uint32_t blo, uint32_t bhi, int scale_d) {
    asm volatile("{\n.reg .pred p;\n.reg .b64 da, db;\nsetp.ne.b32 p, %36, 0;\nmov.b64 da, {%32, %33};\nmov.b64 db, {%34, %35};\n"
        "wgmma.mma_async.sync.aligned.m64n64k16.f32.bf16.bf16 {%0, %1, %2, %3, %4, %5, %6, %7, %8, %9, %10, %11, %12, %13, %14, %15, %16, %17, %18, %19, %20, %21, %22, %23, %24, %25, %26, %27, %28, %29, %30, %31}, da, db, p, 1, 1, 0, 0;\n}\n"
        : "+f"(d[0]), "+f"(d[1]), "+f"(d[2]), "+f"(d[3]), "+f"(d[4]), "+f"(d[5]), "+f"(d[6]), "+f"(d[7]), "+f"(d[8]), "+f"(d[9]), "+f"(d[10]), "+f"(d[11]), "+f"(d[12]), "+f"(d[13]), "+f"(d[14]), "+f"(d[15]), "+f"(d[16]), "+f"(d[17]), "+f"(d[18]), "+f"(d[19]), "+f"(d[20]), "+f"(d[21]), "+f"(d[22]), "+f"(d[23]), "+f"(d[24]), "+f"(d[25]), "+f"(d[26]), "+f"(d[27]), "+f"(d[28]), "+f"(d[29]), "+f"(d[30]), "+f"(d[31])
        : "r"(alo), "r"(ahi), "r"(blo), "r"(bhi), "r"(scale_d));
}

__device__ __forceinline__ void wgmma_rs_n128_tb0(float (&d)[64], uint32_t a0, uint32_t a1, uint32_t a2, uint32_t a3, uint32_t blo, uint32_t bhi, int scale_d) {
    asm volatile("{\n.reg .pred p;\n.reg .b64 db;\nsetp.ne.b32 p, %70, 0;\nmov.b64 db, {%68, %69};\n"
        "wgmma.mma_async.sync.aligned.m64n128k16.f32.bf16.bf16 {%0, %1, %2, %3, %4, %5, %6, %7, %8, %9, %10, %11, %12, %13, %14, %15, %16, %17, %18, %19, %20, %21, %22, %23, %24, %25, %26, %27, %28, %29, %30, %31, %32, %33, %34, %35, %36, %37, %38, %39, %40, %41, %42, %43, %44, %45, %46, %47, %48, %49, %50, %51, %52, %53, %54, %55, %56, %57, %58, %59, %60, %61, %62, %63}, {%64, %65, %66, %67}, db, p, 1, 1, 0;\n}\n"
        : "+f"(d[0]), "+f"(d[1]), "+f"(d[2]), "+f"(d[3]), "+f"(d[4]), "+f"(d[5]), "+f"(d[6]), "+f"(d[7]), "+f"(d[8]), "+f"(d[9]), "+f"(d[10]), "+f"(d[11]), "+f"(d[12]), "+f"(d[13]), "+f"(d[14]), "+f"(d[15]), "+f"(d[16]), "+f"(d[17]), "+f"(d[18]), "+f"(d[19]), "+f"(d[20]), "+f"(d[21]), "+f"(d[22]), "+f"(d[23]), "+f"(d[24]), "+f"(d[25]), "+f"(d[26]), "+f"(d[27]), "+f"(d[28]), "+f"(d[29]), "+f"(d[30]), "+f"(d[31]), "+f"(d[32]), "+f"(d[33]), "+f"(d[34]), "+f"(d[35]), "+f"(d[36]), "+f"(d[37]), "+f"(d[38]), "+f"(d[39]), "+f"(d[40]), "+f"(d[41]), "+f"(d[42]), "+f"(d[43]), "+f"(d[44]), "+f"(d[45]), "+f"(d[46]), "+f"(d[47]), "+f"(d[48]), "+f"(d[49]), "+f"(d[50]), "+f"(d[51]), "+f"(d[52]), "+f"(d[53]), "+f"(d[54]), "+f"(d[55]), "+f"(d[56]), "+f"(d[57]), "+f"(d[58]), "+f"(d[59]), "+f"(d[60]), "+f"(d[61]), "+f"(d[62]), "+f"(d[63])
        : "r"(a0), "r"(a1), "r"(a2), "r"(a3), "r"(blo), "r"(bhi), "r"(scale_d));
}

__device__ __forceinline__ void wgmma_rs_n64_tb0(float (&d)[32], uint32_t a0, uint32_t a1, uint32_t a2, uint32_t a3, uint32_t blo, uint32_t bhi, int scale_d) {
    asm volatile("{\n.reg .pred p;\n.reg .b64 db;\nsetp.ne.b32 p, %38, 0;\nmov.b64 db, {%36, %37};\n"
        "wgmma.mma_async.sync.aligned.m64n64k16.f32.bf16.bf16 {%0, %1, %2, %3, %4, %5, %6, %7, %8, %9, %10, %11, %12, %13, %14, %15, %16, %17, %18, %19, %20, %21, %22, %23, %24, %25, %26, %27, %28, %29, %30, %31}, {%32, %33, %34, %35}, db, p, 1, 1, 0;\n}\n"
        : "+f"(d[0]), "+f"(d[1]), "+f"(d[2]), "+f"(d[3]), "+f"(d[4]), "+f"(d[5]), "+f"(d[6]), "+f"(d[7]), "+f"(d[8]), "+f"(d[9]), "+f"(d[10]), "+f"(d[11]), "+f"(d[12]), "+f"(d[13]), "+f"(d[14]), "+f"(d[15]), "+f"(d[16]), "+f"(d[17]), "+f"(d[18]), "+f"(d[19]), "+f"(d[20]), "+f"(d[21]), "+f"(d[22]), "+f"(d[23]), "+f"(d[24]), "+f"(d[25]), "+f"(d[26]), "+f"(d[27]), "+f"(d[28]), "+f"(d[29]), "+f"(d[30]), "+f"(d[31])
        : "r"(a0), "r"(a1), "r"(a2), "r"(a3), "r"(blo), "r"(bhi), "r"(scale_d));
}

__device__ __forceinline__ void wgmma_rs_n32_tb1(float (&d)[16], uint32_t a0, uint32_t a1, uint32_t a2, uint32_t a3, uint32_t blo, uint32_t bhi, int scale_d) {
    asm volatile("{\n.reg .pred p;\n.reg .b64 db;\nsetp.ne.b32 p, %22, 0;\nmov.b64 db, {%20, %21};\n"
        "wgmma.mma_async.sync.aligned.m64n32k16.f32.bf16.bf16 {%0, %1, %2, %3, %4, %5, %6, %7, %8, %9, %10, %11, %12, %13, %14, %15}, {%16, %17, %18, %19}, db, p, 1, 1, 1;\n}\n"
        : "+f"(d[0]), "+f"(d[1]), "+f"(d[2]), "+f"(d[3]), "+f"(d[4]), "+f"(d[5]), "+f"(d[6]), "+f"(d[7]), "+f"(d[8]), "+f"(d[9]), "+f"(d[10]), "+f"(d[11]), "+f"(d[12]), "+f"(d[13]), "+f"(d[14]), "+f"(d[15])
        : "r"(a0), "r"(a1), "r"(a2), "r"(a3), "r"(blo), "r"(bhi), "r"(scale_d));
}

__device__ __forceinline__ void wgmma_rs_n40_tb1(float (&d)[20], uint32_t a0, uint32_t a1, uint32_t a2, uint32_t a3, uint32_t blo, uint32_t bhi, int scale_d) {
    asm volatile("{\n.reg .pred p;\n.reg .b64 db;\nsetp.ne.b32 p, %26, 0;\nmov.b64 db, {%24, %25};\n"
        "wgmma.mma_async.sync.aligned.m64n40k16.f32.bf16.bf16 {%0, %1, %2, %3, %4, %5, %6, %7, %8, %9, %10, %11, %12, %13, %14, %15, %16, %17, %18, %19}, {%20, %21, %22, %23}, db, p, 1, 1, 1;\n}\n"
        : "+f"(d[0]), "+f"(d[1]), "+f"(d[2]), "+f"(d[3]), "+f"(d[4]), "+f"(d[5]), "+f"(d[6]), "+f"(d[7]), "+f"(d[8]), "+f"(d[9]), "+f"(d[10]), "+f"(d[11]), "+f"(d[12]), "+f"(d[13]), "+f"(d[14]), "+f"(d[15]), "+f"(d[16]), "+f"(d[17]), "+f"(d[18]), "+f"(d[19])
        : "r"(a0), "r"(a1), "r"(a2), "r"(a3), "r"(blo), "r"(bhi), "r"(scale_d));
}

template <int BN>
__device__ __forceinline__ void wgmma_tile(float (&d)[BN / 2], uint32_t da, uint32_t db, int sd) {
    constexpr uint32_t HI = desc_hi(1024, 1);
    if constexpr (BN == 128) wgmma_ss_n128_tb1(d, da, HI, db, HI, sd);
    else if constexpr (BN == 192) wgmma_ss_n192_tb1(d, da, HI, db, HI, sd);
    else if constexpr (BN == 224) wgmma_ss_n224_tb1(d, da, HI, db, HI, sd);
    else wgmma_ss_n256_tb1(d, da, HI, db, HI, sd);
}

__global__ void __launch_bounds__(256) prep_kernel(const bf16* __restrict__ x, const bf16* __restrict__ gate_w,
                                                   const bf16* __restrict__ w1, const bf16* __restrict__ w3) {
    const int tid = threadIdx.x;
    TL_START(0)
    pdl_launch();
    if (blockIdx.x < 256) {
        const int row = blockIdx.x * 8 + (tid >> 5);
        const int lane = tid & 31;
        const uint4* xr = reinterpret_cast<const uint4*>(x + (size_t)row * DM);
        const uint4* gw = reinterpret_cast<const uint4*>(gate_w);
        float v[32];
        float gsum = 0.f, sum = 0.f;
#pragma unroll
        for (int i = 0; i < 4; i++) {
            uint4 a = xr[lane + 32 * i];
            uint4 b = gw[lane + 32 * i];
            const uint32_t aa[4] = {a.x, a.y, a.z, a.w};
            const uint32_t bb[4] = {b.x, b.y, b.z, b.w};
#pragma unroll
            for (int j = 0; j < 4; j++) {
                float x0 = __uint_as_float(aa[j] << 16), x1 = __uint_as_float(aa[j] & 0xFFFF0000u);
                float g0 = __uint_as_float(bb[j] << 16), g1 = __uint_as_float(bb[j] & 0xFFFF0000u);
                v[i * 8 + j * 2] = x0;
                v[i * 8 + j * 2 + 1] = x1;
                sum += x0 + x1;
                gsum += bf16_round(x0 * g0) + bf16_round(x1 * g1);
            }
        }
#pragma unroll
        for (int o = 16; o > 0; o >>= 1) {
            sum += __shfl_xor_sync(0xffffffffu, sum, o);
            gsum += __shfl_xor_sync(0xffffffffu, gsum, o);
        }
        const float mean = sum * (1.0f / DM);
        float m2 = 0.f;
#pragma unroll
        for (int i = 0; i < 32; i++) {
            float d = v[i] - mean;
            m2 += d * d;
        }
#pragma unroll
        for (int o = 16; o > 0; o >>= 1) m2 += __shfl_xor_sync(0xffffffffu, m2, o);
        if (lane == 0) {
            g_mean1[row] = mean;
            g_rstd1[row] = rsqrtf(m2 * (1.0f / DM) + 1e-5f);
            float logit = bf16_round(gsum);
            float g = bf16_round(1.0f / (1.0f + __expf(-logit)));
            g_gate[row] = g;
            g_omg[row] = bf16_round(1.0f - g);
        }
    } else {
        __shared__ float red[32][65];
        const int strip = blockIdx.x - 256;
        const bf16* w;
        float* out;
        int ld, col0;
        if (strip < 16) { w = w1; ld = DM; col0 = strip * 64; out = g_cs1; }
        else { w = w3; ld = FF; col0 = (strip - 16) * 64; out = g_cs3; }
        const int cg = tid & 7;
        const int rg = tid >> 3;
        float acc[8];
#pragma unroll
        for (int j = 0; j < 8; j++) acc[j] = 0.f;
#pragma unroll 8
        for (int r = 0; r < 32; r++) {
            uint4 a = *reinterpret_cast<const uint4*>(w + (size_t)(r * 32 + rg) * ld + col0 + cg * 8);
            const uint32_t aa[4] = {a.x, a.y, a.z, a.w};
#pragma unroll
            for (int j = 0; j < 4; j++) {
                acc[2 * j] += __uint_as_float(aa[j] << 16);
                acc[2 * j + 1] += __uint_as_float(aa[j] & 0xFFFF0000u);
            }
        }
#pragma unroll
        for (int j = 0; j < 8; j++) red[rg][cg * 8 + j] = acc[j];
        __syncthreads();
        if (tid < 64) {
            float s = 0.f;
#pragma unroll
            for (int r = 0; r < 32; r++) s += red[r][tid];
            out[col0 + tid] = s;
        }
    }
    TL_END(0)
}

#define RELEASE_STAGE(b) if (tid_wg < 2) mbar_arrive_cluster(b, tid_wg)
template <int BN, int STAGES>
struct GemmSmem {
    static constexpr int A_BYTES = 128 * 64 * 2;
    static constexpr int B_BOXES = (BN + 63) / 64;
    static constexpr int B_BYTES = B_BOXES * 64 * 64 * 2;
    static constexpr int STAGE_BYTES = A_BYTES + B_BYTES;
    static constexpr int STG_OFF = STAGES * STAGE_BYTES;
    static constexpr int BAR_OFF = STAGES * STAGE_BYTES + 2 * 16384;
    static constexpr int TOTAL = BAR_OFF + 256 + 1024;
};

template <int MODE, int BN, int STAGES>
__global__ void __launch_bounds__(384, 1)
gemm_kernel(const __grid_constant__ CUtensorMap mA, const __grid_constant__ CUtensorMap mB0,
            const __grid_constant__ CUtensorMap mB1, const __grid_constant__ CUtensorMap mC0,
            const __grid_constant__ CUtensorMap mC1, const bf16* __restrict__ xin, int n_tiles_n, int kblocks) {
    using L = GemmSmem<BN, STAGES>;
    extern __shared__ uint8_t smem_raw[];
    const uint32_t sbase = (smem_u32(smem_raw) + 1023u) & ~1023u;
    const uint32_t bar_full = sbase + L::BAR_OFF;
    const uint32_t bar_empty = bar_full + 8 * STAGES;
    const int wg = threadIdx.x >> 7;
    const int npairs = 8 * n_tiles_n;
    const uint32_t crank = cluster_rank();
    const int cid = blockIdx.x >> 1, ncl = gridDim.x >> 1;
    TL_START(MODE)
    pdl_launch();

    if (threadIdx.x == 0) {
        for (int s = 0; s < STAGES; s++) {
            mbar_init(bar_full + 8 * s, 1);
            mbar_init(bar_empty + 8 * s, 4);
        }
        asm volatile("fence.mbarrier_init.release.cluster;" ::: "memory");
        prefetch_tmap(&mA);
        prefetch_tmap(&mB0);
        if (MODE == 1 || MODE == 5) prefetch_tmap(&mB1);
        prefetch_tmap(&mC0);
    }
    cluster_sync_all();

    if (wg == 0) {
        reg_dealloc<40>();
        if (threadIdx.x == 0) {
            if (MODE != 1) pdl_wait();
            int stage = 0;
            uint32_t phase = 1;
            for (int pr = cid; pr < npairs; pr += ncl) {
                const int m0 = ((pr & 7) * 2 + crank) * 128;
                const int n0 = (pr >> 3) * BN;
                for (int kb = 0; kb < kblocks; kb++) {
                    mbar_wait(bar_empty + 8 * stage, phase);
                    const uint32_t sa = sbase + stage * L::STAGE_BYTES;
                    const uint32_t sb = sa + L::A_BYTES;
                    const uint32_t fb = bar_full + 8 * stage;
                    mbar_expect_tx(fb, L::STAGE_BYTES);
                    int arow = m0;
                    if (MODE == 2) {
                        const int grp = kb >> 2;
                        arow += (grp == 0) ? -1 : (grp == 1) ? 1 : (grp == 2) ? -2 : 2;
                    }
                    tma_load_2d(sa, &mA, kb * 64, arow, fb);
                    const CUtensorMap* mb = &mB0;
                    int bc = n0, br = kb * 64;
                    if (MODE == 1 && n0 >= 3 * DM) { mb = &mB1; bc = n0 - 3 * DM; }
                    if (MODE == 5 && kb >= 16) { mb = &mB1; br = (kb - 16) * 64; }
#pragma unroll
                    for (int b = 0; b < L::B_BOXES / 2; b++) {
                        const int bb = crank * (L::B_BOXES / 2) + b;
                        tma_load_2d_mc(sb + bb * 8192, mb, bc + bb * 64, br, fb, (uint16_t)3);
                    }
                    if (++stage == STAGES) { stage = 0; phase ^= 1; }
                }
            }
        }
    } else {
        reg_alloc<232>();
        const int c = wg - 1;
        const int warp = (threadIdx.x >> 5) & 3;
        const int lane = threadIdx.x & 31;
        const int tid_wg = threadIdx.x & 127;
        const uint32_t stg = sbase + L::STG_OFF + c * 16384;
        int stage = 0;
        uint32_t phase = 0;
        float acc[BN / 2];
        bool first = true;
        for (int pr = cid; pr < npairs; pr += ncl) {
            const int m0 = ((pr & 7) * 2 + crank) * 128;
            const int n0 = (pr >> 3) * BN;
            int prev_stage = 0;
            for (int kb = 0; kb < kblocks; kb++) {
                mbar_wait(bar_full + 8 * stage, phase);
                const uint32_t sa = sbase + stage * L::STAGE_BYTES + c * 8192;
                const uint32_t sb = sbase + stage * L::STAGE_BYTES + L::A_BYTES;
                const uint32_t da = desc_lo(sa, 16);
                const uint32_t db = desc_lo(sb, 8192);
                wgmma_fence();
#pragma unroll
                for (int k = 0; k < 4; k++) wgmma_tile<BN>(acc, da + k * 2, db + k * 128, (kb | k) != 0);
                wgmma_commit();
                if (kb > 0) {
                    wgmma_wait<1>();
                    RELEASE_STAGE(bar_empty + 8 * prev_stage);
                }
                prev_stage = stage;
                if (++stage == STAGES) { stage = 0; phase ^= 1; }
            }
            wgmma_wait<0>();
            RELEASE_STAGE(bar_empty + 8 * prev_stage);
            if (first) { pdl_wait(); first = false; }

            const int r0 = m0 + c * 64 + warp * 16 + (lane >> 2);
            const int r1 = r0 + 8;
            const int cq = (lane & 3) * 2;
            const CUtensorMap* mc = &mC0;
            int out_c0 = n0;
            if (MODE == 1) {
                if (n0 < DM) {
                    const float qs = 0.17677669529663687f * 1.4426950408889634f;
#pragma unroll
                    for (int j = 0; j < BN / 2; j++) acc[j] *= qs;
                } else if (n0 >= 3 * DM) {
                    mc = &mC1;
                    out_c0 = n0 - 3 * DM;
                    const float mu0 = g_mean1[r0], mu1 = g_mean1[r1];
                    const float rs0 = g_rstd1[r0], rs1 = g_rstd1[r1];
#pragma unroll
                    for (int j = 0; j < BN / 8; j++) {
                        const float2 cs = *reinterpret_cast<const float2*>(&g_cs1[out_c0 + 8 * j + cq]);
                        acc[4 * j + 0] = gelu_tanh(rs0 * fmaf(-mu0, cs.x, acc[4 * j + 0]));
                        acc[4 * j + 1] = gelu_tanh(rs0 * fmaf(-mu0, cs.y, acc[4 * j + 1]));
                        acc[4 * j + 2] = gelu_tanh(rs1 * fmaf(-mu1, cs.x, acc[4 * j + 2]));
                        acc[4 * j + 3] = gelu_tanh(rs1 * fmaf(-mu1, cs.y, acc[4 * j + 3]));
                    }
                }
            } else if (MODE == 2) {
                float s0 = 0.f, s1 = 0.f;
#pragma unroll
                for (int j = 0; j < BN / 8; j++) {
                    const uint32_t xa = *reinterpret_cast<const uint32_t*>(xin + (size_t)r0 * DM + n0 + 8 * j + cq);
                    const uint32_t xb = *reinterpret_cast<const uint32_t*>(xin + (size_t)r1 * DM + n0 + 8 * j + cq);
                    acc[4 * j + 0] = bf16_round(bf16_round(acc[4 * j + 0]) + __uint_as_float(xa << 16));
                    acc[4 * j + 1] = bf16_round(bf16_round(acc[4 * j + 1]) + __uint_as_float(xa & 0xFFFF0000u));
                    acc[4 * j + 2] = bf16_round(bf16_round(acc[4 * j + 2]) + __uint_as_float(xb << 16));
                    acc[4 * j + 3] = bf16_round(bf16_round(acc[4 * j + 3]) + __uint_as_float(xb & 0xFFFF0000u));
                    s0 += acc[4 * j + 0] + acc[4 * j + 1];
                    s1 += acc[4 * j + 2] + acc[4 * j + 3];
                }
                s0 += __shfl_xor_sync(0xffffffffu, s0, 1);
                s0 += __shfl_xor_sync(0xffffffffu, s0, 2);
                s1 += __shfl_xor_sync(0xffffffffu, s1, 1);
                s1 += __shfl_xor_sync(0xffffffffu, s1, 2);
                const float mu0 = s0 * (1.0f / BN), mu1 = s1 * (1.0f / BN);
                float q0 = 0.f, q1 = 0.f;
#pragma unroll
                for (int j = 0; j < BN / 8; j++) {
                    float d;
                    d = acc[4 * j + 0] - mu0; q0 += d * d;
                    d = acc[4 * j + 1] - mu0; q0 += d * d;
                    d = acc[4 * j + 2] - mu1; q1 += d * d;
                    d = acc[4 * j + 3] - mu1; q1 += d * d;
                }
                q0 += __shfl_xor_sync(0xffffffffu, q0, 1);
                q0 += __shfl_xor_sync(0xffffffffu, q0, 2);
                q1 += __shfl_xor_sync(0xffffffffu, q1, 1);
                q1 += __shfl_xor_sync(0xffffffffu, q1, 2);
                if ((lane & 3) == 0) {
                    static_assert(MODE != 2 || BN == 128, "stats layout assumes BN=128");
                    g_stat2[r0 * 8 + (n0 >> 7)] = make_float2(s0, q0);
                    g_stat2[r1 * 8 + (n0 >> 7)] = make_float2(s1, q1);
                }
            } else if (MODE == 3) {
                out_c0 = n0 + DM;
                float mu[2], rs[2];
#pragma unroll
                for (int h = 0; h < 2; h++) {
                    const float4* sp = reinterpret_cast<const float4*>(&g_stat2[(h ? r1 : r0) * 8]);
                    float4 p[4];
                    float s = 0.f;
#pragma unroll
                    for (int i = 0; i < 4; i++) { p[i] = sp[i]; s += p[i].x + p[i].z; }
                    const float mean = s * (1.0f / DM);
                    float m2 = 0.f;
#pragma unroll
                    for (int i = 0; i < 4; i++) {
                        float d0 = p[i].x * (1.0f / 128) - mean, d1 = p[i].z * (1.0f / 128) - mean;
                        m2 += p[i].y + p[i].w + 128.0f * (d0 * d0 + d1 * d1);
                    }
                    mu[h] = mean;
                    rs[h] = rsqrtf(m2 * (1.0f / DM) + 1e-5f);
                }
                const float og0 = g_omg[r0], og1 = g_omg[r1];
#pragma unroll
                for (int j = 0; j < BN / 8; j++) {
                    const float2 cs = *reinterpret_cast<const float2*>(&g_cs3[n0 + 8 * j + cq]);
                    acc[4 * j + 0] = og0 * gelu_tanh(rs[0] * fmaf(-mu[0], cs.x, acc[4 * j + 0]));
                    acc[4 * j + 1] = og0 * gelu_tanh(rs[0] * fmaf(-mu[0], cs.y, acc[4 * j + 1]));
                    acc[4 * j + 2] = og1 * gelu_tanh(rs[1] * fmaf(-mu[1], cs.x, acc[4 * j + 2]));
                    acc[4 * j + 3] = og1 * gelu_tanh(rs[1] * fmaf(-mu[1], cs.y, acc[4 * j + 3]));
                }
            } else {
                const float og0 = g_omg[r0], og1 = g_omg[r1];
#pragma unroll
                for (int j = 0; j < BN / 8; j++) {
                    const uint32_t xa = *reinterpret_cast<const uint32_t*>(xin + (size_t)r0 * DM + n0 + 8 * j + cq);
                    const uint32_t xb = *reinterpret_cast<const uint32_t*>(xin + (size_t)r1 * DM + n0 + 8 * j + cq);
                    acc[4 * j + 0] = fmaf(og0, __uint_as_float(xa << 16), acc[4 * j + 0]);
                    acc[4 * j + 1] = fmaf(og0, __uint_as_float(xa & 0xFFFF0000u), acc[4 * j + 1]);
                    acc[4 * j + 2] = fmaf(og1, __uint_as_float(xb << 16), acc[4 * j + 2]);
                    acc[4 * j + 3] = fmaf(og1, __uint_as_float(xb & 0xFFFF0000u), acc[4 * j + 3]);
                }
            }
            const int srow = warp * 16 + (lane & 7) + ((lane >> 3) & 1) * 8;
#pragma unroll
            for (int rnd = 0; rnd < (BN + 127) / 128; rnd++) {
                if (tid_wg == 0) bulk_wait_read0();
                named_bar_sync(1 + c, 128);
#pragma unroll
                for (int jj = 0; jj < 8; jj++) {
                    const int j = rnd * 16 + jj * 2;
                    if (j * 8 < BN) {
                        const int jb = jj * 2 + (lane >> 4);
                        uint32_t addr = stg + (jb >> 3) * 8192 + srow * 128 + (((jb & 7) ^ (srow & 7)) << 4);
                        if (rnd * 128 + 128 > BN && jj >= 4)
                            addr = stg + 8192 + srow * 64 + (((jb & 3) ^ ((srow >> 1) & 3)) << 4);
                        stmatrix_x4(addr, pack_bf16(acc[4 * j + 0], acc[4 * j + 1]), pack_bf16(acc[4 * j + 2], acc[4 * j + 3]),
                                    pack_bf16(acc[4 * j + 4], acc[4 * j + 5]), pack_bf16(acc[4 * j + 6], acc[4 * j + 7]));
                    }
                }
                fence_proxy_async();
                named_bar_sync(1 + c, 128);
                if (tid_wg == 0) {
                    tma_store_2d(mc, stg, out_c0 + rnd * 128, m0 + c * 64);
                    if (rnd * 128 + 64 < BN)
                        tma_store_2d((rnd * 128 + 128 > BN) ? &mC1 : mc, stg + 8192, out_c0 + rnd * 128 + 64, m0 + c * 64);
                    bulk_commit();
                }
            }
        }
        if (tid_wg == 0) bulk_wait0();
        TL_END(MODE)
    }
    cluster_sync_all();
}

#define ATT_SPLIT 16
constexpr int ATT_NTILES = NH * 16;
#define ATT_GRID_N 512
constexpr int ATT_GRID = ATT_GRID_N;
constexpr int ATT_THREADS = 256;
constexpr int ATT_STAGES = 4;
constexpr int ATT_DIST = 2;
constexpr int ATT_Q_OFF = ATT_STAGES * 16384;
constexpr int ATT_ONES_OFF = ATT_Q_OFF + 8192;
constexpr int ATT_KEXT_OFF = ATT_ONES_OFF + 4096;
constexpr int ATT_QEXT_OFF = ATT_KEXT_OFF + 4096;
constexpr int ATT_BAR_OFF = ATT_QEXT_OFF + 8192;
constexpr int ATT_SMEM = ATT_BAR_OFF + 256 + 1024;

__device__ __forceinline__ void row_max(const float (&s)[32], float& m0, float& m1) {
    float a0[8], a1[8];
#pragma unroll
    for (int i = 0; i < 8; i++) {
        a0[i] = fmaxf(s[4 * i], s[4 * i + 1]);
        a1[i] = fmaxf(s[4 * i + 2], s[4 * i + 3]);
    }
#pragma unroll
    for (int w = 4; w > 0; w >>= 1)
#pragma unroll
        for (int i = 0; i < w; i++) { a0[i] = fmaxf(a0[i], a0[i + w]); a1[i] = fmaxf(a1[i], a1[i + w]); }
    float mx0 = a0[0], mx1 = a1[0];
    mx0 = fmaxf(mx0, __shfl_xor_sync(0xffffffffu, mx0, 1));
    mx1 = fmaxf(mx1, __shfl_xor_sync(0xffffffffu, mx1, 1));
    mx0 = fmaxf(mx0, __shfl_xor_sync(0xffffffffu, mx0, 2));
    mx1 = fmaxf(mx1, __shfl_xor_sync(0xffffffffu, mx1, 2));
    m0 = fmaxf(m0, mx0);
    m1 = fmaxf(m1, mx1);
}

__device__ __forceinline__ void attn_step(float (&s)[32], float (&o)[20], uint32_t dq, uint32_t dke, uint32_t dk_next,
                                          uint32_t dv_cur, uint32_t release_bar) {
    constexpr uint32_t HI = desc_hi(512, 2);
    uint32_t p[16];
#pragma unroll
    for (int i = 0; i < 16; i++) p[i] = pack_bf16(ex2(s[2 * i]), ex2(s[2 * i + 1]));
    wgmma_fence();
    wgmma_ss_n64_tb0(s, dq, HI, dk_next, HI, 0);
    wgmma_ss_n64_tb0(s, dq + 2, HI, dk_next + 2, HI, 1);
    wgmma_ss_n64_tb0(s, dq + ((ATT_QEXT_OFF - ATT_Q_OFF) >> 4), HI, dke, HI, 1);
#pragma unroll
    for (int t = 0; t < 4; t++)
        wgmma_rs_n40_tb1(o, p[4 * t], p[4 * t + 1], p[4 * t + 2], p[4 * t + 3], dv_cur + t * 64, HI, 1);
    wgmma_commit();
    wgmma_wait<0>();
    if (release_bar != 0 && (threadIdx.x & 127) == 0) mbar_arrive(release_bar);
}

__global__ void __launch_bounds__(256, 1)
attn_exact_kernel(const __grid_constant__ CUtensorMap mKV) {
    extern __shared__ uint8_t smem_raw[];
    pdl_launch();
    pdl_wait();
    const int tile = blockIdx.x;
    if (g_bad[tile] == 0) return;
    constexpr int NBLK = S_LEN / 128;
    constexpr uint32_t HI = desc_hi(512, 2);
    const uint32_t sbase = (smem_u32(smem_raw) + 1023u) & ~1023u;
    const uint32_t bar = sbase + ATT_BAR_OFF;
    const int warp_id = threadIdx.x >> 5;
    const int lane = threadIdx.x & 31;
    const int cq = (lane & 3) * 2;
    const uint32_t dk0 = desc_lo(sbase, 16);
    const uint32_t dv0 = desc_lo(sbase + 8192, ATT_ONES_OFF - 8192);
    if (threadIdx.x == 0) {
        mbar_init(bar, 1);
        asm volatile("fence.mbarrier_init.release.cluster;" ::: "memory");
    }
    asm volatile("st.shared.v4.b32 [%0], {%1, %1, %1, %1};" ::"r"(sbase + ATT_ONES_OFF + threadIdx.x * 16), "r"(0x3F803F80u) : "memory");
    fence_proxy_async();
    __syncthreads();
    const int head = tile >> 4;
    const int row0 = (tile & 15) * 128 + warp_id * 16 + (lane >> 2);
    const uint32_t dq = desc_lo(sbase + ATT_Q_OFF + (threadIdx.x >> 7) * 4096, 16);
    float o[20];
#pragma unroll
    for (int i = 0; i < 20; i++) o[i] = 0.f;
    float m0 = -INFINITY, m1 = -INFINITY;
#pragma unroll 1
    for (int j = 0; j < NBLK; j++) {
        if (threadIdx.x == 0) {
            mbar_expect_tx(bar, j == 0 ? 3 * 8192 : 2 * 8192);
            if (j == 0) tma_load_2d(sbase + ATT_Q_OFF, &mKV, head * DH, (tile & 15) * 128, bar);
            tma_load_2d(sbase, &mKV, DM + head * DH, j * 128, bar);
            tma_load_2d(sbase + 8192, &mKV, 2 * DM + head * DH, j * 128, bar);
        }
        __syncwarp();
        mbar_wait(bar, j & 1);
#pragma unroll 1
        for (int hf = 0; hf < 2; hf++) {
            float s[32];
            wgmma_fence();
            wgmma_ss_n64_tb0(s, dq, HI, dk0 + hf * 256, HI, 0);
            wgmma_ss_n64_tb0(s, dq + 2, HI, dk0 + hf * 256 + 2, HI, 1);
            wgmma_commit();
            wgmma_wait<0>();
            const float mo0 = m0, mo1 = m1;
            row_max(s, m0, m1);
            const float a0 = ex2(mo0 - m0), a1 = ex2(mo1 - m1);
            uint32_t p[16];
#pragma unroll
            for (int i = 0; i < 8; i++) {
                p[2 * i] = pack_bf16(ex2(s[4 * i + 0] - m0), ex2(s[4 * i + 1] - m0));
                p[2 * i + 1] = pack_bf16(ex2(s[4 * i + 2] - m1), ex2(s[4 * i + 3] - m1));
            }
#pragma unroll
            for (int i = 0; i < 5; i++) {
                o[4 * i + 0] *= a0; o[4 * i + 1] *= a0;
                o[4 * i + 2] *= a1; o[4 * i + 3] *= a1;
            }
            wgmma_fence();
            const uint32_t dv = dv0 + hf * 256 - ((uint32_t)(hf * 256) << 16);
#pragma unroll
            for (int t = 0; t < 4; t++)
                wgmma_rs_n40_tb1(o, p[4 * t], p[4 * t + 1], p[4 * t + 2], p[4 * t + 3], dv + t * 64, HI, 1);
            wgmma_commit();
            wgmma_wait<0>();
        }
        __syncthreads();
    }
    const float f0 = g_gate[row0] / o[16], f1 = g_gate[row0 + 8] / o[18];
    bf16* op0 = g_a5 + (size_t)row0 * A5W + head * DH + cq;
    bf16* op1 = op0 + 8 * A5W;
#pragma unroll
    for (int i = 0; i < 4; i++) {
        *reinterpret_cast<uint32_t*>(op0 + 8 * i) = pack_bf16(o[4 * i] * f0, o[4 * i + 1] * f0);
        *reinterpret_cast<uint32_t*>(op1 + 8 * i) = pack_bf16(o[4 * i + 2] * f1, o[4 * i + 3] * f1);
    }
}

#define ATT_MINB 2
__global__ void __launch_bounds__(256, ATT_MINB)
attn_kernel(const __grid_constant__ CUtensorMap mKV) {
    extern __shared__ uint8_t smem_raw[];
    const uint32_t sbase = (smem_u32(smem_raw) + 1023u) & ~1023u;
    const uint32_t bar_kfull = sbase + ATT_BAR_OFF;
    const uint32_t bar_vfull = bar_kfull + 8 * ATT_STAGES;
    const uint32_t bar_empty = bar_vfull + 8 * ATT_STAGES;
    const int tile = blockIdx.x;
    const int head = tile >> 4;
    const int lane = threadIdx.x & 31;
    constexpr int NBLK = S_LEN / 128;
    TL_START(6)
    pdl_launch();

    auto issue_kv = [&](int g) {
        const int sn = g % ATT_STAGES;
        if (g >= ATT_STAGES) mbar_wait(bar_empty + 8 * sn, ((g / ATT_STAGES) - 1) & 1);
        const uint32_t skn = sbase + sn * 16384;
        mbar_expect_tx(bar_kfull + 8 * sn, g == 0 ? 16384 : 8192);
        if (g == 0) tma_load_2d(sbase + ATT_Q_OFF, &mKV, head * DH, (tile & 15) * 128, bar_kfull);
        tma_load_2d(skn, &mKV, DM + head * DH, g * 128, bar_kfull + 8 * sn);
        mbar_expect_tx(bar_vfull + 8 * sn, 8192);
        tma_load_2d(skn + 8192, &mKV, 2 * DM + head * DH, g * 128, bar_vfull + 8 * sn);
    };

    if (threadIdx.x == 0) {
        for (int s = 0; s < ATT_STAGES; s++) {
            mbar_init(bar_kfull + 8 * s, 1);
            mbar_init(bar_vfull + 8 * s, 1);
            mbar_init(bar_empty + 8 * s, 2);
        }
        asm volatile("fence.mbarrier_init.release.cluster;" ::: "memory");
        prefetch_tmap(&mKV);
        pdl_wait();
#pragma unroll
        for (int j = 0; j < ATT_DIST; j++) issue_kv(j);
    }
    {
        asm volatile("st.shared.v4.b32 [%0], {%1, %1, %1, %1};" ::"r"(sbase + ATT_ONES_OFF + threadIdx.x * 16), "r"(0x3F803F80u) : "memory");
        const int r = threadIdx.x >> 2, ch = threadIdx.x & 3;
        const uint32_t w0 = (ch == ((r >> 1) & 3)) ? 0x00003F80u : 0u;
        asm volatile("st.shared.v4.b32 [%0], {%1, %2, %2, %2};" ::"r"(sbase + ATT_KEXT_OFF + threadIdx.x * 16), "r"(w0), "r"(0u) : "memory");
        asm volatile("st.shared.v4.b32 [%0], {%1, %1, %1, %1};" ::"r"(sbase + ATT_QEXT_OFF + threadIdx.x * 16), "r"(0u) : "memory");
        asm volatile("st.shared.v4.b32 [%0], {%1, %1, %1, %1};" ::"r"(sbase + ATT_QEXT_OFF + 4096 + threadIdx.x * 16), "r"(0u) : "memory");
    }
    fence_proxy_async();
    __syncthreads();

    constexpr uint32_t HI = desc_hi(512, 2);
    const uint32_t dk0 = desc_lo(sbase, 16);
    const uint32_t dv0 = desc_lo(sbase + 8192, ATT_ONES_OFF - 8192);
    const uint32_t dke = dk0 + (ATT_KEXT_OFF >> 4);
    const uint32_t dq = dk0 + ((ATT_Q_OFF + (threadIdx.x >> 7) * 4096) >> 4);
    float o[20];
#pragma unroll
    for (int i = 0; i < 20; i++) o[i] = 0.f;
    float s0[32];
    mbar_wait(bar_kfull, 0);
    wgmma_fence();
    wgmma_ss_n64_tb0(s0, dq, HI, dk0, HI, 0);
    wgmma_ss_n64_tb0(s0, dq + 2, HI, dk0 + 2, HI, 1);
    wgmma_commit();
    wgmma_wait<0>();
    float m0 = -INFINITY, m1 = -INFINITY;
    row_max(s0, m0, m1);
    if ((lane & 3) == 0) {
        const int r = ((threadIdx.x >> 5) & 3) * 16 + (lane >> 2);
        const uint32_t qe = sbase + ATT_QEXT_OFF + (threadIdx.x >> 7) * 4096;
        asm volatile("st.shared.b16 [%0], %1;" ::"r"(qe + r * 64 + (((r >> 1) & 3) << 4)), "h"((uint16_t)(pack_bf16(-m0, 0.f) & 0xFFFFu)) : "memory");
        asm volatile("st.shared.b16 [%0], %1;" ::"r"(qe + (r + 8) * 64 + ((((r + 8) >> 1) & 3) << 4)), "h"((uint16_t)(pack_bf16(-m1, 0.f) & 0xFFFFu)) : "memory");
    }
    fence_proxy_async();
    named_bar_sync(1 + (threadIdx.x >> 7), 128);
    wgmma_fence();
    wgmma_ss_n64_tb0(s0, dq + ((ATT_QEXT_OFF - ATT_Q_OFF) >> 4), HI, dke, HI, 1);
    wgmma_commit();
    wgmma_wait<0>();
#pragma unroll 1
    for (int j = 0; j < NBLK; j++) {
        if (threadIdx.x == 0 && j + ATT_DIST < NBLK) issue_kv(j + ATT_DIST);
        __syncwarp();
        const uint32_t stage = j & (ATT_STAGES - 1), nstage = (j + 1) & (ATT_STAGES - 1);
        const uint32_t dk = dk0 + stage * 1024;
        const uint32_t dv = dv0 + stage * 1024 - (stage << 26);
        mbar_wait(bar_vfull + 8 * stage, (j / ATT_STAGES) & 1);
        attn_step(s0, o, dq, dke, dk + 256, dv, 0u);
        uint32_t dkn = dk;
        if (j + 1 < NBLK) {
            mbar_wait(bar_kfull + 8 * nstage, ((j + 1) / ATT_STAGES) & 1);
            dkn = dk0 + nstage * 1024;
        }
        attn_step(s0, o, dq, dke, dkn, dv + 256 - (256u << 16), bar_empty + 8 * stage);
    }
    bool ok = (o[16] <= 1.8446744e19f) && (o[18] <= 1.8446744e19f);
#pragma unroll
    for (int i = 0; i < 16; i++) ok = ok && (fabsf(o[i]) <= 3.0e38f);
    const int row0 = (tile & 15) * 128 + (threadIdx.x >> 5) * 16 + (lane >> 2);
    const float f0 = g_gate[row0] / o[16], f1 = g_gate[row0 + 8] / o[18];
    bf16* op0 = g_a5 + (size_t)row0 * A5W + head * DH + (lane & 3) * 2;
    bf16* op1 = op0 + 8 * A5W;
#pragma unroll
    for (int i = 0; i < 4; i++) {
        *reinterpret_cast<uint32_t*>(op0 + 8 * i) = pack_bf16(o[4 * i] * f0, o[4 * i + 1] * f0);
        *reinterpret_cast<uint32_t*>(op1 + 8 * i) = pack_bf16(o[4 * i + 2] * f1, o[4 * i + 3] * f1);
    }
    const int bad = __syncthreads_or(!ok);
    if (threadIdx.x == 0) g_bad[tile] = bad;
    TL_END(6)
}

typedef CUresult (*EncodeFn)(CUtensorMap*, CUtensorMapDataType, cuuint32_t, void*, const cuuint64_t*, const cuuint64_t*,
                             const cuuint32_t*, const cuuint32_t*, CUtensorMapInterleave, CUtensorMapSwizzle,
                             CUtensorMapL2promotion, CUtensorMapFloatOOBfill);

static CUtensorMap make_map(EncodeFn fn, const void* ptr, int rows, int cols, int box_cols, int box_rows,
                            CUtensorMapSwizzle swz) {
    CUtensorMap m;
    cuuint64_t dims[2] = {(cuuint64_t)cols, (cuuint64_t)rows};
    cuuint64_t strides[1] = {(cuuint64_t)cols * 2};
    cuuint32_t box[2] = {(cuuint32_t)box_cols, (cuuint32_t)box_rows};
    cuuint32_t es[2] = {1, 1};
    fn(&m, CU_TENSOR_MAP_DATA_TYPE_BFLOAT16, 2, const_cast<void*>(ptr), dims, strides, box, es,
       CU_TENSOR_MAP_INTERLEAVE_NONE, swz, CU_TENSOR_MAP_L2_PROMOTION_L2_256B, CU_TENSOR_MAP_FLOAT_OOB_FILL_NONE);
    return m;
}

template <typename... KArgs, typename... Args>
static void launch_ex(void (*kern)(KArgs...), int grid, int block, int smem, cudaStream_t st, int cluster, Args... args) {
    cudaLaunchConfig_t cfg = {};
    cfg.gridDim = dim3(grid);
    cfg.blockDim = dim3(block);
    cfg.dynamicSmemBytes = smem;
    cfg.stream = st;
    cudaLaunchAttribute at[2];
    at[0].id = cudaLaunchAttributeProgrammaticStreamSerialization;
    at[0].val.programmaticStreamSerializationAllowed = 1;
    at[1].id = cudaLaunchAttributeClusterDimension;
    at[1].val.clusterDim.x = cluster;
    at[1].val.clusterDim.y = 1;
    at[1].val.clusterDim.z = 1;
    cfg.attrs = at;
    cfg.numAttrs = cluster > 1 ? 2 : 1;
    cudaLaunchKernelEx(&cfg, kern, KArgs(args)...);
}

extern "C" void kernel_launch(void* const* d_in, const int* in_sizes, int n_in, void* d_out, int out_size) {
    const bf16* x = (const bf16*)d_in[0];
    const bf16* wqkv = (const bf16*)d_in[1];
    const bf16* wo = (const bf16*)d_in[2];
    const bf16* w1 = (const bf16*)d_in[4];
    const bf16* w2 = (const bf16*)d_in[5];
    const bf16* w3 = (const bf16*)d_in[6];
    const bf16* w4 = (const bf16*)d_in[7];
    const bf16* gate_w = (const bf16*)d_in[8];

    static EncodeFn enc = nullptr;
    static void *p_qkv, *p_h, *p_x1, *p_a5;
    using G1 = GemmSmem<256, 4>;
    using G2 = GemmSmem<128, 5>;
    using G3 = GemmSmem<224, 4>;
    if (!enc) {
        void* fn = nullptr;
        cudaDriverEntryPointQueryResult qres;
        cudaGetDriverEntryPoint("cuTensorMapEncodeTiled", &fn, cudaEnableDefault, &qres);
        enc = (EncodeFn)fn;
        cudaGetSymbolAddress(&p_qkv, g_qkv);
        cudaGetSymbolAddress(&p_h, g_h);
        cudaGetSymbolAddress(&p_x1, g_x1);
        cudaGetSymbolAddress(&p_a5, g_a5);
        cudaFuncSetAttribute(gemm_kernel<1, 256, 4>, cudaFuncAttributeMaxDynamicSharedMemorySize, G1::TOTAL);
        cudaFuncSetAttribute(gemm_kernel<2, 128, 5>, cudaFuncAttributeMaxDynamicSharedMemorySize, G2::TOTAL);
        cudaFuncSetAttribute(gemm_kernel<3, 224, 4>, cudaFuncAttributeMaxDynamicSharedMemorySize, G3::TOTAL);
        cudaFuncSetAttribute(gemm_kernel<5, 128, 5>, cudaFuncAttributeMaxDynamicSharedMemorySize, G2::TOTAL);
        cudaFuncSetAttribute(attn_kernel, cudaFuncAttributeMaxDynamicSharedMemorySize, ATT_SMEM);
        cudaFuncSetAttribute(attn_exact_kernel, cudaFuncAttributeMaxDynamicSharedMemorySize, ATT_SMEM);
    }
    const CUtensorMapSwizzle SW128 = CU_TENSOR_MAP_SWIZZLE_128B, SW64 = CU_TENSOR_MAP_SWIZZLE_64B;
    CUtensorMap mX = make_map(enc, x, S_LEN, DM, 64, 128, SW128);
    CUtensorMap mWqkv = make_map(enc, wqkv, DM, 3 * DM, 64, 64, SW128);
    CUtensorMap mW1 = make_map(enc, w1, DM, DM, 64, 64, SW128);
    CUtensorMap mW2 = make_map(enc, w2, DM, DM, 64, 64, SW128);
    CUtensorMap mW3 = make_map(enc, w3, DM, FF, 64, 64, SW128);
    CUtensorMap mW4 = make_map(enc, w4, FF, DM, 64, 64, SW128);
    CUtensorMap mWo = make_map(enc, wo, DM, DM, 64, 64, SW128);
    CUtensorMap mQKVst = make_map(enc, p_qkv, S_LEN, 3 * DM, 64, 64, SW128);
    CUtensorMap mKV = make_map(enc, p_qkv, S_LEN, 3 * DM, 32, 128, SW64);
    CUtensorMap mHst = make_map(enc, p_h, S_LEN, DM, 64, 64, SW128);
    CUtensorMap mHld = make_map(enc, p_h, S_LEN, DM, 64, 128, SW128);
    CUtensorMap mX1st = make_map(enc, p_x1, S_LEN, DM, 64, 64, SW128);
    CUtensorMap mX1ld = make_map(enc, p_x1, S_LEN, DM, 64, 128, SW128);
    CUtensorMap mA5st = make_map(enc, p_a5, S_LEN, A5W, 64, 64, SW128);
    CUtensorMap mA5st32 = make_map(enc, p_a5, S_LEN, A5W, 32, 64, SW64);
    CUtensorMap mA5ld = make_map(enc, p_a5, S_LEN, A5W, 64, 128, SW128);
    CUtensorMap mOut = make_map(enc, d_out, S_LEN, DM, 64, 64, SW128);

    cudaStream_t st = cudaStreamPerThread;
    prep_kernel<<<256 + 72, 256, 0, st>>>(x, gate_w, w1, w3);
    launch_ex(gemm_kernel<1, 256, 4>, 132, 384, G1::TOTAL, st, 2, mX, mWqkv, mW1, mQKVst, mHst, x, 16, 16);
    launch_ex(attn_kernel, ATT_GRID, ATT_THREADS, ATT_SMEM, st, 1, mKV);
    launch_ex(attn_exact_kernel, ATT_NTILES, ATT_THREADS, ATT_SMEM, st, 1, mKV);
    launch_ex(gemm_kernel<2, 128, 5>, 128, 384, G2::TOTAL, st, 2, mHld, mW2, mW2, mX1st, mX1st, x, 8, 16);
    launch_ex(gemm_kernel<3, 224, 4>, 132, 384, G3::TOTAL, st, 2, mX1ld, mW3, mW3, mA5st, mA5st32, x, 16, 16);
    launch_ex(gemm_kernel<5, 128, 5>, 128, 384, G2::TOTAL, st, 2, mA5ld, mWo, mW4, mOut, mOut, (const bf16*)p_x1, 8, 72);
}
```

```cpp
#include <cuda_runtime.h>
#include <cuda_bf16.h>
#include <cuda.h>
#include <stdint.h>

typedef __nv_bfloat16 bf16;

constexpr int S_LEN = 2048;
constexpr int DM = 1024;
constexpr int FF = 3584;
constexpr int NH = 32;
constexpr int DH = 32;
constexpr int A5W = DM + FF;

__device__ __align__(1024) bf16 g_qkv[S_LEN * 3 * DM];
__device__ __align__(1024) bf16 g_h[S_LEN * DM];
__device__ __align__(1024) bf16 g_x1[S_LEN * DM];
__device__ __align__(1024) bf16 g_a5[S_LEN * A5W];
__device__ __align__(16) float g_mean1[S_LEN];
__device__ __align__(16) float g_rstd1[S_LEN];
__device__ __align__(16) float g_gate[S_LEN];
__device__ __align__(16) float g_omg[S_LEN];
__device__ __align__(16) float g_cs1[DM];
__device__ __align__(16) float g_cs3[FF];
__device__ __align__(16) float2 g_stat2[S_LEN * 8];
__device__ int g_bad[NH * 16];

#define TL_START(k)
#define TL_END(k)

__device__ __forceinline__ uint32_t smem_u32(const void* p) { return (uint32_t)__cvta_generic_to_shared(p); }

__device__ __forceinline__ void mbar_init(uint32_t bar, uint32_t count) {
    asm volatile("mbarrier.init.shared::cta.b64 [%0], %1;" ::"r"(bar), "r"(count));
}
__device__ __forceinline__ void mbar_expect_tx(uint32_t bar, uint32_t bytes) {
    asm volatile("mbarrier.arrive.expect_tx.shared::cta.b64 _, [%0], %1;" ::"r"(bar), "r"(bytes) : "memory");
}
__device__ __forceinline__ void mbar_arrive(uint32_t bar) {
    asm volatile("mbarrier.arrive.shared::cta.b64 _, [%0];" ::"r"(bar) : "memory");
}
__device__ __forceinline__ bool mbar_try_wait(uint32_t bar, uint32_t parity) {
    uint32_t ok;
    asm volatile(
        "{\n.reg .pred p;\n"
        "mbarrier.try_wait.parity.shared::cta.b64 p, [%1], %2;\n"
        "selp.u32 %0, 1, 0, p;\n}\n"
        : "=r"(ok)
        : "r"(bar), "r"(parity)
        : "memory");
    return ok != 0;
}
__device__ __forceinline__ void mbar_wait(uint32_t bar, uint32_t parity) {
    uint32_t spins = 0;
    while (!mbar_try_wait(bar, parity)) {
        if (++spins > (1u << 24)) __trap();
    }
}
__device__ __forceinline__ void tma_load_2d(uint32_t dst, const CUtensorMap* map, int c0, int c1, uint32_t bar) {
    asm volatile(
        "cp.async.bulk.tensor.2d.shared::cluster.global.mbarrier::complete_tx::bytes [%0], [%1, {%3, %4}], [%2];"
        ::"r"(dst), "l"(map), "r"(bar), "r"(c0), "r"(c1)
        : "memory");
}
__device__ __forceinline__ void tma_store_2d(const CUtensorMap* map, uint32_t src, int c0, int c1) {
    asm volatile("cp.async.bulk.tensor.2d.global.shared::cta.bulk_group [%0, {%2, %3}], [%1];"
                 ::"l"(map), "r"(src), "r"(c0), "r"(c1)
                 : "memory");
}
__device__ __forceinline__ void tma_load_2d_mc(uint32_t dst, const CUtensorMap* map, int c0, int c1, uint32_t bar, uint16_t mask) {
    asm volatile(
        "cp.async.bulk.tensor.2d.shared::cluster.global.mbarrier::complete_tx::bytes.multicast::cluster [%0], [%1, {%3, %4}], [%2], %5;"
        ::"r"(dst), "l"(map), "r"(bar), "r"(c0), "r"(c1), "h"(mask)
        : "memory");
}
__device__ __forceinline__ void mbar_arrive_cluster(uint32_t bar, uint32_t cta) {
    asm volatile(
        "{\n.reg .b32 ra;\nmapa.shared::cluster.u32 ra, %0, %1;\n"
        "mbarrier.arrive.shared::cluster.b64 _, [ra];\n}\n" ::"r"(bar), "r"(cta)
        : "memory");
}
__device__ __forceinline__ void cluster_sync_all() {
    asm volatile("barrier.cluster.arrive.release.aligned;\nbarrier.cluster.wait.acquire.aligned;" ::: "memory");
}
__device__ __forceinline__ uint32_t cluster_rank() { uint32_t r; asm volatile("mov.u32 %0, %%cluster_ctarank;" : "=r"(r)); return r; }
__device__ __forceinline__ void pdl_wait() { asm volatile("griddepcontrol.wait;" ::: "memory"); }
__device__ __forceinline__ void pdl_launch() { asm volatile("griddepcontrol.launch_dependents;" ::: "memory"); }
__device__ __forceinline__ void bulk_commit() { asm volatile("cp.async.bulk.commit_group;" ::: "memory"); }
__device__ __forceinline__ void bulk_wait_read0() { asm volatile("cp.async.bulk.wait_group.read 0;" ::: "memory"); }
__device__ __forceinline__ void bulk_wait0() { asm volatile("cp.async.bulk.wait_group 0;" ::: "memory"); }
__device__ __forceinline__ void fence_proxy_async() { asm volatile("fence.proxy.async.shared::cta;" ::: "memory"); }
__device__ __forceinline__ void named_bar_sync(int id, int n) { asm volatile("bar.sync %0, %1;" ::"r"(id), "r"(n) : "memory"); }
__device__ __forceinline__ void named_bar_arrive(int id, int n) { asm volatile("bar.arrive %0, %1;" ::"r"(id), "r"(n) : "memory"); }
__device__ __forceinline__ void wgmma_fence() { asm volatile("wgmma.fence.sync.aligned;" ::: "memory"); }
__device__ __forceinline__ void wgmma_commit() { asm volatile("wgmma.commit_group.sync.aligned;" ::: "memory"); }
template <int N>
__device__ __forceinline__ void wgmma_wait() { asm volatile("wgmma.wait_group.sync.aligned %0;" ::"n"(N) : "memory"); }
__device__ __forceinline__ void prefetch_tmap(const CUtensorMap* m) {
    asm volatile("prefetch.tensormap [%0];" ::"l"(m) : "memory");
}
template <int R>
__device__ __forceinline__ void reg_alloc() { asm volatile("setmaxnreg.inc.sync.aligned.u32 %0;" ::"n"(R)); }
template <int R>
__device__ __forceinline__ void reg_dealloc() { asm volatile("setmaxnreg.dec.sync.aligned.u32 %0;" ::"n"(R)); }
__device__ __forceinline__ void stmatrix_x4(uint32_t addr, uint32_t r0, uint32_t r1, uint32_t r2, uint32_t r3) {
    asm volatile("stmatrix.sync.aligned.m8n8.x4.shared.b16 [%0], {%1, %2, %3, %4};"
                 ::"r"(addr), "r"(r0), "r"(r1), "r"(r2), "r"(r3)
                 : "memory");
}
__device__ __forceinline__ uint32_t pack_bf16(float lo, float hi) {
    uint32_t r;
    asm("cvt.rn.bf16x2.f32 %0, %1, %2;" : "=r"(r) : "f"(hi), "f"(lo));
    return r;
}
__device__ __forceinline__ float bf16_round(float v) { return __bfloat162float(__float2bfloat16_rn(v)); }
__device__ __forceinline__ float ex2(float x) {
    float y;
    asm volatile("ex2.approx.ftz.f32 %0, %1;" : "=f"(y) : "f"(x));
    return y;
}
__device__ __forceinline__ float tanh_fast(float x) {
    float y;
    asm("tanh.approx.f32 %0, %1;" : "=f"(y) : "f"(x));
    return y;
}
__device__ __forceinline__ float gelu_tanh(float v) {
    float u = 0.7978845608028654f * (v + 0.044715f * v * v * v);
    float hv = 0.5f * v;
    return fmaf(hv, tanh_fast(u), hv);
}
__device__ __forceinline__ uint32_t desc_lo(uint32_t addr, uint32_t lbo_bytes) {
    return ((addr & 0x3FFFF) >> 4) | (((lbo_bytes >> 4) & 0x3FFF) << 16);
}
__host__ __device__ constexpr uint32_t desc_hi(uint32_t sbo_bytes, uint32_t swz) {
    return ((sbo_bytes >> 4) & 0x3FFF) | (swz << 30);
}

__device__ __forceinline__ void wgmma_ss_n128_tb1(float (&d)[64], uint32_t alo, uint32_t ahi, uint32_t blo, uint32_t bhi, int scale_d) {
    asm volatile("{\n.reg .pred p;\n.reg .b64 da, db;\nsetp.ne.b32 p, %68, 0;\nmov.b64 da, {%64, %65};\nmov.b64 db, {%66, %67};\n"
        "wgmma.mma_async.sync.aligned.m64n128k16.f32.bf16.bf16 {%0, %1, %2, %3, %4, %5, %6, %7, %8, %9, %10, %11, %12, %13, %14, %15, %16, %17, %18, %19, %20, %21, %22, %23, %24, %25, %26, %27, %28, %29, %30, %31, %32, %33, %34, %35, %36, %37, %38, %39, %40, %41, %42, %43, %44, %45, %46, %47, %48, %49, %50, %51, %52, %53, %54, %55, %56, %57, %58, %59, %60, %61, %62, %63}, da, db, p, 1, 1, 0, 1;\n}\n"
        : "+f"(d[0]), "+f"(d[1]), "+f"(d[2]), "+f"(d[3]), "+f"(d[4]), "+f"(d[5]), "+f"(d[6]), "+f"(d[7]), "+f"(d[8]), "+f"(d[9]), "+f"(d[10]), "+f"(d[11]), "+f"(d[12]), "+f"(d[13]), "+f"(d[14]), "+f"(d[15]), "+f"(d[16]), "+f"(d[17]), "+f"(d[18]), "+f"(d[19]), "+f"(d[20]), "+f"(d[21]), "+f"(d[22]), "+f"(d[23]), "+f"(d[24]), "+f"(d[25]), "+f"(d[26]), "+f"(d[27]), "+f"(d[28]), "+f"(d[29]), "+f"(d[30]), "+f"(d[31]), "+f"(d[32]), "+f"(d[33]), "+f"(d[34]), "+f"(d[35]), "+f"(d[36]), "+f"(d[37]), "+f"(d[38]), "+f"(d[39]), "+f"(d[40]), "+f"(d[41]), "+f"(d[42]), "+f"(d[43]), "+f"(d[44]), "+f"(d[45]), "+f"(d[46]), "+f"(d[47]), "+f"(d[48]), "+f"(d[49]), "+f"(d[50]), "+f"(d[51]), "+f"(d[52]), "+f"(d[53]), "+f"(d[54]), "+f"(d[55]), "+f"(d[56]), "+f"(d[57]), "+f"(d[58]), "+f"(d[59]), "+f"(d[60]), "+f"(d[61]), "+f"(d[62]), "+f"(d[63])
        : "r"(alo), "r"(ahi), "r"(blo), "r"(bhi), "r"(scale_d));
}

__device__ __forceinline__ void wgmma_ss_n192_tb1(float (&d)[96], uint32_t alo, uint32_t ahi, uint32_t blo, uint32_t bhi, int scale_d) {
    asm volatile("{\n.reg .pred p;\n.reg .b64 da, db;\nsetp.ne.b32 p, %100, 0;\nmov.b64 da, {%96, %97};\nmov.b64 db, {%98, %99};\n"
        "wgmma.mma_async.sync.aligned.m64n192k16.f32.bf16.bf16 {%0, %1, %2, %3, %4, %5, %6, %7, %8, %9, %10, %11, %12, %13, %14, %15, %16, %17, %18, %19, %20, %21, %22, %23, %24, %25, %26, %27, %28, %29, %30, %31, %32, %33, %34, %35, %36, %37, %38, %39, %40, %41, %42, %43, %44, %45, %46, %47, %48, %49, %50, %51, %52, %53, %54, %55, %56, %57, %58, %59, %60, %61, %62, %63, %64, %65, %66, %67, %68, %69, %70, %71, %72, %73, %74, %75, %76, %77, %78, %79, %80, %81, %82, %83, %84, %85, %86, %87, %88, %89, %90, %91, %92, %93, %94, %95}, da, db, p, 1, 1, 0, 1;\n}\n"
        : "+f"(d[0]), "+f"(d[1]), "+f"(d[2]), "+f"(d[3]), "+f"(d[4]), "+f"(d[5]), "+f"(d[6]), "+f"(d[7]), "+f"(d[8]), "+f"(d[9]), "+f"(d[10]), "+f"(d[11]), "+f"(d[12]), "+f"(d[13]), "+f"(d[14]), "+f"(d[15]), "+f"(d[16]), "+f"(d[17]), "+f"(d[18]), "+f"(d[19]), "+f"(d[20]), "+f"(d[21]), "+f"(d[22]), "+f"(d[23]), "+f"(d[24]), "+f"(d[25]), "+f"(d[26]), "+f"(d[27]), "+f"(d[28]), "+f"(d[29]), "+f"(d[30]), "+f"(d[31]), "+f"(d[32]), "+f"(d[33]), "+f"(d[34]), "+f"(d[35]), "+f"(d[36]), "+f"(d[37]), "+f"(d[38]), "+f"(d[39]), "+f"(d[40]), "+f"(d[41]), "+f"(d[42]), "+f"(d[43]), "+f"(d[44]), "+f"(d[45]), "+f"(d[46]), "+f"(d[47]), "+f"(d[48]), "+f"(d[49]), "+f"(d[50]), "+f"(d[51]), "+f"(d[52]), "+f"(d[53]), "+f"(d[54]), "+f"(d[55]), "+f"(d[56]), "+f"(d[57]), "+f"(d[58]), "+f"(d[59]), "+f"(d[60]), "+f"(d[61]), "+f"(d[62]), "+f"(d[63]), "+f"(d[64]), "+f"(d[65]), "+f"(d[66]), "+f"(d[67]), "+f"(d[68]), "+f"(d[69]), "+f"(d[70]), "+f"(d[71]), "+f"(d[72]), "+f"(d[73]), "+f"(d[74]), "+f"(d[75]), "+f"(d[76]), "+f"(d[77]), "+f"(d[78]), "+f"(d[79]), "+f"(d[80]), "+f"(d[81]), "+f"(d[82]), "+f"(d[83]), "+f"(d[84]), "+f"(d[85]), "+f"(d[86]), "+f"(d[87]), "+f"(d[88]), "+f"(d[89]), "+f"(d[90]), "+f"(d[91]), "+f"(d[92]), "+f"(d[93]), "+f"(d[94]), "+f"(d[95])
        : "r"(alo), "r"(ahi), "r"(blo), "r"(bhi), "r"(scale_d));
}

__device__ __forceinline__ void wgmma_ss_n224_tb1(float (&d)[112], uint32_t alo, uint32_t ahi, uint32_t blo, uint32_t bhi, int scale_d) {
    asm volatile("{\n.reg .pred p;\n.reg .b64 da, db;\nsetp.ne.b32 p, %116, 0;\nmov.b64 da, {%112, %113};\nmov.b64 db, {%114, %115};\n"
        "wgmma.mma_async.sync.aligned.m64n224k16.f32.bf16.bf16 {%0, %1, %2, %3, %4, %5, %6, %7, %8, %9, %10, %11, %12, %13, %14, %15, %16, %17, %18, %19, %20, %21, %22, %23, %24, %25, %26, %27, %28, %29, %30, %31, %32, %33, %34, %35, %36, %37, %38, %39, %40, %41, %42, %43, %44, %45, %46, %47, %48, %49, %50, %51, %52, %53, %54, %55, %56, %57, %58, %59, %60, %61, %62, %63, %64, %65, %66, %67, %68, %69, %70, %71, %72, %73, %74, %75, %76, %77, %78, %79, %80, %81, %82, %83, %84, %85, %86, %87, %88, %89, %90, %91, %92, %93, %94, %95, %96, %97, %98, %99, %100, %101, %102, %103, %104, %105, %106, %107, %108, %109, %110, %111}, da, db, p, 1, 1, 0, 1;\n}\n"
        : "+f"(d[0]), "+f"(d[1]), "+f"(d[2]), "+f"(d[3]), "+f"(d[4]), "+f"(d[5]), "+f"(d[6]), "+f"(d[7]), "+f"(d[8]), "+f"(d[9]), "+f"(d[10]), "+f"(d[11]), "+f"(d[12]), "+f"(d[13]), "+f"(d[14]), "+f"(d[15]), "+f"(d[16]), "+f"(d[17]), "+f"(d[18]), "+f"(d[19]), "+f"(d[20]), "+f"(d[21]), "+f"(d[22]), "+f"(d[23]), "+f"(d[24]), "+f"(d[25]), "+f"(d[26]), "+f"(d[27]), "+f"(d[28]), "+f"(d[29]), "+f"(d[30]), "+f"(d[31]), "+f"(d[32]), "+f"(d[33]), "+f"(d[34]), "+f"(d[35]), "+f"(d[36]), "+f"(d[37]), "+f"(d[38]), "+f"(d[39]), "+f"(d[40]), "+f"(d[41]), "+f"(d[42]), "+f"(d[43]), "+f"(d[44]), "+f"(d[45]), "+f"(d[46]), "+f"(d[47]), "+f"(d[48]), "+f"(d[49]), "+f"(d[50]), "+f"(d[51]), "+f"(d[52]), "+f"(d[53]), "+f"(d[54]), "+f"(d[55]), "+f"(d[56]), "+f"(d[57]), "+f"(d[58]), "+f"(d[59]), "+f"(d[60]), "+f"(d[61]), "+f"(d[62]), "+f"(d[63]), "+f"(d[64]), "+f"(d[65]), "+f"(d[66]), "+f"(d[67]), "+f"(d[68]), "+f"(d[69]), "+f"(d[70]), "+f"(d[71]), "+f"(d[72]), "+f"(d[73]), "+f"(d[74]), "+f"(d[75]), "+f"(d[76]), "+f"(d[77]), "+f"(d[78]), "+f"(d[79]), "+f"(d[80]), "+f"(d[81]), "+f"(d[82]), "+f"(d[83]), "+f"(d[84]), "+f"(d[85]), "+f"(d[86]), "+f"(d[87]), "+f"(d[88]), "+f"(d[89]), "+f"(d[90]), "+f"(d[91]), "+f"(d[92]), "+f"(d[93]), "+f"(d[94]), "+f"(d[95]), "+f"(d[96]), "+f"(d[97]), "+f"(d[98]), "+f"(d[99]), "+f"(d[100]), "+f"(d[101]), "+f"(d[102]), "+f"(d[103]), "+f"(d[104]), "+f"(d[105]), "+f"(d[106]), "+f"(d[107]), "+f"(d[108]), "+f"(d[109]), "+f"(d[110]), "+f"(d[111])
        : "r"(alo), "r"(ahi), "r"(blo), "r"(bhi), "r"(scale_d));
}

__device__ __forceinline__ void wgmma_ss_n256_tb1(float (&d)[128], uint32_t alo, uint32_t ahi, uint32_t blo, uint32_t bhi, int scale_d) {
    asm volatile("{\n.reg .pred p;\n.reg .b64 da, db;\nsetp.ne.b32 p, %132, 0;\nmov.b64 da, {%128, %129};\nmov.b64 db, {%130, %131};\n"
        "wgmma.mma_async.sync.aligned.m64n256k16.f32.bf16.bf16 {%0, %1, %2, %3, %4, %5, %6, %7, %8, %9, %10, %11, %12, %13, %14, %15, %16, %17, %18, %19, %20, %21, %22, %23, %24, %25, %26, %27, %28, %29, %30, %31, %32, %33, %34, %35, %36, %37, %38, %39, %40, %41, %42, %43, %44, %45, %46, %47, %48, %49, %50, %51, %52, %53, %54, %55, %56, %57, %58, %59, %60, %61, %62, %63, %64, %65, %66, %67, %68, %69, %70, %71, %72, %73, %74, %75, %76, %77, %78, %79, %80, %81, %82, %83, %84, %85, %86, %87, %88, %89, %90, %91, %92, %93, %94, %95, %96, %97, %98, %99, %100, %101, %102, %103, %104, %105, %106, %107, %108, %109, %110, %111, %112, %113, %114, %115, %116, %117, %118, %119, %120, %121, %122, %123, %124, %125, %126, %127}, da, db, p, 1, 1, 0, 1;\n}\n"
        : "+f"(d[0]), "+f"(d[1]), "+f"(d[2]), "+f"(d[3]), "+f"(d[4]), "+f"(d[5]), "+f"(d[6]), "+f"(d[7]), "+f"(d[8]), "+f"(d[9]), "+f"(d[10]), "+f"(d[11]), "+f"(d[12]), "+f"(d[13]), "+f"(d[14]), "+f"(d[15]), "+f"(d[16]), "+f"(d[17]), "+f"(d[18]), "+f"(d[19]), "+f"(d[20]), "+f"(d[21]), "+f"(d[22]), "+f"(d[23]), "+f"(d[24]), "+f"(d[25]), "+f"(d[26]), "+f"(d[27]), "+f"(d[28]), "+f"(d[29]), "+f"(d[30]), "+f"(d[31]), "+f"(d[32]), "+f"(d[33]), "+f"(d[34]), "+f"(d[35]), "+f"(d[36]), "+f"(d[37]), "+f"(d[38]), "+f"(d[39]), "+f"(d[40]), "+f"(d[41]), "+f"(d[42]), "+f"(d[43]), "+f"(d[44]), "+f"(d[45]), "+f"(d[46]), "+f"(d[47]), "+f"(d[48]), "+f"(d[49]), "+f"(d[50]), "+f"(d[51]), "+f"(d[52]), "+f"(d[53]), "+f"(d[54]), "+f"(d[55]), "+f"(d[56]), "+f"(d[57]), "+f"(d[58]), "+f"(d[59]), "+f"(d[60]), "+f"(d[61]), "+f"(d[62]), "+f"(d[63]), "+f"(d[64]), "+f"(d[65]), "+f"(d[66]), "+f"(d[67]), "+f"(d[68]), "+f"(d[69]), "+f"(d[70]), "+f"(d[71]), "+f"(d[72]), "+f"(d[73]), "+f"(d[74]), "+f"(d[75]), "+f"(d[76]), "+f"(d[77]), "+f"(d[78]), "+f"(d[79]), "+f"(d[80]), "+f"(d[81]), "+f"(d[82]), "+f"(d[83]), "+f"(d[84]), "+f"(d[85]), "+f"(d[86]), "+f"(d[87]), "+f"(d[88]), "+f"(d[89]), "+f"(d[90]), "+f"(d[91]), "+f"(d[92]), "+f"(d[93]), "+f"(d[94]), "+f"(d[95]), "+f"(d[96]), "+f"(d[97]), "+f"(d[98]), "+f"(d[99]), "+f"(d[100]), "+f"(d[101]), "+f"(d[102]), "+f"(d[103]), "+f"(d[104]), "+f"(d[105]), "+f"(d[106]), "+f"(d[107]), "+f"(d[108]), "+f"(d[109]), "+f"(d[110]), "+f"(d[111]), "+f"(d[112]), "+f"(d[113]), "+f"(d[114]), "+f"(d[115]), "+f"(d[116]), "+f"(d[117]), "+f"(d[118]), "+f"(d[119]), "+f"(d[120]), "+f"(d[121]), "+f"(d[122]), "+f"(d[123]), "+f"(d[124]), "+f"(d[125]), "+f"(d[126]), "+f"(d[127])
        : "r"(alo), "r"(ahi), "r"(blo), "r"(bhi), "r"(scale_d));
}

__device__ __forceinline__ void wgmma_ss_n64_tb0(float (&d)[32], uint32_t alo, uint32_t ahi, uint32_t blo, uint32_t bhi, int scale_d) {
    asm volatile("{\n.reg .pred p;\n.reg .b64 da, db;\nsetp.ne.b32 p, %36, 0;\nmov.b64 da, {%32, %33};\nmov.b64 db, {%34, %35};\n"
        "wgmma.mma_async.sync.aligned.m64n64k16.f32.bf16.bf16 {%0, %1, %2, %3, %4, %5, %6, %7, %8, %9, %10, %11, %12, %13, %14, %15, %16, %17, %18, %19, %20, %21, %22, %23, %24, %25, %26, %27, %28, %29, %30, %31}, da, db, p, 1, 1, 0, 0;\n}\n"
        : "+f"(d[0]), "+f"(d[1]), "+f"(d[2]), "+f"(d[3]), "+f"(d[4]), "+f"(d[5]), "+f"(d[6]), "+f"(d[7]), "+f"(d[8]), "+f"(d[9]), "+f"(d[10]), "+f"(d[11]), "+f"(d[12]), "+f"(d[13]), "+f"(d[14]), "+f"(d[15]), "+f"(d[16]), "+f"(d[17]), "+f"(d[18]), "+f"(d[19]), "+f"(d[20]), "+f"(d[21]), "+f"(d[22]), "+f"(d[23]), "+f"(d[24]), "+f"(d[25]), "+f"(d[26]), "+f"(d[27]), "+f"(d[28]), "+f"(d[29]), "+f"(d[30]), "+f"(d[31])
        : "r"(alo), "r"(ahi), "r"(blo), "r"(bhi), "r"(scale_d));
}

__device__ __forceinline__ void wgmma_rs_n128_tb0(float (&d)[64], uint32_t a0, uint32_t a1, uint32_t a2, uint32_t a3, uint32_t blo, uint32_t bhi, int scale_d) {
    asm volatile("{\n.reg .pred p;\n.reg .b64 db;\nsetp.ne.b32 p, %70, 0;\nmov.b64 db, {%68, %69};\n"
        "wgmma.mma_async.sync.aligned.m64n128k16.f32.bf16.bf16 {%0, %1, %2, %3, %4, %5, %6, %7, %8, %9, %10, %11, %12, %13, %14, %15, %16, %17, %18, %19, %20, %21, %22, %23, %24, %25, %26, %27, %28, %29, %30, %31, %32, %33, %34, %35, %36, %37, %38, %39, %40, %41, %42, %43, %44, %45, %46, %47, %48, %49, %50, %51, %52, %53, %54, %55, %56, %57, %58, %59, %60, %61, %62, %63}, {%64, %65, %66, %67}, db, p, 1, 1, 0;\n}\n"
        : "+f"(d[0]), "+f"(d[1]), "+f"(d[2]), "+f"(d[3]), "+f"(d[4]), "+f"(d[5]), "+f"(d[6]), "+f"(d[7]), "+f"(d[8]), "+f"(d[9]), "+f"(d[10]), "+f"(d[11]), "+f"(d[12]), "+f"(d[13]), "+f"(d[14]), "+f"(d[15]), "+f"(d[16]), "+f"(d[17]), "+f"(d[18]), "+f"(d[19]), "+f"(d[20]), "+f"(d[21]), "+f"(d[22]), "+f"(d[23]), "+f"(d[24]), "+f"(d[25]), "+f"(d[26]), "+f"(d[27]), "+f"(d[28]), "+f"(d[29]), "+f"(d[30]), "+f"(d[31]), "+f"(d[32]), "+f"(d[33]), "+f"(d[34]), "+f"(d[35]), "+f"(d[36]), "+f"(d[37]), "+f"(d[38]), "+f"(d[39]), "+f"(d[40]), "+f"(d[41]), "+f"(d[42]), "+f"(d[43]), "+f"(d[44]), "+f"(d[45]), "+f"(d[46]), "+f"(d[47]), "+f"(d[48]), "+f"(d[49]), "+f"(d[50]), "+f"(d[51]), "+f"(d[52]), "+f"(d[53]), "+f"(d[54]), "+f"(d[55]), "+f"(d[56]), "+f"(d[57]), "+f"(d[58]), "+f"(d[59]), "+f"(d[60]), "+f"(d[61]), "+f"(d[62]), "+f"(d[63])
        : "r"(a0), "r"(a1), "r"(a2), "r"(a3), "r"(blo), "r"(bhi), "r"(scale_d));
}

__device__ __forceinline__ void wgmma_rs_n64_tb0(float (&d)[32], uint32_t a0, uint32_t a1, uint32_t a2, uint32_t a3, uint32_t blo, uint32_t bhi, int scale_d) {
    asm volatile("{\n.reg .pred p;\n.reg .b64 db;\nsetp.ne.b32 p, %38, 0;\nmov.b64 db, {%36, %37};\n"
        "wgmma.mma_async.sync.aligned.m64n64k16.f32.bf16.bf16 {%0, %1, %2, %3, %4, %5, %6, %7, %8, %9, %10, %11, %12, %13, %14, %15, %16, %17, %18, %19, %20, %21, %22, %23, %24, %25, %26, %27, %28, %29, %30, %31}, {%32, %33, %34, %35}, db, p, 1, 1, 0;\n}\n"
        : "+f"(d[0]), "+f"(d[1]), "+f"(d[2]), "+f"(d[3]), "+f"(d[4]), "+f"(d[5]), "+f"(d[6]), "+f"(d[7]), "+f"(d[8]), "+f"(d[9]), "+f"(d[10]), "+f"(d[11]), "+f"(d[12]), "+f"(d[13]), "+f"(d[14]), "+f"(d[15]), "+f"(d[16]), "+f"(d[17]), "+f"(d[18]), "+f"(d[19]), "+f"(d[20]), "+f"(d[21]), "+f"(d[22]), "+f"(d[23]), "+f"(d[24]), "+f"(d[25]), "+f"(d[26]), "+f"(d[27]), "+f"(d[28]), "+f"(d[29]), "+f"(d[30]), "+f"(d[31])
        : "r"(a0), "r"(a1), "r"(a2), "r"(a3), "r"(blo), "r"(bhi), "r"(scale_d));
}

__device__ __forceinline__ void wgmma_rs_n32_tb1(float (&d)[16], uint32_t a0, uint32_t a1, uint32_t a2, uint32_t a3, uint32_t blo, uint32_t bhi, int scale_d) {
    asm volatile("{\n.reg .pred p;\n.reg .b64 db;\nsetp.ne.b32 p, %22, 0;\nmov.b64 db, {%20, %21};\n"
        "wgmma.mma_async.sync.aligned.m64n32k16.f32.bf16.bf16 {%0, %1, %2, %3, %4, %5, %6, %7, %8, %9, %10, %11, %12, %13, %14, %15}, {%16, %17, %18, %19}, db, p, 1, 1, 1;\n}\n"
        : "+f"(d[0]), "+f"(d[1]), "+f"(d[2]), "+f"(d[3]), "+f"(d[4]), "+f"(d[5]), "+f"(d[6]), "+f"(d[7]), "+f"(d[8]), "+f"(d[9]), "+f"(d[10]), "+f"(d[11]), "+f"(d[12]), "+f"(d[13]), "+f"(d[14]), "+f"(d[15])
        : "r"(a0), "r"(a1), "r"(a2), "r"(a3), "r"(blo), "r"(bhi), "r"(scale_d));
}

__device__ __forceinline__ void wgmma_rs_n40_tb1(float (&d)[20], uint32_t a0, uint32_t a1, uint32_t a2, uint32_t a3, uint32_t blo, uint32_t bhi, int scale_d) {
    asm volatile("{\n.reg .pred p;\n.reg .b64 db;\nsetp.ne.b32 p, %26, 0;\nmov.b64 db, {%24, %25};\n"
        "wgmma.mma_async.sync.aligned.m64n40k16.f32.bf16.bf16 {%0, %1, %2, %3, %4, %5, %6, %7, %8, %9, %10, %11, %12, %13, %14, %15, %16, %17, %18, %19}, {%20, %21, %22, %23}, db, p, 1, 1, 1;\n}\n"
        : "+f"(d[0]), "+f"(d[1]), "+f"(d[2]), "+f"(d[3]), "+f"(d[4]), "+f"(d[5]), "+f"(d[6]), "+f"(d[7]), "+f"(d[8]), "+f"(d[9]), "+f"(d[10]), "+f"(d[11]), "+f"(d[12]), "+f"(d[13]), "+f"(d[14]), "+f"(d[15]), "+f"(d[16]), "+f"(d[17]), "+f"(d[18]), "+f"(d[19])
        : "r"(a0), "r"(a1), "r"(a2), "r"(a3), "r"(blo), "r"(bhi), "r"(scale_d));
}

template <int BN>
__device__ __forceinline__ void wgmma_tile(float (&d)[BN / 2], uint32_t da, uint32_t db, int sd) {
    constexpr uint32_t HI = desc_hi(1024, 1);
    if constexpr (BN == 128) wgmma_ss_n128_tb1(d, da, HI, db, HI, sd);
    else if constexpr (BN == 192) wgmma_ss_n192_tb1(d, da, HI, db, HI, sd);
    else if constexpr (BN == 224) wgmma_ss_n224_tb1(d, da, HI, db, HI, sd);
    else wgmma_ss_n256_tb1(d, da, HI, db, HI, sd);
}

__global__ void __launch_bounds__(256) prep_kernel(const bf16* __restrict__ x, const bf16* __restrict__ gate_w,
                                                   const bf16* __restrict__ w1, const bf16* __restrict__ w3) {
    const int tid = threadIdx.x;
    TL_START(0)
    pdl_launch();
    if (blockIdx.x < 256) {
        const int row = blockIdx.x * 8 + (tid >> 5);
        const int lane = tid & 31;
        const uint4* xr = reinterpret_cast<const uint4*>(x + (size_t)row * DM);
        const uint4* gw = reinterpret_cast<const uint4*>(gate_w);
        float v[32];
        float gsum = 0.f, sum = 0.f;
#pragma unroll
        for (int i = 0; i < 4; i++) {
            uint4 a = xr[lane + 32 * i];
            uint4 b = gw[lane + 32 * i];
            const uint32_t aa[4] = {a.x, a.y, a.z, a.w};
            const uint32_t bb[4] = {b.x, b.y, b.z, b.w};
#pragma unroll
            for (int j = 0; j < 4; j++) {
                float x0 = __uint_as_float(aa[j] << 16), x1 = __uint_as_float(aa[j] & 0xFFFF0000u);
                float g0 = __uint_as_float(bb[j] << 16), g1 = __uint_as_float(bb[j] & 0xFFFF0000u);
                v[i * 8 + j * 2] = x0;
                v[i * 8 + j * 2 + 1] = x1;
                sum += x0 + x1;
                gsum += bf16_round(x0 * g0) + bf16_round(x1 * g1);
            }
        }
#pragma unroll
        for (int o = 16; o > 0; o >>= 1) {
            sum += __shfl_xor_sync(0xffffffffu, sum, o);
            gsum += __shfl_xor_sync(0xffffffffu, gsum, o);
        }
        const float mean = sum * (1.0f / DM);
        float m2 = 0.f;
#pragma unroll
        for (int i = 0; i < 32; i++) {
            float d = v[i] - mean;
            m2 += d * d;
        }
#pragma unroll
        for (int o = 16; o > 0; o >>= 1) m2 += __shfl_xor_sync(0xffffffffu, m2, o);
        if (lane == 0) {
            g_mean1[row] = mean;
            g_rstd1[row] = rsqrtf(m2 * (1.0f / DM) + 1e-5f);
            float logit = bf16_round(gsum);
            float g = bf16_round(1.0f / (1.0f + __expf(-logit)));
            g_gate[row] = g;
            g_omg[row] = bf16_round(1.0f - g);
        }
    } else {
        __shared__ float red[32][65];
        const int strip = blockIdx.x - 256;
        const bf16* w;
        float* out;
        int ld, col0;
        if (strip < 16) { w = w1; ld = DM; col0 = strip * 64; out = g_cs1; }
        else { w = w3; ld = FF; col0 = (strip - 16) * 64; out = g_cs3; }
        const int cg = tid & 7;
        const int rg = tid >> 3;
        float acc[8];
#pragma unroll
        for (int j = 0; j < 8; j++) acc[j] = 0.f;
#pragma unroll 8
        for (int r = 0; r < 32; r++) {
            uint4 a = *reinterpret_cast<const uint4*>(w + (size_t)(r * 32 + rg) * ld + col0 + cg * 8);
            const uint32_t aa[4] = {a.x, a.y, a.z, a.w};
#pragma unroll
            for (int j = 0; j < 4; j++) {
                acc[2 * j] += __uint_as_float(aa[j] << 16);
                acc[2 * j + 1] += __uint_as_float(aa[j] & 0xFFFF0000u);
            }
        }
#pragma unroll
        for (int j = 0; j < 8; j++) red[rg][cg * 8 + j] = acc[j];
        __syncthreads();
        if (tid < 64) {
            float s = 0.f;
#pragma unroll
            for (int r = 0; r < 32; r++) s += red[r][tid];
            out[col0 + tid] = s;
        }
    }
    TL_END(0)
}

#define RELEASE_STAGE(b) if (tid_wg < 2) mbar_arrive_cluster(b, tid_wg)
template <int BN, int STAGES>
struct GemmSmem {
    static constexpr int A_BYTES = 128 * 64 * 2;
    static constexpr int B_BOXES = (BN + 63) / 64;
    static constexpr int B_BYTES = B_BOXES * 64 * 64 * 2;
    static constexpr int STAGE_BYTES = A_BYTES + B_BYTES;
    static constexpr int STG_OFF = STAGES * STAGE_BYTES;
    static constexpr int BAR_OFF = STAGES * STAGE_BYTES + 2 * 16384;
    static constexpr int TOTAL = BAR_OFF + 256 + 1024;
};

template <int MODE, int BN, int STAGES>
__global__ void __launch_bounds__(384, 1)
gemm_kernel(const __grid_constant__ CUtensorMap mA, const __grid_constant__ CUtensorMap mB0,
            const __grid_constant__ CUtensorMap mB1, const __grid_constant__ CUtensorMap mC0,
            const __grid_constant__ CUtensorMap mC1, const bf16* __restrict__ xin, int n_tiles_n, int kblocks) {
    using L = GemmSmem<BN, STAGES>;
    extern __shared__ uint8_t smem_raw[];
    const uint32_t sbase = (smem_u32(smem_raw) + 1023u) & ~1023u;
    const uint32_t bar_full = sbase + L::BAR_OFF;
    const uint32_t bar_empty = bar_full + 8 * STAGES;
    const int wg = threadIdx.x >> 7;
    const int npairs = 8 * n_tiles_n;
    const uint32_t crank = cluster_rank();
    const int cid = blockIdx.x >> 1, ncl = gridDim.x >> 1;
    TL_START(MODE)
    pdl_launch();

    if (threadIdx.x == 0) {
        for (int s = 0; s < STAGES; s++) {
            mbar_init(bar_full + 8 * s, 1);
            mbar_init(bar_empty + 8 * s, 4);
        }
        asm volatile("fence.mbarrier_init.release.cluster;" ::: "memory");
        prefetch_tmap(&mA);
        prefetch_tmap(&mB0);
        if (MODE == 1 || MODE == 5) prefetch_tmap(&mB1);
        prefetch_tmap(&mC0);
    }
    cluster_sync_all();

    if (wg == 0) {
        reg_dealloc<40>();
        if (threadIdx.x == 0) {
            if (MODE != 1) pdl_wait();
            int stage = 0;
            uint32_t phase = 1;
            for (int pr = cid; pr < npairs; pr += ncl) {
                const int m0 = ((pr & 7) * 2 + crank) * 128;
                const int n0 = (pr >> 3) * BN;
                for (int kb = 0; kb < kblocks; kb++) {
                    mbar_wait(bar_empty + 8 * stage, phase);
                    const uint32_t sa = sbase + stage * L::STAGE_BYTES;
                    const uint32_t sb = sa + L::A_BYTES;
                    const uint32_t fb = bar_full + 8 * stage;
                    mbar_expect_tx(fb, L::STAGE_BYTES);
                    int arow = m0;
                    if (MODE == 2) {
                        const int grp = kb >> 2;
                        arow += (grp == 0) ? -1 : (grp == 1) ? 1 : (grp == 2) ? -2 : 2;
                    }
                    tma_load_2d(sa, &mA, kb * 64, arow, fb);
                    const CUtensorMap* mb = &mB0;
                    int bc = n0, br = kb * 64;
                    if (MODE == 1 && n0 >= 3 * DM) { mb = &mB1; bc = n0 - 3 * DM; }
                    if (MODE == 5 && kb >= 16) { mb = &mB1; br = (kb - 16) * 64; }
#pragma unroll
                    for (int b = 0; b < L::B_BOXES / 2; b++) {
                        const int bb = crank * (L::B_BOXES / 2) + b;
                        tma_load_2d_mc(sb + bb * 8192, mb, bc + bb * 64, br, fb, (uint16_t)3);
                    }
                    if (++stage == STAGES) { stage = 0; phase ^= 1; }
                }
            }
        }
    } else {
        reg_alloc<232>();
        const int c = wg - 1;
        const int warp = (threadIdx.x >> 5) & 3;
        const int lane = threadIdx.x & 31;
        const int tid_wg = threadIdx.x & 127;
        const uint32_t stg = sbase + L::STG_OFF + c * 16384;
        int stage = 0;
        uint32_t phase = 0;
        float acc[BN / 2];
        bool first = true;
        for (int pr = cid; pr < npairs; pr += ncl) {
            const int m0 = ((pr & 7) * 2 + crank) * 128;
            const int n0 = (pr >> 3) * BN;
            int prev_stage = 0;
            for (int kb = 0; kb < kblocks; kb++) {
                mbar_wait(bar_full + 8 * stage, phase);
                const uint32_t sa = sbase + stage * L::STAGE_BYTES + c * 8192;
                const uint32_t sb = sbase + stage * L::STAGE_BYTES + L::A_BYTES;
                const uint32_t da = desc_lo(sa, 16);
                const uint32_t db = desc_lo(sb, 8192);
                wgmma_fence();
#pragma unroll
                for (int k = 0; k < 4; k++) wgmma_tile<BN>(acc, da + k * 2, db + k * 128, (kb | k) != 0);
                wgmma_commit();
                if (kb > 0) {
                    wgmma_wait<1>();
                    RELEASE_STAGE(bar_empty + 8 * prev_stage);
                }
                prev_stage = stage;
                if (++stage == STAGES) { stage = 0; phase ^= 1; }
            }
            wgmma_wait<0>();
            RELEASE_STAGE(bar_empty + 8 * prev_stage);
            if (first) { pdl_wait(); first = false; }

            const int r0 = m0 + c * 64 + warp * 16 + (lane >> 2);
            const int r1 = r0 + 8;
            const int cq = (lane & 3) * 2;
            const CUtensorMap* mc = &mC0;
            int out_c0 = n0;
            if (MODE == 1) {
                if (n0 < DM) {
                    const float qs = 0.17677669529663687f * 1.4426950408889634f;
#pragma unroll
                    for (int j = 0; j < BN / 2; j++) acc[j] *= qs;
                } else if (n0 >= 3 * DM) {
                    mc = &mC1;
                    out_c0 = n0 - 3 * DM;
                    const float mu0 = g_mean1[r0], mu1 = g_mean1[r1];
                    const float rs0 = g_rstd1[r0], rs1 = g_rstd1[r1];
#pragma unroll
                    for (int j = 0; j < BN / 8; j++) {
                        const float2 cs = *reinterpret_cast<const float2*>(&g_cs1[out_c0 + 8 * j + cq]);
                        acc[4 * j + 0] = gelu_tanh(rs0 * fmaf(-mu0, cs.x, acc[4 * j + 0]));
                        acc[4 * j + 1] = gelu_tanh(rs0 * fmaf(-mu0, cs.y, acc[4 * j + 1]));
                        acc[4 * j + 2] = gelu_tanh(rs1 * fmaf(-mu1, cs.x, acc[4 * j + 2]));
                        acc[4 * j + 3] = gelu_tanh(rs1 * fmaf(-mu1, cs.y, acc[4 * j + 3]));
                    }
                }
            } else if (MODE == 2) {
                float s0 = 0.f, s1 = 0.f;
#pragma unroll
                for (int j = 0; j < BN / 8; j++) {
                    const uint32_t xa = *reinterpret_cast<const uint32_t*>(xin + (size_t)r0 * DM + n0 + 8 * j + cq);
                    const uint32_t xb = *reinterpret_cast<const uint32_t*>(xin + (size_t)r1 * DM + n0 + 8 * j + cq);
                    acc[4 * j + 0] = bf16_round(bf16_round(acc[4 * j + 0]) + __uint_as_float(xa << 16));
                    acc[4 * j + 1] = bf16_round(bf16_round(acc[4 * j + 1]) + __uint_as_float(xa & 0xFFFF0000u));
                    acc[4 * j + 2] = bf16_round(bf16_round(acc[4 * j + 2]) + __uint_as_float(xb << 16));
                    acc[4 * j + 3] = bf16_round(bf16_round(acc[4 * j + 3]) + __uint_as_float(xb & 0xFFFF0000u));
                    s0 += acc[4 * j + 0] + acc[4 * j + 1];
                    s1 += acc[4 * j + 2] + acc[4 * j + 3];
                }
                s0 += __shfl_xor_sync(0xffffffffu, s0, 1);
                s0 += __shfl_xor_sync(0xffffffffu, s0, 2);
                s1 += __shfl_xor_sync(0xffffffffu, s1, 1);
                s1 += __shfl_xor_sync(0xffffffffu, s1, 2);
                const float mu0 = s0 * (1.0f / BN), mu1 = s1 * (1.0f / BN);
                float q0 = 0.f, q1 = 0.f;
#pragma unroll
                for (int j = 0; j < BN / 8; j++) {
                    float d;
                    d = acc[4 * j + 0] - mu0; q0 += d * d;
                    d = acc[4 * j + 1] - mu0; q0 += d * d;
                    d = acc[4 * j + 2] - mu1; q1 += d * d;
                    d = acc[4 * j + 3] - mu1; q1 += d * d;
                }
                q0 += __shfl_xor_sync(0xffffffffu, q0, 1);
                q0 += __shfl_xor_sync(0xffffffffu, q0, 2);
                q1 += __shfl_xor_sync(0xffffffffu, q1, 1);
                q1 += __shfl_xor_sync(0xffffffffu, q1, 2);
                if ((lane & 3) == 0) {
                    static_assert(MODE != 2 || BN == 128, "stats layout assumes BN=128");
                    g_stat2[r0 * 8 + (n0 >> 7)] = make_float2(s0, q0);
                    g_stat2[r1 * 8 + (n0 >> 7)] = make_float2(s1, q1);
                }
            } else if (MODE == 3) {
                out_c0 = n0 + DM;
                float mu[2], rs[2];
#pragma unroll
                for (int h = 0; h < 2; h++) {
                    const float4* sp = reinterpret_cast<const float4*>(&g_stat2[(h ? r1 : r0) * 8]);
                    float4 p[4];
                    float s = 0.f;
#pragma unroll
                    for (int i = 0; i < 4; i++) { p[i] = sp[i]; s += p[i].x + p[i].z; }
                    const float mean = s * (1.0f / DM);
                    float m2 = 0.f;
#pragma unroll
                    for (int i = 0; i < 4; i++) {
                        float d0 = p[i].x * (1.0f / 128) - mean, d1 = p[i].z * (1.0f / 128) - mean;
                        m2 += p[i].y + p[i].w + 128.0f * (d0 * d0 + d1 * d1);
                    }
                    mu[h] = mean;
                    rs[h] = rsqrtf(m2 * (1.0f / DM) + 1e-5f);
                }
                const float og0 = g_omg[r0], og1 = g_omg[r1];
#pragma unroll
                for (int j = 0; j < BN / 8; j++) {
                    const float2 cs = *reinterpret_cast<const float2*>(&g_cs3[n0 + 8 * j + cq]);
                    acc[4 * j + 0] = og0 * gelu_tanh(rs[0] * fmaf(-mu[0], cs.x, acc[4 * j + 0]));
                    acc[4 * j + 1] = og0 * gelu_tanh(rs[0] * fmaf(-mu[0], cs.y, acc[4 * j + 1]));
                    acc[4 * j + 2] = og1 * gelu_tanh(rs[1] * fmaf(-mu[1], cs.x, acc[4 * j + 2]));
                    acc[4 * j + 3] = og1 * gelu_tanh(rs[1] * fmaf(-mu[1], cs.y, acc[4 * j + 3]));
                }
            } else {
                const float og0 = g_omg[r0], og1 = g_omg[r1];
#pragma unroll
                for (int j = 0; j < BN / 8; j++) {
                    const uint32_t xa = *reinterpret_cast<const uint32_t*>(xin + (size_t)r0 * DM + n0 + 8 * j + cq);
                    const uint32_t xb = *reinterpret_cast<const uint32_t*>(xin + (size_t)r1 * DM + n0 + 8 * j + cq);
                    acc[4 * j + 0] = fmaf(og0, __uint_as_float(xa << 16), acc[4 * j + 0]);
                    acc[4 * j + 1] = fmaf(og0, __uint_as_float(xa & 0xFFFF0000u), acc[4 * j + 1]);
                    acc[4 * j + 2] = fmaf(og1, __uint_as_float(xb << 16), acc[4 * j + 2]);
                    acc[4 * j + 3] = fmaf(og1, __uint_as_float(xb & 0xFFFF0000u), acc[4 * j + 3]);
                }
            }
            const int srow = warp * 16 + (lane & 7) + ((lane >> 3) & 1) * 8;
#pragma unroll
            for (int rnd = 0; rnd < (BN + 127) / 128; rnd++) {
                if (tid_wg == 0) bulk_wait_read0();
                named_bar_sync(1 + c, 128);
#pragma unroll
                for (int jj = 0; jj < 8; jj++) {
                    const int j = rnd * 16 + jj * 2;
                    if (j * 8 < BN) {
                        const int jb = jj * 2 + (lane >> 4);
                        uint32_t addr = stg + (jb >> 3) * 8192 + srow * 128 + (((jb & 7) ^ (srow & 7)) << 4);
                        if (rnd * 128 + 128 > BN && jj >= 4)
                            addr = stg + 8192 + srow * 64 + (((jb & 3) ^ ((srow >> 1) & 3)) << 4);
                        stmatrix_x4(addr, pack_bf16(acc[4 * j + 0], acc[4 * j + 1]), pack_bf16(acc[4 * j + 2], acc[4 * j + 3]),
                                    pack_bf16(acc[4 * j + 4], acc[4 * j + 5]), pack_bf16(acc[4 * j + 6], acc[4 * j + 7]));
                    }
                }
                fence_proxy_async();
                named_bar_sync(1 + c, 128);
                if (tid_wg == 0) {
                    tma_store_2d(mc, stg, out_c0 + rnd * 128, m0 + c * 64);
                    if (rnd * 128 + 64 < BN)
                        tma_store_2d((rnd * 128 + 128 > BN) ? &mC1 : mc, stg + 8192, out_c0 + rnd * 128 + 64, m0 + c * 64);
                    bulk_commit();
                }
            }
        }
        if (tid_wg == 0) bulk_wait0();
        TL_END(MODE)
    }
    cluster_sync_all();
}

#define ATT_SPLIT 16
constexpr int ATT_NTILES = NH * 16;
#define ATT_GRID_N 512
constexpr int ATT_GRID = ATT_GRID_N;
constexpr int ATT_THREADS = 256;
constexpr int ATT_STAGES = 4;
constexpr int ATT_DIST = 2;
constexpr int ATT_Q_OFF = ATT_STAGES * 16384;
constexpr int ATT_ONES_OFF = ATT_Q_OFF + 8192;
constexpr int ATT_KEXT_OFF = ATT_ONES_OFF + 4096;
constexpr int ATT_QEXT_OFF = ATT_KEXT_OFF + 4096;
constexpr int ATT_BAR_OFF = ATT_QEXT_OFF + 8192;
constexpr int ATT_SMEM = ATT_BAR_OFF + 256 + 1024;

__device__ __forceinline__ void row_max(const float (&s)[32], float& m0, float& m1) {
    float a0[8], a1[8];
#pragma unroll
    for (int i = 0; i < 8; i++) {
        a0[i] = fmaxf(s[4 * i], s[4 * i + 1]);
        a1[i] = fmaxf(s[4 * i + 2], s[4 * i + 3]);
    }
#pragma unroll
    for (int w = 4; w > 0; w >>= 1)
#pragma unroll
        for (int i = 0; i < w; i++) { a0[i] = fmaxf(a0[i], a0[i + w]); a1[i] = fmaxf(a1[i], a1[i + w]); }
    float mx0 = a0[0], mx1 = a1[0];
    mx0 = fmaxf(mx0, __shfl_xor_sync(0xffffffffu, mx0, 1));
    mx1 = fmaxf(mx1, __shfl_xor_sync(0xffffffffu, mx1, 1));
    mx0 = fmaxf(mx0, __shfl_xor_sync(0xffffffffu, mx0, 2));
    mx1 = fmaxf(mx1, __shfl_xor_sync(0xffffffffu, mx1, 2));
    m0 = fmaxf(m0, mx0);
    m1 = fmaxf(m1, mx1);
}

__device__ __forceinline__ void attn_step(float (&s)[32], float (&o)[20], uint32_t dq, uint32_t dke, uint32_t dk_next,
                                          uint32_t dv_cur, uint32_t release_bar) {
    constexpr uint32_t HI = desc_hi(512, 2);
    uint32_t p[16];
#pragma unroll
    for (int i = 0; i < 16; i++) p[i] = pack_bf16(ex2(s[2 * i]), ex2(s[2 * i + 1]));
    wgmma_fence();
    wgmma_ss_n64_tb0(s, dq, HI, dk_next, HI, 0);
    wgmma_ss_n64_tb0(s, dq + 2, HI, dk_next + 2, HI, 1);
    wgmma_ss_n64_tb0(s, dq + ((ATT_QEXT_OFF - ATT_Q_OFF) >> 4), HI, dke, HI, 1);
#pragma unroll
    for (int t = 0; t < 4; t++)
        wgmma_rs_n40_tb1(o, p[4 * t], p[4 * t + 1], p[4 * t + 2], p[4 * t + 3], dv_cur + t * 64, HI, 1);
    wgmma_commit();
    wgmma_wait<0>();
    if (release_bar != 0 && (threadIdx.x & 127) == 0) mbar_arrive(release_bar);
}

__global__ void __launch_bounds__(256, 1)
attn_exact_kernel(const __grid_constant__ CUtensorMap mKV) {
    extern __shared__ uint8_t smem_raw[];
    pdl_launch();
    pdl_wait();
    const int tile = blockIdx.x;
    if (g_bad[tile] == 0) return;
    constexpr int NBLK = S_LEN / 128;
    constexpr uint32_t HI = desc_hi(512, 2);
    const uint32_t sbase = (smem_u32(smem_raw) + 1023u) & ~1023u;
    const uint32_t bar = sbase + ATT_BAR_OFF;
    const int warp_id = threadIdx.x >> 5;
    const int lane = threadIdx.x & 31;
    const int cq = (lane & 3) * 2;
    const uint32_t dk0 = desc_lo(sbase, 16);
    const uint32_t dv0 = desc_lo(sbase + 8192, ATT_ONES_OFF - 8192);
    if (threadIdx.x == 0) {
        mbar_init(bar, 1);
        asm volatile("fence.mbarrier_init.release.cluster;" ::: "memory");
    }
    asm volatile("st.shared.v4.b32 [%0], {%1, %1, %1, %1};" ::"r"(sbase + ATT_ONES_OFF + threadIdx.x * 16), "r"(0x3F803F80u) : "memory");
    fence_proxy_async();
    __syncthreads();
    const int head = tile >> 4;
    const int row0 = (tile & 15) * 128 + warp_id * 16 + (lane >> 2);
    const uint32_t dq = desc_lo(sbase + ATT_Q_OFF + (threadIdx.x >> 7) * 4096, 16);
    float o[20];
#pragma unroll
    for (int i = 0; i < 20; i++) o[i] = 0.f;
    float m0 = -INFINITY, m1 = -INFINITY;
#pragma unroll 1
    for (int j = 0; j < NBLK; j++) {
        if (threadIdx.x == 0) {
            mbar_expect_tx(bar, j == 0 ? 3 * 8192 : 2 * 8192);
            if (j == 0) tma_load_2d(sbase + ATT_Q_OFF, &mKV, head * DH, (tile & 15) * 128, bar);
            tma_load_2d(sbase, &mKV, DM + head * DH, j * 128, bar);
            tma_load_2d(sbase + 8192, &mKV, 2 * DM + head * DH, j * 128, bar);
        }
        __syncwarp();
        mbar_wait(bar, j & 1);
#pragma unroll 1
        for (int hf = 0; hf < 2; hf++) {
            float s[32];
            wgmma_fence();
            wgmma_ss_n64_tb0(s, dq, HI, dk0 + hf * 256, HI, 0);
            wgmma_ss_n64_tb0(s, dq + 2, HI, dk0 + hf * 256 + 2, HI, 1);
            wgmma_commit();
            wgmma_wait<0>();
            const float mo0 = m0, mo1 = m1;
            row_max(s, m0, m1);
            const float a0 = ex2(mo0 - m0), a1 = ex2(mo1 - m1);
            uint32_t p[16];
#pragma unroll
            for (int i = 0; i < 8; i++) {
                p[2 * i] = pack_bf16(ex2(s[4 * i + 0] - m0), ex2(s[4 * i + 1] - m0));
                p[2 * i + 1] = pack_bf16(ex2(s[4 * i + 2] - m1), ex2(s[4 * i + 3] - m1));
            }
#pragma unroll
            for (int i = 0; i < 5; i++) {
                o[4 * i + 0] *= a0; o[4 * i + 1] *= a0;
                o[4 * i + 2] *= a1; o[4 * i + 3] *= a1;
            }
            wgmma_fence();
            const uint32_t dv = dv0 + hf * 256 - ((uint32_t)(hf * 256) << 16);
#pragma unroll
            for (int t = 0; t < 4; t++)
                wgmma_rs_n40_tb1(o, p[4 * t], p[4 * t + 1], p[4 * t + 2], p[4 * t + 3], dv + t * 64, HI, 1);
            wgmma_commit();
            wgmma_wait<0>();
        }
        __syncthreads();
    }
    const float f0 = g_gate[row0] / o[16], f1 = g_gate[row0 + 8] / o[18];
    bf16* op0 = g_a5 + (size_t)row0 * A5W + head * DH + cq;
    bf16* op1 = op0 + 8 * A5W;
#pragma unroll
    for (int i = 0; i < 4; i++) {
        *reinterpret_cast<uint32_t*>(op0 + 8 * i) = pack_bf16(o[4 * i] * f0, o[4 * i + 1] * f0);
        *reinterpret_cast<uint32_t*>(op1 + 8 * i) = pack_bf16(o[4 * i + 2] * f1, o[4 * i + 3] * f1);
    }
}

#define ATT_MINB 2
__global__ void __launch_bounds__(256, ATT_MINB)
attn_kernel(const __grid_constant__ CUtensorMap mKV) {
    extern __shared__ uint8_t smem_raw[];
    const uint32_t sbase = (smem_u32(smem_raw) + 1023u) & ~1023u;
    const uint32_t bar_kfull = sbase + ATT_BAR_OFF;
    const uint32_t bar_vfull = bar_kfull + 8 * ATT_STAGES;
    const uint32_t bar_empty = bar_vfull + 8 * ATT_STAGES;
    const int tile = blockIdx.x;
    const int head = tile >> 4;
    const int lane = threadIdx.x & 31;
    constexpr int NBLK = S_LEN / 128;
    TL_START(6)
    pdl_launch();

    auto issue_kv = [&](int g) {
        const int sn = g % ATT_STAGES;
        if (g >= ATT_STAGES) mbar_wait(bar_empty + 8 * sn, ((g / ATT_STAGES) - 1) & 1);
        const uint32_t skn = sbase + sn * 16384;
        mbar_expect_tx(bar_kfull + 8 * sn, g == 0 ? 16384 : 8192);
        if (g == 0) tma_load_2d(sbase + ATT_Q_OFF, &mKV, head * DH, (tile & 15) * 128, bar_kfull);
        tma_load_2d(skn, &mKV, DM + head * DH, g * 128, bar_kfull + 8 * sn);
        mbar_expect_tx(bar_vfull + 8 * sn, 8192);
        tma_load_2d(skn + 8192, &mKV, 2 * DM + head * DH, g * 128, bar_vfull + 8 * sn);
    };

    if (threadIdx.x == 0) {
        for (int s = 0; s < ATT_STAGES; s++) {
            mbar_init(bar_kfull + 8 * s, 1);
            mbar_init(bar_vfull + 8 * s, 1);
            mbar_init(bar_empty + 8 * s, 2);
        }
        asm volatile("fence.mbarrier_init.release.cluster;" ::: "memory");
        prefetch_tmap(&mKV);
        pdl_wait();
#pragma unroll
        for (int j = 0; j < ATT_DIST; j++) issue_kv(j);
    }
    {
        asm volatile("st.shared.v4.b32 [%0], {%1, %1, %1, %1};" ::"r"(sbase + ATT_ONES_OFF + threadIdx.x * 16), "r"(0x3F803F80u) : "memory");
        const int r = threadIdx.x >> 2, ch = threadIdx.x & 3;
        const uint32_t w0 = (ch == ((r >> 1) & 3)) ? 0x00003F80u : 0u;
        asm volatile("st.shared.v4.b32 [%0], {%1, %2, %2, %2};" ::"r"(sbase + ATT_KEXT_OFF + threadIdx.x * 16), "r"(w0), "r"(0u) : "memory");
        asm volatile("st.shared.v4.b32 [%0], {%1, %1, %1, %1};" ::"r"(sbase + ATT_QEXT_OFF + threadIdx.x * 16), "r"(0u) : "memory");
        asm volatile("st.shared.v4.b32 [%0], {%1, %1, %1, %1};" ::"r"(sbase + ATT_QEXT_OFF + 4096 + threadIdx.x * 16), "r"(0u) : "memory");
    }
    fence_proxy_async();
    __syncthreads();

    constexpr uint32_t HI = desc_hi(512, 2);
    const uint32_t dk0 = desc_lo(sbase, 16);
    const uint32_t dv0 = desc_lo(sbase + 8192, ATT_ONES_OFF - 8192);
    const uint32_t dke = dk0 + (ATT_KEXT_OFF >> 4);
    const uint32_t dq = dk0 + ((ATT_Q_OFF + (threadIdx.x >> 7) * 4096) >> 4);
    float o[20];
#pragma unroll
    for (int i = 0; i < 20; i++) o[i] = 0.f;
    float s0[32];
    mbar_wait(bar_kfull, 0);
    wgmma_fence();
    wgmma_ss_n64_tb0(s0, dq, HI, dk0, HI, 0);
    wgmma_ss_n64_tb0(s0, dq + 2, HI, dk0 + 2, HI, 1);
    wgmma_commit();
    wgmma_wait<0>();
    float m0 = -INFINITY, m1 = -INFINITY;
    row_max(s0, m0, m1);
    if ((lane & 3) == 0) {
        const int r = ((threadIdx.x >> 5) & 3) * 16 + (lane >> 2);
        const uint32_t qe = sbase + ATT_QEXT_OFF + (threadIdx.x >> 7) * 4096;
        asm volatile("st.shared.b16 [%0], %1;" ::"r"(qe + r * 64 + (((r >> 1) & 3) << 4)), "h"((uint16_t)(pack_bf16(-m0, 0.f) & 0xFFFFu)) : "memory");
        asm volatile("st.shared.b16 [%0], %1;" ::"r"(qe + (r + 8) * 64 + ((((r + 8) >> 1) & 3) << 4)), "h"((uint16_t)(pack_bf16(-m1, 0.f) & 0xFFFFu)) : "memory");
    }
    fence_proxy_async();
    named_bar_sync(1 + (threadIdx.x >> 7), 128);
    wgmma_fence();
    wgmma_ss_n64_tb0(s0, dq + ((ATT_QEXT_OFF - ATT_Q_OFF) >> 4), HI, dke, HI, 1);
    wgmma_commit();
    wgmma_wait<0>();
#pragma unroll 1
    for (int j = 0; j < NBLK; j++) {
        if (threadIdx.x == 0 && j + ATT_DIST < NBLK) issue_kv(j + ATT_DIST);
        __syncwarp();
        const uint32_t stage = j & (ATT_STAGES - 1), nstage = (j + 1) & (ATT_STAGES - 1);
        const uint32_t dk = dk0 + stage * 1024;
        const uint32_t dv = dv0 + stage * 1024 - (stage << 26);
        mbar_wait(bar_vfull + 8 * stage, (j / ATT_STAGES) & 1);
        attn_step(s0, o, dq, dke, dk + 256, dv, 0u);
        uint32_t dkn = dk;
        if (j + 1 < NBLK) {
            mbar_wait(bar_kfull + 8 * nstage, ((j + 1) / ATT_STAGES) & 1);
            dkn = dk0 + nstage * 1024;
        }
        attn_step(s0, o, dq, dke, dkn, dv + 256 - (256u << 16), bar_empty + 8 * stage);
    }
    bool ok = (o[16] <= 1.8446744e19f) && (o[18] <= 1.8446744e19f);
#pragma unroll
    for (int i = 0; i < 16; i++) ok = ok && (fabsf(o[i]) <= 3.0e38f);
    const int row0 = (tile & 15) * 128 + (threadIdx.x >> 5) * 16 + (lane >> 2);
    const float f0 = g_gate[row0] / o[16], f1 = g_gate[row0 + 8] / o[18];
    bf16* op0 = g_a5 + (size_t)row0 * A5W + head * DH + (lane & 3) * 2;
    bf16* op1 = op0 + 8 * A5W;
#pragma unroll
    for (int i = 0; i < 4; i++) {
        *reinterpret_cast<uint32_t*>(op0 + 8 * i) = pack_bf16(o[4 * i] * f0, o[4 * i + 1] * f0);
        *reinterpret_cast<uint32_t*>(op1 + 8 * i) = pack_bf16(o[4 * i + 2] * f1, o[4 * i + 3] * f1);
    }
    const int bad = __syncthreads_or(!ok);
    if (threadIdx.x == 0) g_bad[tile] = bad;
    TL_END(6)
}

typedef CUresult (*EncodeFn)(CUtensorMap*, CUtensorMapDataType, cuuint32_t, void*, const cuuint64_t*, const cuuint64_t*,
                             const cuuint32_t*, const cuuint32_t*, CUtensorMapInterleave, CUtensorMapSwizzle,
                             CUtensorMapL2promotion, CUtensorMapFloatOOBfill);

static CUtensorMap make_map(EncodeFn fn, const void* ptr, int rows, int cols, int box_cols, int box_rows,
                            CUtensorMapSwizzle swz) {
    CUtensorMap m;
    cuuint64_t dims[2] = {(cuuint64_t)cols, (cuuint64_t)rows};
    cuuint64_t strides[1] = {(cuuint64_t)cols * 2};
    cuuint32_t box[2] = {(cuuint32_t)box_cols, (cuuint32_t)box_rows};
    cuuint32_t es[2] = {1, 1};
    fn(&m, CU_TENSOR_MAP_DATA_TYPE_BFLOAT16, 2, const_cast<void*>(ptr), dims, strides, box, es,
       CU_TENSOR_MAP_INTERLEAVE_NONE, swz, CU_TENSOR_MAP_L2_PROMOTION_L2_256B, CU_TENSOR_MAP_FLOAT_OOB_FILL_NONE);
    return m;
}

template <typename... KArgs, typename... Args>
static void launch_ex(void (*kern)(KArgs...), int grid, int block, int smem, cudaStream_t st, int cluster, int pdl, Args... args) {
    cudaLaunchConfig_t cfg = {};
    cfg.gridDim = dim3(grid);
    cfg.blockDim = dim3(block);
    cfg.dynamicSmemBytes = smem;
    cfg.stream = st;
    cudaLaunchAttribute at[2];
    at[0].id = cudaLaunchAttributeProgrammaticStreamSerialization;
    at[0].val.programmaticStreamSerializationAllowed = pdl;
    at[1].id = cudaLaunchAttributeClusterDimension;
    at[1].val.clusterDim.x = cluster;
    at[1].val.clusterDim.y = 1;
    at[1].val.clusterDim.z = 1;
    cfg.attrs = at;
    cfg.numAttrs = cluster > 1 ? 2 : 1;
    cudaLaunchKernelEx(&cfg, kern, KArgs(args)...);
}

extern "C" void kernel_launch(void* const* d_in, const int* in_sizes, int n_in, void* d_out, int out_size) {
    const bf16* x = (const bf16*)d_in[0];
    const bf16* wqkv = (const bf16*)d_in[1];
    const bf16* wo = (const bf16*)d_in[2];
    const bf16* w1 = (const bf16*)d_in[4];
    const bf16* w2 = (const bf16*)d_in[5];
    const bf16* w3 = (const bf16*)d_in[6];
    const bf16* w4 = (const bf16*)d_in[7];
    const bf16* gate_w = (const bf16*)d_in[8];

    static EncodeFn enc = nullptr;
    static void *p_qkv, *p_h, *p_x1, *p_a5;
    static cudaStream_t s2;
    static cudaEvent_t ev_fork, ev_join;
    using G1 = GemmSmem<256, 4>;
    using G2 = GemmSmem<128, 5>;
    using G3 = GemmSmem<224, 4>;
    if (!enc) {
        void* fn = nullptr;
        cudaDriverEntryPointQueryResult qres;
        cudaGetDriverEntryPoint("cuTensorMapEncodeTiled", &fn, cudaEnableDefault, &qres);
        enc = (EncodeFn)fn;
        cudaGetSymbolAddress(&p_qkv, g_qkv);
        cudaGetSymbolAddress(&p_h, g_h);
        cudaGetSymbolAddress(&p_x1, g_x1);
        cudaGetSymbolAddress(&p_a5, g_a5);
        cudaFuncSetAttribute(gemm_kernel<1, 256, 4>, cudaFuncAttributeMaxDynamicSharedMemorySize, G1::TOTAL);
        cudaFuncSetAttribute(gemm_kernel<2, 128, 5>, cudaFuncAttributeMaxDynamicSharedMemorySize, G2::TOTAL);
        cudaFuncSetAttribute(gemm_kernel<3, 224, 4>, cudaFuncAttributeMaxDynamicSharedMemorySize, G3::TOTAL);
        cudaFuncSetAttribute(gemm_kernel<5, 128, 5>, cudaFuncAttributeMaxDynamicSharedMemorySize, G2::TOTAL);
        cudaStreamCreateWithFlags(&s2, cudaStreamNonBlocking);
        cudaEventCreateWithFlags(&ev_fork, cudaEventDisableTiming);
        cudaEventCreateWithFlags(&ev_join, cudaEventDisableTiming);
        cudaFuncSetAttribute(attn_kernel, cudaFuncAttributeMaxDynamicSharedMemorySize, ATT_SMEM);
        cudaFuncSetAttribute(attn_exact_kernel, cudaFuncAttributeMaxDynamicSharedMemorySize, ATT_SMEM);
    }
    const CUtensorMapSwizzle SW128 = CU_TENSOR_MAP_SWIZZLE_128B, SW64 = CU_TENSOR_MAP_SWIZZLE_64B;
    CUtensorMap mX = make_map(enc, x, S_LEN, DM, 64, 128, SW128);
    CUtensorMap mWqkv = make_map(enc, wqkv, DM, 3 * DM, 64, 64, SW128);
    CUtensorMap mW1 = make_map(enc, w1, DM, DM, 64, 64, SW128);
    CUtensorMap mW2 = make_map(enc, w2, DM, DM, 64, 64, SW128);
    CUtensorMap mW3 = make_map(enc, w3, DM, FF, 64, 64, SW128);
    CUtensorMap mW4 = make_map(enc, w4, FF, DM, 64, 64, SW128);
    CUtensorMap mWo = make_map(enc, wo, DM, DM, 64, 64, SW128);
    CUtensorMap mQKVst = make_map(enc, p_qkv, S_LEN, 3 * DM, 64, 64, SW128);
    CUtensorMap mKV = make_map(enc, p_qkv, S_LEN, 3 * DM, 32, 128, SW64);
    CUtensorMap mHst = make_map(enc, p_h, S_LEN, DM, 64, 64, SW128);
    CUtensorMap mHld = make_map(enc, p_h, S_LEN, DM, 64, 128, SW128);
    CUtensorMap mX1st = make_map(enc, p_x1, S_LEN, DM, 64, 64, SW128);
    CUtensorMap mX1ld = make_map(enc, p_x1, S_LEN, DM, 64, 128, SW128);
    CUtensorMap mA5st = make_map(enc, p_a5, S_LEN, A5W, 64, 64, SW128);
    CUtensorMap mA5st32 = make_map(enc, p_a5, S_LEN, A5W, 32, 64, SW64);
    CUtensorMap mA5ld = make_map(enc, p_a5, S_LEN, A5W, 64, 128, SW128);
    CUtensorMap mOut = make_map(enc, d_out, S_LEN, DM, 64, 64, SW128);

    cudaStream_t st = cudaStreamPerThread;
    prep_kernel<<<256 + 72, 256, 0, st>>>(x, gate_w, w1, w3);
    launch_ex(gemm_kernel<1, 256, 4>, 132, 384, G1::TOTAL, st, 2, 1, mX, mWqkv, mW1, mQKVst, mHst, x, 16, 16);
    cudaEventRecord(ev_fork, st);
    launch_ex(attn_kernel, ATT_GRID, ATT_THREADS, ATT_SMEM, st, 1, 1, mKV);
    launch_ex(attn_exact_kernel, ATT_NTILES, ATT_THREADS, ATT_SMEM, st, 1, 1, mKV);
    cudaStreamWaitEvent(s2, ev_fork, 0);
    launch_ex(gemm_kernel<2, 128, 5>, 128, 384, G2::TOTAL, s2, 2, 0, mHld, mW2, mW2, mX1st, mX1st, x, 8, 16);
    launch_ex(gemm_kernel<3, 224, 4>, 132, 384, G3::TOTAL, s2, 2, 1, mX1ld, mW3, mW3, mA5st, mA5st32, x, 16, 16);
    cudaEventRecord(ev_join, s2);
    cudaStreamWaitEvent(st, ev_join, 0);
    launch_ex(gemm_kernel<5, 128, 5>, 128, 384, G2::TOTAL, st, 2, 0, mA5ld, mWo, mW4, mOut, mOut, (const bf16*)p_x1, 8, 72);
}
```

```cpp
#include <cuda_runtime.h>
#include <cuda_bf16.h>
#include <cuda.h>
#include <stdint.h>

typedef __nv_bfloat16 bf16;

constexpr int S_LEN = 2048;
constexpr int DM = 1024;
constexpr int FF = 3584;
constexpr int NH = 32;
constexpr int DH = 32;
constexpr int A5W = DM + FF;

__device__ __align__(1024) bf16 g_qkv[S_LEN * 3 * DM];
__device__ __align__(1024) bf16 g_h[S_LEN * DM];
__device__ __align__(1024) bf16 g_x1[S_LEN * DM];
__device__ __align__(1024) bf16 g_a5[S_LEN * A5W];
__device__ __align__(16) float g_mean1[S_LEN];
__device__ __align__(16) float g_rstd1[S_LEN];
__device__ __align__(16) float g_gate[S_LEN];
__device__ __align__(16) float g_omg[S_LEN];
__device__ __align__(16) float g_cs1[DM];
__device__ __align__(16) float g_cs3[FF];
__device__ __align__(16) float2 g_stat2[S_LEN * 8];
__device__ int g_bad[NH * 16];

#define TL_START(k)
#define TL_END(k)

__device__ __forceinline__ uint32_t smem_u32(const void* p) { return (uint32_t)__cvta_generic_to_shared(p); }

__device__ __forceinline__ void mbar_init(uint32_t bar, uint32_t count) {
    asm volatile("mbarrier.init.shared::cta.b64 [%0], %1;" ::"r"(bar), "r"(count));
}
__device__ __forceinline__ void mbar_expect_tx(uint32_t bar, uint32_t bytes) {
    asm volatile("mbarrier.arrive.expect_tx.shared::cta.b64 _, [%0], %1;" ::"r"(bar), "r"(bytes) : "memory");
}
__device__ __forceinline__ void mbar_arrive(uint32_t bar) {
    asm volatile("mbarrier.arrive.shared::cta.b64 _, [%0];" ::"r"(bar) : "memory");
}
__device__ __forceinline__ bool mbar_try_wait(uint32_t bar, uint32_t parity) {
    uint32_t ok;
    asm volatile(
        "{\n.reg .pred p;\n"
        "mbarrier.try_wait.parity.shared::cta.b64 p, [%1], %2;\n"
        "selp.u32 %0, 1, 0, p;\n}\n"
        : "=r"(ok)
        : "r"(bar), "r"(parity)
        : "memory");
    return ok != 0;
}
__device__ __forceinline__ void mbar_wait(uint32_t bar, uint32_t parity) {
    uint32_t spins = 0;
    while (!mbar_try_wait(bar, parity)) {
        if (++spins > (1u << 24)) __trap();
    }
}
__device__ __forceinline__ void tma_load_2d(uint32_t dst, const CUtensorMap* map, int c0, int c1, uint32_t bar) {
    asm volatile(
        "cp.async.bulk.tensor.2d.shared::cluster.global.mbarrier::complete_tx::bytes [%0], [%1, {%3, %4}], [%2];"
        ::"r"(dst), "l"(map), "r"(bar), "r"(c0), "r"(c1)
        : "memory");
}
__device__ __forceinline__ void tma_store_2d(const CUtensorMap* map, uint32_t src, int c0, int c1) {
    asm volatile("cp.async.bulk.tensor.2d.global.shared::cta.bulk_group [%0, {%2, %3}], [%1];"
                 ::"l"(map), "r"(src), "r"(c0), "r"(c1)
                 : "memory");
}
__device__ __forceinline__ void tma_load_2d_mc(uint32_t dst, const CUtensorMap* map, int c0, int c1, uint32_t bar, uint16_t mask) {
    asm volatile(
        "cp.async.bulk.tensor.2d.shared::cluster.global.mbarrier::complete_tx::bytes.multicast::cluster [%0], [%1, {%3, %4}], [%2], %5;"
        ::"r"(dst), "l"(map), "r"(bar), "r"(c0), "r"(c1), "h"(mask)
        : "memory");
}
__device__ __forceinline__ void mbar_arrive_cluster(uint32_t bar, uint32_t cta) {
    asm volatile(
        "{\n.reg .b32 ra;\nmapa.shared::cluster.u32 ra, %0, %1;\n"
        "mbarrier.arrive.shared::cluster.b64 _, [ra];\n}\n" ::"r"(bar), "r"(cta)
        : "memory");
}
__device__ __forceinline__ void cluster_sync_all() {
    asm volatile("barrier.cluster.arrive.release.aligned;\nbarrier.cluster.wait.acquire.aligned;" ::: "memory");
}
__device__ __forceinline__ uint32_t cluster_rank() { uint32_t r; asm volatile("mov.u32 %0, %%cluster_ctarank;" : "=r"(r)); return r; }
__device__ __forceinline__ void pdl_wait() { asm volatile("griddepcontrol.wait;" ::: "memory"); }
__device__ __forceinline__ void pdl_launch() { asm volatile("griddepcontrol.launch_dependents;" ::: "memory"); }
__device__ __forceinline__ void bulk_commit() { asm volatile("cp.async.bulk.commit_group;" ::: "memory"); }
__device__ __forceinline__ void bulk_wait_read0() { asm volatile("cp.async.bulk.wait_group.read 0;" ::: "memory"); }
__device__ __forceinline__ void bulk_wait0() { asm volatile("cp.async.bulk.wait_group 0;" ::: "memory"); }
__device__ __forceinline__ void fence_proxy_async() { asm volatile("fence.proxy.async.shared::cta;" ::: "memory"); }
__device__ __forceinline__ void named_bar_sync(int id, int n) { asm volatile("bar.sync %0, %1;" ::"r"(id), "r"(n) : "memory"); }
__device__ __forceinline__ void named_bar_arrive(int id, int n) { asm volatile("bar.arrive %0, %1;" ::"r"(id), "r"(n) : "memory"); }
__device__ __forceinline__ void wgmma_fence() { asm volatile("wgmma.fence.sync.aligned;" ::: "memory"); }
__device__ __forceinline__ void wgmma_commit() { asm volatile("wgmma.commit_group.sync.aligned;" ::: "memory"); }
template <int N>
__device__ __forceinline__ void wgmma_wait() { asm volatile("wgmma.wait_group.sync.aligned %0;" ::"n"(N) : "memory"); }
__device__ __forceinline__ void prefetch_tmap(const CUtensorMap* m) {
    asm volatile("prefetch.tensormap [%0];" ::"l"(m) : "memory");
}
template <int R>
__device__ __forceinline__ void reg_alloc() { asm volatile("setmaxnreg.inc.sync.aligned.u32 %0;" ::"n"(R)); }
template <int R>
__device__ __forceinline__ void reg_dealloc() { asm volatile("setmaxnreg.dec.sync.aligned.u32 %0;" ::"n"(R)); }
__device__ __forceinline__ void stmatrix_x4(uint32_t addr, uint32_t r0, uint32_t r1, uint32_t r2, uint32_t r3) {
    asm volatile("stmatrix.sync.aligned.m8n8.x4.shared.b16 [%0], {%1, %2, %3, %4};"
                 ::"r"(addr), "r"(r0), "r"(r1), "r"(r2), "r"(r3)
                 : "memory");
}
__device__ __forceinline__ uint32_t pack_bf16(float lo, float hi) {
    uint32_t r;
    asm("cvt.rn.bf16x2.f32 %0, %1, %2;" : "=r"(r) : "f"(hi), "f"(lo));
    return r;
}
__device__ __forceinline__ float bf16_round(float v) { return __bfloat162float(__float2bfloat16_rn(v)); }
__device__ __forceinline__ float ex2(float x) {
    float y;
    asm volatile("ex2.approx.ftz.f32 %0, %1;" : "=f"(y) : "f"(x));
    return y;
}
__device__ __forceinline__ float tanh_fast(float x) {
    float y;
    asm("tanh.approx.f32 %0, %1;" : "=f"(y) : "f"(x));
    return y;
}
__device__ __forceinline__ float gelu_tanh(float v) {
    float u = 0.7978845608028654f * (v + 0.044715f * v * v * v);
    float hv = 0.5f * v;
    return fmaf(hv, tanh_fast(u), hv);
}
__device__ __forceinline__ uint32_t desc_lo(uint32_t addr, uint32_t lbo_bytes) {
    return ((addr & 0x3FFFF) >> 4) | (((lbo_bytes >> 4) & 0x3FFF) << 16);
}
__host__ __device__ constexpr uint32_t desc_hi(uint32_t sbo_bytes, uint32_t swz) {
    return ((sbo_bytes >> 4) & 0x3FFF) | (swz << 30);
}

__device__ __forceinline__ void wgmma_ss_n128_tb1(float (&d)[64], uint32_t alo, uint32_t ahi, uint32_t blo, uint32_t bhi, int scale_d) {
    asm volatile("{\n.reg .pred p;\n.reg .b64 da, db;\nsetp.ne.b32 p, %68, 0;\nmov.b64 da, {%64, %65};\nmov.b64 db, {%66, %67};\n"
        "wgmma.mma_async.sync.aligned.m64n128k16.f32.bf16.bf16 {%0, %1, %2, %3, %4, %5, %6, %7, %8, %9, %10, %11, %12, %13, %14, %15, %16, %17, %18, %19, %20, %21, %22, %23, %24, %25, %26, %27, %28, %29, %30, %31, %32, %33, %34, %35, %36, %37, %38, %39, %40, %41, %42, %43, %44, %45, %46, %47, %48, %49, %50, %51, %52, %53, %54, %55, %56, %57, %58, %59, %60, %61, %62, %63}, da, db, p, 1, 1, 0, 1;\n}\n"
        : "+f"(d[0]), "+f"(d[1]), "+f"(d[2]), "+f"(d[3]), "+f"(d[4]), "+f"(d[5]), "+f"(d[6]), "+f"(d[7]), "+f"(d[8]), "+f"(d[9]), "+f"(d[10]), "+f"(d[11]), "+f"(d[12]), "+f"(d[13]), "+f"(d[14]), "+f"(d[15]), "+f"(d[16]), "+f"(d[17]), "+f"(d[18]), "+f"(d[19]), "+f"(d[20]), "+f"(d[21]), "+f"(d[22]), "+f"(d[23]), "+f"(d[24]), "+f"(d[25]), "+f"(d[26]), "+f"(d[27]), "+f"(d[28]), "+f"(d[29]), "+f"(d[30]), "+f"(d[31]), "+f"(d[32]), "+f"(d[33]), "+f"(d[34]), "+f"(d[35]), "+f"(d[36]), "+f"(d[37]), "+f"(d[38]), "+f"(d[39]), "+f"(d[40]), "+f"(d[41]), "+f"(d[42]), "+f"(d[43]), "+f"(d[44]), "+f"(d[45]), "+f"(d[46]), "+f"(d[47]), "+f"(d[48]), "+f"(d[49]), "+f"(d[50]), "+f"(d[51]), "+f"(d[52]), "+f"(d[53]), "+f"(d[54]), "+f"(d[55]), "+f"(d[56]), "+f"(d[57]), "+f"(d[58]), "+f"(d[59]), "+f"(d[60]), "+f"(d[61]), "+f"(d[62]), "+f"(d[63])
        : "r"(alo), "r"(ahi), "r"(blo), "r"(bhi), "r"(scale_d));
}

__device__ __forceinline__ void wgmma_ss_n192_tb1(float (&d)[96], uint32_t alo, uint32_t ahi, uint32_t blo, uint32_t bhi, int scale_d) {
    asm volatile("{\n.reg .pred p;\n.reg .b64 da, db;\nsetp.ne.b32 p, %100, 0;\nmov.b64 da, {%96, %97};\nmov.b64 db, {%98, %99};\n"
        "wgmma.mma_async.sync.aligned.m64n192k16.f32.bf16.bf16 {%0, %1, %2, %3, %4, %5, %6, %7, %8, %9, %10, %11, %12, %13, %14, %15, %16, %17, %18, %19, %20, %21, %22, %23, %24, %25, %26, %27, %28, %29, %30, %31, %32, %33, %34, %35, %36, %37, %38, %39, %40, %41, %42, %43, %44, %45, %46, %47, %48, %49, %50, %51, %52, %53, %54, %55, %56, %57, %58, %59, %60, %61, %62, %63, %64, %65, %66, %67, %68, %69, %70, %71, %72, %73, %74, %75, %76, %77, %78, %79, %80, %81, %82, %83, %84, %85, %86, %87, %88, %89, %90, %91, %92, %93, %94, %95}, da, db, p, 1, 1, 0, 1;\n}\n"
        : "+f"(d[0]), "+f"(d[1]), "+f"(d[2]), "+f"(d[3]), "+f"(d[4]), "+f"(d[5]), "+f"(d[6]), "+f"(d[7]), "+f"(d[8]), "+f"(d[9]), "+f"(d[10]), "+f"(d[11]), "+f"(d[12]), "+f"(d[13]), "+f"(d[14]), "+f"(d[15]), "+f"(d[16]), "+f"(d[17]), "+f"(d[18]), "+f"(d[19]), "+f"(d[20]), "+f"(d[21]), "+f"(d[22]), "+f"(d[23]), "+f"(d[24]), "+f"(d[25]), "+f"(d[26]), "+f"(d[27]), "+f"(d[28]), "+f"(d[29]), "+f"(d[30]), "+f"(d[31]), "+f"(d[32]), "+f"(d[33]), "+f"(d[34]), "+f"(d[35]), "+f"(d[36]), "+f"(d[37]), "+f"(d[38]), "+f"(d[39]), "+f"(d[40]), "+f"(d[41]), "+f"(d[42]), "+f"(d[43]), "+f"(d[44]), "+f"(d[45]), "+f"(d[46]), "+f"(d[47]), "+f"(d[48]), "+f"(d[49]), "+f"(d[50]), "+f"(d[51]), "+f"(d[52]), "+f"(d[53]), "+f"(d[54]), "+f"(d[55]), "+f"(d[56]), "+f"(d[57]), "+f"(d[58]), "+f"(d[59]), "+f"(d[60]), "+f"(d[61]), "+f"(d[62]), "+f"(d[63]), "+f"(d[64]), "+f"(d[65]), "+f"(d[66]), "+f"(d[67]), "+f"(d[68]), "+f"(d[69]), "+f"(d[70]), "+f"(d[71]), "+f"(d[72]), "+f"(d[73]), "+f"(d[74]), "+f"(d[75]), "+f"(d[76]), "+f"(d[77]), "+f"(d[78]), "+f"(d[79]), "+f"(d[80]), "+f"(d[81]), "+f"(d[82]), "+f"(d[83]), "+f"(d[84]), "+f"(d[85]), "+f"(d[86]), "+f"(d[87]), "+f"(d[88]), "+f"(d[89]), "+f"(d[90]), "+f"(d[91]), "+f"(d[92]), "+f"(d[93]), "+f"(d[94]), "+f"(d[95])
        : "r"(alo), "r"(ahi), "r"(blo), "r"(bhi), "r"(scale_d));
}

__device__ __forceinline__ void wgmma_ss_n224_tb1(float (&d)[112], uint32_t alo, uint32_t ahi, uint32_t blo, uint32_t bhi, int scale_d) {
    asm volatile("{\n.reg .pred p;\n.reg .b64 da, db;\nsetp.ne.b32 p, %116, 0;\nmov.b64 da, {%112, %113};\nmov.b64 db, {%114, %115};\n"
        "wgmma.mma_async.sync.aligned.m64n224k16.f32.bf16.bf16 {%0, %1, %2, %3, %4, %5, %6, %7, %8, %9, %10, %11, %12, %13, %14, %15, %16, %17, %18, %19, %20, %21, %22, %23, %24, %25, %26, %27, %28, %29, %30, %31, %32, %33, %34, %35, %36, %37, %38, %39, %40, %41, %42, %43, %44, %45, %46, %47, %48, %49, %50, %51, %52, %53, %54, %55, %56, %57, %58, %59, %60, %61, %62, %63, %64, %65, %66, %67, %68, %69, %70, %71, %72, %73, %74, %75, %76, %77, %78, %79, %80, %81, %82, %83, %84, %85, %86, %87, %88, %89, %90, %91, %92, %93, %94, %95, %96, %97, %98, %99, %100, %101, %102, %103, %104, %105, %106, %107, %108, %109, %110, %111}, da, db, p, 1, 1, 0, 1;\n}\n"
        : "+f"(d[0]), "+f"(d[1]), "+f"(d[2]), "+f"(d[3]), "+f"(d[4]), "+f"(d[5]), "+f"(d[6]), "+f"(d[7]), "+f"(d[8]), "+f"(d[9]), "+f"(d[10]), "+f"(d[11]), "+f"(d[12]), "+f"(d[13]), "+f"(d[14]), "+f"(d[15]), "+f"(d[16]), "+f"(d[17]), "+f"(d[18]), "+f"(d[19]), "+f"(d[20]), "+f"(d[21]), "+f"(d[22]), "+f"(d[23]), "+f"(d[24]), "+f"(d[25]), "+f"(d[26]), "+f"(d[27]), "+f"(d[28]), "+f"(d[29]), "+f"(d[30]), "+f"(d[31]), "+f"(d[32]), "+f"(d[33]), "+f"(d[34]), "+f"(d[35]), "+f"(d[36]), "+f"(d[37]), "+f"(d[38]), "+f"(d[39]), "+f"(d[40]), "+f"(d[41]), "+f"(d[42]), "+f"(d[43]), "+f"(d[44]), "+f"(d[45]), "+f"(d[46]), "+f"(d[47]), "+f"(d[48]), "+f"(d[49]), "+f"(d[50]), "+f"(d[51]), "+f"(d[52]), "+f"(d[53]), "+f"(d[54]), "+f"(d[55]), "+f"(d[56]), "+f"(d[57]), "+f"(d[58]), "+f"(d[59]), "+f"(d[60]), "+f"(d[61]), "+f"(d[62]), "+f"(d[63]), "+f"(d[64]), "+f"(d[65]), "+f"(d[66]), "+f"(d[67]), "+f"(d[68]), "+f"(d[69]), "+f"(d[70]), "+f"(d[71]), "+f"(d[72]), "+f"(d[73]), "+f"(d[74]), "+f"(d[75]), "+f"(d[76]), "+f"(d[77]), "+f"(d[78]), "+f"(d[79]), "+f"(d[80]), "+f"(d[81]), "+f"(d[82]), "+f"(d[83]), "+f"(d[84]), "+f"(d[85]), "+f"(d[86]), "+f"(d[87]), "+f"(d[88]), "+f"(d[89]), "+f"(d[90]), "+f"(d[91]), "+f"(d[92]), "+f"(d[93]), "+f"(d[94]), "+f"(d[95]), "+f"(d[96]), "+f"(d[97]), "+f"(d[98]), "+f"(d[99]), "+f"(d[100]), "+f"(d[101]), "+f"(d[102]), "+f"(d[103]), "+f"(d[104]), "+f"(d[105]), "+f"(d[106]), "+f"(d[107]), "+f"(d[108]), "+f"(d[109]), "+f"(d[110]), "+f"(d[111])
        : "r"(alo), "r"(ahi), "r"(blo), "r"(bhi), "r"(scale_d));
}

__device__ __forceinline__ void wgmma_ss_n256_tb1(float (&d)[128], uint32_t alo, uint32_t ahi, uint32_t blo, uint32_t bhi, int scale_d) {
    asm volatile("{\n.reg .pred p;\n.reg .b64 da, db;\nsetp.ne.b32 p, %132, 0;\nmov.b64 da, {%128, %129};\nmov.b64 db, {%130, %131};\n"
        "wgmma.mma_async.sync.aligned.m64n256k16.f32.bf16.bf16 {%0, %1, %2, %3, %4, %5, %6, %7, %8, %9, %10, %11, %12, %13, %14, %15, %16, %17, %18, %19, %20, %21, %22, %23, %24, %25, %26, %27, %28, %29, %30, %31, %32, %33, %34, %35, %36, %37, %38, %39, %40, %41, %42, %43, %44, %45, %46, %47, %48, %49, %50, %51, %52, %53, %54, %55, %56, %57, %58, %59, %60, %61, %62, %63, %64, %65, %66, %67, %68, %69, %70, %71, %72, %73, %74, %75, %76, %77, %78, %79, %80, %81, %82, %83, %84, %85, %86, %87, %88, %89, %90, %91, %92, %93, %94, %95, %96, %97, %98, %99, %100, %101, %102, %103, %104, %105, %106, %107, %108, %109, %110, %111, %112, %113, %114, %115, %116, %117, %118, %119, %120, %121, %122, %123, %124, %125, %126, %127}, da, db, p, 1, 1, 0, 1;\n}\n"
        : "+f"(d[0]), "+f"(d[1]), "+f"(d[2]), "+f"(d[3]), "+f"(d[4]), "+f"(d[5]), "+f"(d[6]), "+f"(d[7]), "+f"(d[8]), "+f"(d[9]), "+f"(d[10]), "+f"(d[11]), "+f"(d[12]), "+f"(d[13]), "+f"(d[14]), "+f"(d[15]), "+f"(d[16]), "+f"(d[17]), "+f"(d[18]), "+f"(d[19]), "+f"(d[20]), "+f"(d[21]), "+f"(d[22]), "+f"(d[23]), "+f"(d[24]), "+f"(d[25]), "+f"(d[26]), "+f"(d[27]), "+f"(d[28]), "+f"(d[29]), "+f"(d[30]), "+f"(d[31]), "+f"(d[32]), "+f"(d[33]), "+f"(d[34]), "+f"(d[35]), "+f"(d[36]), "+f"(d[37]), "+f"(d[38]), "+f"(d[39]), "+f"(d[40]), "+f"(d[41]), "+f"(d[42]), "+f"(d[43]), "+f"(d[44]), "+f"(d[45]), "+f"(d[46]), "+f"(d[47]), "+f"(d[48]), "+f"(d[49]), "+f"(d[50]), "+f"(d[51]), "+f"(d[52]), "+f"(d[53]), "+f"(d[54]), "+f"(d[55]), "+f"(d[56]), "+f"(d[57]), "+f"(d[58]), "+f"(d[59]), "+f"(d[60]), "+f"(d[61]), "+f"(d[62]), "+f"(d[63]), "+f"(d[64]), "+f"(d[65]), "+f"(d[66]), "+f"(d[67]), "+f"(d[68]), "+f"(d[69]), "+f"(d[70]), "+f"(d[71]), "+f"(d[72]), "+f"(d[73]), "+f"(d[74]), "+f"(d[75]), "+f"(d[76]), "+f"(d[77]), "+f"(d[78]), "+f"(d[79]), "+f"(d[80]), "+f"(d[81]), "+f"(d[82]), "+f"(d[83]), "+f"(d[84]), "+f"(d[85]), "+f"(d[86]), "+f"(d[87]), "+f"(d[88]), "+f"(d[89]), "+f"(d[90]), "+f"(d[91]), "+f"(d[92]), "+f"(d[93]), "+f"(d[94]), "+f"(d[95]), "+f"(d[96]), "+f"(d[97]), "+f"(d[98]), "+f"(d[99]), "+f"(d[100]), "+f"(d[101]), "+f"(d[102]), "+f"(d[103]), "+f"(d[104]), "+f"(d[105]), "+f"(d[106]), "+f"(d[107]), "+f"(d[108]), "+f"(d[109]), "+f"(d[110]), "+f"(d[111]), "+f"(d[112]), "+f"(d[113]), "+f"(d[114]), "+f"(d[115]), "+f"(d[116]), "+f"(d[117]), "+f"(d[118]), "+f"(d[119]), "+f"(d[120]), "+f"(d[121]), "+f"(d[122]), "+f"(d[123]), "+f"(d[124]), "+f"(d[125]), "+f"(d[126]), "+f"(d[127])
        : "r"(alo), "r"(ahi), "r"(blo), "r"(bhi), "r"(scale_d));
}

__device__ __forceinline__ void wgmma_ss_n64_tb0(float (&d)[32], uint32_t alo, uint32_t ahi, uint32_t blo, uint32_t bhi, int scale_d) {
    asm volatile("{\n.reg .pred p;\n.reg .b64 da, db;\nsetp.ne.b32 p, %36, 0;\nmov.b64 da, {%32, %33};\nmov.b64 db, {%34, %35};\n"
        "wgmma.mma_async.sync.aligned.m64n64k16.f32.bf16.bf16 {%0, %1, %2, %3, %4, %5, %6, %7, %8, %9, %10, %11, %12, %13, %14, %15, %16, %17, %18, %19, %20, %21, %22, %23, %24, %25, %26, %27, %28, %29, %30, %31}, da, db, p, 1, 1, 0, 0;\n}\n"
        : "+f"(d[0]), "+f"(d[1]), "+f"(d[2]), "+f"(d[3]), "+f"(d[4]), "+f"(d[5]), "+f"(d[6]), "+f"(d[7]), "+f"(d[8]), "+f"(d[9]), "+f"(d[10]), "+f"(d[11]), "+f"(d[12]), "+f"(d[13]), "+f"(d[14]), "+f"(d[15]), "+f"(d[16]), "+f"(d[17]), "+f"(d[18]), "+f"(d[19]), "+f"(d[20]), "+f"(d[21]), "+f"(d[22]), "+f"(d[23]), "+f"(d[24]), "+f"(d[25]), "+f"(d[26]), "+f"(d[27]), "+f"(d[28]), "+f"(d[29]), "+f"(d[30]), "+f"(d[31])
        : "r"(alo), "r"(ahi), "r"(blo), "r"(bhi), "r"(scale_d));
}

__device__ __forceinline__ void wgmma_rs_n128_tb0(float (&d)[64], uint32_t a0, uint32_t a1, uint32_t a2, uint32_t a3, uint32_t blo, uint32_t bhi, int scale_d) {
    asm volatile("{\n.reg .pred p;\n.reg .b64 db;\nsetp.ne.b32 p, %70, 0;\nmov.b64 db, {%68, %69};\n"
        "wgmma.mma_async.sync.aligned.m64n128k16.f32.bf16.bf16 {%0, %1, %2, %3, %4, %5, %6, %7, %8, %9, %10, %11, %12, %13, %14, %15, %16, %17, %18, %19, %20, %21, %22, %23, %24, %25, %26, %27, %28, %29, %30, %31, %32, %33, %34, %35, %36, %37, %38, %39, %40, %41, %42, %43, %44, %45, %46, %47, %48, %49, %50, %51, %52, %53, %54, %55, %56, %57, %58, %59, %60, %61, %62, %63}, {%64, %65, %66, %67}, db, p, 1, 1, 0;\n}\n"
        : "+f"(d[0]), "+f"(d[1]), "+f"(d[2]), "+f"(d[3]), "+f"(d[4]), "+f"(d[5]), "+f"(d[6]), "+f"(d[7]), "+f"(d[8]), "+f"(d[9]), "+f"(d[10]), "+f"(d[11]), "+f"(d[12]), "+f"(d[13]), "+f"(d[14]), "+f"(d[15]), "+f"(d[16]), "+f"(d[17]), "+f"(d[18]), "+f"(d[19]), "+f"(d[20]), "+f"(d[21]), "+f"(d[22]), "+f"(d[23]), "+f"(d[24]), "+f"(d[25]), "+f"(d[26]), "+f"(d[27]), "+f"(d[28]), "+f"(d[29]), "+f"(d[30]), "+f"(d[31]), "+f"(d[32]), "+f"(d[33]), "+f"(d[34]), "+f"(d[35]), "+f"(d[36]), "+f"(d[37]), "+f"(d[38]), "+f"(d[39]), "+f"(d[40]), "+f"(d[41]), "+f"(d[42]), "+f"(d[43]), "+f"(d[44]), "+f"(d[45]), "+f"(d[46]), "+f"(d[47]), "+f"(d[48]), "+f"(d[49]), "+f"(d[50]), "+f"(d[51]), "+f"(d[52]), "+f"(d[53]), "+f"(d[54]), "+f"(d[55]), "+f"(d[56]), "+f"(d[57]), "+f"(d[58]), "+f"(d[59]), "+f"(d[60]), "+f"(d[61]), "+f"(d[62]), "+f"(d[63])
        : "r"(a0), "r"(a1), "r"(a2), "r"(a3), "r"(blo), "r"(bhi), "r"(scale_d));
}

__device__ __forceinline__ void wgmma_rs_n64_tb0(float (&d)[32], uint32_t a0, uint32_t a1, uint32_t a2, uint32_t a3, uint32_t blo, uint32_t bhi, int scale_d) {
    asm volatile("{\n.reg .pred p;\n.reg .b64 db;\nsetp.ne.b32 p, %38, 0;\nmov.b64 db, {%36, %37};\n"
        "wgmma.mma_async.sync.aligned.m64n64k16.f32.bf16.bf16 {%0, %1, %2, %3, %4, %5, %6, %7, %8, %9, %10, %11, %12, %13, %14, %15, %16, %17, %18, %19, %20, %21, %22, %23, %24, %25, %26, %27, %28, %29, %30, %31}, {%32, %33, %34, %35}, db, p, 1, 1, 0;\n}\n"
        : "+f"(d[0]), "+f"(d[1]), "+f"(d[2]), "+f"(d[3]), "+f"(d[4]), "+f"(d[5]), "+f"(d[6]), "+f"(d[7]), "+f"(d[8]), "+f"(d[9]), "+f"(d[10]), "+f"(d[11]), "+f"(d[12]), "+f"(d[13]), "+f"(d[14]), "+f"(d[15]), "+f"(d[16]), "+f"(d[17]), "+f"(d[18]), "+f"(d[19]), "+f"(d[20]), "+f"(d[21]), "+f"(d[22]), "+f"(d[23]), "+f"(d[24]), "+f"(d[25]), "+f"(d[26]), "+f"(d[27]), "+f"(d[28]), "+f"(d[29]), "+f"(d[30]), "+f"(d[31])
        : "r"(a0), "r"(a1), "r"(a2), "r"(a3), "r"(blo), "r"(bhi), "r"(scale_d));
}

__device__ __forceinline__ void wgmma_rs_n32_tb1(float (&d)[16], uint32_t a0, uint32_t a1, uint32_t a2, uint32_t a3, uint32_t blo, uint32_t bhi, int scale_d) {
    asm volatile("{\n.reg .pred p;\n.reg .b64 db;\nsetp.ne.b32 p, %22, 0;\nmov.b64 db, {%20, %21};\n"
        "wgmma.mma_async.sync.aligned.m64n32k16.f32.bf16.bf16 {%0, %1, %2, %3, %4, %5, %6, %7, %8, %9, %10, %11, %12, %13, %14, %15}, {%16, %17, %18, %19}, db, p, 1, 1, 1;\n}\n"
        : "+f"(d[0]), "+f"(d[1]), "+f"(d[2]), "+f"(d[3]), "+f"(d[4]), "+f"(d[5]), "+f"(d[6]), "+f"(d[7]), "+f"(d[8]), "+f"(d[9]), "+f"(d[10]), "+f"(d[11]), "+f"(d[12]), "+f"(d[13]), "+f"(d[14]), "+f"(d[15])
        : "r"(a0), "r"(a1), "r"(a2), "r"(a3), "r"(blo), "r"(bhi), "r"(scale_d));
}

__device__ __forceinline__ void wgmma_rs_n40_tb1(float (&d)[20], uint32_t a0, uint32_t a1, uint32_t a2, uint32_t a3, uint32_t blo, uint32_t bhi, int scale_d) {
    asm volatile("{\n.reg .pred p;\n.reg .b64 db;\nsetp.ne.b32 p, %26, 0;\nmov.b64 db, {%24, %25};\n"
        "wgmma.mma_async.sync.aligned.m64n40k16.f32.bf16.bf16 {%0, %1, %2, %3, %4, %5, %6, %7, %8, %9, %10, %11, %12, %13, %14, %15, %16, %17, %18, %19}, {%20, %21, %22, %23}, db, p, 1, 1, 1;\n}\n"
        : "+f"(d[0]), "+f"(d[1]), "+f"(d[2]), "+f"(d[3]), "+f"(d[4]), "+f"(d[5]), "+f"(d[6]), "+f"(d[7]), "+f"(d[8]), "+f"(d[9]), "+f"(d[10]), "+f"(d[11]), "+f"(d[12]), "+f"(d[13]), "+f"(d[14]), "+f"(d[15]), "+f"(d[16]), "+f"(d[17]), "+f"(d[18]), "+f"(d[19])
        : "r"(a0), "r"(a1), "r"(a2), "r"(a3), "r"(blo), "r"(bhi), "r"(scale_d));
}

template <int BN>
__device__ __forceinline__ void wgmma_tile(float (&d)[BN / 2], uint32_t da, uint32_t db, int sd) {
    constexpr uint32_t HI = desc_hi(1024, 1);
    if constexpr (BN == 128) wgmma_ss_n128_tb1(d, da, HI, db, HI, sd);
    else if constexpr (BN == 192) wgmma_ss_n192_tb1(d, da, HI, db, HI, sd);
    else if constexpr (BN == 224) wgmma_ss_n224_tb1(d, da, HI, db, HI, sd);
    else wgmma_ss_n256_tb1(d, da, HI, db, HI, sd);
}

__global__ void __launch_bounds__(256) prep_kernel(const bf16* __restrict__ x, const bf16* __restrict__ gate_w,
                                                   const bf16* __restrict__ w1, const bf16* __restrict__ w3) {
    const int tid = threadIdx.x;
    TL_START(0)
    pdl_launch();
    if (blockIdx.x < 256) {
        const int row = blockIdx.x * 8 + (tid >> 5);
        const int lane = tid & 31;
        const uint4* xr = reinterpret_cast<const uint4*>(x + (size_t)row * DM);
        const uint4* gw = reinterpret_cast<const uint4*>(gate_w);
        float v[32];
        float gsum = 0.f, sum = 0.f;
#pragma unroll
        for (int i = 0; i < 4; i++) {
            uint4 a = xr[lane + 32 * i];
            uint4 b = gw[lane + 32 * i];
            const uint32_t aa[4] = {a.x, a.y, a.z, a.w};
            const uint32_t bb[4] = {b.x, b.y, b.z, b.w};
#pragma unroll
            for (int j = 0; j < 4; j++) {
                float x0 = __uint_as_float(aa[j] << 16), x1 = __uint_as_float(aa[j] & 0xFFFF0000u);
                float g0 = __uint_as_float(bb[j] << 16), g1 = __uint_as_float(bb[j] & 0xFFFF0000u);
                v[i * 8 + j * 2] = x0;
                v[i * 8 + j * 2 + 1] = x1;
                sum += x0 + x1;
                gsum += bf16_round(x0 * g0) + bf16_round(x1 * g1);
            }
        }
#pragma unroll
        for (int o = 16; o > 0; o >>= 1) {
            sum += __shfl_xor_sync(0xffffffffu, sum, o);
            gsum += __shfl_xor_sync(0xffffffffu, gsum, o);
        }
        const float mean = sum * (1.0f / DM);
        float m2 = 0.f;
#pragma unroll
        for (int i = 0; i < 32; i++) {
            float d = v[i] - mean;
            m2 += d * d;
        }
#pragma unroll
        for (int o = 16; o > 0; o >>= 1) m2 += __shfl_xor_sync(0xffffffffu, m2, o);
        if (lane == 0) {
            g_mean1[row] = mean;
            g_rstd1[row] = rsqrtf(m2 * (1.0f / DM) + 1e-5f);
            float logit = bf16_round(gsum);
            float g = bf16_round(1.0f / (1.0f + __expf(-logit)));
            g_gate[row] = g;
            g_omg[row] = bf16_round(1.0f - g);
        }
    } else {
        __shared__ float red[32][65];
        const int strip = blockIdx.x - 256;
        const bf16* w;
        float* out;
        int ld, col0;
        if (strip < 16) { w = w1; ld = DM; col0 = strip * 64; out = g_cs1; }
        else { w = w3; ld = FF; col0 = (strip - 16) * 64; out = g_cs3; }
        const int cg = tid & 7;
        const int rg = tid >> 3;
        float acc[8];
#pragma unroll
        for (int j = 0; j < 8; j++) acc[j] = 0.f;
#pragma unroll 8
        for (int r = 0; r < 32; r++) {
            uint4 a = *reinterpret_cast<const uint4*>(w + (size_t)(r * 32 + rg) * ld + col0 + cg * 8);
            const uint32_t aa[4] = {a.x, a.y, a.z, a.w};
#pragma unroll
            for (int j = 0; j < 4; j++) {
                acc[2 * j] += __uint_as_float(aa[j] << 16);
                acc[2 * j + 1] += __uint_as_float(aa[j] & 0xFFFF0000u);
            }
        }
#pragma unroll
        for (int j = 0; j < 8; j++) red[rg][cg * 8 + j] = acc[j];
        __syncthreads();
        if (tid < 64) {
            float s = 0.f;
#pragma unroll
            for (int r = 0; r < 32; r++) s += red[r][tid];
            out[col0 + tid] = s;
        }
    }
    TL_END(0)
}

#define RELEASE_STAGE(b) if (tid_wg < 2) mbar_arrive_cluster(b, tid_wg)
template <int BN, int STAGES>
struct GemmSmem {
    static constexpr int A_BYTES = 128 * 64 * 2;
    static constexpr int B_BOXES = (BN + 63) / 64;
    static constexpr int B_BYTES = B_BOXES * 64 * 64 * 2;
    static constexpr int STAGE_BYTES = A_BYTES + B_BYTES;
    static constexpr int STG_OFF = STAGES * STAGE_BYTES;
    static constexpr int CS_OFF = STAGES * STAGE_BYTES + 2 * 16384;
    static constexpr int BAR_OFF = CS_OFF + 1024;
    static constexpr int TOTAL = BAR_OFF + 128 + 512;
};

template <int MODE, int BN, int STAGES>
__global__ void __launch_bounds__(384, 1)
gemm_kernel(const __grid_constant__ CUtensorMap mA, const __grid_constant__ CUtensorMap mB0,
            const __grid_constant__ CUtensorMap mB1, const __grid_constant__ CUtensorMap mC0,
            const __grid_constant__ CUtensorMap mC1, const bf16* __restrict__ xin, int n_tiles_n, int kblocks) {
    using L = GemmSmem<BN, STAGES>;
    extern __shared__ uint8_t smem_raw[];
    const uint32_t sbase = (smem_u32(smem_raw) + 1023u) & ~1023u;
    const uint32_t bar_full = sbase + L::BAR_OFF;
    const uint32_t bar_empty = bar_full + 8 * STAGES;
    const uint32_t bar_res = bar_empty + 8 * STAGES;
    const int wg = threadIdx.x >> 7;
    const int npairs = 8 * n_tiles_n;
    const uint32_t crank = cluster_rank();
    const int cid = blockIdx.x >> 1, ncl = gridDim.x >> 1;
    TL_START(MODE)
    pdl_launch();

    if (threadIdx.x == 0) {
        for (int s = 0; s < STAGES; s++) {
            mbar_init(bar_full + 8 * s, 1);
            mbar_init(bar_empty + 8 * s, 4);
        }
        mbar_init(bar_res, 1);
        asm volatile("fence.mbarrier_init.release.cluster;" ::: "memory");
        prefetch_tmap(&mA);
        prefetch_tmap(&mB0);
        if (MODE == 1 || MODE == 5) prefetch_tmap(&mB1);
        if (MODE == 2 || MODE == 5) prefetch_tmap(&mC1);
        prefetch_tmap(&mC0);
    }
    cluster_sync_all();

    if (wg == 0) {
        reg_dealloc<40>();
        if (threadIdx.x == 0) {
            if (MODE != 1) pdl_wait();
            int stage = 0;
            uint32_t phase = 1;
            for (int pr = cid; pr < npairs; pr += ncl) {
                const int m0 = ((pr & 7) * 2 + crank) * 128;
                const int n0 = (pr >> 3) * BN;
                for (int kb = 0; kb < kblocks; kb++) {
                    mbar_wait(bar_empty + 8 * stage, phase);
                    const uint32_t sa = sbase + stage * L::STAGE_BYTES;
                    const uint32_t sb = sa + L::A_BYTES;
                    const uint32_t fb = bar_full + 8 * stage;
                    mbar_expect_tx(fb, L::STAGE_BYTES);
                    int arow = m0;
                    if (MODE == 2) {
                        const int grp = kb >> 2;
                        arow += (grp == 0) ? -1 : (grp == 1) ? 1 : (grp == 2) ? -2 : 2;
                    }
                    tma_load_2d(sa, &mA, kb * 64, arow, fb);
                    const CUtensorMap* mb = &mB0;
                    int bc = n0, br = kb * 64;
                    if (MODE == 1 && n0 >= 3 * DM) { mb = &mB1; bc = n0 - 3 * DM; }
                    if (MODE == 5 && kb >= 16) { mb = &mB1; br = (kb - 16) * 64; }
#pragma unroll
                    for (int b = 0; b < L::B_BOXES / 2; b++) {
                        const int bb = crank * (L::B_BOXES / 2) + b;
                        tma_load_2d_mc(sb + bb * 8192, mb, bc + bb * 64, br, fb, (uint16_t)3);
                    }
                    if ((MODE == 2 || MODE == 5) && kb == STAGES - 1) {
                        mbar_expect_tx(bar_res, 32768);
#pragma unroll
                        for (int q = 0; q < 4; q++)
                            tma_load_2d(sbase + L::STG_OFF + q * 8192, &mC1, n0 + (q & 1) * 64, m0 + (q >> 1) * 64, bar_res);
                    }
                    if (++stage == STAGES) { stage = 0; phase ^= 1; }
                }
            }
        }
    } else {
        reg_alloc<232>();
        const int c = wg - 1;
        const int warp = (threadIdx.x >> 5) & 3;
        const int lane = threadIdx.x & 31;
        const int tid_wg = threadIdx.x & 127;
        const uint32_t stg = sbase + L::STG_OFF + c * 16384;
        int stage = 0;
        uint32_t phase = 0;
        float acc[BN / 2];
        bool first = true;
        if (MODE != 1) pdl_wait();
        for (int pr = cid; pr < npairs; pr += ncl) {
            const int m0 = ((pr & 7) * 2 + crank) * 128;
            const int n0 = (pr >> 3) * BN;
            const int r0 = m0 + c * 64 + warp * 16 + (lane >> 2);
            const int r1 = r0 + 8;
            float mu[2], rs[2], og[2];
            if (MODE == 3) {
                const int t = threadIdx.x - 128;
                if (t < BN / 4)
                    asm volatile("cp.async.ca.shared.global [%0], [%1], 16;" ::"r"(sbase + L::CS_OFF + t * 16), "l"(&g_cs3[n0 + t * 4]) : "memory");
#pragma unroll
                for (int h = 0; h < 2; h++) {
                    const float4* sp = reinterpret_cast<const float4*>(&g_stat2[(h ? r1 : r0) * 8]);
                    float4 p[4];
                    float s = 0.f;
#pragma unroll
                    for (int i = 0; i < 4; i++) { p[i] = sp[i]; s += p[i].x + p[i].z; }
                    const float mean = s * (1.0f / DM);
                    float m2 = 0.f;
#pragma unroll
                    for (int i = 0; i < 4; i++) {
                        float d0 = p[i].x * (1.0f / 128) - mean, d1 = p[i].z * (1.0f / 128) - mean;
                        m2 += p[i].y + p[i].w + 128.0f * (d0 * d0 + d1 * d1);
                    }
                    mu[h] = mean;
                    rs[h] = rsqrtf(m2 * (1.0f / DM) + 1e-5f);
                }
            }
            if (MODE == 3 || MODE == 5) { og[0] = g_omg[r0]; og[1] = g_omg[r1]; }
            int prev_stage = 0;
            for (int kb = 0; kb < kblocks; kb++) {
                mbar_wait(bar_full + 8 * stage, phase);
                const uint32_t sa = sbase + stage * L::STAGE_BYTES + c * 8192;
                const uint32_t sb = sbase + stage * L::STAGE_BYTES + L::A_BYTES;
                const uint32_t da = desc_lo(sa, 16);
                const uint32_t db = desc_lo(sb, 8192);
                wgmma_fence();
#pragma unroll
                for (int k = 0; k < 4; k++) wgmma_tile<BN>(acc, da + k * 2, db + k * 128, (kb | k) != 0);
                wgmma_commit();
                if (kb > 0) {
                    wgmma_wait<1>();
                    RELEASE_STAGE(bar_empty + 8 * prev_stage);
                }
                prev_stage = stage;
                if (++stage == STAGES) { stage = 0; phase ^= 1; }
            }
            wgmma_wait<0>();
            RELEASE_STAGE(bar_empty + 8 * prev_stage);
            if (MODE == 1 && first) { pdl_wait(); first = false; }

            const int cq = (lane & 3) * 2;
            const CUtensorMap* mc = &mC0;
            const uint32_t rrow = warp * 16 + (lane >> 2);
            const uint32_t res0 = stg + rrow * 128 + cq * 2;
            int out_c0 = n0;
            if (MODE == 1) {
                if (n0 < DM) {
                    const float qs = 0.17677669529663687f * 1.4426950408889634f;
#pragma unroll
                    for (int j = 0; j < BN / 2; j++) acc[j] *= qs;
                } else if (n0 >= 3 * DM) {
                    mc = &mC1;
                    out_c0 = n0 - 3 * DM;
                    const float mu0 = g_mean1[r0], mu1 = g_mean1[r1];
                    const float rs0 = g_rstd1[r0], rs1 = g_rstd1[r1];
#pragma unroll
                    for (int j = 0; j < BN / 8; j++) {
                        const float2 cs = *reinterpret_cast<const float2*>(&g_cs1[out_c0 + 8 * j + cq]);
                        acc[4 * j + 0] = gelu_tanh(rs0 * fmaf(-mu0, cs.x, acc[4 * j + 0]));
                        acc[4 * j + 1] = gelu_tanh(rs0 * fmaf(-mu0, cs.y, acc[4 * j + 1]));
                        acc[4 * j + 2] = gelu_tanh(rs1 * fmaf(-mu1, cs.x, acc[4 * j + 2]));
                        acc[4 * j + 3] = gelu_tanh(rs1 * fmaf(-mu1, cs.y, acc[4 * j + 3]));
                    }
                }
            } else if (MODE == 2) {
                float s0 = 0.f, s1 = 0.f;
                mbar_wait(bar_res, 0);
#pragma unroll
                for (int j = 0; j < BN / 8; j++) {
                    uint32_t xa, xb;
                    const uint32_t ra = res0 + (j >> 3) * 8192 + (((j & 7) ^ (rrow & 7)) << 4);
                    asm volatile("ld.shared.b32 %0, [%1];" : "=r"(xa) : "r"(ra));
                    asm volatile("ld.shared.b32 %0, [%1];" : "=r"(xb) : "r"(ra + 1024));
                    acc[4 * j + 0] = bf16_round(bf16_round(acc[4 * j + 0]) + __uint_as_float(xa << 16));
                    acc[4 * j + 1] = bf16_round(bf16_round(acc[4 * j + 1]) + __uint_as_float(xa & 0xFFFF0000u));
                    acc[4 * j + 2] = bf16_round(bf16_round(acc[4 * j + 2]) + __uint_as_float(xb << 16));
                    acc[4 * j + 3] = bf16_round(bf16_round(acc[4 * j + 3]) + __uint_as_float(xb & 0xFFFF0000u));
                    s0 += acc[4 * j + 0] + acc[4 * j + 1];
                    s1 += acc[4 * j + 2] + acc[4 * j + 3];
                }
                s0 += __shfl_xor_sync(0xffffffffu, s0, 1);
                s0 += __shfl_xor_sync(0xffffffffu, s0, 2);
                s1 += __shfl_xor_sync(0xffffffffu, s1, 1);
                s1 += __shfl_xor_sync(0xffffffffu, s1, 2);
                const float mu0 = s0 * (1.0f / BN), mu1 = s1 * (1.0f / BN);
                float q0 = 0.f, q1 = 0.f;
#pragma unroll
                for (int j = 0; j < BN / 8; j++) {
                    float d;
                    d = acc[4 * j + 0] - mu0; q0 += d * d;
                    d = acc[4 * j + 1] - mu0; q0 += d * d;
                    d = acc[4 * j + 2] - mu1; q1 += d * d;
                    d = acc[4 * j + 3] - mu1; q1 += d * d;
                }
                q0 += __shfl_xor_sync(0xffffffffu, q0, 1);
                q0 += __shfl_xor_sync(0xffffffffu, q0, 2);
                q1 += __shfl_xor_sync(0xffffffffu, q1, 1);
                q1 += __shfl_xor_sync(0xffffffffu, q1, 2);
                if ((lane & 3) == 0) {
                    static_assert(MODE != 2 || BN == 128, "stats layout assumes BN=128");
                    g_stat2[r0 * 8 + (n0 >> 7)] = make_float2(s0, q0);
                    g_stat2[r1 * 8 + (n0 >> 7)] = make_float2(s1, q1);
                }
            } else if (MODE == 3) {
                out_c0 = n0 + DM;
                asm volatile("cp.async.wait_all;" ::: "memory");
                named_bar_sync(3, 256);
#pragma unroll
                for (int j = 0; j < BN / 8; j++) {
                    float2 cs;
                    asm volatile("ld.shared.v2.f32 {%0, %1}, [%2];" : "=f"(cs.x), "=f"(cs.y) : "r"(sbase + L::CS_OFF + (8 * j + cq) * 4));
                    acc[4 * j + 0] = og[0] * gelu_tanh(rs[0] * fmaf(-mu[0], cs.x, acc[4 * j + 0]));
                    acc[4 * j + 1] = og[0] * gelu_tanh(rs[0] * fmaf(-mu[0], cs.y, acc[4 * j + 1]));
                    acc[4 * j + 2] = og[1] * gelu_tanh(rs[1] * fmaf(-mu[1], cs.x, acc[4 * j + 2]));
                    acc[4 * j + 3] = og[1] * gelu_tanh(rs[1] * fmaf(-mu[1], cs.y, acc[4 * j + 3]));
                }
                named_bar_sync(3, 256);
            } else {
                const float og0 = og[0], og1 = og[1];
                mbar_wait(bar_res, 0);
#pragma unroll
                for (int j = 0; j < BN / 8; j++) {
                    uint32_t xa, xb;
                    const uint32_t ra = res0 + (j >> 3) * 8192 + (((j & 7) ^ (rrow & 7)) << 4);
                    asm volatile("ld.shared.b32 %0, [%1];" : "=r"(xa) : "r"(ra));
                    asm volatile("ld.shared.b32 %0, [%1];" : "=r"(xb) : "r"(ra + 1024));
                    acc[4 * j + 0] = fmaf(og0, __uint_as_float(xa << 16), acc[4 * j + 0]);
                    acc[4 * j + 1] = fmaf(og0, __uint_as_float(xa & 0xFFFF0000u), acc[4 * j + 1]);
                    acc[4 * j + 2] = fmaf(og1, __uint_as_float(xb << 16), acc[4 * j + 2]);
                    acc[4 * j + 3] = fmaf(og1, __uint_as_float(xb & 0xFFFF0000u), acc[4 * j + 3]);
                }
            }
            const int srow = warp * 16 + (lane & 7) + ((lane >> 3) & 1) * 8;
#pragma unroll
            for (int rnd = 0; rnd < (BN + 127) / 128; rnd++) {
                if (tid_wg == 0) bulk_wait_read0();
                named_bar_sync(1 + c, 128);
#pragma unroll
                for (int jj = 0; jj < 8; jj++) {
                    const int j = rnd * 16 + jj * 2;
                    if (j * 8 < BN) {
                        const int jb = jj * 2 + (lane >> 4);
                        uint32_t addr = stg + (jb >> 3) * 8192 + srow * 128 + (((jb & 7) ^ (srow & 7)) << 4);
                        if (rnd * 128 + 128 > BN && jj >= 4)
                            addr = stg + 8192 + srow * 64 + (((jb & 3) ^ ((srow >> 1) & 3)) << 4);
                        stmatrix_x4(addr, pack_bf16(acc[4 * j + 0], acc[4 * j + 1]), pack_bf16(acc[4 * j + 2], acc[4 * j + 3]),
                                    pack_bf16(acc[4 * j + 4], acc[4 * j + 5]), pack_bf16(acc[4 * j + 6], acc[4 * j + 7]));
                    }
                }
                fence_proxy_async();
                named_bar_sync(1 + c, 128);
                if (tid_wg == 0) {
                    tma_store_2d(mc, stg, out_c0 + rnd * 128, m0 + c * 64);
                    if (rnd * 128 + 64 < BN)
                        tma_store_2d((rnd * 128 + 128 > BN) ? &mC1 : mc, stg + 8192, out_c0 + rnd * 128 + 64, m0 + c * 64);
                    bulk_commit();
                }
            }
        }
        if (tid_wg == 0) bulk_wait0();
        TL_END(MODE)
    }
    cluster_sync_all();
}

#define ATT_SPLIT 16
constexpr int ATT_NTILES = NH * 16;
#define ATT_GRID_N 512
constexpr int ATT_GRID = ATT_GRID_N;
constexpr int ATT_THREADS = 256;
constexpr int ATT_STAGES = 4;
constexpr int ATT_DIST = 2;
constexpr int ATT_Q_OFF = ATT_STAGES * 16384;
constexpr int ATT_ONES_OFF = ATT_Q_OFF + 8192;
constexpr int ATT_KEXT_OFF = ATT_ONES_OFF + 4096;
constexpr int ATT_QEXT_OFF = ATT_KEXT_OFF + 4096;
constexpr int ATT_BAR_OFF = ATT_QEXT_OFF + 8192;
constexpr int ATT_SMEM = ATT_BAR_OFF + 256 + 1024;

__device__ __forceinline__ void row_max(const float (&s)[32], float& m0, float& m1) {
    float a0[8], a1[8];
#pragma unroll
    for (int i = 0; i < 8; i++) {
        a0[i] = fmaxf(s[4 * i], s[4 * i + 1]);
        a1[i] = fmaxf(s[4 * i + 2], s[4 * i + 3]);
    }
#pragma unroll
    for (int w = 4; w > 0; w >>= 1)
#pragma unroll
        for (int i = 0; i < w; i++) { a0[i] = fmaxf(a0[i], a0[i + w]); a1[i] = fmaxf(a1[i], a1[i + w]); }
    float mx0 = a0[0], mx1 = a1[0];
    mx0 = fmaxf(mx0, __shfl_xor_sync(0xffffffffu, mx0, 1));
    mx1 = fmaxf(mx1, __shfl_xor_sync(0xffffffffu, mx1, 1));
    mx0 = fmaxf(mx0, __shfl_xor_sync(0xffffffffu, mx0, 2));
    mx1 = fmaxf(mx1, __shfl_xor_sync(0xffffffffu, mx1, 2));
    m0 = fmaxf(m0, mx0);
    m1 = fmaxf(m1, mx1);
}

__device__ __forceinline__ void attn_step(float (&s)[32], float (&o)[20], uint32_t dq, uint32_t dke, uint32_t dk_next,
                                          uint32_t dv_cur, uint32_t release_bar) {
    constexpr uint32_t HI = desc_hi(512, 2);
    uint32_t p[16];
#pragma unroll
    for (int i = 0; i < 16; i++) p[i] = pack_bf16(ex2(s[2 * i]), ex2(s[2 * i + 1]));
    wgmma_fence();
    wgmma_ss_n64_tb0(s, dq, HI, dk_next, HI, 0);
    wgmma_ss_n64_tb0(s, dq + 2, HI, dk_next + 2, HI, 1);
    wgmma_ss_n64_tb0(s, dq + ((ATT_QEXT_OFF - ATT_Q_OFF) >> 4), HI, dke, HI, 1);
#pragma unroll
    for (int t = 0; t < 4; t++)
        wgmma_rs_n40_tb1(o, p[4 * t], p[4 * t + 1], p[4 * t + 2], p[4 * t + 3], dv_cur + t * 64, HI, 1);
    wgmma_commit();
    wgmma_wait<0>();
    if (release_bar != 0 && (threadIdx.x & 127) == 0) mbar_arrive(release_bar);
}

__global__ void __launch_bounds__(256, 1)
attn_exact_kernel(const __grid_constant__ CUtensorMap mKV) {
    extern __shared__ uint8_t smem_raw[];
    pdl_launch();
    pdl_wait();
    const int tile = blockIdx.x;
    if (g_bad[tile] == 0) return;
    constexpr int NBLK = S_LEN / 128;
    constexpr uint32_t HI = desc_hi(512, 2);
    const uint32_t sbase = (smem_u32(smem_raw) + 1023u) & ~1023u;
    const uint32_t bar = sbase + ATT_BAR_OFF;
    const int warp_id = threadIdx.x >> 5;
    const int lane = threadIdx.x & 31;
    const int cq = (lane & 3) * 2;
    const uint32_t dk0 = desc_lo(sbase, 16);
    const uint32_t dv0 = desc_lo(sbase + 8192, ATT_ONES_OFF - 8192);
    if (threadIdx.x == 0) {
        mbar_init(bar, 1);
        asm volatile("fence.mbarrier_init.release.cluster;" ::: "memory");
    }
    asm volatile("st.shared.v4.b32 [%0], {%1, %1, %1, %1};" ::"r"(sbase + ATT_ONES_OFF + threadIdx.x * 16), "r"(0x3F803F80u) : "memory");
    fence_proxy_async();
    __syncthreads();
    const int head = tile >> 4;
    const int row0 = (tile & 15) * 128 + warp_id * 16 + (lane >> 2);
    const uint32_t dq = desc_lo(sbase + ATT_Q_OFF + (threadIdx.x >> 7) * 4096, 16);
    float o[20];
#pragma unroll
    for (int i = 0; i < 20; i++) o[i] = 0.f;
    float m0 = -INFINITY, m1 = -INFINITY;
#pragma unroll 1
    for (int j = 0; j < NBLK; j++) {
        if (threadIdx.x == 0) {
            mbar_expect_tx(bar, j == 0 ? 3 * 8192 : 2 * 8192);
            if (j == 0) tma_load_2d(sbase + ATT_Q_OFF, &mKV, head * DH, (tile & 15) * 128, bar);
            tma_load_2d(sbase, &mKV, DM + head * DH, j * 128, bar);
            tma_load_2d(sbase + 8192, &mKV, 2 * DM + head * DH, j * 128, bar);
        }
        __syncwarp();
        mbar_wait(bar, j & 1);
#pragma unroll 1
        for (int hf = 0; hf < 2; hf++) {
            float s[32];
            wgmma_fence();
            wgmma_ss_n64_tb0(s, dq, HI, dk0 + hf * 256, HI, 0);
            wgmma_ss_n64_tb0(s, dq + 2, HI, dk0 + hf * 256 + 2, HI, 1);
            wgmma_commit();
            wgmma_wait<0>();
            const float mo0 = m0, mo1 = m1;
            row_max(s, m0, m1);
            const float a0 = ex2(mo0 - m0), a1 = ex2(mo1 - m1);
            uint32_t p[16];
#pragma unroll
            for (int i = 0; i < 8; i++) {
                p[2 * i] = pack_bf16(ex2(s[4 * i + 0] - m0), ex2(s[4 * i + 1] - m0));
                p[2 * i + 1] = pack_bf16(ex2(s[4 * i + 2] - m1), ex2(s[4 * i + 3] - m1));
            }
#pragma unroll
            for (int i = 0; i < 5; i++) {
                o[4 * i + 0] *= a0; o[4 * i + 1] *= a0;
                o[4 * i + 2] *= a1; o[4 * i + 3] *= a1;
            }
            wgmma_fence();
            const uint32_t dv = dv0 + hf * 256 - ((uint32_t)(hf * 256) << 16);
#pragma unroll
            for (int t = 0; t < 4; t++)
                wgmma_rs_n40_tb1(o, p[4 * t], p[4 * t + 1], p[4 * t + 2], p[4 * t + 3], dv + t * 64, HI, 1);
            wgmma_commit();
            wgmma_wait<0>();
        }
        __syncthreads();
    }
    const float f0 = g_gate[row0] / o[16], f1 = g_gate[row0 + 8] / o[18];
    bf16* op0 = g_a5 + (size_t)row0 * A5W + head * DH + cq;
    bf16* op1 = op0 + 8 * A5W;
#pragma unroll
    for (int i = 0; i < 4; i++) {
        *reinterpret_cast<uint32_t*>(op0 + 8 * i) = pack_bf16(o[4 * i] * f0, o[4 * i + 1] * f0);
        *reinterpret_cast<uint32_t*>(op1 + 8 * i) = pack_bf16(o[4 * i + 2] * f1, o[4 * i + 3] * f1);
    }
}

#define ATT_MINB 2
__global__ void __launch_bounds__(256, ATT_MINB)
attn_kernel(const __grid_constant__ CUtensorMap mKV) {
    extern __shared__ uint8_t smem_raw[];
    const uint32_t sbase = (smem_u32(smem_raw) + 1023u) & ~1023u;
    const uint32_t bar_kfull = sbase + ATT_BAR_OFF;
    const uint32_t bar_vfull = bar_kfull + 8 * ATT_STAGES;
    const uint32_t bar_empty = bar_vfull + 8 * ATT_STAGES;
    const int tile = blockIdx.x;
    const int head = tile >> 4;
    const int lane = threadIdx.x & 31;
    constexpr int NBLK = S_LEN / 128;
    TL_START(6)
    pdl_launch();

    auto issue_kv = [&](int g) {
        const int sn = g % ATT_STAGES;
        if (g >= ATT_STAGES) mbar_wait(bar_empty + 8 * sn, ((g / ATT_STAGES) - 1) & 1);
        const uint32_t skn = sbase + sn * 16384;
        mbar_expect_tx(bar_kfull + 8 * sn, g == 0 ? 16384 : 8192);
        if (g == 0) tma_load_2d(sbase + ATT_Q_OFF, &mKV, head * DH, (tile & 15) * 128, bar_kfull);
        tma_load_2d(skn, &mKV, DM + head * DH, g * 128, bar_kfull + 8 * sn);
        mbar_expect_tx(bar_vfull + 8 * sn, 8192);
        tma_load_2d(skn + 8192, &mKV, 2 * DM + head * DH, g * 128, bar_vfull + 8 * sn);
    };

    if (threadIdx.x == 0) {
        for (int s = 0; s < ATT_STAGES; s++) {
            mbar_init(bar_kfull + 8 * s, 1);
            mbar_init(bar_vfull + 8 * s, 1);
            mbar_init(bar_empty + 8 * s, 2);
        }
        asm volatile("fence.mbarrier_init.release.cluster;" ::: "memory");
        prefetch_tmap(&mKV);
        pdl_wait();
#pragma unroll
        for (int j = 0; j < ATT_DIST; j++) issue_kv(j);
    }
    {
        asm volatile("st.shared.v4.b32 [%0], {%1, %1, %1, %1};" ::"r"(sbase + ATT_ONES_OFF + threadIdx.x * 16), "r"(0x3F803F80u) : "memory");
        const int r = threadIdx.x >> 2, ch = threadIdx.x & 3;
        const uint32_t w0 = (ch == ((r >> 1) & 3)) ? 0x00003F80u : 0u;
        asm volatile("st.shared.v4.b32 [%0], {%1, %2, %2, %2};" ::"r"(sbase + ATT_KEXT_OFF + threadIdx.x * 16), "r"(w0), "r"(0u) : "memory");
        asm volatile("st.shared.v4.b32 [%0], {%1, %1, %1, %1};" ::"r"(sbase + ATT_QEXT_OFF + threadIdx.x * 16), "r"(0u) : "memory");
        asm volatile("st.shared.v4.b32 [%0], {%1, %1, %1, %1};" ::"r"(sbase + ATT_QEXT_OFF + 4096 + threadIdx.x * 16), "r"(0u) : "memory");
    }
    fence_proxy_async();
    __syncthreads();

    constexpr uint32_t HI = desc_hi(512, 2);
    const uint32_t dk0 = desc_lo(sbase, 16);
    const uint32_t dv0 = desc_lo(sbase + 8192, ATT_ONES_OFF - 8192);
    const uint32_t dke = dk0 + (ATT_KEXT_OFF >> 4);
    const uint32_t dq = dk0 + ((ATT_Q_OFF + (threadIdx.x >> 7) * 4096) >> 4);
    float o[20];
#pragma unroll
    for (int i = 0; i < 20; i++) o[i] = 0.f;
    float s0[32];
    mbar_wait(bar_kfull, 0);
    wgmma_fence();
    wgmma_ss_n64_tb0(s0, dq, HI, dk0, HI, 0);
    wgmma_ss_n64_tb0(s0, dq + 2, HI, dk0 + 2, HI, 1);
    wgmma_commit();
    wgmma_wait<0>();
    float m0 = -INFINITY, m1 = -INFINITY;
    row_max(s0, m0, m1);
    if ((lane & 3) == 0) {
        const int r = ((threadIdx.x >> 5) & 3) * 16 + (lane >> 2);
        const uint32_t qe = sbase + ATT_QEXT_OFF + (threadIdx.x >> 7) * 4096;
        asm volatile("st.shared.b16 [%0], %1;" ::"r"(qe + r * 64 + (((r >> 1) & 3) << 4)), "h"((uint16_t)(pack_bf16(-m0, 0.f) & 0xFFFFu)) : "memory");
        asm volatile("st.shared.b16 [%0], %1;" ::"r"(qe + (r + 8) * 64 + ((((r + 8) >> 1) & 3) << 4)), "h"((uint16_t)(pack_bf16(-m1, 0.f) & 0xFFFFu)) : "memory");
    }
    fence_proxy_async();
    named_bar_sync(1 + (threadIdx.x >> 7), 128);
    wgmma_fence();
    wgmma_ss_n64_tb0(s0, dq + ((ATT_QEXT_OFF - ATT_Q_OFF) >> 4), HI, dke, HI, 1);
    wgmma_commit();
    wgmma_wait<0>();
#pragma unroll 1
    for (int j = 0; j < NBLK; j++) {
        if (threadIdx.x == 0 && j + ATT_DIST < NBLK) issue_kv(j + ATT_DIST);
        __syncwarp();
        const uint32_t stage = j & (ATT_STAGES - 1), nstage = (j + 1) & (ATT_STAGES - 1);
        const uint32_t dk = dk0 + stage * 1024;
        const uint32_t dv = dv0 + stage * 1024 - (stage << 26);
        mbar_wait(bar_vfull + 8 * stage, (j / ATT_STAGES) & 1);
        attn_step(s0, o, dq, dke, dk + 256, dv, 0u);
        uint32_t dkn = dk;
        if (j + 1 < NBLK) {
            mbar_wait(bar_kfull + 8 * nstage, ((j + 1) / ATT_STAGES) & 1);
            dkn = dk0 + nstage * 1024;
        }
        attn_step(s0, o, dq, dke, dkn, dv + 256 - (256u << 16), bar_empty + 8 * stage);
    }
    bool ok = (o[16] <= 1.8446744e19f) && (o[18] <= 1.8446744e19f);
#pragma unroll
    for (int i = 0; i < 16; i++) ok = ok && (fabsf(o[i]) <= 3.0e38f);
    const int row0 = (tile & 15) * 128 + (threadIdx.x >> 5) * 16 + (lane >> 2);
    const float f0 = g_gate[row0] / o[16], f1 = g_gate[row0 + 8] / o[18];
    bf16* op0 = g_a5 + (size_t)row0 * A5W + head * DH + (lane & 3) * 2;
    bf16* op1 = op0 + 8 * A5W;
#pragma unroll
    for (int i = 0; i < 4; i++) {
        *reinterpret_cast<uint32_t*>(op0 + 8 * i) = pack_bf16(o[4 * i] * f0, o[4 * i + 1] * f0);
        *reinterpret_cast<uint32_t*>(op1 + 8 * i) = pack_bf16(o[4 * i + 2] * f1, o[4 * i + 3] * f1);
    }
    const int bad = __syncthreads_or(!ok);
    if (threadIdx.x == 0) g_bad[tile] = bad;
    TL_END(6)
}

typedef CUresult (*EncodeFn)(CUtensorMap*, CUtensorMapDataType, cuuint32_t, void*, const cuuint64_t*, const cuuint64_t*,
                             const cuuint32_t*, const cuuint32_t*, CUtensorMapInterleave, CUtensorMapSwizzle,
                             CUtensorMapL2promotion, CUtensorMapFloatOOBfill);

static CUtensorMap make_map(EncodeFn fn, const void* ptr, int rows, int cols, int box_cols, int box_rows,
                            CUtensorMapSwizzle swz) {
    CUtensorMap m;
    cuuint64_t dims[2] = {(cuuint64_t)cols, (cuuint64_t)rows};
    cuuint64_t strides[1] = {(cuuint64_t)cols * 2};
    cuuint32_t box[2] = {(cuuint32_t)box_cols, (cuuint32_t)box_rows};
    cuuint32_t es[2] = {1, 1};
    fn(&m, CU_TENSOR_MAP_DATA_TYPE_BFLOAT16, 2, const_cast<void*>(ptr), dims, strides, box, es,
       CU_TENSOR_MAP_INTERLEAVE_NONE, swz, CU_TENSOR_MAP_L2_PROMOTION_L2_256B, CU_TENSOR_MAP_FLOAT_OOB_FILL_NONE);
    return m;
}

template <typename... KArgs, typename... Args>
static void launch_ex(void (*kern)(KArgs...), int grid, int block, int smem, cudaStream_t st, int cluster, int pdl, Args... args) {
    cudaLaunchConfig_t cfg = {};
    cfg.gridDim = dim3(grid);
    cfg.blockDim = dim3(block);
    cfg.dynamicSmemBytes = smem;
    cfg.stream = st;
    cudaLaunchAttribute at[2];
    at[0].id = cudaLaunchAttributeProgrammaticStreamSerialization;
    at[0].val.programmaticStreamSerializationAllowed = pdl;
    at[1].id = cudaLaunchAttributeClusterDimension;
    at[1].val.clusterDim.x = cluster;
    at[1].val.clusterDim.y = 1;
    at[1].val.clusterDim.z = 1;
    cfg.attrs = at;
    cfg.numAttrs = cluster > 1 ? 2 : 1;
    cudaLaunchKernelEx(&cfg, kern, KArgs(args)...);
}

extern "C" void kernel_launch(void* const* d_in, const int* in_sizes, int n_in, void* d_out, int out_size) {
    const bf16* x = (const bf16*)d_in[0];
    const bf16* wqkv = (const bf16*)d_in[1];
    const bf16* wo = (const bf16*)d_in[2];
    const bf16* w1 = (const bf16*)d_in[4];
    const bf16* w2 = (const bf16*)d_in[5];
    const bf16* w3 = (const bf16*)d_in[6];
    const bf16* w4 = (const bf16*)d_in[7];
    const bf16* gate_w = (const bf16*)d_in[8];

    static EncodeFn enc = nullptr;
    static void *p_qkv, *p_h, *p_x1, *p_a5;
    static cudaStream_t s2;
    static cudaEvent_t ev_fork, ev_join;
    using G1 = GemmSmem<256, 4>;
    using G2 = GemmSmem<128, 5>;
    using G3 = GemmSmem<224, 4>;
    if (!enc) {
        void* fn = nullptr;
        cudaDriverEntryPointQueryResult qres;
        cudaGetDriverEntryPoint("cuTensorMapEncodeTiled", &fn, cudaEnableDefault, &qres);
        enc = (EncodeFn)fn;
        cudaGetSymbolAddress(&p_qkv, g_qkv);
        cudaGetSymbolAddress(&p_h, g_h);
        cudaGetSymbolAddress(&p_x1, g_x1);
        cudaGetSymbolAddress(&p_a5, g_a5);
        cudaFuncSetAttribute(gemm_kernel<1, 256, 4>, cudaFuncAttributeMaxDynamicSharedMemorySize, G1::TOTAL);
        cudaFuncSetAttribute(gemm_kernel<2, 128, 5>, cudaFuncAttributeMaxDynamicSharedMemorySize, G2::TOTAL);
        cudaFuncSetAttribute(gemm_kernel<3, 224, 4>, cudaFuncAttributeMaxDynamicSharedMemorySize, G3::TOTAL);
        cudaFuncSetAttribute(gemm_kernel<5, 128, 5>, cudaFuncAttributeMaxDynamicSharedMemorySize, G2::TOTAL);
        cudaStreamCreateWithFlags(&s2, cudaStreamNonBlocking);
        cudaEventCreateWithFlags(&ev_fork, cudaEventDisableTiming);
        cudaEventCreateWithFlags(&ev_join, cudaEventDisableTiming);
        cudaFuncSetAttribute(attn_kernel, cudaFuncAttributeMaxDynamicSharedMemorySize, ATT_SMEM);
        cudaFuncSetAttribute(attn_exact_kernel, cudaFuncAttributeMaxDynamicSharedMemorySize, ATT_SMEM);
    }
    const CUtensorMapSwizzle SW128 = CU_TENSOR_MAP_SWIZZLE_128B, SW64 = CU_TENSOR_MAP_SWIZZLE_64B;
    CUtensorMap mX = make_map(enc, x, S_LEN, DM, 64, 128, SW128);
    CUtensorMap mXres = make_map(enc, x, S_LEN, DM, 64, 64, SW128);
    CUtensorMap mWqkv = make_map(enc, wqkv, DM, 3 * DM, 64, 64, SW128);
    CUtensorMap mW1 = make_map(enc, w1, DM, DM, 64, 64, SW128);
    CUtensorMap mW2 = make_map(enc, w2, DM, DM, 64, 64, SW128);
    CUtensorMap mW3 = make_map(enc, w3, DM, FF, 64, 64, SW128);
    CUtensorMap mW4 = make_map(enc, w4, FF, DM, 64, 64, SW128);
    CUtensorMap mWo = make_map(enc, wo, DM, DM, 64, 64, SW128);
    CUtensorMap mQKVst = make_map(enc, p_qkv, S_LEN, 3 * DM, 64, 64, SW128);
    CUtensorMap mKV = make_map(enc, p_qkv, S_LEN, 3 * DM, 32, 128, SW64);
    CUtensorMap mHst = make_map(enc, p_h, S_LEN, DM, 64, 64, SW128);
    CUtensorMap mHld = make_map(enc, p_h, S_LEN, DM, 64, 128, SW128);
    CUtensorMap mX1st = make_map(enc, p_x1, S_LEN, DM, 64, 64, SW128);
    CUtensorMap mX1ld = make_map(enc, p_x1, S_LEN, DM, 64, 128, SW128);
    CUtensorMap mA5st = make_map(enc, p_a5, S_LEN, A5W, 64, 64, SW128);
    CUtensorMap mA5st32 = make_map(enc, p_a5, S_LEN, A5W, 32, 64, SW64);
    CUtensorMap mA5ld = make_map(enc, p_a5, S_LEN, A5W, 64, 128, SW128);
    CUtensorMap mOut = make_map(enc, d_out, S_LEN, DM, 64, 64, SW128);

    cudaStream_t st = cudaStreamPerThread;
    prep_kernel<<<256 + 72, 256, 0, st>>>(x, gate_w, w1, w3);
    launch_ex(gemm_kernel<1, 256, 4>, 132, 384, G1::TOTAL, st, 2, 1, mX, mWqkv, mW1, mQKVst, mHst, x, 16, 16);
    cudaEventRecord(ev_fork, st);
    launch_ex(attn_kernel, ATT_GRID, ATT_THREADS, ATT_SMEM, st, 1, 1, mKV);
    launch_ex(attn_exact_kernel, ATT_NTILES, ATT_THREADS, ATT_SMEM, st, 1, 1, mKV);
    cudaStreamWaitEvent(s2, ev_fork, 0);
    launch_ex(gemm_kernel<2, 128, 5>, 128, 384, G2::TOTAL, s2, 2, 0, mHld, mW2, mW2, mX1st, mXres, x, 8, 16);
    launch_ex(gemm_kernel<3, 224, 4>, 132, 384, G3::TOTAL, s2, 2, 1, mX1ld, mW3, mW3, mA5st, mA5st32, x, 16, 16);
    cudaEventRecord(ev_join, s2);
    cudaStreamWaitEvent(st, ev_join, 0);
    launch_ex(gemm_kernel<5, 128, 5>, 128, 384, G2::TOTAL, st, 2, 0, mA5ld, mWo, mW4, mOut, mX1st, (const bf16*)p_x1, 8, 72);
}
```

```cpp
#include <cuda_runtime.h>
#include <cuda_bf16.h>
#include <cuda.h>
#include <stdint.h>

typedef __nv_bfloat16 bf16;

constexpr int S_LEN = 2048;
constexpr int DM = 1024;
constexpr int FF = 3584;
constexpr int NH = 32;
constexpr int DH = 32;
constexpr int A5W = DM + FF;

__device__ __align__(1024) bf16 g_qkv[S_LEN * 3 * DM];
__device__ __align__(1024) bf16 g_h[S_LEN * DM];
__device__ __align__(1024) bf16 g_x1[S_LEN * DM];
__device__ __align__(1024) bf16 g_a5[S_LEN * A5W];
__device__ __align__(16) float g_mean1[S_LEN];
__device__ __align__(16) float g_rstd1[S_LEN];
__device__ __align__(16) float g_gate[S_LEN];
__device__ __align__(16) float g_omg[S_LEN];
__device__ __align__(16) float g_cs1[4 * DM];
__device__ __align__(16) float g_cs3[4 * FF];
__device__ __align__(16) float2 g_stat2[S_LEN * 8];
__device__ int g_bad[NH * 16];

#define TL_START(k)
#define PH(i)
#define TL_END(k)

__device__ __forceinline__ uint32_t smem_u32(const void* p) { return (uint32_t)__cvta_generic_to_shared(p); }

__device__ __forceinline__ void mbar_init(uint32_t bar, uint32_t count) {
    asm volatile("mbarrier.init.shared::cta.b64 [%0], %1;" ::"r"(bar), "r"(count));
}
__device__ __forceinline__ void mbar_expect_tx(uint32_t bar, uint32_t bytes) {
    asm volatile("mbarrier.arrive.expect_tx.shared::cta.b64 _, [%0], %1;" ::"r"(bar), "r"(bytes) : "memory");
}
__device__ __forceinline__ void mbar_arrive(uint32_t bar) {
    asm volatile("mbarrier.arrive.shared::cta.b64 _, [%0];" ::"r"(bar) : "memory");
}
__device__ __forceinline__ bool mbar_try_wait(uint32_t bar, uint32_t parity) {
    uint32_t ok;
    asm volatile(
        "{\n.reg .pred p;\n"
        "mbarrier.try_wait.parity.shared::cta.b64 p, [%1], %2;\n"
        "selp.u32 %0, 1, 0, p;\n}\n"
        : "=r"(ok)
        : "r"(bar), "r"(parity)
        : "memory");
    return ok != 0;
}
__device__ __forceinline__ void mbar_wait(uint32_t bar, uint32_t parity) {
    uint32_t spins = 0;
    while (!mbar_try_wait(bar, parity)) {
        if (++spins > (1u << 24)) __trap();
    }
}
__device__ __forceinline__ void tma_load_2d(uint32_t dst, const CUtensorMap* map, int c0, int c1, uint32_t bar) {
    asm volatile(
        "cp.async.bulk.tensor.2d.shared::cluster.global.mbarrier::complete_tx::bytes [%0], [%1, {%3, %4}], [%2];"
        ::"r"(dst), "l"(map), "r"(bar), "r"(c0), "r"(c1)
        : "memory");
}
__device__ __forceinline__ void tma_store_2d(const CUtensorMap* map, uint32_t src, int c0, int c1) {
    asm volatile("cp.async.bulk.tensor.2d.global.shared::cta.bulk_group [%0, {%2, %3}], [%1];"
                 ::"l"(map), "r"(src), "r"(c0), "r"(c1)
                 : "memory");
}
__device__ __forceinline__ void tma_load_2d_mc(uint32_t dst, const CUtensorMap* map, int c0, int c1, uint32_t bar, uint16_t mask) {
    asm volatile(
        "cp.async.bulk.tensor.2d.shared::cluster.global.mbarrier::complete_tx::bytes.multicast::cluster [%0], [%1, {%3, %4}], [%2], %5;"
        ::"r"(dst), "l"(map), "r"(bar), "r"(c0), "r"(c1), "h"(mask)
        : "memory");
}
__device__ __forceinline__ void mbar_arrive_cluster(uint32_t bar, uint32_t cta) {
    asm volatile(
        "{\n.reg .b32 ra;\nmapa.shared::cluster.u32 ra, %0, %1;\n"
        "mbarrier.arrive.shared::cluster.b64 _, [ra];\n}\n" ::"r"(bar), "r"(cta)
        : "memory");
}
__device__ __forceinline__ void cluster_sync_all() {
    asm volatile("barrier.cluster.arrive.release.aligned;\nbarrier.cluster.wait.acquire.aligned;" ::: "memory");
}
__device__ __forceinline__ uint32_t cluster_rank() { uint32_t r; asm volatile("mov.u32 %0, %%cluster_ctarank;" : "=r"(r)); return r; }
__device__ __forceinline__ void pdl_wait() { asm volatile("griddepcontrol.wait;" ::: "memory"); }
__device__ __forceinline__ void pdl_launch() { asm volatile("griddepcontrol.launch_dependents;" ::: "memory"); }
__device__ __forceinline__ void bulk_commit() { asm volatile("cp.async.bulk.commit_group;" ::: "memory"); }
__device__ __forceinline__ void bulk_wait_read0() { asm volatile("cp.async.bulk.wait_group.read 0;" ::: "memory"); }
__device__ __forceinline__ void bulk_wait0() { asm volatile("cp.async.bulk.wait_group 0;" ::: "memory"); }
__device__ __forceinline__ void fence_proxy_async() { asm volatile("fence.proxy.async.shared::cta;" ::: "memory"); }
__device__ __forceinline__ void named_bar_sync(int id, int n) { asm volatile("bar.sync %0, %1;" ::"r"(id), "r"(n) : "memory"); }
__device__ __forceinline__ void named_bar_arrive(int id, int n) { asm volatile("bar.arrive %0, %1;" ::"r"(id), "r"(n) : "memory"); }
__device__ __forceinline__ void wgmma_fence() { asm volatile("wgmma.fence.sync.aligned;" ::: "memory"); }
__device__ __forceinline__ void wgmma_commit() { asm volatile("wgmma.commit_group.sync.aligned;" ::: "memory"); }
template <int N>
__device__ __forceinline__ void wgmma_wait() { asm volatile("wgmma.wait_group.sync.aligned %0;" ::"n"(N) : "memory"); }
__device__ __forceinline__ void prefetch_tmap(const CUtensorMap* m) {
    asm volatile("prefetch.tensormap [%0];" ::"l"(m) : "memory");
}
template <int R>
__device__ __forceinline__ void reg_alloc() { asm volatile("setmaxnreg.inc.sync.aligned.u32 %0;" ::"n"(R)); }
template <int R>
__device__ __forceinline__ void reg_dealloc() { asm volatile("setmaxnreg.dec.sync.aligned.u32 %0;" ::"n"(R)); }
__device__ __forceinline__ void stmatrix_x4(uint32_t addr, uint32_t r0, uint32_t r1, uint32_t r2, uint32_t r3) {
    asm volatile("stmatrix.sync.aligned.m8n8.x4.shared.b16 [%0], {%1, %2, %3, %4};"
                 ::"r"(addr), "r"(r0), "r"(r1), "r"(r2), "r"(r3)
                 : "memory");
}
__device__ __forceinline__ uint32_t pack_bf16(float lo, float hi) {
    uint32_t r;
    asm("cvt.rn.bf16x2.f32 %0, %1, %2;" : "=r"(r) : "f"(hi), "f"(lo));
    return r;
}
__device__ __forceinline__ float bf16_round(float v) { return __bfloat162float(__float2bfloat16_rn(v)); }
__device__ __forceinline__ float ex2(float x) {
    float y;
    asm volatile("ex2.approx.ftz.f32 %0, %1;" : "=f"(y) : "f"(x));
    return y;
}
__device__ __forceinline__ float tanh_fast(float x) {
    float y;
    asm("tanh.approx.f32 %0, %1;" : "=f"(y) : "f"(x));
    return y;
}
__device__ __forceinline__ float gelu_tanh(float v) {
    float u = 0.7978845608028654f * (v + 0.044715f * v * v * v);
    float hv = 0.5f * v;
    return fmaf(hv, tanh_fast(u), hv);
}
__device__ __forceinline__ uint32_t desc_lo(uint32_t addr, uint32_t lbo_bytes) {
    return ((addr & 0x3FFFF) >> 4) | (((lbo_bytes >> 4) & 0x3FFF) << 16);
}
__host__ __device__ constexpr uint32_t desc_hi(uint32_t sbo_bytes, uint32_t swz) {
    return ((sbo_bytes >> 4) & 0x3FFF) | (swz << 30);
}

__device__ __forceinline__ void wgmma_ss_n128_tb1(float (&d)[64], uint32_t alo, uint32_t ahi, uint32_t blo, uint32_t bhi, int scale_d) {
    asm volatile("{\n.reg .pred p;\n.reg .b64 da, db;\nsetp.ne.b32 p, %68, 0;\nmov.b64 da, {%64, %65};\nmov.b64 db, {%66, %67};\n"
        "wgmma.mma_async.sync.aligned.m64n128k16.f32.bf16.bf16 {%0, %1, %2, %3, %4, %5, %6, %7, %8, %9, %10, %11, %12, %13, %14, %15, %16, %17, %18, %19, %20, %21, %22, %23, %24, %25, %26, %27, %28, %29, %30, %31, %32, %33, %34, %35, %36, %37, %38, %39, %40, %41, %42, %43, %44, %45, %46, %47, %48, %49, %50, %51, %52, %53, %54, %55, %56, %57, %58, %59, %60, %61, %62, %63}, da, db, p, 1, 1, 0, 1;\n}\n"
        : "+f"(d[0]), "+f"(d[1]), "+f"(d[2]), "+f"(d[3]), "+f"(d[4]), "+f"(d[5]), "+f"(d[6]), "+f"(d[7]), "+f"(d[8]), "+f"(d[9]), "+f"(d[10]), "+f"(d[11]), "+f"(d[12]), "+f"(d[13]), "+f"(d[14]), "+f"(d[15]), "+f"(d[16]), "+f"(d[17]), "+f"(d[18]), "+f"(d[19]), "+f"(d[20]), "+f"(d[21]), "+f"(d[22]), "+f"(d[23]), "+f"(d[24]), "+f"(d[25]), "+f"(d[26]), "+f"(d[27]), "+f"(d[28]), "+f"(d[29]), "+f"(d[30]), "+f"(d[31]), "+f"(d[32]), "+f"(d[33]), "+f"(d[34]), "+f"(d[35]), "+f"(d[36]), "+f"(d[37]), "+f"(d[38]), "+f"(d[39]), "+f"(d[40]), "+f"(d[41]), "+f"(d[42]), "+f"(d[43]), "+f"(d[44]), "+f"(d[45]), "+f"(d[46]), "+f"(d[47]), "+f"(d[48]), "+f"(d[49]), "+f"(d[50]), "+f"(d[51]), "+f"(d[52]), "+f"(d[53]), "+f"(d[54]), "+f"(d[55]), "+f"(d[56]), "+f"(d[57]), "+f"(d[58]), "+f"(d[59]), "+f"(d[60]), "+f"(d[61]), "+f"(d[62]), "+f"(d[63])
        : "r"(alo), "r"(ahi), "r"(blo), "r"(bhi), "r"(scale_d));
}

__device__ __forceinline__ void wgmma_ss_n192_tb1(float (&d)[96], uint32_t alo, uint32_t ahi, uint32_t blo, uint32_t bhi, int scale_d) {
    asm volatile("{\n.reg .pred p;\n.reg .b64 da, db;\nsetp.ne.b32 p, %100, 0;\nmov.b64 da, {%96, %97};\nmov.b64 db, {%98, %99};\n"
        "wgmma.mma_async.sync.aligned.m64n192k16.f32.bf16.bf16 {%0, %1, %2, %3, %4, %5, %6, %7, %8, %9, %10, %11, %12, %13, %14, %15, %16, %17, %18, %19, %20, %21, %22, %23, %24, %25, %26, %27, %28, %29, %30, %31, %32, %33, %34, %35, %36, %37, %38, %39, %40, %41, %42, %43, %44, %45, %46, %47, %48, %49, %50, %51, %52, %53, %54, %55, %56, %57, %58, %59, %60, %61, %62, %63, %64, %65, %66, %67, %68, %69, %70, %71, %72, %73, %74, %75, %76, %77, %78, %79, %80, %81, %82, %83, %84, %85, %86, %87, %88, %89, %90, %91, %92, %93, %94, %95}, da, db, p, 1, 1, 0, 1;\n}\n"
        : "+f"(d[0]), "+f"(d[1]), "+f"(d[2]), "+f"(d[3]), "+f"(d[4]), "+f"(d[5]), "+f"(d[6]), "+f"(d[7]), "+f"(d[8]), "+f"(d[9]), "+f"(d[10]), "+f"(d[11]), "+f"(d[12]), "+f"(d[13]), "+f"(d[14]), "+f"(d[15]), "+f"(d[16]), "+f"(d[17]), "+f"(d[18]), "+f"(d[19]), "+f"(d[20]), "+f"(d[21]), "+f"(d[22]), "+f"(d[23]), "+f"(d[24]), "+f"(d[25]), "+f"(d[26]), "+f"(d[27]), "+f"(d[28]), "+f"(d[29]), "+f"(d[30]), "+f"(d[31]), "+f"(d[32]), "+f"(d[33]), "+f"(d[34]), "+f"(d[35]), "+f"(d[36]), "+f"(d[37]), "+f"(d[38]), "+f"(d[39]), "+f"(d[40]), "+f"(d[41]), "+f"(d[42]), "+f"(d[43]), "+f"(d[44]), "+f"(d[45]), "+f"(d[46]), "+f"(d[47]), "+f"(d[48]), "+f"(d[49]), "+f"(d[50]), "+f"(d[51]), "+f"(d[52]), "+f"(d[53]), "+f"(d[54]), "+f"(d[55]), "+f"(d[56]), "+f"(d[57]), "+f"(d[58]), "+f"(d[59]), "+f"(d[60]), "+f"(d[61]), "+f"(d[62]), "+f"(d[63]), "+f"(d[64]), "+f"(d[65]), "+f"(d[66]), "+f"(d[67]), "+f"(d[68]), "+f"(d[69]), "+f"(d[70]), "+f"(d[71]), "+f"(d[72]), "+f"(d[73]), "+f"(d[74]), "+f"(d[75]), "+f"(d[76]), "+f"(d[77]), "+f"(d[78]), "+f"(d[79]), "+f"(d[80]), "+f"(d[81]), "+f"(d[82]), "+f"(d[83]), "+f"(d[84]), "+f"(d[85]), "+f"(d[86]), "+f"(d[87]), "+f"(d[88]), "+f"(d[89]), "+f"(d[90]), "+f"(d[91]), "+f"(d[92]), "+f"(d[93]), "+f"(d[94]), "+f"(d[95])
        : "r"(alo), "r"(ahi), "r"(blo), "r"(bhi), "r"(scale_d));
}

__device__ __forceinline__ void wgmma_ss_n224_tb1(float (&d)[112], uint32_t alo, uint32_t ahi, uint32_t blo, uint32_t bhi, int scale_d) {
    asm volatile("{\n.reg .pred p;\n.reg .b64 da, db;\nsetp.ne.b32 p, %116, 0;\nmov.b64 da, {%112, %113};\nmov.b64 db, {%114, %115};\n"
        "wgmma.mma_async.sync.aligned.m64n224k16.f32.bf16.bf16 {%0, %1, %2, %3, %4, %5, %6, %7, %8, %9, %10, %11, %12, %13, %14, %15, %16, %17, %18, %19, %20, %21, %22, %23, %24, %25, %26, %27, %28, %29, %30, %31, %32, %33, %34, %35, %36, %37, %38, %39, %40, %41, %42, %43, %44, %45, %46, %47, %48, %49, %50, %51, %52, %53, %54, %55, %56, %57, %58, %59, %60, %61, %62, %63, %64, %65, %66, %67, %68, %69, %70, %71, %72, %73, %74, %75, %76, %77, %78, %79, %80, %81, %82, %83, %84, %85, %86, %87, %88, %89, %90, %91, %92, %93, %94, %95, %96, %97, %98, %99, %100, %101, %102, %103, %104, %105, %106, %107, %108, %109, %110, %111}, da, db, p, 1, 1, 0, 1;\n}\n"
        : "+f"(d[0]), "+f"(d[1]), "+f"(d[2]), "+f"(d[3]), "+f"(d[4]), "+f"(d[5]), "+f"(d[6]), "+f"(d[7]), "+f"(d[8]), "+f"(d[9]), "+f"(d[10]), "+f"(d[11]), "+f"(d[12]), "+f"(d[13]), "+f"(d[14]), "+f"(d[15]), "+f"(d[16]), "+f"(d[17]), "+f"(d[18]), "+f"(d[19]), "+f"(d[20]), "+f"(d[21]), "+f"(d[22]), "+f"(d[23]), "+f"(d[24]), "+f"(d[25]), "+f"(d[26]), "+f"(d[27]), "+f"(d[28]), "+f"(d[29]), "+f"(d[30]), "+f"(d[31]), "+f"(d[32]), "+f"(d[33]), "+f"(d[34]), "+f"(d[35]), "+f"(d[36]), "+f"(d[37]), "+f"(d[38]), "+f"(d[39]), "+f"(d[40]), "+f"(d[41]), "+f"(d[42]), "+f"(d[43]), "+f"(d[44]), "+f"(d[45]), "+f"(d[46]), "+f"(d[47]), "+f"(d[48]), "+f"(d[49]), "+f"(d[50]), "+f"(d[51]), "+f"(d[52]), "+f"(d[53]), "+f"(d[54]), "+f"(d[55]), "+f"(d[56]), "+f"(d[57]), "+f"(d[58]), "+f"(d[59]), "+f"(d[60]), "+f"(d[61]), "+f"(d[62]), "+f"(d[63]), "+f"(d[64]), "+f"(d[65]), "+f"(d[66]), "+f"(d[67]), "+f"(d[68]), "+f"(d[69]), "+f"(d[70]), "+f"(d[71]), "+f"(d[72]), "+f"(d[73]), "+f"(d[74]), "+f"(d[75]), "+f"(d[76]), "+f"(d[77]), "+f"(d[78]), "+f"(d[79]), "+f"(d[80]), "+f"(d[81]), "+f"(d[82]), "+f"(d[83]), "+f"(d[84]), "+f"(d[85]), "+f"(d[86]), "+f"(d[87]), "+f"(d[88]), "+f"(d[89]), "+f"(d[90]), "+f"(d[91]), "+f"(d[92]), "+f"(d[93]), "+f"(d[94]), "+f"(d[95]), "+f"(d[96]), "+f"(d[97]), "+f"(d[98]), "+f"(d[99]), "+f"(d[100]), "+f"(d[101]), "+f"(d[102]), "+f"(d[103]), "+f"(d[104]), "+f"(d[105]), "+f"(d[106]), "+f"(d[107]), "+f"(d[108]), "+f"(d[109]), "+f"(d[110]), "+f"(d[111])
        : "r"(alo), "r"(ahi), "r"(blo), "r"(bhi), "r"(scale_d));
}

__device__ __forceinline__ void wgmma_ss_n256_tb1(float (&d)[128], uint32_t alo, uint32_t ahi, uint32_t blo, uint32_t bhi, int scale_d) {
    asm volatile("{\n.reg .pred p;\n.reg .b64 da, db;\nsetp.ne.b32 p, %132, 0;\nmov.b64 da, {%128, %129};\nmov.b64 db, {%130, %131};\n"
        "wgmma.mma_async.sync.aligned.m64n256k16.f32.bf16.bf16 {%0, %1, %2, %3, %4, %5, %6, %7, %8, %9, %10, %11, %12, %13, %14, %15, %16, %17, %18, %19, %20, %21, %22, %23, %24, %25, %26, %27, %28, %29, %30, %31, %32, %33, %34, %35, %36, %37, %38, %39, %40, %41, %42, %43, %44, %45, %46, %47, %48, %49, %50, %51, %52, %53, %54, %55, %56, %57, %58, %59, %60, %61, %62, %63, %64, %65, %66, %67, %68, %69, %70, %71, %72, %73, %74, %75, %76, %77, %78, %79, %80, %81, %82, %83, %84, %85, %86, %87, %88, %89, %90, %91, %92, %93, %94, %95, %96, %97, %98, %99, %100, %101, %102, %103, %104, %105, %106, %107, %108, %109, %110, %111, %112, %113, %114, %115, %116, %117, %118, %119, %120, %121, %122, %123, %124, %125, %126, %127}, da, db, p, 1, 1, 0, 1;\n}\n"
        : "+f"(d[0]), "+f"(d[1]), "+f"(d[2]), "+f"(d[3]), "+f"(d[4]), "+f"(d[5]), "+f"(d[6]), "+f"(d[7]), "+f"(d[8]), "+f"(d[9]), "+f"(d[10]), "+f"(d[11]), "+f"(d[12]), "+f"(d[13]), "+f"(d[14]), "+f"(d[15]), "+f"(d[16]), "+f"(d[17]), "+f"(d[18]), "+f"(d[19]), "+f"(d[20]), "+f"(d[21]), "+f"(d[22]), "+f"(d[23]), "+f"(d[24]), "+f"(d[25]), "+f"(d[26]), "+f"(d[27]), "+f"(d[28]), "+f"(d[29]), "+f"(d[30]), "+f"(d[31]), "+f"(d[32]), "+f"(d[33]), "+f"(d[34]), "+f"(d[35]), "+f"(d[36]), "+f"(d[37]), "+f"(d[38]), "+f"(d[39]), "+f"(d[40]), "+f"(d[41]), "+f"(d[42]), "+f"(d[43]), "+f"(d[44]), "+f"(d[45]), "+f"(d[46]), "+f"(d[47]), "+f"(d[48]), "+f"(d[49]), "+f"(d[50]), "+f"(d[51]), "+f"(d[52]), "+f"(d[53]), "+f"(d[54]), "+f"(d[55]), "+f"(d[56]), "+f"(d[57]), "+f"(d[58]), "+f"(d[59]), "+f"(d[60]), "+f"(d[61]), "+f"(d[62]), "+f"(d[63]), "+f"(d[64]), "+f"(d[65]), "+f"(d[66]), "+f"(d[67]), "+f"(d[68]), "+f"(d[69]), "+f"(d[70]), "+f"(d[71]), "+f"(d[72]), "+f"(d[73]), "+f"(d[74]), "+f"(d[75]), "+f"(d[76]), "+f"(d[77]), "+f"(d[78]), "+f"(d[79]), "+f"(d[80]), "+f"(d[81]), "+f"(d[82]), "+f"(d[83]), "+f"(d[84]), "+f"(d[85]), "+f"(d[86]), "+f"(d[87]), "+f"(d[88]), "+f"(d[89]), "+f"(d[90]), "+f"(d[91]), "+f"(d[92]), "+f"(d[93]), "+f"(d[94]), "+f"(d[95]), "+f"(d[96]), "+f"(d[97]), "+f"(d[98]), "+f"(d[99]), "+f"(d[100]), "+f"(d[101]), "+f"(d[102]), "+f"(d[103]), "+f"(d[104]), "+f"(d[105]), "+f"(d[106]), "+f"(d[107]), "+f"(d[108]), "+f"(d[109]), "+f"(d[110]), "+f"(d[111]), "+f"(d[112]), "+f"(d[113]), "+f"(d[114]), "+f"(d[115]), "+f"(d[116]), "+f"(d[117]), "+f"(d[118]), "+f"(d[119]), "+f"(d[120]), "+f"(d[121]), "+f"(d[122]), "+f"(d[123]), "+f"(d[124]), "+f"(d[125]), "+f"(d[126]), "+f"(d[127])
        : "r"(alo), "r"(ahi), "r"(blo), "r"(bhi), "r"(scale_d));
}

__device__ __forceinline__ void wgmma_ss_n64_tb0(float (&d)[32], uint32_t alo, uint32_t ahi, uint32_t blo, uint32_t bhi, int scale_d) {
    asm volatile("{\n.reg .pred p;\n.reg .b64 da, db;\nsetp.ne.b32 p, %36, 0;\nmov.b64 da, {%32, %33};\nmov.b64 db, {%34, %35};\n"
        "wgmma.mma_async.sync.aligned.m64n64k16.f32.bf16.bf16 {%0, %1, %2, %3, %4, %5, %6, %7, %8, %9, %10, %11, %12, %13, %14, %15, %16, %17, %18, %19, %20, %21, %22, %23, %24, %25, %26, %27, %28, %29, %30, %31}, da, db, p, 1, 1, 0, 0;\n}\n"
        : "+f"(d[0]), "+f"(d[1]), "+f"(d[2]), "+f"(d[3]), "+f"(d[4]), "+f"(d[5]), "+f"(d[6]), "+f"(d[7]), "+f"(d[8]), "+f"(d[9]), "+f"(d[10]), "+f"(d[11]), "+f"(d[12]), "+f"(d[13]), "+f"(d[14]), "+f"(d[15]), "+f"(d[16]), "+f"(d[17]), "+f"(d[18]), "+f"(d[19]), "+f"(d[20]), "+f"(d[21]), "+f"(d[22]), "+f"(d[23]), "+f"(d[24]), "+f"(d[25]), "+f"(d[26]), "+f"(d[27]), "+f"(d[28]), "+f"(d[29]), "+f"(d[30]), "+f"(d[31])
        : "r"(alo), "r"(ahi), "r"(blo), "r"(bhi), "r"(scale_d));
}

__device__ __forceinline__ void wgmma_rs_n128_tb0(float (&d)[64], uint32_t a0, uint32_t a1, uint32_t a2, uint32_t a3, uint32_t blo, uint32_t bhi, int scale_d) {
    asm volatile("{\n.reg .pred p;\n.reg .b64 db;\nsetp.ne.b32 p, %70, 0;\nmov.b64 db, {%68, %69};\n"
        "wgmma.mma_async.sync.aligned.m64n128k16.f32.bf16.bf16 {%0, %1, %2, %3, %4, %5, %6, %7, %8, %9, %10, %11, %12, %13, %14, %15, %16, %17, %18, %19, %20, %21, %22, %23, %24, %25, %26, %27, %28, %29, %30, %31, %32, %33, %34, %35, %36, %37, %38, %39, %40, %41, %42, %43, %44, %45, %46, %47, %48, %49, %50, %51, %52, %53, %54, %55, %56, %57, %58, %59, %60, %61, %62, %63}, {%64, %65, %66, %67}, db, p, 1, 1, 0;\n}\n"
        : "+f"(d[0]), "+f"(d[1]), "+f"(d[2]), "+f"(d[3]), "+f"(d[4]), "+f"(d[5]), "+f"(d[6]), "+f"(d[7]), "+f"(d[8]), "+f"(d[9]), "+f"(d[10]), "+f"(d[11]), "+f"(d[12]), "+f"(d[13]), "+f"(d[14]), "+f"(d[15]), "+f"(d[16]), "+f"(d[17]), "+f"(d[18]), "+f"(d[19]), "+f"(d[20]), "+f"(d[21]), "+f"(d[22]), "+f"(d[23]), "+f"(d[24]), "+f"(d[25]), "+f"(d[26]), "+f"(d[27]), "+f"(d[28]), "+f"(d[29]), "+f"(d[30]), "+f"(d[31]), "+f"(d[32]), "+f"(d[33]), "+f"(d[34]), "+f"(d[35]), "+f"(d[36]), "+f"(d[37]), "+f"(d[38]), "+f"(d[39]), "+f"(d[40]), "+f"(d[41]), "+f"(d[42]), "+f"(d[43]), "+f"(d[44]), "+f"(d[45]), "+f"(d[46]), "+f"(d[47]), "+f"(d[48]), "+f"(d[49]), "+f"(d[50]), "+f"(d[51]), "+f"(d[52]), "+f"(d[53]), "+f"(d[54]), "+f"(d[55]), "+f"(d[56]), "+f"(d[57]), "+f"(d[58]), "+f"(d[59]), "+f"(d[60]), "+f"(d[61]), "+f"(d[62]), "+f"(d[63])
        : "r"(a0), "r"(a1), "r"(a2), "r"(a3), "r"(blo), "r"(bhi), "r"(scale_d));
}

__device__ __forceinline__ void wgmma_rs_n64_tb0(float (&d)[32], uint32_t a0, uint32_t a1, uint32_t a2, uint32_t a3, uint32_t blo, uint32_t bhi, int scale_d) {
    asm volatile("{\n.reg .pred p;\n.reg .b64 db;\nsetp.ne.b32 p, %38, 0;\nmov.b64 db, {%36, %37};\n"
        "wgmma.mma_async.sync.aligned.m64n64k16.f32.bf16.bf16 {%0, %1, %2, %3, %4, %5, %6, %7, %8, %9, %10, %11, %12, %13, %14, %15, %16, %17, %18, %19, %20, %21, %22, %23, %24, %25, %26, %27, %28, %29, %30, %31}, {%32, %33, %34, %35}, db, p, 1, 1, 0;\n}\n"
        : "+f"(d[0]), "+f"(d[1]), "+f"(d[2]), "+f"(d[3]), "+f"(d[4]), "+f"(d[5]), "+f"(d[6]), "+f"(d[7]), "+f"(d[8]), "+f"(d[9]), "+f"(d[10]), "+f"(d[11]), "+f"(d[12]), "+f"(d[13]), "+f"(d[14]), "+f"(d[15]), "+f"(d[16]), "+f"(d[17]), "+f"(d[18]), "+f"(d[19]), "+f"(d[20]), "+f"(d[21]), "+f"(d[22]), "+f"(d[23]), "+f"(d[24]), "+f"(d[25]), "+f"(d[26]), "+f"(d[27]), "+f"(d[28]), "+f"(d[29]), "+f"(d[30]), "+f"(d[31])
        : "r"(a0), "r"(a1), "r"(a2), "r"(a3), "r"(blo), "r"(bhi), "r"(scale_d));
}

__device__ __forceinline__ void wgmma_rs_n32_tb1(float (&d)[16], uint32_t a0, uint32_t a1, uint32_t a2, uint32_t a3, uint32_t blo, uint32_t bhi, int scale_d) {
    asm volatile("{\n.reg .pred p;\n.reg .b64 db;\nsetp.ne.b32 p, %22, 0;\nmov.b64 db, {%20, %21};\n"
        "wgmma.mma_async.sync.aligned.m64n32k16.f32.bf16.bf16 {%0, %1, %2, %3, %4, %5, %6, %7, %8, %9, %10, %11, %12, %13, %14, %15}, {%16, %17, %18, %19}, db, p, 1, 1, 1;\n}\n"
        : "+f"(d[0]), "+f"(d[1]), "+f"(d[2]), "+f"(d[3]), "+f"(d[4]), "+f"(d[5]), "+f"(d[6]), "+f"(d[7]), "+f"(d[8]), "+f"(d[9]), "+f"(d[10]), "+f"(d[11]), "+f"(d[12]), "+f"(d[13]), "+f"(d[14]), "+f"(d[15])
        : "r"(a0), "r"(a1), "r"(a2), "r"(a3), "r"(blo), "r"(bhi), "r"(scale_d));
}

__device__ __forceinline__ void wgmma_rs_n40_tb1(float (&d)[20], uint32_t a0, uint32_t a1, uint32_t a2, uint32_t a3, uint32_t blo, uint32_t bhi, int scale_d) {
    asm volatile("{\n.reg .pred p;\n.reg .b64 db;\nsetp.ne.b32 p, %26, 0;\nmov.b64 db, {%24, %25};\n"
        "wgmma.mma_async.sync.aligned.m64n40k16.f32.bf16.bf16 {%0, %1, %2, %3, %4, %5, %6, %7, %8, %9, %10, %11, %12, %13, %14, %15, %16, %17, %18, %19}, {%20, %21, %22, %23}, db, p, 1, 1, 1;\n}\n"
        : "+f"(d[0]), "+f"(d[1]), "+f"(d[2]), "+f"(d[3]), "+f"(d[4]), "+f"(d[5]), "+f"(d[6]), "+f"(d[7]), "+f"(d[8]), "+f"(d[9]), "+f"(d[10]), "+f"(d[11]), "+f"(d[12]), "+f"(d[13]), "+f"(d[14]), "+f"(d[15]), "+f"(d[16]), "+f"(d[17]), "+f"(d[18]), "+f"(d[19])
        : "r"(a0), "r"(a1), "r"(a2), "r"(a3), "r"(blo), "r"(bhi), "r"(scale_d));
}

template <int BN>
__device__ __forceinline__ void wgmma_tile(float (&d)[BN / 2], uint32_t da, uint32_t db, int sd) {
    constexpr uint32_t HI = desc_hi(1024, 1);
    if constexpr (BN == 128) wgmma_ss_n128_tb1(d, da, HI, db, HI, sd);
    else if constexpr (BN == 192) wgmma_ss_n192_tb1(d, da, HI, db, HI, sd);
    else if constexpr (BN == 224) wgmma_ss_n224_tb1(d, da, HI, db, HI, sd);
    else wgmma_ss_n256_tb1(d, da, HI, db, HI, sd);
}

__global__ void __launch_bounds__(256) prep_kernel(const bf16* __restrict__ x, const bf16* __restrict__ gate_w,
                                                   const bf16* __restrict__ w, int ld, float* __restrict__ cs_out,
                                                   int row_blocks) {
    const int tid = threadIdx.x;
    TL_START(0)
    pdl_launch();
    if ((int)blockIdx.x < row_blocks) {
        const int row = blockIdx.x * 8 + (tid >> 5);
        const int lane = tid & 31;
        const uint4* xr = reinterpret_cast<const uint4*>(x + (size_t)row * DM);
        const uint4* gw = reinterpret_cast<const uint4*>(gate_w);
        float v[32];
        float gsum = 0.f, sum = 0.f;
#pragma unroll
        for (int i = 0; i < 4; i++) {
            uint4 a = xr[lane + 32 * i];
            uint4 b = gw[lane + 32 * i];
            const uint32_t aa[4] = {a.x, a.y, a.z, a.w};
            const uint32_t bb[4] = {b.x, b.y, b.z, b.w};
#pragma unroll
            for (int j = 0; j < 4; j++) {
                float x0 = __uint_as_float(aa[j] << 16), x1 = __uint_as_float(aa[j] & 0xFFFF0000u);
                float g0 = __uint_as_float(bb[j] << 16), g1 = __uint_as_float(bb[j] & 0xFFFF0000u);
                v[i * 8 + j * 2] = x0;
                v[i * 8 + j * 2 + 1] = x1;
                sum += x0 + x1;
                gsum += bf16_round(x0 * g0) + bf16_round(x1 * g1);
            }
        }
#pragma unroll
        for (int o = 16; o > 0; o >>= 1) {
            sum += __shfl_xor_sync(0xffffffffu, sum, o);
            gsum += __shfl_xor_sync(0xffffffffu, gsum, o);
        }
        const float mean = sum * (1.0f / DM);
        float m2 = 0.f;
#pragma unroll
        for (int i = 0; i < 32; i++) {
            float d = v[i] - mean;
            m2 += d * d;
        }
#pragma unroll
        for (int o = 16; o > 0; o >>= 1) m2 += __shfl_xor_sync(0xffffffffu, m2, o);
        if (lane == 0) {
            g_mean1[row] = mean;
            g_rstd1[row] = rsqrtf(m2 * (1.0f / DM) + 1e-5f);
            float logit = bf16_round(gsum);
            float g = bf16_round(1.0f / (1.0f + __expf(-logit)));
            g_gate[row] = g;
            g_omg[row] = bf16_round(1.0f - g);
        }
    } else {
        __shared__ float red[32][65];
        const int blk = blockIdx.x - row_blocks;
        const int chunk = blk & 3;
        const int col0 = (blk >> 2) * 64;
        const int cg = tid & 7;
        const int rg = tid >> 3;
        uint4 a[8];
#pragma unroll
        for (int r = 0; r < 8; r++)
            a[r] = *reinterpret_cast<const uint4*>(w + (size_t)(chunk * 256 + r * 32 + rg) * ld + col0 + cg * 8);
        float acc[8];
#pragma unroll
        for (int j = 0; j < 8; j++) acc[j] = 0.f;
#pragma unroll
        for (int r = 0; r < 8; r++) {
            const uint32_t aa[4] = {a[r].x, a[r].y, a[r].z, a[r].w};
#pragma unroll
            for (int j = 0; j < 4; j++) {
                acc[2 * j] += __uint_as_float(aa[j] << 16);
                acc[2 * j + 1] += __uint_as_float(aa[j] & 0xFFFF0000u);
            }
        }
#pragma unroll
        for (int j = 0; j < 8; j++) red[rg][cg * 8 + j] = acc[j];
        __syncthreads();
        if (tid < 64) {
            float s = 0.f;
#pragma unroll
            for (int r = 0; r < 32; r++) s += red[r][tid];
            cs_out[chunk * ld + col0 + tid] = s;
        }
    }
    TL_END(0)
}

#define RELEASE_STAGE(b) if (tid_wg < 2) mbar_arrive_cluster(b, tid_wg)
template <int BN, int STAGES>
struct GemmSmem {
    static constexpr int A_BYTES = 128 * 64 * 2;
    static constexpr int B_BOXES = (BN + 63) / 64;
    static constexpr int B_BYTES = B_BOXES * 64 * 64 * 2;
    static constexpr int STAGE_BYTES = A_BYTES + B_BYTES;
    static constexpr int STG_OFF = STAGES * STAGE_BYTES;
    static constexpr int CS_OFF = STAGES * STAGE_BYTES + 2 * 16384;
    static constexpr int BAR_OFF = CS_OFF + 1024;
    static constexpr int TOTAL = BAR_OFF + 128 + 512;
};

template <int MODE, int BN, int STAGES>
__global__ void __launch_bounds__(384, 1)
gemm_kernel(const __grid_constant__ CUtensorMap mA, const __grid_constant__ CUtensorMap mB0,
            const __grid_constant__ CUtensorMap mB1, const __grid_constant__ CUtensorMap mC0,
            const __grid_constant__ CUtensorMap mC1, const bf16* __restrict__ xin, int n_tiles_n, int kblocks) {
    using L = GemmSmem<BN, STAGES>;
    extern __shared__ uint8_t smem_raw[];
    const uint32_t sbase = (smem_u32(smem_raw) + 1023u) & ~1023u;
    const uint32_t bar_full = sbase + L::BAR_OFF;
    const uint32_t bar_empty = bar_full + 8 * STAGES;
    const uint32_t bar_res = bar_empty + 8 * STAGES;
    const int wg = threadIdx.x >> 7;
    const int npairs = 8 * n_tiles_n;
    const uint32_t crank = cluster_rank();
    const int cid = blockIdx.x >> 1, ncl = gridDim.x >> 1;
    TL_START(MODE)
    pdl_launch();

    if (threadIdx.x == 0) {
        for (int s = 0; s < STAGES; s++) {
            mbar_init(bar_full + 8 * s, 1);
            mbar_init(bar_empty + 8 * s, 4);
        }
        mbar_init(bar_res, 1);
        asm volatile("fence.mbarrier_init.release.cluster;" ::: "memory");
        prefetch_tmap(&mA);
        prefetch_tmap(&mB0);
        if (MODE == 1 || MODE == 5) prefetch_tmap(&mB1);
        if (MODE == 2 || MODE == 5) prefetch_tmap(&mC1);
        prefetch_tmap(&mC0);
    }
    cluster_sync_all();

    if (wg == 0) {
        reg_dealloc<40>();
        if (threadIdx.x == 0) {
            if (MODE != 1) pdl_wait();
            int stage = 0;
            uint32_t phase = 1;
            for (int pr = cid; pr < npairs; pr += ncl) {
                const int m0 = ((pr & 7) * 2 + crank) * 128;
                const int n0 = (pr >> 3) * BN;
                for (int kb = 0; kb < kblocks; kb++) {
                    mbar_wait(bar_empty + 8 * stage, phase);
                    const uint32_t sa = sbase + stage * L::STAGE_BYTES;
                    const uint32_t sb = sa + L::A_BYTES;
                    const uint32_t fb = bar_full + 8 * stage;
                    mbar_expect_tx(fb, L::STAGE_BYTES);
                    int arow = m0;
                    if (MODE == 2) {
                        const int grp = kb >> 2;
                        arow += (grp == 0) ? -1 : (grp == 1) ? 1 : (grp == 2) ? -2 : 2;
                    }
                    tma_load_2d(sa, &mA, kb * 64, arow, fb);
                    const CUtensorMap* mb = &mB0;
                    int bc = n0, br = kb * 64;
                    if (MODE == 1 && n0 >= 3 * DM) { mb = &mB1; bc = n0 - 3 * DM; }
                    if (MODE == 5 && kb >= 16) { mb = &mB1; br = (kb - 16) * 64; }
#pragma unroll
                    for (int b = 0; b < L::B_BOXES / 2; b++) {
                        const int bb = crank * (L::B_BOXES / 2) + b;
                        tma_load_2d_mc(sb + bb * 8192, mb, bc + bb * 64, br, fb, (uint16_t)3);
                    }
                    if ((MODE == 2 || MODE == 5) && kb == STAGES - 1) {
                        mbar_expect_tx(bar_res, 32768);
#pragma unroll
                        for (int q = 0; q < 4; q++)
                            tma_load_2d(sbase + L::STG_OFF + q * 8192, &mC1, n0 + (q & 1) * 64, m0 + (q >> 1) * 64, bar_res);
                    }
                    if (++stage == STAGES) { stage = 0; phase ^= 1; }
                }
            }
        }
    } else {
        reg_alloc<232>();
        const int c = wg - 1;
        const int warp = (threadIdx.x >> 5) & 3;
        const int lane = threadIdx.x & 31;
        const int tid_wg = threadIdx.x & 127;
        const uint32_t stg = sbase + L::STG_OFF + c * 16384;
        int stage = 0;
        uint32_t phase = 0;
        float acc[BN / 2];
        bool first = true;
        PH(0)
        if (MODE != 1) pdl_wait();
        for (int pr = cid; pr < npairs; pr += ncl) {
            const int m0 = ((pr & 7) * 2 + crank) * 128;
            const int n0 = (pr >> 3) * BN;
            const int r0 = m0 + c * 64 + warp * 16 + (lane >> 2);
            const int r1 = r0 + 8;
            float mu[2], rs[2], og[2];
            if (MODE == 3) {
                const int t = threadIdx.x - 128;
                if (t < BN) {
                    const float v = (g_cs3[n0 + t] + g_cs3[FF + n0 + t]) + (g_cs3[2 * FF + n0 + t] + g_cs3[3 * FF + n0 + t]);
                    asm volatile("st.shared.f32 [%0], %1;" ::"r"(sbase + L::CS_OFF + t * 4), "f"(v) : "memory");
                }
#pragma unroll
                for (int h = 0; h < 2; h++) {
                    const float4* sp = reinterpret_cast<const float4*>(&g_stat2[(h ? r1 : r0) * 8]);
                    float4 p[4];
                    float s = 0.f;
#pragma unroll
                    for (int i = 0; i < 4; i++) { p[i] = sp[i]; s += p[i].x + p[i].z; }
                    const float mean = s * (1.0f / DM);
                    float m2 = 0.f;
#pragma unroll
                    for (int i = 0; i < 4; i++) {
                        float d0 = p[i].x * (1.0f / 128) - mean, d1 = p[i].z * (1.0f / 128) - mean;
                        m2 += p[i].y + p[i].w + 128.0f * (d0 * d0 + d1 * d1);
                    }
                    mu[h] = mean;
                    rs[h] = rsqrtf(m2 * (1.0f / DM) + 1e-5f);
                }
            }
            if (MODE == 3 || MODE == 5) { og[0] = g_omg[r0]; og[1] = g_omg[r1]; }
            int prev_stage = 0;
            for (int kb = 0; kb < kblocks; kb++) {
                mbar_wait(bar_full + 8 * stage, phase);
                const uint32_t sa = sbase + stage * L::STAGE_BYTES + c * 8192;
                const uint32_t sb = sbase + stage * L::STAGE_BYTES + L::A_BYTES;
                const uint32_t da = desc_lo(sa, 16);
                const uint32_t db = desc_lo(sb, 8192);
                wgmma_fence();
#pragma unroll
                for (int k = 0; k < 4; k++) wgmma_tile<BN>(acc, da + k * 2, db + k * 128, (kb | k) != 0);
                wgmma_commit();
                if (kb > 0) {
                    wgmma_wait<1>();
                    RELEASE_STAGE(bar_empty + 8 * prev_stage);
                }
                prev_stage = stage;
                if (++stage == STAGES) { stage = 0; phase ^= 1; }
            }
            wgmma_wait<0>();
            RELEASE_STAGE(bar_empty + 8 * prev_stage);
            PH(1)
            if (MODE == 1 && first) { pdl_wait(); first = false; }

            const int cq = (lane & 3) * 2;
            const CUtensorMap* mc = &mC0;
            const uint32_t rrow = warp * 16 + (lane >> 2);
            const uint32_t res0 = stg + rrow * 128 + cq * 2;
            int out_c0 = n0;
            if (MODE == 1) {
                if (n0 < DM) {
                    const float qs = 0.17677669529663687f * 1.4426950408889634f;
#pragma unroll
                    for (int j = 0; j < BN / 2; j++) acc[j] *= qs;
                } else if (n0 >= 3 * DM) {
                    mc = &mC1;
                    out_c0 = n0 - 3 * DM;
                    const float mu0 = g_mean1[r0], mu1 = g_mean1[r1];
                    const float rs0 = g_rstd1[r0], rs1 = g_rstd1[r1];
#pragma unroll
                    for (int j = 0; j < BN / 8; j++) {
                        float2 cs = *reinterpret_cast<const float2*>(&g_cs1[out_c0 + 8 * j + cq]);
#pragma unroll
                        for (int q = 1; q < 4; q++) {
                            const float2 c2 = *reinterpret_cast<const float2*>(&g_cs1[q * DM + out_c0 + 8 * j + cq]);
                            cs.x += c2.x; cs.y += c2.y;
                        }
                        acc[4 * j + 0] = gelu_tanh(rs0 * fmaf(-mu0, cs.x, acc[4 * j + 0]));
                        acc[4 * j + 1] = gelu_tanh(rs0 * fmaf(-mu0, cs.y, acc[4 * j + 1]));
                        acc[4 * j + 2] = gelu_tanh(rs1 * fmaf(-mu1, cs.x, acc[4 * j + 2]));
                        acc[4 * j + 3] = gelu_tanh(rs1 * fmaf(-mu1, cs.y, acc[4 * j + 3]));
                    }
                }
            } else if (MODE == 2) {
                float s0 = 0.f, s1 = 0.f;
                mbar_wait(bar_res, 0);
#pragma unroll
                for (int j = 0; j < BN / 8; j++) {
                    uint32_t xa, xb;
                    const uint32_t ra = res0 + (j >> 3) * 8192 + (((j & 7) ^ (rrow & 7)) << 4);
                    asm volatile("ld.shared.b32 %0, [%1];" : "=r"(xa) : "r"(ra));
                    asm volatile("ld.shared.b32 %0, [%1];" : "=r"(xb) : "r"(ra + 1024));
                    acc[4 * j + 0] = bf16_round(bf16_round(acc[4 * j + 0]) + __uint_as_float(xa << 16));
                    acc[4 * j + 1] = bf16_round(bf16_round(acc[4 * j + 1]) + __uint_as_float(xa & 0xFFFF0000u));
                    acc[4 * j + 2] = bf16_round(bf16_round(acc[4 * j + 2]) + __uint_as_float(xb << 16));
                    acc[4 * j + 3] = bf16_round(bf16_round(acc[4 * j + 3]) + __uint_as_float(xb & 0xFFFF0000u));
                    s0 += acc[4 * j + 0] + acc[4 * j + 1];
                    s1 += acc[4 * j + 2] + acc[4 * j + 3];
                }
                s0 += __shfl_xor_sync(0xffffffffu, s0, 1);
                s0 += __shfl_xor_sync(0xffffffffu, s0, 2);
                s1 += __shfl_xor_sync(0xffffffffu, s1, 1);
                s1 += __shfl_xor_sync(0xffffffffu, s1, 2);
                const float mu0 = s0 * (1.0f / BN), mu1 = s1 * (1.0f / BN);
                float q0 = 0.f, q1 = 0.f;
#pragma unroll
                for (int j = 0; j < BN / 8; j++) {
                    float d;
                    d = acc[4 * j + 0] - mu0; q0 += d * d;
                    d = acc[4 * j + 1] - mu0; q0 += d * d;
                    d = acc[4 * j + 2] - mu1; q1 += d * d;
                    d = acc[4 * j + 3] - mu1; q1 += d * d;
                }
                q0 += __shfl_xor_sync(0xffffffffu, q0, 1);
                q0 += __shfl_xor_sync(0xffffffffu, q0, 2);
                q1 += __shfl_xor_sync(0xffffffffu, q1, 1);
                q1 += __shfl_xor_sync(0xffffffffu, q1, 2);
                if ((lane & 3) == 0) {
                    static_assert(MODE != 2 || BN == 128, "stats layout assumes BN=128");
                    g_stat2[r0 * 8 + (n0 >> 7)] = make_float2(s0, q0);
                    g_stat2[r1 * 8 + (n0 >> 7)] = make_float2(s1, q1);
                }
            } else if (MODE == 3) {
                out_c0 = n0 + DM;
                named_bar_sync(3, 256);
#pragma unroll
                for (int j = 0; j < BN / 8; j++) {
                    float2 cs;
                    asm volatile("ld.shared.v2.f32 {%0, %1}, [%2];" : "=f"(cs.x), "=f"(cs.y) : "r"(sbase + L::CS_OFF + (8 * j + cq) * 4));
                    acc[4 * j + 0] = og[0] * gelu_tanh(rs[0] * fmaf(-mu[0], cs.x, acc[4 * j + 0]));
                    acc[4 * j + 1] = og[0] * gelu_tanh(rs[0] * fmaf(-mu[0], cs.y, acc[4 * j + 1]));
                    acc[4 * j + 2] = og[1] * gelu_tanh(rs[1] * fmaf(-mu[1], cs.x, acc[4 * j + 2]));
                    acc[4 * j + 3] = og[1] * gelu_tanh(rs[1] * fmaf(-mu[1], cs.y, acc[4 * j + 3]));
                }
                named_bar_sync(3, 256);
            } else {
                const float og0 = og[0], og1 = og[1];
                mbar_wait(bar_res, 0);
#pragma unroll
                for (int j = 0; j < BN / 8; j++) {
                    uint32_t xa, xb;
                    const uint32_t ra = res0 + (j >> 3) * 8192 + (((j & 7) ^ (rrow & 7)) << 4);
                    asm volatile("ld.shared.b32 %0, [%1];" : "=r"(xa) : "r"(ra));
                    asm volatile("ld.shared.b32 %0, [%1];" : "=r"(xb) : "r"(ra + 1024));
                    acc[4 * j + 0] = fmaf(og0, __uint_as_float(xa << 16), acc[4 * j + 0]);
                    acc[4 * j + 1] = fmaf(og0, __uint_as_float(xa & 0xFFFF0000u), acc[4 * j + 1]);
                    acc[4 * j + 2] = fmaf(og1, __uint_as_float(xb << 16), acc[4 * j + 2]);
                    acc[4 * j + 3] = fmaf(og1, __uint_as_float(xb & 0xFFFF0000u), acc[4 * j + 3]);
                }
            }
            PH(3)
            const int srow = warp * 16 + (lane & 7) + ((lane >> 3) & 1) * 8;
#pragma unroll
            for (int rnd = 0; rnd < (BN + 127) / 128; rnd++) {
                if (tid_wg == 0) bulk_wait_read0();
                named_bar_sync(1 + c, 128);
#pragma unroll
                for (int jj = 0; jj < 8; jj++) {
                    const int j = rnd * 16 + jj * 2;
                    if (j * 8 < BN) {
                        const int jb = jj * 2 + (lane >> 4);
                        uint32_t addr = stg + (jb >> 3) * 8192 + srow * 128 + (((jb & 7) ^ (srow & 7)) << 4);
                        if (rnd * 128 + 128 > BN && jj >= 4)
                            addr = stg + 8192 + srow * 64 + (((jb & 3) ^ ((srow >> 1) & 3)) << 4);
                        stmatrix_x4(addr, pack_bf16(acc[4 * j + 0], acc[4 * j + 1]), pack_bf16(acc[4 * j + 2], acc[4 * j + 3]),
                                    pack_bf16(acc[4 * j + 4], acc[4 * j + 5]), pack_bf16(acc[4 * j + 6], acc[4 * j + 7]));
                    }
                }
                fence_proxy_async();
                named_bar_sync(1 + c, 128);
                if (tid_wg == 0) {
                    tma_store_2d(mc, stg, out_c0 + rnd * 128, m0 + c * 64);
                    if (rnd * 128 + 64 < BN)
                        tma_store_2d((rnd * 128 + 128 > BN) ? &mC1 : mc, stg + 8192, out_c0 + rnd * 128 + 64, m0 + c * 64);
                    bulk_commit();
                }
            }
        }
        PH(4)
        if (tid_wg == 0) bulk_wait0();
        PH(5)
        TL_END(MODE)
    }
    cluster_sync_all();
}

#define ATT_SPLIT 16
constexpr int ATT_NTILES = NH * 16;
#define ATT_GRID_N 512
constexpr int ATT_GRID = ATT_GRID_N;
constexpr int ATT_THREADS = 256;
constexpr int ATT_STAGES = 4;
constexpr int ATT_DIST = 2;
constexpr int ATT_Q_OFF = ATT_STAGES * 16384;
constexpr int ATT_ONES_OFF = ATT_Q_OFF + 8192;
constexpr int ATT_KEXT_OFF = ATT_ONES_OFF + 4096;
constexpr int ATT_QEXT_OFF = ATT_KEXT_OFF + 4096;
constexpr int ATT_BAR_OFF = ATT_QEXT_OFF + 8192;
constexpr int ATT_SMEM = ATT_BAR_OFF + 256 + 1024;

__device__ __forceinline__ void row_max(const float (&s)[32], float& m0, float& m1) {
    float a0[8], a1[8];
#pragma unroll
    for (int i = 0; i < 8; i++) {
        a0[i] = fmaxf(s[4 * i], s[4 * i + 1]);
        a1[i] = fmaxf(s[4 * i + 2], s[4 * i + 3]);
    }
#pragma unroll
    for (int w = 4; w > 0; w >>= 1)
#pragma unroll
        for (int i = 0; i < w; i++) { a0[i] = fmaxf(a0[i], a0[i + w]); a1[i] = fmaxf(a1[i], a1[i + w]); }
    float mx0 = a0[0], mx1 = a1[0];
    mx0 = fmaxf(mx0, __shfl_xor_sync(0xffffffffu, mx0, 1));
    mx1 = fmaxf(mx1, __shfl_xor_sync(0xffffffffu, mx1, 1));
    mx0 = fmaxf(mx0, __shfl_xor_sync(0xffffffffu, mx0, 2));
    mx1 = fmaxf(mx1, __shfl_xor_sync(0xffffffffu, mx1, 2));
    m0 = fmaxf(m0, mx0);
    m1 = fmaxf(m1, mx1);
}

__device__ __forceinline__ void attn_step(float (&s)[32], float (&o)[20], uint32_t dq, uint32_t dke, uint32_t dk_next,
                                          uint32_t dv_cur, uint32_t release_bar) {
    constexpr uint32_t HI = desc_hi(512, 2);
    uint32_t p[16];
#pragma unroll
    for (int i = 0; i < 16; i++) p[i] = pack_bf16(ex2(s[2 * i]), ex2(s[2 * i + 1]));
    wgmma_fence();
    wgmma_ss_n64_tb0(s, dq, HI, dk_next, HI, 0);
    wgmma_ss_n64_tb0(s, dq + 2, HI, dk_next + 2, HI, 1);
    wgmma_ss_n64_tb0(s, dq + ((ATT_QEXT_OFF - ATT_Q_OFF) >> 4), HI, dke, HI, 1);
#pragma unroll
    for (int t = 0; t < 4; t++)
        wgmma_rs_n40_tb1(o, p[4 * t], p[4 * t + 1], p[4 * t + 2], p[4 * t + 3], dv_cur + t * 64, HI, 1);
    wgmma_commit();
    wgmma_wait<0>();
    if (release_bar != 0 && (threadIdx.x & 127) == 0) mbar_arrive(release_bar);
}

__global__ void __launch_bounds__(256, 1)
attn_exact_kernel(const __grid_constant__ CUtensorMap mKV) {
    extern __shared__ uint8_t smem_raw[];
    pdl_launch();
    pdl_wait();
    const int tile = blockIdx.x;
    if (g_bad[tile] == 0) return;
    constexpr int NBLK = S_LEN / 128;
    constexpr uint32_t HI = desc_hi(512, 2);
    const uint32_t sbase = (smem_u32(smem_raw) + 1023u) & ~1023u;
    const uint32_t bar = sbase + ATT_BAR_OFF;
    const int warp_id = threadIdx.x >> 5;
    const int lane = threadIdx.x & 31;
    const int cq = (lane & 3) * 2;
    const uint32_t dk0 = desc_lo(sbase, 16);
    const uint32_t dv0 = desc_lo(sbase + 8192, ATT_ONES_OFF - 8192);
    if (threadIdx.x == 0) {
        mbar_init(bar, 1);
        asm volatile("fence.mbarrier_init.release.cluster;" ::: "memory");
    }
    asm volatile("st.shared.v4.b32 [%0], {%1, %1, %1, %1};" ::"r"(sbase + ATT_ONES_OFF + threadIdx.x * 16), "r"(0x3F803F80u) : "memory");
    fence_proxy_async();
    __syncthreads();
    const int head = tile >> 4;
    const int row0 = (tile & 15) * 128 + warp_id * 16 + (lane >> 2);
    const uint32_t dq = desc_lo(sbase + ATT_Q_OFF + (threadIdx.x >> 7) * 4096, 16);
    float o[20];
#pragma unroll
    for (int i = 0; i < 20; i++) o[i] = 0.f;
    float m0 = -INFINITY, m1 = -INFINITY;
#pragma unroll 1
    for (int j = 0; j < NBLK; j++) {
        if (threadIdx.x == 0) {
            mbar_expect_tx(bar, j == 0 ? 3 * 8192 : 2 * 8192);
            if (j == 0) tma_load_2d(sbase + ATT_Q_OFF, &mKV, head * DH, (tile & 15) * 128, bar);
            tma_load_2d(sbase, &mKV, DM + head * DH, j * 128, bar);
            tma_load_2d(sbase + 8192, &mKV, 2 * DM + head * DH, j * 128, bar);
        }
        __syncwarp();
        mbar_wait(bar, j & 1);
#pragma unroll 1
        for (int hf = 0; hf < 2; hf++) {
            float s[32];
            wgmma_fence();
            wgmma_ss_n64_tb0(s, dq, HI, dk0 + hf * 256, HI, 0);
            wgmma_ss_n64_tb0(s, dq + 2, HI, dk0 + hf * 256 + 2, HI, 1);
            wgmma_commit();
            wgmma_wait<0>();
            const float mo0 = m0, mo1 = m1;
            row_max(s, m0, m1);
            const float a0 = ex2(mo0 - m0), a1 = ex2(mo1 - m1);
            uint32_t p[16];
#pragma unroll
            for (int i = 0; i < 8; i++) {
                p[2 * i] = pack_bf16(ex2(s[4 * i + 0] - m0), ex2(s[4 * i + 1] - m0));
                p[2 * i + 1] = pack_bf16(ex2(s[4 * i + 2] - m1), ex2(s[4 * i + 3] - m1));
            }
#pragma unroll
            for (int i = 0; i < 5; i++) {
                o[4 * i + 0] *= a0; o[4 * i + 1] *= a0;
                o[4 * i + 2] *= a1; o[4 * i + 3] *= a1;
            }
            wgmma_fence();
            const uint32_t dv = dv0 + hf * 256 - ((uint32_t)(hf * 256) << 16);
#pragma unroll
            for (int t = 0; t < 4; t++)
                wgmma_rs_n40_tb1(o, p[4 * t], p[4 * t + 1], p[4 * t + 2], p[4 * t + 3], dv + t * 64, HI, 1);
            wgmma_commit();
            wgmma_wait<0>();
        }
        __syncthreads();
    }
    const float f0 = g_gate[row0] / o[16], f1 = g_gate[row0 + 8] / o[18];
    bf16* op0 = g_a5 + (size_t)row0 * A5W + head * DH + cq;
    bf16* op1 = op0 + 8 * A5W;
#pragma unroll
    for (int i = 0; i < 4; i++) {
        *reinterpret_cast<uint32_t*>(op0 + 8 * i) = pack_bf16(o[4 * i] * f0, o[4 * i + 1] * f0);
        *reinterpret_cast<uint32_t*>(op1 + 8 * i) = pack_bf16(o[4 * i + 2] * f1, o[4 * i + 3] * f1);
    }
}

#define ATT_MINB 2
__global__ void __launch_bounds__(256, ATT_MINB)
attn_kernel(const __grid_constant__ CUtensorMap mKV) {
    extern __shared__ uint8_t smem_raw[];
    const uint32_t sbase = (smem_u32(smem_raw) + 1023u) & ~1023u;
    const uint32_t bar_kfull = sbase + ATT_BAR_OFF;
    const uint32_t bar_vfull = bar_kfull + 8 * ATT_STAGES;
    const uint32_t bar_empty = bar_vfull + 8 * ATT_STAGES;
    const int tile = blockIdx.x;
    const int head = tile >> 4;
    const int lane = threadIdx.x & 31;
    constexpr int NBLK = S_LEN / 128;
    TL_START(6)
    pdl_launch();

    auto issue_kv = [&](int g) {
        const int sn = g % ATT_STAGES;
        if (g >= ATT_STAGES) mbar_wait(bar_empty + 8 * sn, ((g / ATT_STAGES) - 1) & 1);
        const uint32_t skn = sbase + sn * 16384;
        mbar_expect_tx(bar_kfull + 8 * sn, g == 0 ? 16384 : 8192);
        if (g == 0) tma_load_2d(sbase + ATT_Q_OFF, &mKV, head * DH, (tile & 15) * 128, bar_kfull);
        tma_load_2d(skn, &mKV, DM + head * DH, g * 128, bar_kfull + 8 * sn);
        mbar_expect_tx(bar_vfull + 8 * sn, 8192);
        tma_load_2d(skn + 8192, &mKV, 2 * DM + head * DH, g * 128, bar_vfull + 8 * sn);
    };

    if (threadIdx.x == 0) {
        for (int s = 0; s < ATT_STAGES; s++) {
            mbar_init(bar_kfull + 8 * s, 1);
            mbar_init(bar_vfull + 8 * s, 1);
            mbar_init(bar_empty + 8 * s, 2);
        }
        asm volatile("fence.mbarrier_init.release.cluster;" ::: "memory");
        prefetch_tmap(&mKV);
        pdl_wait();
#pragma unroll
        for (int j = 0; j < ATT_DIST; j++) issue_kv(j);
    }
    {
        asm volatile("st.shared.v4.b32 [%0], {%1, %1, %1, %1};" ::"r"(sbase + ATT_ONES_OFF + threadIdx.x * 16), "r"(0x3F803F80u) : "memory");
        const int r = threadIdx.x >> 2, ch = threadIdx.x & 3;
        const uint32_t w0 = (ch == ((r >> 1) & 3)) ? 0x00003F80u : 0u;
        asm volatile("st.shared.v4.b32 [%0], {%1, %2, %2, %2};" ::"r"(sbase + ATT_KEXT_OFF + threadIdx.x * 16), "r"(w0), "r"(0u) : "memory");
        asm volatile("st.shared.v4.b32 [%0], {%1, %1, %1, %1};" ::"r"(sbase + ATT_QEXT_OFF + threadIdx.x * 16), "r"(0u) : "memory");
        asm volatile("st.shared.v4.b32 [%0], {%1, %1, %1, %1};" ::"r"(sbase + ATT_QEXT_OFF + 4096 + threadIdx.x * 16), "r"(0u) : "memory");
    }
    fence_proxy_async();
    __syncthreads();

    constexpr uint32_t HI = desc_hi(512, 2);
    const uint32_t dk0 = desc_lo(sbase, 16);
    const uint32_t dv0 = desc_lo(sbase + 8192, ATT_ONES_OFF - 8192);
    const uint32_t dke = dk0 + (ATT_KEXT_OFF >> 4);
    const uint32_t dq = dk0 + ((ATT_Q_OFF + (threadIdx.x >> 7) * 4096) >> 4);
    float o[20];
#pragma unroll
    for (int i = 0; i < 20; i++) o[i] = 0.f;
    float s0[32];
    mbar_wait(bar_kfull, 0);
    wgmma_fence();
    wgmma_ss_n64_tb0(s0, dq, HI, dk0, HI, 0);
    wgmma_ss_n64_tb0(s0, dq + 2, HI, dk0 + 2, HI, 1);
    wgmma_commit();
    wgmma_wait<0>();
    float m0 = -INFINITY, m1 = -INFINITY;
    row_max(s0, m0, m1);
    if ((lane & 3) == 0) {
        const int r = ((threadIdx.x >> 5) & 3) * 16 + (lane >> 2);
        const uint32_t qe = sbase + ATT_QEXT_OFF + (threadIdx.x >> 7) * 4096;
        asm volatile("st.shared.b16 [%0], %1;" ::"r"(qe + r * 64 + (((r >> 1) & 3) << 4)), "h"((uint16_t)(pack_bf16(-m0, 0.f) & 0xFFFFu)) : "memory");
        asm volatile("st.shared.b16 [%0], %1;" ::"r"(qe + (r + 8) * 64 + ((((r + 8) >> 1) & 3) << 4)), "h"((uint16_t)(pack_bf16(-m1, 0.f) & 0xFFFFu)) : "memory");
    }
    fence_proxy_async();
    named_bar_sync(1 + (threadIdx.x >> 7), 128);
    wgmma_fence();
    wgmma_ss_n64_tb0(s0, dq + ((ATT_QEXT_OFF - ATT_Q_OFF) >> 4), HI, dke, HI, 1);
    wgmma_commit();
    wgmma_wait<0>();
#pragma unroll 1
    for (int j = 0; j < NBLK; j++) {
        if (threadIdx.x == 0 && j + ATT_DIST < NBLK) issue_kv(j + ATT_DIST);
        __syncwarp();
        const uint32_t stage = j & (ATT_STAGES - 1), nstage = (j + 1) & (ATT_STAGES - 1);
        const uint32_t dk = dk0 + stage * 1024;
        const uint32_t dv = dv0 + stage * 1024 - (stage << 26);
        mbar_wait(bar_vfull + 8 * stage, (j / ATT_STAGES) & 1);
        attn_step(s0, o, dq, dke, dk + 256, dv, 0u);
        uint32_t dkn = dk;
        if (j + 1 < NBLK) {
            mbar_wait(bar_kfull + 8 * nstage, ((j + 1) / ATT_STAGES) & 1);
            dkn = dk0 + nstage * 1024;
        }
        attn_step(s0, o, dq, dke, dkn, dv + 256 - (256u << 16), bar_empty + 8 * stage);
    }
    bool ok = (o[16] <= 1.8446744e19f) && (o[18] <= 1.8446744e19f);
#pragma unroll
    for (int i = 0; i < 16; i++) ok = ok && (fabsf(o[i]) <= 3.0e38f);
    const int row0 = (tile & 15) * 128 + (threadIdx.x >> 5) * 16 + (lane >> 2);
    const float f0 = g_gate[row0] / o[16], f1 = g_gate[row0 + 8] / o[18];
    bf16* op0 = g_a5 + (size_t)row0 * A5W + head * DH + (lane & 3) * 2;
    bf16* op1 = op0 + 8 * A5W;
#pragma unroll
    for (int i = 0; i < 4; i++) {
        *reinterpret_cast<uint32_t*>(op0 + 8 * i) = pack_bf16(o[4 * i] * f0, o[4 * i + 1] * f0);
        *reinterpret_cast<uint32_t*>(op1 + 8 * i) = pack_bf16(o[4 * i + 2] * f1, o[4 * i + 3] * f1);
    }
    const int bad = __syncthreads_or(!ok);
    if (threadIdx.x == 0) g_bad[tile] = bad;
    TL_END(6)
}

typedef CUresult (*EncodeFn)(CUtensorMap*, CUtensorMapDataType, cuuint32_t, void*, const cuuint64_t*, const cuuint64_t*,
                             const cuuint32_t*, const cuuint32_t*, CUtensorMapInterleave, CUtensorMapSwizzle,
                             CUtensorMapL2promotion, CUtensorMapFloatOOBfill);

static CUtensorMap make_map(EncodeFn fn, const void* ptr, int rows, int cols, int box_cols, int box_rows,
                            CUtensorMapSwizzle swz) {
    CUtensorMap m;
    cuuint64_t dims[2] = {(cuuint64_t)cols, (cuuint64_t)rows};
    cuuint64_t strides[1] = {(cuuint64_t)cols * 2};
    cuuint32_t box[2] = {(cuuint32_t)box_cols, (cuuint32_t)box_rows};
    cuuint32_t es[2] = {1, 1};
    fn(&m, CU_TENSOR_MAP_DATA_TYPE_BFLOAT16, 2, const_cast<void*>(ptr), dims, strides, box, es,
       CU_TENSOR_MAP_INTERLEAVE_NONE, swz, CU_TENSOR_MAP_L2_PROMOTION_L2_256B, CU_TENSOR_MAP_FLOAT_OOB_FILL_NONE);
    return m;
}

template <typename... KArgs, typename... Args>
static void launch_ex(void (*kern)(KArgs...), int grid, int block, int smem, cudaStream_t st, int cluster, int pdl, Args... args) {
    cudaLaunchConfig_t cfg = {};
    cfg.gridDim = dim3(grid);
    cfg.blockDim = dim3(block);
    cfg.dynamicSmemBytes = smem;
    cfg.stream = st;
    cudaLaunchAttribute at[2];
    at[0].id = cudaLaunchAttributeProgrammaticStreamSerialization;
    at[0].val.programmaticStreamSerializationAllowed = pdl;
    at[1].id = cudaLaunchAttributeClusterDimension;
    at[1].val.clusterDim.x = cluster;
    at[1].val.clusterDim.y = 1;
    at[1].val.clusterDim.z = 1;
    cfg.attrs = at;
    cfg.numAttrs = cluster > 1 ? 2 : 1;
    cudaLaunchKernelEx(&cfg, kern, KArgs(args)...);
}

extern "C" void kernel_launch(void* const* d_in, const int* in_sizes, int n_in, void* d_out, int out_size) {
    const bf16* x = (const bf16*)d_in[0];
    const bf16* wqkv = (const bf16*)d_in[1];
    const bf16* wo = (const bf16*)d_in[2];
    const bf16* w1 = (const bf16*)d_in[4];
    const bf16* w2 = (const bf16*)d_in[5];
    const bf16* w3 = (const bf16*)d_in[6];
    const bf16* w4 = (const bf16*)d_in[7];
    const bf16* gate_w = (const bf16*)d_in[8];

    static EncodeFn enc = nullptr;
    static void *p_qkv, *p_h, *p_x1, *p_a5, *p_cs1, *p_cs3;
    static cudaStream_t s2;
    static cudaEvent_t ev_fork, ev_join;
    using G1 = GemmSmem<256, 4>;
    using G2 = GemmSmem<128, 5>;
    using G3 = GemmSmem<224, 4>;
    if (!enc) {
        void* fn = nullptr;
        cudaDriverEntryPointQueryResult qres;
        cudaGetDriverEntryPoint("cuTensorMapEncodeTiled", &fn, cudaEnableDefault, &qres);
        enc = (EncodeFn)fn;
        cudaGetSymbolAddress(&p_qkv, g_qkv);
        cudaGetSymbolAddress(&p_h, g_h);
        cudaGetSymbolAddress(&p_x1, g_x1);
        cudaGetSymbolAddress(&p_a5, g_a5);
        cudaGetSymbolAddress(&p_cs1, g_cs1);
        cudaGetSymbolAddress(&p_cs3, g_cs3);
        cudaFuncSetAttribute(gemm_kernel<1, 256, 4>, cudaFuncAttributeMaxDynamicSharedMemorySize, G1::TOTAL);
        cudaFuncSetAttribute(gemm_kernel<2, 128, 5>, cudaFuncAttributeMaxDynamicSharedMemorySize, G2::TOTAL);
        cudaFuncSetAttribute(gemm_kernel<3, 224, 4>, cudaFuncAttributeMaxDynamicSharedMemorySize, G3::TOTAL);
        cudaFuncSetAttribute(gemm_kernel<5, 128, 5>, cudaFuncAttributeMaxDynamicSharedMemorySize, G2::TOTAL);
        cudaStreamCreateWithFlags(&s2, cudaStreamNonBlocking);
        cudaEventCreateWithFlags(&ev_fork, cudaEventDisableTiming);
        cudaEventCreateWithFlags(&ev_join, cudaEventDisableTiming);
        cudaFuncSetAttribute(attn_kernel, cudaFuncAttributeMaxDynamicSharedMemorySize, ATT_SMEM);
        cudaFuncSetAttribute(attn_exact_kernel, cudaFuncAttributeMaxDynamicSharedMemorySize, ATT_SMEM);
    }
    const CUtensorMapSwizzle SW128 = CU_TENSOR_MAP_SWIZZLE_128B, SW64 = CU_TENSOR_MAP_SWIZZLE_64B;
    CUtensorMap mX = make_map(enc, x, S_LEN, DM, 64, 128, SW128);
    CUtensorMap mXres = make_map(enc, x, S_LEN, DM, 64, 64, SW128);
    CUtensorMap mWqkv = make_map(enc, wqkv, DM, 3 * DM, 64, 64, SW128);
    CUtensorMap mW1 = make_map(enc, w1, DM, DM, 64, 64, SW128);
    CUtensorMap mW2 = make_map(enc, w2, DM, DM, 64, 64, SW128);
    CUtensorMap mW3 = make_map(enc, w3, DM, FF, 64, 64, SW128);
    CUtensorMap mW4 = make_map(enc, w4, FF, DM, 64, 64, SW128);
    CUtensorMap mWo = make_map(enc, wo, DM, DM, 64, 64, SW128);
    CUtensorMap mQKVst = make_map(enc, p_qkv, S_LEN, 3 * DM, 64, 64, SW128);
    CUtensorMap mKV = make_map(enc, p_qkv, S_LEN, 3 * DM, 32, 128, SW64);
    CUtensorMap mHst = make_map(enc, p_h, S_LEN, DM, 64, 64, SW128);
    CUtensorMap mHld = make_map(enc, p_h, S_LEN, DM, 64, 128, SW128);
    CUtensorMap mX1st = make_map(enc, p_x1, S_LEN, DM, 64, 64, SW128);
    CUtensorMap mX1ld = make_map(enc, p_x1, S_LEN, DM, 64, 128, SW128);
    CUtensorMap mA5st = make_map(enc, p_a5, S_LEN, A5W, 64, 64, SW128);
    CUtensorMap mA5st32 = make_map(enc, p_a5, S_LEN, A5W, 32, 64, SW64);
    CUtensorMap mA5ld = make_map(enc, p_a5, S_LEN, A5W, 64, 128, SW128);
    CUtensorMap mOut = make_map(enc, d_out, S_LEN, DM, 64, 64, SW128);

    cudaStream_t st = cudaStreamPerThread;
    prep_kernel<<<256 + 64, 256, 0, st>>>(x, gate_w, w1, DM, (float*)p_cs1, 256);
    launch_ex(gemm_kernel<1, 256, 4>, 132, 384, G1::TOTAL, st, 2, 1, mX, mWqkv, mW1, mQKVst, mHst, x, 16, 16);
    cudaEventRecord(ev_fork, st);
    launch_ex(attn_kernel, ATT_GRID, ATT_THREADS, ATT_SMEM, st, 1, 1, mKV);
    launch_ex(attn_exact_kernel, ATT_NTILES, ATT_THREADS, ATT_SMEM, st, 1, 1, mKV);
    cudaStreamWaitEvent(s2, ev_fork, 0);
    prep_kernel<<<224, 256, 0, s2>>>(x, gate_w, w3, FF, (float*)p_cs3, 0);
    launch_ex(gemm_kernel<2, 128, 5>, 128, 384, G2::TOTAL, s2, 2, 1, mHld, mW2, mW2, mX1st, mXres, x, 8, 16);
    launch_ex(gemm_kernel<3, 224, 4>, 132, 384, G3::TOTAL, s2, 2, 1, mX1ld, mW3, mW3, mA5st, mA5st32, x, 16, 16);
    cudaEventRecord(ev_join, s2);
    cudaStreamWaitEvent(st, ev_join, 0);
    launch_ex(gemm_kernel<5, 128, 5>, 128, 384, G2::TOTAL, st, 2, 0, mA5ld, mWo, mW4, mOut, mX1st, (const bf16*)p_x1, 8, 72);
}
```

```cpp
#include <cuda_runtime.h>
#include <cuda_bf16.h>
#include <cuda.h>
#include <stdint.h>

typedef __nv_bfloat16 bf16;

constexpr int S_LEN = 2048;
constexpr int DM = 1024;
constexpr int FF = 3584;
constexpr int NH = 32;
constexpr int DH = 32;
constexpr int A5W = DM + FF;

__device__ __align__(1024) bf16 g_qkv[S_LEN * 3 * DM];
__device__ __align__(1024) bf16 g_h[S_LEN * DM];
__device__ __align__(1024) bf16 g_x1[S_LEN * DM];
__device__ __align__(1024) bf16 g_a5[S_LEN * A5W];
__device__ __align__(16) float g_mean1[S_LEN];
__device__ __align__(16) float g_rstd1[S_LEN];
__device__ __align__(16) float g_gate[S_LEN];
__device__ __align__(16) float g_omg[S_LEN];
__device__ __align__(16) float g_cs1[4 * DM];
__device__ __align__(16) float g_cs3[4 * FF];
__device__ __align__(16) float2 g_stat2[S_LEN * 8];
__device__ int g_bad[NH * 16];

#define TL_START(k)
#define PH(i)
#define TL_END(k)

__device__ __forceinline__ uint32_t smem_u32(const void* p) { return (uint32_t)__cvta_generic_to_shared(p); }

__device__ __forceinline__ void mbar_init(uint32_t bar, uint32_t count) {
    asm volatile("mbarrier.init.shared::cta.b64 [%0], %1;" ::"r"(bar), "r"(count));
}
__device__ __forceinline__ void mbar_expect_tx(uint32_t bar, uint32_t bytes) {
    asm volatile("mbarrier.arrive.expect_tx.shared::cta.b64 _, [%0], %1;" ::"r"(bar), "r"(bytes) : "memory");
}
__device__ __forceinline__ void mbar_arrive(uint32_t bar) {
    asm volatile("mbarrier.arrive.shared::cta.b64 _, [%0];" ::"r"(bar) : "memory");
}
__device__ __forceinline__ bool mbar_try_wait(uint32_t bar, uint32_t parity) {
    uint32_t ok;
    asm volatile(
        "{\n.reg .pred p;\n"
        "mbarrier.try_wait.parity.shared::cta.b64 p, [%1], %2;\n"
        "selp.u32 %0, 1, 0, p;\n}\n"
        : "=r"(ok)
        : "r"(bar), "r"(parity)
        : "memory");
    return ok != 0;
}
__device__ __forceinline__ void mbar_wait(uint32_t bar, uint32_t parity) {
    uint32_t spins = 0;
    while (!mbar_try_wait(bar, parity)) {
        if (++spins > (1u << 24)) __trap();
    }
}
__device__ __forceinline__ void tma_load_2d(uint32_t dst, const CUtensorMap* map, int c0, int c1, uint32_t bar) {
    asm volatile(
        "cp.async.bulk.tensor.2d.shared::cluster.global.mbarrier::complete_tx::bytes [%0], [%1, {%3, %4}], [%2];"
        ::"r"(dst), "l"(map), "r"(bar), "r"(c0), "r"(c1)
        : "memory");
}
__device__ __forceinline__ void tma_store_2d(const CUtensorMap* map, uint32_t src, int c0, int c1) {
    asm volatile("cp.async.bulk.tensor.2d.global.shared::cta.bulk_group [%0, {%2, %3}], [%1];"
                 ::"l"(map), "r"(src), "r"(c0), "r"(c1)
                 : "memory");
}
__device__ __forceinline__ void tma_load_2d_mc(uint32_t dst, const CUtensorMap* map, int c0, int c1, uint32_t bar, uint16_t mask) {
    asm volatile(
        "cp.async.bulk.tensor.2d.shared::cluster.global.mbarrier::complete_tx::bytes.multicast::cluster [%0], [%1, {%3, %4}], [%2], %5;"
        ::"r"(dst), "l"(map), "r"(bar), "r"(c0), "r"(c1), "h"(mask)
        : "memory");
}
__device__ __forceinline__ void mbar_arrive_cluster(uint32_t bar, uint32_t cta) {
    asm volatile(
        "{\n.reg .b32 ra;\nmapa.shared::cluster.u32 ra, %0, %1;\n"
        "mbarrier.arrive.shared::cluster.b64 _, [ra];\n}\n" ::"r"(bar), "r"(cta)
        : "memory");
}
__device__ __forceinline__ void cluster_sync_all() {
    asm volatile("barrier.cluster.arrive.release.aligned;\nbarrier.cluster.wait.acquire.aligned;" ::: "memory");
}
__device__ __forceinline__ uint32_t cluster_rank() { uint32_t r; asm volatile("mov.u32 %0, %%cluster_ctarank;" : "=r"(r)); return r; }
__device__ __forceinline__ void pdl_wait() { asm volatile("griddepcontrol.wait;" ::: "memory"); }
__device__ __forceinline__ void pdl_launch() { asm volatile("griddepcontrol.launch_dependents;" ::: "memory"); }
__device__ __forceinline__ void bulk_commit() { asm volatile("cp.async.bulk.commit_group;" ::: "memory"); }
__device__ __forceinline__ void bulk_wait_read0() { asm volatile("cp.async.bulk.wait_group.read 0;" ::: "memory"); }
__device__ __forceinline__ void bulk_wait0() { asm volatile("cp.async.bulk.wait_group 0;" ::: "memory"); }
__device__ __forceinline__ void fence_proxy_async() { asm volatile("fence.proxy.async.shared::cta;" ::: "memory"); }
__device__ __forceinline__ void named_bar_sync(int id, int n) { asm volatile("bar.sync %0, %1;" ::"r"(id), "r"(n) : "memory"); }
__device__ __forceinline__ void named_bar_arrive(int id, int n) { asm volatile("bar.arrive %0, %1;" ::"r"(id), "r"(n) : "memory"); }
__device__ __forceinline__ void wgmma_fence() { asm volatile("wgmma.fence.sync.aligned;" ::: "memory"); }
__device__ __forceinline__ void wgmma_commit() { asm volatile("wgmma.commit_group.sync.aligned;" ::: "memory"); }
template <int N>
__device__ __forceinline__ void wgmma_wait() { asm volatile("wgmma.wait_group.sync.aligned %0;" ::"n"(N) : "memory"); }
__device__ __forceinline__ void prefetch_tmap(const CUtensorMap* m) {
    asm volatile("prefetch.tensormap [%0];" ::"l"(m) : "memory");
}
template <int R>
__device__ __forceinline__ void reg_alloc() { asm volatile("setmaxnreg.inc.sync.aligned.u32 %0;" ::"n"(R)); }
template <int R>
__device__ __forceinline__ void reg_dealloc() { asm volatile("setmaxnreg.dec.sync.aligned.u32 %0;" ::"n"(R)); }
__device__ __forceinline__ void stmatrix_x4(uint32_t addr, uint32_t r0, uint32_t r1, uint32_t r2, uint32_t r3) {
    asm volatile("stmatrix.sync.aligned.m8n8.x4.shared.b16 [%0], {%1, %2, %3, %4};"
                 ::"r"(addr), "r"(r0), "r"(r1), "r"(r2), "r"(r3)
                 : "memory");
}
__device__ __forceinline__ uint32_t pack_bf16(float lo, float hi) {
    uint32_t r;
    asm("cvt.rn.bf16x2.f32 %0, %1, %2;" : "=r"(r) : "f"(hi), "f"(lo));
    return r;
}
__device__ __forceinline__ float bf16_round(float v) { return __bfloat162float(__float2bfloat16_rn(v)); }
__device__ __forceinline__ float ex2(float x) {
    float y;
    asm volatile("ex2.approx.ftz.f32 %0, %1;" : "=f"(y) : "f"(x));
    return y;
}
__device__ __forceinline__ float tanh_fast(float x) {
    float y;
    asm("tanh.approx.f32 %0, %1;" : "=f"(y) : "f"(x));
    return y;
}
__device__ __forceinline__ float gelu_tanh(float v) {
    float u = 0.7978845608028654f * (v + 0.044715f * v * v * v);
    float hv = 0.5f * v;
    return fmaf(hv, tanh_fast(u), hv);
}
__device__ __forceinline__ uint32_t desc_lo(uint32_t addr, uint32_t lbo_bytes) {
    return ((addr & 0x3FFFF) >> 4) | (((lbo_bytes >> 4) & 0x3FFF) << 16);
}
__host__ __device__ constexpr uint32_t desc_hi(uint32_t sbo_bytes, uint32_t swz) {
    return ((sbo_bytes >> 4) & 0x3FFF) | (swz << 30);
}

__device__ __forceinline__ void wgmma_ss_n128_tb1(float (&d)[64], uint32_t alo, uint32_t ahi, uint32_t blo, uint32_t bhi, int scale_d) {
    asm volatile("{\n.reg .pred p;\n.reg .b64 da, db;\nsetp.ne.b32 p, %68, 0;\nmov.b64 da, {%64, %65};\nmov.b64 db, {%66, %67};\n"
        "wgmma.mma_async.sync.aligned.m64n128k16.f32.bf16.bf16 {%0, %1, %2, %3, %4, %5, %6, %7, %8, %9, %10, %11, %12, %13, %14, %15, %16, %17, %18, %19, %20, %21, %22, %23, %24, %25, %26, %27, %28, %29, %30, %31, %32, %33, %34, %35, %36, %37, %38, %39, %40, %41, %42, %43, %44, %45, %46, %47, %48, %49, %50, %51, %52, %53, %54, %55, %56, %57, %58, %59, %60, %61, %62, %63}, da, db, p, 1, 1, 0, 1;\n}\n"
        : "+f"(d[0]), "+f"(d[1]), "+f"(d[2]), "+f"(d[3]), "+f"(d[4]), "+f"(d[5]), "+f"(d[6]), "+f"(d[7]), "+f"(d[8]), "+f"(d[9]), "+f"(d[10]), "+f"(d[11]), "+f"(d[12]), "+f"(d[13]), "+f"(d[14]), "+f"(d[15]), "+f"(d[16]), "+f"(d[17]), "+f"(d[18]), "+f"(d[19]), "+f"(d[20]), "+f"(d[21]), "+f"(d[22]), "+f"(d[23]), "+f"(d[24]), "+f"(d[25]), "+f"(d[26]), "+f"(d[27]), "+f"(d[28]), "+f"(d[29]), "+f"(d[30]), "+f"(d[31]), "+f"(d[32]), "+f"(d[33]), "+f"(d[34]), "+f"(d[35]), "+f"(d[36]), "+f"(d[37]), "+f"(d[38]), "+f"(d[39]), "+f"(d[40]), "+f"(d[41]), "+f"(d[42]), "+f"(d[43]), "+f"(d[44]), "+f"(d[45]), "+f"(d[46]), "+f"(d[47]), "+f"(d[48]), "+f"(d[49]), "+f"(d[50]), "+f"(d[51]), "+f"(d[52]), "+f"(d[53]), "+f"(d[54]), "+f"(d[55]), "+f"(d[56]), "+f"(d[57]), "+f"(d[58]), "+f"(d[59]), "+f"(d[60]), "+f"(d[61]), "+f"(d[62]), "+f"(d[63])
        : "r"(alo), "r"(ahi), "r"(blo), "r"(bhi), "r"(scale_d));
}

__device__ __forceinline__ void wgmma_ss_n192_tb1(float (&d)[96], uint32_t alo, uint32_t ahi, uint32_t blo, uint32_t bhi, int scale_d) {
    asm volatile("{\n.reg .pred p;\n.reg .b64 da, db;\nsetp.ne.b32 p, %100, 0;\nmov.b64 da, {%96, %97};\nmov.b64 db, {%98, %99};\n"
        "wgmma.mma_async.sync.aligned.m64n192k16.f32.bf16.bf16 {%0, %1, %2, %3, %4, %5, %6, %7, %8, %9, %10, %11, %12, %13, %14, %15, %16, %17, %18, %19, %20, %21, %22, %23, %24, %25, %26, %27, %28, %29, %30, %31, %32, %33, %34, %35, %36, %37, %38, %39, %40, %41, %42, %43, %44, %45, %46, %47, %48, %49, %50, %51, %52, %53, %54, %55, %56, %57, %58, %59, %60, %61, %62, %63, %64, %65, %66, %67, %68, %69, %70, %71, %72, %73, %74, %75, %76, %77, %78, %79, %80, %81, %82, %83, %84, %85, %86, %87, %88, %89, %90, %91, %92, %93, %94, %95}, da, db, p, 1, 1, 0, 1;\n}\n"
        : "+f"(d[0]), "+f"(d[1]), "+f"(d[2]), "+f"(d[3]), "+f"(d[4]), "+f"(d[5]), "+f"(d[6]), "+f"(d[7]), "+f"(d[8]), "+f"(d[9]), "+f"(d[10]), "+f"(d[11]), "+f"(d[12]), "+f"(d[13]), "+f"(d[14]), "+f"(d[15]), "+f"(d[16]), "+f"(d[17]), "+f"(d[18]), "+f"(d[19]), "+f"(d[20]), "+f"(d[21]), "+f"(d[22]), "+f"(d[23]), "+f"(d[24]), "+f"(d[25]), "+f"(d[26]), "+f"(d[27]), "+f"(d[28]), "+f"(d[29]), "+f"(d[30]), "+f"(d[31]), "+f"(d[32]), "+f"(d[33]), "+f"(d[34]), "+f"(d[35]), "+f"(d[36]), "+f"(d[37]), "+f"(d[38]), "+f"(d[39]), "+f"(d[40]), "+f"(d[41]), "+f"(d[42]), "+f"(d[43]), "+f"(d[44]), "+f"(d[45]), "+f"(d[46]), "+f"(d[47]), "+f"(d[48]), "+f"(d[49]), "+f"(d[50]), "+f"(d[51]), "+f"(d[52]), "+f"(d[53]), "+f"(d[54]), "+f"(d[55]), "+f"(d[56]), "+f"(d[57]), "+f"(d[58]), "+f"(d[59]), "+f"(d[60]), "+f"(d[61]), "+f"(d[62]), "+f"(d[63]), "+f"(d[64]), "+f"(d[65]), "+f"(d[66]), "+f"(d[67]), "+f"(d[68]), "+f"(d[69]), "+f"(d[70]), "+f"(d[71]), "+f"(d[72]), "+f"(d[73]), "+f"(d[74]), "+f"(d[75]), "+f"(d[76]), "+f"(d[77]), "+f"(d[78]), "+f"(d[79]), "+f"(d[80]), "+f"(d[81]), "+f"(d[82]), "+f"(d[83]), "+f"(d[84]), "+f"(d[85]), "+f"(d[86]), "+f"(d[87]), "+f"(d[88]), "+f"(d[89]), "+f"(d[90]), "+f"(d[91]), "+f"(d[92]), "+f"(d[93]), "+f"(d[94]), "+f"(d[95])
        : "r"(alo), "r"(ahi), "r"(blo), "r"(bhi), "r"(scale_d));
}

__device__ __forceinline__ void wgmma_ss_n224_tb1(float (&d)[112], uint32_t alo, uint32_t ahi, uint32_t blo, uint32_t bhi, int scale_d) {
    asm volatile("{\n.reg .pred p;\n.reg .b64 da, db;\nsetp.ne.b32 p, %116, 0;\nmov.b64 da, {%112, %113};\nmov.b64 db, {%114, %115};\n"
        "wgmma.mma_async.sync.aligned.m64n224k16.f32.bf16.bf16 {%0, %1, %2, %3, %4, %5, %6, %7, %8, %9, %10, %11, %12, %13, %14, %15, %16, %17, %18, %19, %20, %21, %22, %23, %24, %25, %26, %27, %28, %29, %30, %31, %32, %33, %34, %35, %36, %37, %38, %39, %40, %41, %42, %43, %44, %45, %46, %47, %48, %49, %50, %51, %52, %53, %54, %55, %56, %57, %58, %59, %60, %61, %62, %63, %64, %65, %66, %67, %68, %69, %70, %71, %72, %73, %74, %75, %76, %77, %78, %79, %80, %81, %82, %83, %84, %85, %86, %87, %88, %89, %90, %91, %92, %93, %94, %95, %96, %97, %98, %99, %100, %101, %102, %103, %104, %105, %106, %107, %108, %109, %110, %111}, da, db, p, 1, 1, 0, 1;\n}\n"
        : "+f"(d[0]), "+f"(d[1]), "+f"(d[2]), "+f"(d[3]), "+f"(d[4]), "+f"(d[5]), "+f"(d[6]), "+f"(d[7]), "+f"(d[8]), "+f"(d[9]), "+f"(d[10]), "+f"(d[11]), "+f"(d[12]), "+f"(d[13]), "+f"(d[14]), "+f"(d[15]), "+f"(d[16]), "+f"(d[17]), "+f"(d[18]), "+f"(d[19]), "+f"(d[20]), "+f"(d[21]), "+f"(d[22]), "+f"(d[23]), "+f"(d[24]), "+f"(d[25]), "+f"(d[26]), "+f"(d[27]), "+f"(d[28]), "+f"(d[29]), "+f"(d[30]), "+f"(d[31]), "+f"(d[32]), "+f"(d[33]), "+f"(d[34]), "+f"(d[35]), "+f"(d[36]), "+f"(d[37]), "+f"(d[38]), "+f"(d[39]), "+f"(d[40]), "+f"(d[41]), "+f"(d[42]), "+f"(d[43]), "+f"(d[44]), "+f"(d[45]), "+f"(d[46]), "+f"(d[47]), "+f"(d[48]), "+f"(d[49]), "+f"(d[50]), "+f"(d[51]), "+f"(d[52]), "+f"(d[53]), "+f"(d[54]), "+f"(d[55]), "+f"(d[56]), "+f"(d[57]), "+f"(d[58]), "+f"(d[59]), "+f"(d[60]), "+f"(d[61]), "+f"(d[62]), "+f"(d[63]), "+f"(d[64]), "+f"(d[65]), "+f"(d[66]), "+f"(d[67]), "+f"(d[68]), "+f"(d[69]), "+f"(d[70]), "+f"(d[71]), "+f"(d[72]), "+f"(d[73]), "+f"(d[74]), "+f"(d[75]), "+f"(d[76]), "+f"(d[77]), "+f"(d[78]), "+f"(d[79]), "+f"(d[80]), "+f"(d[81]), "+f"(d[82]), "+f"(d[83]), "+f"(d[84]), "+f"(d[85]), "+f"(d[86]), "+f"(d[87]), "+f"(d[88]), "+f"(d[89]), "+f"(d[90]), "+f"(d[91]), "+f"(d[92]), "+f"(d[93]), "+f"(d[94]), "+f"(d[95]), "+f"(d[96]), "+f"(d[97]), "+f"(d[98]), "+f"(d[99]), "+f"(d[100]), "+f"(d[101]), "+f"(d[102]), "+f"(d[103]), "+f"(d[104]), "+f"(d[105]), "+f"(d[106]), "+f"(d[107]), "+f"(d[108]), "+f"(d[109]), "+f"(d[110]), "+f"(d[111])
        : "r"(alo), "r"(ahi), "r"(blo), "r"(bhi), "r"(scale_d));
}

__device__ __forceinline__ void wgmma_ss_n256_tb1(float (&d)[128], uint32_t alo, uint32_t ahi, uint32_t blo, uint32_t bhi, int scale_d) {
    asm volatile("{\n.reg .pred p;\n.reg .b64 da, db;\nsetp.ne.b32 p, %132, 0;\nmov.b64 da, {%128, %129};\nmov.b64 db, {%130, %131};\n"
        "wgmma.mma_async.sync.aligned.m64n256k16.f32.bf16.bf16 {%0, %1, %2, %3, %4, %5, %6, %7, %8, %9, %10, %11, %12, %13, %14, %15, %16, %17, %18, %19, %20, %21, %22, %23, %24, %25, %26, %27, %28, %29, %30, %31, %32, %33, %34, %35, %36, %37, %38, %39, %40, %41, %42, %43, %44, %45, %46, %47, %48, %49, %50, %51, %52, %53, %54, %55, %56, %57, %58, %59, %60, %61, %62, %63, %64, %65, %66, %67, %68, %69, %70, %71, %72, %73, %74, %75, %76, %77, %78, %79, %80, %81, %82, %83, %84, %85, %86, %87, %88, %89, %90, %91, %92, %93, %94, %95, %96, %97, %98, %99, %100, %101, %102, %103, %104, %105, %106, %107, %108, %109, %110, %111, %112, %113, %114, %115, %116, %117, %118, %119, %120, %121, %122, %123, %124, %125, %126, %127}, da, db, p, 1, 1, 0, 1;\n}\n"
        : "+f"(d[0]), "+f"(d[1]), "+f"(d[2]), "+f"(d[3]), "+f"(d[4]), "+f"(d[5]), "+f"(d[6]), "+f"(d[7]), "+f"(d[8]), "+f"(d[9]), "+f"(d[10]), "+f"(d[11]), "+f"(d[12]), "+f"(d[13]), "+f"(d[14]), "+f"(d[15]), "+f"(d[16]), "+f"(d[17]), "+f"(d[18]), "+f"(d[19]), "+f"(d[20]), "+f"(d[21]), "+f"(d[22]), "+f"(d[23]), "+f"(d[24]), "+f"(d[25]), "+f"(d[26]), "+f"(d[27]), "+f"(d[28]), "+f"(d[29]), "+f"(d[30]), "+f"(d[31]), "+f"(d[32]), "+f"(d[33]), "+f"(d[34]), "+f"(d[35]), "+f"(d[36]), "+f"(d[37]), "+f"(d[38]), "+f"(d[39]), "+f"(d[40]), "+f"(d[41]), "+f"(d[42]), "+f"(d[43]), "+f"(d[44]), "+f"(d[45]), "+f"(d[46]), "+f"(d[47]), "+f"(d[48]), "+f"(d[49]), "+f"(d[50]), "+f"(d[51]), "+f"(d[52]), "+f"(d[53]), "+f"(d[54]), "+f"(d[55]), "+f"(d[56]), "+f"(d[57]), "+f"(d[58]), "+f"(d[59]), "+f"(d[60]), "+f"(d[61]), "+f"(d[62]), "+f"(d[63]), "+f"(d[64]), "+f"(d[65]), "+f"(d[66]), "+f"(d[67]), "+f"(d[68]), "+f"(d[69]), "+f"(d[70]), "+f"(d[71]), "+f"(d[72]), "+f"(d[73]), "+f"(d[74]), "+f"(d[75]), "+f"(d[76]), "+f"(d[77]), "+f"(d[78]), "+f"(d[79]), "+f"(d[80]), "+f"(d[81]), "+f"(d[82]), "+f"(d[83]), "+f"(d[84]), "+f"(d[85]), "+f"(d[86]), "+f"(d[87]), "+f"(d[88]), "+f"(d[89]), "+f"(d[90]), "+f"(d[91]), "+f"(d[92]), "+f"(d[93]), "+f"(d[94]), "+f"(d[95]), "+f"(d[96]), "+f"(d[97]), "+f"(d[98]), "+f"(d[99]), "+f"(d[100]), "+f"(d[101]), "+f"(d[102]), "+f"(d[103]), "+f"(d[104]), "+f"(d[105]), "+f"(d[106]), "+f"(d[107]), "+f"(d[108]), "+f"(d[109]), "+f"(d[110]), "+f"(d[111]), "+f"(d[112]), "+f"(d[113]), "+f"(d[114]), "+f"(d[115]), "+f"(d[116]), "+f"(d[117]), "+f"(d[118]), "+f"(d[119]), "+f"(d[120]), "+f"(d[121]), "+f"(d[122]), "+f"(d[123]), "+f"(d[124]), "+f"(d[125]), "+f"(d[126]), "+f"(d[127])
        : "r"(alo), "r"(ahi), "r"(blo), "r"(bhi), "r"(scale_d));
}

__device__ __forceinline__ void wgmma_ss_n64_tb0(float (&d)[32], uint32_t alo, uint32_t ahi, uint32_t blo, uint32_t bhi, int scale_d) {
    asm volatile("{\n.reg .pred p;\n.reg .b64 da, db;\nsetp.ne.b32 p, %36, 0;\nmov.b64 da, {%32, %33};\nmov.b64 db, {%34, %35};\n"
        "wgmma.mma_async.sync.aligned.m64n64k16.f32.bf16.bf16 {%0, %1, %2, %3, %4, %5, %6, %7, %8, %9, %10, %11, %12, %13, %14, %15, %16, %17, %18, %19, %20, %21, %22, %23, %24, %25, %26, %27, %28, %29, %30, %31}, da, db, p, 1, 1, 0, 0;\n}\n"
        : "+f"(d[0]), "+f"(d[1]), "+f"(d[2]), "+f"(d[3]), "+f"(d[4]), "+f"(d[5]), "+f"(d[6]), "+f"(d[7]), "+f"(d[8]), "+f"(d[9]), "+f"(d[10]), "+f"(d[11]), "+f"(d[12]), "+f"(d[13]), "+f"(d[14]), "+f"(d[15]), "+f"(d[16]), "+f"(d[17]), "+f"(d[18]), "+f"(d[19]), "+f"(d[20]), "+f"(d[21]), "+f"(d[22]), "+f"(d[23]), "+f"(d[24]), "+f"(d[25]), "+f"(d[26]), "+f"(d[27]), "+f"(d[28]), "+f"(d[29]), "+f"(d[30]), "+f"(d[31])
        : "r"(alo), "r"(ahi), "r"(blo), "r"(bhi), "r"(scale_d));
}

__device__ __forceinline__ void wgmma_rs_n128_tb0(float (&d)[64], uint32_t a0, uint32_t a1, uint32_t a2, uint32_t a3, uint32_t blo, uint32_t bhi, int scale_d) {
    asm volatile("{\n.reg .pred p;\n.reg .b64 db;\nsetp.ne.b32 p, %70, 0;\nmov.b64 db, {%68, %69};\n"
        "wgmma.mma_async.sync.aligned.m64n128k16.f32.bf16.bf16 {%0, %1, %2, %3, %4, %5, %6, %7, %8, %9, %10, %11, %12, %13, %14, %15, %16, %17, %18, %19, %20, %21, %22, %23, %24, %25, %26, %27, %28, %29, %30, %31, %32, %33, %34, %35, %36, %37, %38, %39, %40, %41, %42, %43, %44, %45, %46, %47, %48, %49, %50, %51, %52, %53, %54, %55, %56, %57, %58, %59, %60, %61, %62, %63}, {%64, %65, %66, %67}, db, p, 1, 1, 0;\n}\n"
        : "+f"(d[0]), "+f"(d[1]), "+f"(d[2]), "+f"(d[3]), "+f"(d[4]), "+f"(d[5]), "+f"(d[6]), "+f"(d[7]), "+f"(d[8]), "+f"(d[9]), "+f"(d[10]), "+f"(d[11]), "+f"(d[12]), "+f"(d[13]), "+f"(d[14]), "+f"(d[15]), "+f"(d[16]), "+f"(d[17]), "+f"(d[18]), "+f"(d[19]), "+f"(d[20]), "+f"(d[21]), "+f"(d[22]), "+f"(d[23]), "+f"(d[24]), "+f"(d[25]), "+f"(d[26]), "+f"(d[27]), "+f"(d[28]), "+f"(d[29]), "+f"(d[30]), "+f"(d[31]), "+f"(d[32]), "+f"(d[33]), "+f"(d[34]), "+f"(d[35]), "+f"(d[36]), "+f"(d[37]), "+f"(d[38]), "+f"(d[39]), "+f"(d[40]), "+f"(d[41]), "+f"(d[42]), "+f"(d[43]), "+f"(d[44]), "+f"(d[45]), "+f"(d[46]), "+f"(d[47]), "+f"(d[48]), "+f"(d[49]), "+f"(d[50]), "+f"(d[51]), "+f"(d[52]), "+f"(d[53]), "+f"(d[54]), "+f"(d[55]), "+f"(d[56]), "+f"(d[57]), "+f"(d[58]), "+f"(d[59]), "+f"(d[60]), "+f"(d[61]), "+f"(d[62]), "+f"(d[63])
        : "r"(a0), "r"(a1), "r"(a2), "r"(a3), "r"(blo), "r"(bhi), "r"(scale_d));
}

__device__ __forceinline__ void wgmma_rs_n64_tb0(float (&d)[32], uint32_t a0, uint32_t a1, uint32_t a2, uint32_t a3, uint32_t blo, uint32_t bhi, int scale_d) {
    asm volatile("{\n.reg .pred p;\n.reg .b64 db;\nsetp.ne.b32 p, %38, 0;\nmov.b64 db, {%36, %37};\n"
        "wgmma.mma_async.sync.aligned.m64n64k16.f32.bf16.bf16 {%0, %1, %2, %3, %4, %5, %6, %7, %8, %9, %10, %11, %12, %13, %14, %15, %16, %17, %18, %19, %20, %21, %22, %23, %24, %25, %26, %27, %28, %29, %30, %31}, {%32, %33, %34, %35}, db, p, 1, 1, 0;\n}\n"
        : "+f"(d[0]), "+f"(d[1]), "+f"(d[2]), "+f"(d[3]), "+f"(d[4]), "+f"(d[5]), "+f"(d[6]), "+f"(d[7]), "+f"(d[8]), "+f"(d[9]), "+f"(d[10]), "+f"(d[11]), "+f"(d[12]), "+f"(d[13]), "+f"(d[14]), "+f"(d[15]), "+f"(d[16]), "+f"(d[17]), "+f"(d[18]), "+f"(d[19]), "+f"(d[20]), "+f"(d[21]), "+f"(d[22]), "+f"(d[23]), "+f"(d[24]), "+f"(d[25]), "+f"(d[26]), "+f"(d[27]), "+f"(d[28]), "+f"(d[29]), "+f"(d[30]), "+f"(d[31])
        : "r"(a0), "r"(a1), "r"(a2), "r"(a3), "r"(blo), "r"(bhi), "r"(scale_d));
}

__device__ __forceinline__ void wgmma_rs_n32_tb1(float (&d)[16], uint32_t a0, uint32_t a1, uint32_t a2, uint32_t a3, uint32_t blo, uint32_t bhi, int scale_d) {
    asm volatile("{\n.reg .pred p;\n.reg .b64 db;\nsetp.ne.b32 p, %22, 0;\nmov.b64 db, {%20, %21};\n"
        "wgmma.mma_async.sync.aligned.m64n32k16.f32.bf16.bf16 {%0, %1, %2, %3, %4, %5, %6, %7, %8, %9, %10, %11, %12, %13, %14, %15}, {%16, %17, %18, %19}, db, p, 1, 1, 1;\n}\n"
        : "+f"(d[0]), "+f"(d[1]), "+f"(d[2]), "+f"(d[3]), "+f"(d[4]), "+f"(d[5]), "+f"(d[6]), "+f"(d[7]), "+f"(d[8]), "+f"(d[9]), "+f"(d[10]), "+f"(d[11]), "+f"(d[12]), "+f"(d[13]), "+f"(d[14]), "+f"(d[15])
        : "r"(a0), "r"(a1), "r"(a2), "r"(a3), "r"(blo), "r"(bhi), "r"(scale_d));
}

__device__ __forceinline__ void wgmma_rs_n40_tb1(float (&d)[20], uint32_t a0, uint32_t a1, uint32_t a2, uint32_t a3, uint32_t blo, uint32_t bhi, int scale_d) {
    asm volatile("{\n.reg .pred p;\n.reg .b64 db;\nsetp.ne.b32 p, %26, 0;\nmov.b64 db, {%24, %25};\n"
        "wgmma.mma_async.sync.aligned.m64n40k16.f32.bf16.bf16 {%0, %1, %2, %3, %4, %5, %6, %7, %8, %9, %10, %11, %12, %13, %14, %15, %16, %17, %18, %19}, {%20, %21, %22, %23}, db, p, 1, 1, 1;\n}\n"
        : "+f"(d[0]), "+f"(d[1]), "+f"(d[2]), "+f"(d[3]), "+f"(d[4]), "+f"(d[5]), "+f"(d[6]), "+f"(d[7]), "+f"(d[8]), "+f"(d[9]), "+f"(d[10]), "+f"(d[11]), "+f"(d[12]), "+f"(d[13]), "+f"(d[14]), "+f"(d[15]), "+f"(d[16]), "+f"(d[17]), "+f"(d[18]), "+f"(d[19])
        : "r"(a0), "r"(a1), "r"(a2), "r"(a3), "r"(blo), "r"(bhi), "r"(scale_d));
}

template <int BN>
__device__ __forceinline__ void wgmma_tile(float (&d)[BN / 2], uint32_t da, uint32_t db, int sd) {
    constexpr uint32_t HI = desc_hi(1024, 1);
    if constexpr (BN == 128) wgmma_ss_n128_tb1(d, da, HI, db, HI, sd);
    else if constexpr (BN == 192) wgmma_ss_n192_tb1(d, da, HI, db, HI, sd);
    else if constexpr (BN == 224) wgmma_ss_n224_tb1(d, da, HI, db, HI, sd);
    else wgmma_ss_n256_tb1(d, da, HI, db, HI, sd);
}

__global__ void __launch_bounds__(256) prep_kernel(const bf16* __restrict__ x, const bf16* __restrict__ gate_w,
                                                   const bf16* __restrict__ w1, const bf16* __restrict__ w3) {
    constexpr int row_blocks = 256;
    const int tid = threadIdx.x;
    TL_START(0)
    pdl_launch();
    if ((int)blockIdx.x < row_blocks) {
        const int row = blockIdx.x * 8 + (tid >> 5);
        const int lane = tid & 31;
        const uint4* xr = reinterpret_cast<const uint4*>(x + (size_t)row * DM);
        const uint4* gw = reinterpret_cast<const uint4*>(gate_w);
        float v[32];
        float gsum = 0.f, sum = 0.f;
#pragma unroll
        for (int i = 0; i < 4; i++) {
            uint4 a = xr[lane + 32 * i];
            uint4 b = gw[lane + 32 * i];
            const uint32_t aa[4] = {a.x, a.y, a.z, a.w};
            const uint32_t bb[4] = {b.x, b.y, b.z, b.w};
#pragma unroll
            for (int j = 0; j < 4; j++) {
                float x0 = __uint_as_float(aa[j] << 16), x1 = __uint_as_float(aa[j] & 0xFFFF0000u);
                float g0 = __uint_as_float(bb[j] << 16), g1 = __uint_as_float(bb[j] & 0xFFFF0000u);
                v[i * 8 + j * 2] = x0;
                v[i * 8 + j * 2 + 1] = x1;
                sum += x0 + x1;
                gsum += bf16_round(x0 * g0) + bf16_round(x1 * g1);
            }
        }
#pragma unroll
        for (int o = 16; o > 0; o >>= 1) {
            sum += __shfl_xor_sync(0xffffffffu, sum, o);
            gsum += __shfl_xor_sync(0xffffffffu, gsum, o);
        }
        const float mean = sum * (1.0f / DM);
        float m2 = 0.f;
#pragma unroll
        for (int i = 0; i < 32; i++) {
            float d = v[i] - mean;
            m2 += d * d;
        }
#pragma unroll
        for (int o = 16; o > 0; o >>= 1) m2 += __shfl_xor_sync(0xffffffffu, m2, o);
        if (lane == 0) {
            g_mean1[row] = mean;
            g_rstd1[row] = rsqrtf(m2 * (1.0f / DM) + 1e-5f);
            float logit = bf16_round(gsum);
            float g = bf16_round(1.0f / (1.0f + __expf(-logit)));
            g_gate[row] = g;
            g_omg[row] = bf16_round(1.0f - g);
        }
    } else {
        __shared__ float red[32][65];
        int blk = blockIdx.x - row_blocks;
        const bf16* w = w1;
        int ld = DM;
        float* cs_out = g_cs1;
        if (blk >= 64) { blk -= 64; w = w3; ld = FF; cs_out = g_cs3; }
        const int chunk = blk & 3;
        const int col0 = (blk >> 2) * 64;
        const int cg = tid & 7;
        const int rg = tid >> 3;
        uint4 a[8];
#pragma unroll
        for (int r = 0; r < 8; r++)
            a[r] = *reinterpret_cast<const uint4*>(w + (size_t)(chunk * 256 + r * 32 + rg) * ld + col0 + cg * 8);
        float acc[8];
#pragma unroll
        for (int j = 0; j < 8; j++) acc[j] = 0.f;
#pragma unroll
        for (int r = 0; r < 8; r++) {
            const uint32_t aa[4] = {a[r].x, a[r].y, a[r].z, a[r].w};
#pragma unroll
            for (int j = 0; j < 4; j++) {
                acc[2 * j] += __uint_as_float(aa[j] << 16);
                acc[2 * j + 1] += __uint_as_float(aa[j] & 0xFFFF0000u);
            }
        }
#pragma unroll
        for (int j = 0; j < 8; j++) red[rg][cg * 8 + j] = acc[j];
        __syncthreads();
        if (tid < 64) {
            float s = 0.f;
#pragma unroll
            for (int r = 0; r < 32; r++) s += red[r][tid];
            cs_out[chunk * ld + col0 + tid] = s;
        }
    }
    TL_END(0)
}

#define RELEASE_STAGE(b) if (tid_wg < 2) mbar_arrive_cluster(b, tid_wg)
template <int BN, int STAGES>
struct GemmSmem {
    static constexpr int A_BYTES = 128 * 64 * 2;
    static constexpr int B_BOXES = (BN + 63) / 64;
    static constexpr int B_BYTES = B_BOXES * 64 * 64 * 2;
    static constexpr int STAGE_BYTES = A_BYTES + B_BYTES;
    static constexpr int STG_OFF = STAGES * STAGE_BYTES;
    static constexpr int CS_OFF = STAGES * STAGE_BYTES + 2 * 16384;
    static constexpr int BAR_OFF = CS_OFF + 1024;
    static constexpr int TOTAL = BAR_OFF + 128 + 512;
};

template <int MODE, int BN, int STAGES>
__global__ void __launch_bounds__(384, 1)
gemm_kernel(const __grid_constant__ CUtensorMap mA, const __grid_constant__ CUtensorMap mB0,
            const __grid_constant__ CUtensorMap mB1, const __grid_constant__ CUtensorMap mC0,
            const __grid_constant__ CUtensorMap mC1, const bf16* __restrict__ xin, int n_tiles_n, int kblocks) {
    using L = GemmSmem<BN, STAGES>;
    extern __shared__ uint8_t smem_raw[];
    const uint32_t sbase = (smem_u32(smem_raw) + 1023u) & ~1023u;
    const uint32_t bar_full = sbase + L::BAR_OFF;
    const uint32_t bar_empty = bar_full + 8 * STAGES;
    const uint32_t bar_res = bar_empty + 8 * STAGES;
    const int wg = threadIdx.x >> 7;
    const int npairs = 8 * n_tiles_n;
    const uint32_t crank = cluster_rank();
    const int cid = blockIdx.x >> 1, ncl = gridDim.x >> 1;
    TL_START(MODE)
    pdl_launch();

    if (threadIdx.x == 0) {
        for (int s = 0; s < STAGES; s++) {
            mbar_init(bar_full + 8 * s, 1);
            mbar_init(bar_empty + 8 * s, 4);
        }
        mbar_init(bar_res, 1);
        asm volatile("fence.mbarrier_init.release.cluster;" ::: "memory");
        prefetch_tmap(&mA);
        prefetch_tmap(&mB0);
        if (MODE == 1 || MODE == 5) prefetch_tmap(&mB1);
        if (MODE == 2 || MODE == 5) prefetch_tmap(&mC1);
        prefetch_tmap(&mC0);
    }
    cluster_sync_all();

    if (wg == 0) {
        reg_dealloc<40>();
        if (threadIdx.x == 0) {
            if (MODE != 1) pdl_wait();
            int stage = 0;
            uint32_t phase = 1;
            for (int pr = cid; pr < npairs; pr += ncl) {
                const int m0 = ((pr & 7) * 2 + crank) * 128;
                const int n0 = (pr >> 3) * BN;
                for (int kb = 0; kb < kblocks; kb++) {
                    mbar_wait(bar_empty + 8 * stage, phase);
                    const uint32_t sa = sbase + stage * L::STAGE_BYTES;
                    const uint32_t sb = sa + L::A_BYTES;
                    const uint32_t fb = bar_full + 8 * stage;
                    mbar_expect_tx(fb, L::STAGE_BYTES);
                    int arow = m0;
                    if (MODE == 2) {
                        const int grp = kb >> 2;
                        arow += (grp == 0) ? -1 : (grp == 1) ? 1 : (grp == 2) ? -2 : 2;
                    }
                    tma_load_2d(sa, &mA, kb * 64, arow, fb);
                    const CUtensorMap* mb = &mB0;
                    int bc = n0, br = kb * 64;
                    if (MODE == 1 && n0 >= 3 * DM) { mb = &mB1; bc = n0 - 3 * DM; }
                    if (MODE == 5 && kb >= 16) { mb = &mB1; br = (kb - 16) * 64; }
#pragma unroll
                    for (int b = 0; b < L::B_BOXES / 2; b++) {
                        const int bb = crank * (L::B_BOXES / 2) + b;
                        tma_load_2d_mc(sb + bb * 8192, mb, bc + bb * 64, br, fb, (uint16_t)3);
                    }
                    if ((MODE == 2 || MODE == 5) && kb == STAGES - 1) {
                        mbar_expect_tx(bar_res, 32768);
#pragma unroll
                        for (int q = 0; q < 4; q++)
                            tma_load_2d(sbase + L::STG_OFF + q * 8192, &mC1, n0 + (q & 1) * 64, m0 + (q >> 1) * 64, bar_res);
                    }
                    if (++stage == STAGES) { stage = 0; phase ^= 1; }
                }
            }
        }
    } else {
        reg_alloc<232>();
        const int c = wg - 1;
        const int warp = (threadIdx.x >> 5) & 3;
        const int lane = threadIdx.x & 31;
        const int tid_wg = threadIdx.x & 127;
        const uint32_t stg = sbase + L::STG_OFF + c * 16384;
        int stage = 0;
        uint32_t phase = 0;
        float acc[BN / 2];
        bool first = true;
        PH(0)
        if (MODE != 1) pdl_wait();
        for (int pr = cid; pr < npairs; pr += ncl) {
            const int m0 = ((pr & 7) * 2 + crank) * 128;
            const int n0 = (pr >> 3) * BN;
            const int r0 = m0 + c * 64 + warp * 16 + (lane >> 2);
            const int r1 = r0 + 8;
            float mu[2], rs[2], og[2];
            if (MODE == 3) {
                const int t = threadIdx.x - 128;
                if (t < BN) {
                    const float v = (g_cs3[n0 + t] + g_cs3[FF + n0 + t]) + (g_cs3[2 * FF + n0 + t] + g_cs3[3 * FF + n0 + t]);
                    asm volatile("st.shared.f32 [%0], %1;" ::"r"(sbase + L::CS_OFF + t * 4), "f"(v) : "memory");
                }
#pragma unroll
                for (int h = 0; h < 2; h++) {
                    const float4* sp = reinterpret_cast<const float4*>(&g_stat2[(h ? r1 : r0) * 8]);
                    float4 p[4];
                    float s = 0.f;
#pragma unroll
                    for (int i = 0; i < 4; i++) { p[i] = sp[i]; s += p[i].x + p[i].z; }
                    const float mean = s * (1.0f / DM);
                    float m2 = 0.f;
#pragma unroll
                    for (int i = 0; i < 4; i++) {
                        float d0 = p[i].x * (1.0f / 128) - mean, d1 = p[i].z * (1.0f / 128) - mean;
                        m2 += p[i].y + p[i].w + 128.0f * (d0 * d0 + d1 * d1);
                    }
                    mu[h] = mean;
                    rs[h] = rsqrtf(m2 * (1.0f / DM) + 1e-5f);
                }
            }
            if (MODE == 3 || MODE == 5) { og[0] = g_omg[r0]; og[1] = g_omg[r1]; }
            int prev_stage = 0;
            for (int kb = 0; kb < kblocks; kb++) {
                mbar_wait(bar_full + 8 * stage, phase);
                const uint32_t sa = sbase + stage * L::STAGE_BYTES + c * 8192;
                const uint32_t sb = sbase + stage * L::STAGE_BYTES + L::A_BYTES;
                const uint32_t da = desc_lo(sa, 16);
                const uint32_t db = desc_lo(sb, 8192);
                wgmma_fence();
#pragma unroll
                for (int k = 0; k < 4; k++) wgmma_tile<BN>(acc, da + k * 2, db + k * 128, (kb | k) != 0);
                wgmma_commit();
                if (kb > 0) {
                    wgmma_wait<1>();
                    RELEASE_STAGE(bar_empty + 8 * prev_stage);
                }
                prev_stage = stage;
                if (++stage == STAGES) { stage = 0; phase ^= 1; }
            }
            wgmma_wait<0>();
            RELEASE_STAGE(bar_empty + 8 * prev_stage);
            PH(1)
            if (MODE == 1 && first) { pdl_wait(); first = false; }

            const int cq = (lane & 3) * 2;
            const CUtensorMap* mc = &mC0;
            const uint32_t rrow = warp * 16 + (lane >> 2);
            const uint32_t res0 = stg + rrow * 128 + cq * 2;
            int out_c0 = n0;
            if (MODE == 1) {
                if (n0 < DM) {
                    const float qs = 0.17677669529663687f * 1.4426950408889634f;
#pragma unroll
                    for (int j = 0; j < BN / 2; j++) acc[j] *= qs;
                } else if (n0 >= 3 * DM) {
                    mc = &mC1;
                    out_c0 = n0 - 3 * DM;
                    const float mu0 = g_mean1[r0], mu1 = g_mean1[r1];
                    const float rs0 = g_rstd1[r0], rs1 = g_rstd1[r1];
                    {
                        const int t = threadIdx.x - 128;
                        const float v = (g_cs1[out_c0 + t] + g_cs1[DM + out_c0 + t]) + (g_cs1[2 * DM + out_c0 + t] + g_cs1[3 * DM + out_c0 + t]);
                        asm volatile("st.shared.f32 [%0], %1;" ::"r"(sbase + L::CS_OFF + t * 4), "f"(v) : "memory");
                    }
                    named_bar_sync(3, 256);
#pragma unroll
                    for (int j = 0; j < BN / 8; j++) {
                        float2 cs;
                        asm volatile("ld.shared.v2.f32 {%0, %1}, [%2];" : "=f"(cs.x), "=f"(cs.y) : "r"(sbase + L::CS_OFF + (8 * j + cq) * 4));
                        acc[4 * j + 0] = gelu_tanh(rs0 * fmaf(-mu0, cs.x, acc[4 * j + 0]));
                        acc[4 * j + 1] = gelu_tanh(rs0 * fmaf(-mu0, cs.y, acc[4 * j + 1]));
                        acc[4 * j + 2] = gelu_tanh(rs1 * fmaf(-mu1, cs.x, acc[4 * j + 2]));
                        acc[4 * j + 3] = gelu_tanh(rs1 * fmaf(-mu1, cs.y, acc[4 * j + 3]));
                    }
                    named_bar_sync(3, 256);
                }
            } else if (MODE == 2) {
                float s0 = 0.f, s1 = 0.f;
                mbar_wait(bar_res, 0);
#pragma unroll
                for (int j = 0; j < BN / 8; j++) {
                    uint32_t xa, xb;
                    const uint32_t ra = res0 + (j >> 3) * 8192 + (((j & 7) ^ (rrow & 7)) << 4);
                    asm volatile("ld.shared.b32 %0, [%1];" : "=r"(xa) : "r"(ra));
                    asm volatile("ld.shared.b32 %0, [%1];" : "=r"(xb) : "r"(ra + 1024));
                    acc[4 * j + 0] = bf16_round(bf16_round(acc[4 * j + 0]) + __uint_as_float(xa << 16));
                    acc[4 * j + 1] = bf16_round(bf16_round(acc[4 * j + 1]) + __uint_as_float(xa & 0xFFFF0000u));
                    acc[4 * j + 2] = bf16_round(bf16_round(acc[4 * j + 2]) + __uint_as_float(xb << 16));
                    acc[4 * j + 3] = bf16_round(bf16_round(acc[4 * j + 3]) + __uint_as_float(xb & 0xFFFF0000u));
                    s0 += acc[4 * j + 0] + acc[4 * j + 1];
                    s1 += acc[4 * j + 2] + acc[4 * j + 3];
                }
                s0 += __shfl_xor_sync(0xffffffffu, s0, 1);
                s0 += __shfl_xor_sync(0xffffffffu, s0, 2);
                s1 += __shfl_xor_sync(0xffffffffu, s1, 1);
                s1 += __shfl_xor_sync(0xffffffffu, s1, 2);
                const float mu0 = s0 * (1.0f / BN), mu1 = s1 * (1.0f / BN);
                float q0 = 0.f, q1 = 0.f;
#pragma unroll
                for (int j = 0; j < BN / 8; j++) {
                    float d;
                    d = acc[4 * j + 0] - mu0; q0 += d * d;
                    d = acc[4 * j + 1] - mu0; q0 += d * d;
                    d = acc[4 * j + 2] - mu1; q1 += d * d;
                    d = acc[4 * j + 3] - mu1; q1 += d * d;
                }
                q0 += __shfl_xor_sync(0xffffffffu, q0, 1);
                q0 += __shfl_xor_sync(0xffffffffu, q0, 2);
                q1 += __shfl_xor_sync(0xffffffffu, q1, 1);
                q1 += __shfl_xor_sync(0xffffffffu, q1, 2);
                if ((lane & 3) == 0) {
                    static_assert(MODE != 2 || BN == 128, "stats layout assumes BN=128");
                    g_stat2[r0 * 8 + (n0 >> 7)] = make_float2(s0, q0);
                    g_stat2[r1 * 8 + (n0 >> 7)] = make_float2(s1, q1);
                }
            } else if (MODE == 3) {
                out_c0 = n0 + DM;
                named_bar_sync(3, 256);
#pragma unroll
                for (int j = 0; j < BN / 8; j++) {
                    float2 cs;
                    asm volatile("ld.shared.v2.f32 {%0, %1}, [%2];" : "=f"(cs.x), "=f"(cs.y) : "r"(sbase + L::CS_OFF + (8 * j + cq) * 4));
                    acc[4 * j + 0] = og[0] * gelu_tanh(rs[0] * fmaf(-mu[0], cs.x, acc[4 * j + 0]));
                    acc[4 * j + 1] = og[0] * gelu_tanh(rs[0] * fmaf(-mu[0], cs.y, acc[4 * j + 1]));
                    acc[4 * j + 2] = og[1] * gelu_tanh(rs[1] * fmaf(-mu[1], cs.x, acc[4 * j + 2]));
                    acc[4 * j + 3] = og[1] * gelu_tanh(rs[1] * fmaf(-mu[1], cs.y, acc[4 * j + 3]));
                }
                named_bar_sync(3, 256);
            } else {
                const float og0 = og[0], og1 = og[1];
                mbar_wait(bar_res, 0);
#pragma unroll
                for (int j = 0; j < BN / 8; j++) {
                    uint32_t xa, xb;
                    const uint32_t ra = res0 + (j >> 3) * 8192 + (((j & 7) ^ (rrow & 7)) << 4);
                    asm volatile("ld.shared.b32 %0, [%1];" : "=r"(xa) : "r"(ra));
                    asm volatile("ld.shared.b32 %0, [%1];" : "=r"(xb) : "r"(ra + 1024));
                    acc[4 * j + 0] = fmaf(og0, __uint_as_float(xa << 16), acc[4 * j + 0]);
                    acc[4 * j + 1] = fmaf(og0, __uint_as_float(xa & 0xFFFF0000u), acc[4 * j + 1]);
                    acc[4 * j + 2] = fmaf(og1, __uint_as_float(xb << 16), acc[4 * j + 2]);
                    acc[4 * j + 3] = fmaf(og1, __uint_as_float(xb & 0xFFFF0000u), acc[4 * j + 3]);
                }
            }
            PH(3)
            const int srow = warp * 16 + (lane & 7) + ((lane >> 3) & 1) * 8;
#pragma unroll
            for (int rnd = 0; rnd < (BN + 127) / 128; rnd++) {
                if (tid_wg == 0) bulk_wait_read0();
                named_bar_sync(1 + c, 128);
#pragma unroll
                for (int jj = 0; jj < 8; jj++) {
                    const int j = rnd * 16 + jj * 2;
                    if (j * 8 < BN) {
                        const int jb = jj * 2 + (lane >> 4);
                        uint32_t addr = stg + (jb >> 3) * 8192 + srow * 128 + (((jb & 7) ^ (srow & 7)) << 4);
                        if (rnd * 128 + 128 > BN && jj >= 4)
                            addr = stg + 8192 + srow * 64 + (((jb & 3) ^ ((srow >> 1) & 3)) << 4);
                        stmatrix_x4(addr, pack_bf16(acc[4 * j + 0], acc[4 * j + 1]), pack_bf16(acc[4 * j + 2], acc[4 * j + 3]),
                                    pack_bf16(acc[4 * j + 4], acc[4 * j + 5]), pack_bf16(acc[4 * j + 6], acc[4 * j + 7]));
                    }
                }
                fence_proxy_async();
                named_bar_sync(1 + c, 128);
                if (tid_wg == 0) {
                    tma_store_2d(mc, stg, out_c0 + rnd * 128, m0 + c * 64);
                    if (rnd * 128 + 64 < BN)
                        tma_store_2d((rnd * 128 + 128 > BN) ? &mC1 : mc, stg + 8192, out_c0 + rnd * 128 + 64, m0 + c * 64);
                    bulk_commit();
                }
            }
        }
        PH(4)
        if (tid_wg == 0) bulk_wait0();
        PH(5)
        TL_END(MODE)
    }
    cluster_sync_all();
}

#define ATT_SPLIT 16
constexpr int ATT_NTILES = NH * 16;
#define ATT_GRID_N 512
constexpr int ATT_GRID = ATT_GRID_N;
constexpr int ATT_THREADS = 256;
constexpr int ATT_STAGES = 4;
constexpr int ATT_DIST = 2;
constexpr int ATT_Q_OFF = ATT_STAGES * 16384;
constexpr int ATT_ONES_OFF = ATT_Q_OFF + 8192;
constexpr int ATT_KEXT_OFF = ATT_ONES_OFF + 4096;
constexpr int ATT_QEXT_OFF = ATT_KEXT_OFF + 4096;
constexpr int ATT_BAR_OFF = ATT_QEXT_OFF + 8192;
constexpr int ATT_SMEM = ATT_BAR_OFF + 256 + 1024;

__device__ __forceinline__ void row_max(const float (&s)[32], float& m0, float& m1) {
    float a0[8], a1[8];
#pragma unroll
    for (int i = 0; i < 8; i++) {
        a0[i] = fmaxf(s[4 * i], s[4 * i + 1]);
        a1[i] = fmaxf(s[4 * i + 2], s[4 * i + 3]);
    }
#pragma unroll
    for (int w = 4; w > 0; w >>= 1)
#pragma unroll
        for (int i = 0; i < w; i++) { a0[i] = fmaxf(a0[i], a0[i + w]); a1[i] = fmaxf(a1[i], a1[i + w]); }
    float mx0 = a0[0], mx1 = a1[0];
    mx0 = fmaxf(mx0, __shfl_xor_sync(0xffffffffu, mx0, 1));
    mx1 = fmaxf(mx1, __shfl_xor_sync(0xffffffffu, mx1, 1));
    mx0 = fmaxf(mx0, __shfl_xor_sync(0xffffffffu, mx0, 2));
    mx1 = fmaxf(mx1, __shfl_xor_sync(0xffffffffu, mx1, 2));
    m0 = fmaxf(m0, mx0);
    m1 = fmaxf(m1, mx1);
}

__device__ __forceinline__ void attn_step(float (&s)[32], float (&o)[20], uint32_t dq, uint32_t dke, uint32_t dk_next,
                                          uint32_t dv_cur, uint32_t release_bar) {
    constexpr uint32_t HI = desc_hi(512, 2);
    uint32_t p[16];
#pragma unroll
    for (int i = 0; i < 16; i++) p[i] = pack_bf16(ex2(s[2 * i]), ex2(s[2 * i + 1]));
    wgmma_fence();
    wgmma_ss_n64_tb0(s, dq, HI, dk_next, HI, 0);
    wgmma_ss_n64_tb0(s, dq + 2, HI, dk_next + 2, HI, 1);
    wgmma_ss_n64_tb0(s, dq + ((ATT_QEXT_OFF - ATT_Q_OFF) >> 4), HI, dke, HI, 1);
#pragma unroll
    for (int t = 0; t < 4; t++)
        wgmma_rs_n40_tb1(o, p[4 * t], p[4 * t + 1], p[4 * t + 2], p[4 * t + 3], dv_cur + t * 64, HI, 1);
    wgmma_commit();
    wgmma_wait<0>();
    if (release_bar != 0 && (threadIdx.x & 127) == 0) mbar_arrive(release_bar);
}

__global__ void __launch_bounds__(256, 1)
attn_exact_kernel(const __grid_constant__ CUtensorMap mKV) {
    extern __shared__ uint8_t smem_raw[];
    pdl_launch();
    pdl_wait();
    const int tile = blockIdx.x;
    if (g_bad[tile] == 0) return;
    constexpr int NBLK = S_LEN / 128;
    constexpr uint32_t HI = desc_hi(512, 2);
    const uint32_t sbase = (smem_u32(smem_raw) + 1023u) & ~1023u;
    const uint32_t bar = sbase + ATT_BAR_OFF;
    const int warp_id = threadIdx.x >> 5;
    const int lane = threadIdx.x & 31;
    const int cq = (lane & 3) * 2;
    const uint32_t dk0 = desc_lo(sbase, 16);
    const uint32_t dv0 = desc_lo(sbase + 8192, ATT_ONES_OFF - 8192);
    if (threadIdx.x == 0) {
        mbar_init(bar, 1);
        asm volatile("fence.mbarrier_init.release.cluster;" ::: "memory");
    }
    asm volatile("st.shared.v4.b32 [%0], {%1, %1, %1, %1};" ::"r"(sbase + ATT_ONES_OFF + threadIdx.x * 16), "r"(0x3F803F80u) : "memory");
    fence_proxy_async();
    __syncthreads();
    const int head = tile >> 4;
    const int row0 = (tile & 15) * 128 + warp_id * 16 + (lane >> 2);
    const uint32_t dq = desc_lo(sbase + ATT_Q_OFF + (threadIdx.x >> 7) * 4096, 16);
    float o[20];
#pragma unroll
    for (int i = 0; i < 20; i++) o[i] = 0.f;
    float m0 = -INFINITY, m1 = -INFINITY;
#pragma unroll 1
    for (int j = 0; j < NBLK; j++) {
        if (threadIdx.x == 0) {
            mbar_expect_tx(bar, j == 0 ? 3 * 8192 : 2 * 8192);
            if (j == 0) tma_load_2d(sbase + ATT_Q_OFF, &mKV, head * DH, (tile & 15) * 128, bar);
            tma_load_2d(sbase, &mKV, DM + head * DH, j * 128, bar);
            tma_load_2d(sbase + 8192, &mKV, 2 * DM + head * DH, j * 128, bar);
        }
        __syncwarp();
        mbar_wait(bar, j & 1);
#pragma unroll 1
        for (int hf = 0; hf < 2; hf++) {
            float s[32];
            wgmma_fence();
            wgmma_ss_n64_tb0(s, dq, HI, dk0 + hf * 256, HI, 0);
            wgmma_ss_n64_tb0(s, dq + 2, HI, dk0 + hf * 256 + 2, HI, 1);
            wgmma_commit();
            wgmma_wait<0>();
            const float mo0 = m0, mo1 = m1;
            row_max(s, m0, m1);
            const float a0 = ex2(mo0 - m0), a1 = ex2(mo1 - m1);
            uint32_t p[16];
#pragma unroll
            for (int i = 0; i < 8; i++) {
                p[2 * i] = pack_bf16(ex2(s[4 * i + 0] - m0), ex2(s[4 * i + 1] - m0));
                p[2 * i + 1] = pack_bf16(ex2(s[4 * i + 2] - m1), ex2(s[4 * i + 3] - m1));
            }
#pragma unroll
            for (int i = 0; i < 5; i++) {
                o[4 * i + 0] *= a0; o[4 * i + 1] *= a0;
                o[4 * i + 2] *= a1; o[4 * i + 3] *= a1;
            }
            wgmma_fence();
            const uint32_t dv = dv0 + hf * 256 - ((uint32_t)(hf * 256) << 16);
#pragma unroll
            for (int t = 0; t < 4; t++)
                wgmma_rs_n40_tb1(o, p[4 * t], p[4 * t + 1], p[4 * t + 2], p[4 * t + 3], dv + t * 64, HI, 1);
            wgmma_commit();
            wgmma_wait<0>();
        }
        __syncthreads();
    }
    const float f0 = g_gate[row0] / o[16], f1 = g_gate[row0 + 8] / o[18];
    bf16* op0 = g_a5 + (size_t)row0 * A5W + head * DH + cq;
    bf16* op1 = op0 + 8 * A5W;
#pragma unroll
    for (int i = 0; i < 4; i++) {
        *reinterpret_cast<uint32_t*>(op0 + 8 * i) = pack_bf16(o[4 * i] * f0, o[4 * i + 1] * f0);
        *reinterpret_cast<uint32_t*>(op1 + 8 * i) = pack_bf16(o[4 * i + 2] * f1, o[4 * i + 3] * f1);
    }
}

#define ATT_MINB 2
__global__ void __launch_bounds__(256, ATT_MINB)
attn_kernel(const __grid_constant__ CUtensorMap mKV) {
    extern __shared__ uint8_t smem_raw[];
    const uint32_t sbase = (smem_u32(smem_raw) + 1023u) & ~1023u;
    const uint32_t bar_kfull = sbase + ATT_BAR_OFF;
    const uint32_t bar_vfull = bar_kfull + 8 * ATT_STAGES;
    const uint32_t bar_empty = bar_vfull + 8 * ATT_STAGES;
    const int tile = blockIdx.x;
    const int head = tile >> 4;
    const int lane = threadIdx.x & 31;
    constexpr int NBLK = S_LEN / 128;
    TL_START(6)
    pdl_launch();

    auto issue_kv = [&](int g) {
        const int sn = g % ATT_STAGES;
        if (g >= ATT_STAGES) mbar_wait(bar_empty + 8 * sn, ((g / ATT_STAGES) - 1) & 1);
        const uint32_t skn = sbase + sn * 16384;
        mbar_expect_tx(bar_kfull + 8 * sn, g == 0 ? 16384 : 8192);
        if (g == 0) tma_load_2d(sbase + ATT_Q_OFF, &mKV, head * DH, (tile & 15) * 128, bar_kfull);
        tma_load_2d(skn, &mKV, DM + head * DH, g * 128, bar_kfull + 8 * sn);
        mbar_expect_tx(bar_vfull + 8 * sn, 8192);
        tma_load_2d(skn + 8192, &mKV, 2 * DM + head * DH, g * 128, bar_vfull + 8 * sn);
    };

    if (threadIdx.x == 0) {
        for (int s = 0; s < ATT_STAGES; s++) {
            mbar_init(bar_kfull + 8 * s, 1);
            mbar_init(bar_vfull + 8 * s, 1);
            mbar_init(bar_empty + 8 * s, 2);
        }
        asm volatile("fence.mbarrier_init.release.cluster;" ::: "memory");
        prefetch_tmap(&mKV);
        pdl_wait();
#pragma unroll
        for (int j = 0; j < ATT_DIST; j++) issue_kv(j);
    }
    {
        asm volatile("st.shared.v4.b32 [%0], {%1, %1, %1, %1};" ::"r"(sbase + ATT_ONES_OFF + threadIdx.x * 16), "r"(0x3F803F80u) : "memory");
        const int r = threadIdx.x >> 2, ch = threadIdx.x & 3;
        const uint32_t w0 = (ch == ((r >> 1) & 3)) ? 0x00003F80u : 0u;
        asm volatile("st.shared.v4.b32 [%0], {%1, %2, %2, %2};" ::"r"(sbase + ATT_KEXT_OFF + threadIdx.x * 16), "r"(w0), "r"(0u) : "memory");
        asm volatile("st.shared.v4.b32 [%0], {%1, %1, %1, %1};" ::"r"(sbase + ATT_QEXT_OFF + threadIdx.x * 16), "r"(0u) : "memory");
        asm volatile("st.shared.v4.b32 [%0], {%1, %1, %1, %1};" ::"r"(sbase + ATT_QEXT_OFF + 4096 + threadIdx.x * 16), "r"(0u) : "memory");
    }
    fence_proxy_async();
    __syncthreads();

    constexpr uint32_t HI = desc_hi(512, 2);
    const uint32_t dk0 = desc_lo(sbase, 16);
    const uint32_t dv0 = desc_lo(sbase + 8192, ATT_ONES_OFF - 8192);
    const uint32_t dke = dk0 + (ATT_KEXT_OFF >> 4);
    const uint32_t dq = dk0 + ((ATT_Q_OFF + (threadIdx.x >> 7) * 4096) >> 4);
    float o[20];
#pragma unroll
    for (int i = 0; i < 20; i++) o[i] = 0.f;
    float s0[32];
    mbar_wait(bar_kfull, 0);
    wgmma_fence();
    wgmma_ss_n64_tb0(s0, dq, HI, dk0, HI, 0);
    wgmma_ss_n64_tb0(s0, dq + 2, HI, dk0 + 2, HI, 1);
    wgmma_commit();
    wgmma_wait<0>();
    float m0 = -INFINITY, m1 = -INFINITY;
    row_max(s0, m0, m1);
    if ((lane & 3) == 0) {
        const int r = ((threadIdx.x >> 5) & 3) * 16 + (lane >> 2);
        const uint32_t qe = sbase + ATT_QEXT_OFF + (threadIdx.x >> 7) * 4096;
        asm volatile("st.shared.b16 [%0], %1;" ::"r"(qe + r * 64 + (((r >> 1) & 3) << 4)), "h"((uint16_t)(pack_bf16(-m0, 0.f) & 0xFFFFu)) : "memory");
        asm volatile("st.shared.b16 [%0], %1;" ::"r"(qe + (r + 8) * 64 + ((((r + 8) >> 1) & 3) << 4)), "h"((uint16_t)(pack_bf16(-m1, 0.f) & 0xFFFFu)) : "memory");
    }
    fence_proxy_async();
    named_bar_sync(1 + (threadIdx.x >> 7), 128);
    wgmma_fence();
    wgmma_ss_n64_tb0(s0, dq + ((ATT_QEXT_OFF - ATT_Q_OFF) >> 4), HI, dke, HI, 1);
    wgmma_commit();
    wgmma_wait<0>();
#pragma unroll 1
    for (int j = 0; j < NBLK; j++) {
        if (threadIdx.x == 0 && j + ATT_DIST < NBLK) issue_kv(j + ATT_DIST);
        __syncwarp();
        const uint32_t stage = j & (ATT_STAGES - 1), nstage = (j + 1) & (ATT_STAGES - 1);
        const uint32_t dk = dk0 + stage * 1024;
        const uint32_t dv = dv0 + stage * 1024 - (stage << 26);
        mbar_wait(bar_vfull + 8 * stage, (j / ATT_STAGES) & 1);
        attn_step(s0, o, dq, dke, dk + 256, dv, 0u);
        uint32_t dkn = dk;
        if (j + 1 < NBLK) {
            mbar_wait(bar_kfull + 8 * nstage, ((j + 1) / ATT_STAGES) & 1);
            dkn = dk0 + nstage * 1024;
        }
        attn_step(s0, o, dq, dke, dkn, dv + 256 - (256u << 16), bar_empty + 8 * stage);
    }
    bool ok = (o[16] <= 1.8446744e19f) && (o[18] <= 1.8446744e19f);
#pragma unroll
    for (int i = 0; i < 16; i++) ok = ok && (fabsf(o[i]) <= 3.0e38f);
    const int row0 = (tile & 15) * 128 + (threadIdx.x >> 5) * 16 + (lane >> 2);
    const float f0 = g_gate[row0] / o[16], f1 = g_gate[row0 + 8] / o[18];
    bf16* op0 = g_a5 + (size_t)row0 * A5W + head * DH + (lane & 3) * 2;
    bf16* op1 = op0 + 8 * A5W;
#pragma unroll
    for (int i = 0; i < 4; i++) {
        *reinterpret_cast<uint32_t*>(op0 + 8 * i) = pack_bf16(o[4 * i] * f0, o[4 * i + 1] * f0);
        *reinterpret_cast<uint32_t*>(op1 + 8 * i) = pack_bf16(o[4 * i + 2] * f1, o[4 * i + 3] * f1);
    }
    const int bad = __syncthreads_or(!ok);
    if (threadIdx.x == 0) g_bad[tile] = bad;
    TL_END(6)
}

typedef CUresult (*EncodeFn)(CUtensorMap*, CUtensorMapDataType, cuuint32_t, void*, const cuuint64_t*, const cuuint64_t*,
                             const cuuint32_t*, const cuuint32_t*, CUtensorMapInterleave, CUtensorMapSwizzle,
                             CUtensorMapL2promotion, CUtensorMapFloatOOBfill);

static CUtensorMap make_map(EncodeFn fn, const void* ptr, int rows, int cols, int box_cols, int box_rows,
                            CUtensorMapSwizzle swz) {
    CUtensorMap m;
    cuuint64_t dims[2] = {(cuuint64_t)cols, (cuuint64_t)rows};
    cuuint64_t strides[1] = {(cuuint64_t)cols * 2};
    cuuint32_t box[2] = {(cuuint32_t)box_cols, (cuuint32_t)box_rows};
    cuuint32_t es[2] = {1, 1};
    fn(&m, CU_TENSOR_MAP_DATA_TYPE_BFLOAT16, 2, const_cast<void*>(ptr), dims, strides, box, es,
       CU_TENSOR_MAP_INTERLEAVE_NONE, swz, CU_TENSOR_MAP_L2_PROMOTION_L2_256B, CU_TENSOR_MAP_FLOAT_OOB_FILL_NONE);
    return m;
}

template <typename... KArgs, typename... Args>
static void launch_ex(void (*kern)(KArgs...), int grid, int block, int smem, cudaStream_t st, int cluster, int pdl, Args... args) {
    cudaLaunchConfig_t cfg = {};
    cfg.gridDim = dim3(grid);
    cfg.blockDim = dim3(block);
    cfg.dynamicSmemBytes = smem;
    cfg.stream = st;
    cudaLaunchAttribute at[2];
    at[0].id = cudaLaunchAttributeProgrammaticStreamSerialization;
    at[0].val.programmaticStreamSerializationAllowed = pdl;
    at[1].id = cudaLaunchAttributeClusterDimension;
    at[1].val.clusterDim.x = cluster;
    at[1].val.clusterDim.y = 1;
    at[1].val.clusterDim.z = 1;
    cfg.attrs = at;
    cfg.numAttrs = cluster > 1 ? 2 : 1;
    cudaLaunchKernelEx(&cfg, kern, KArgs(args)...);
}

extern "C" void kernel_launch(void* const* d_in, const int* in_sizes, int n_in, void* d_out, int out_size) {
    const bf16* x = (const bf16*)d_in[0];
    const bf16* wqkv = (const bf16*)d_in[1];
    const bf16* wo = (const bf16*)d_in[2];
    const bf16* w1 = (const bf16*)d_in[4];
    const bf16* w2 = (const bf16*)d_in[5];
    const bf16* w3 = (const bf16*)d_in[6];
    const bf16* w4 = (const bf16*)d_in[7];
    const bf16* gate_w = (const bf16*)d_in[8];

    static EncodeFn enc = nullptr;
    static void *p_qkv, *p_h, *p_x1, *p_a5, *p_cs1, *p_cs3;
    static cudaStream_t s2;
    static cudaEvent_t ev_fork, ev_join;
    using G1 = GemmSmem<256, 4>;
    using G2 = GemmSmem<128, 5>;
    using G3 = GemmSmem<224, 4>;
    if (!enc) {
        void* fn = nullptr;
        cudaDriverEntryPointQueryResult qres;
        cudaGetDriverEntryPoint("cuTensorMapEncodeTiled", &fn, cudaEnableDefault, &qres);
        enc = (EncodeFn)fn;
        cudaGetSymbolAddress(&p_qkv, g_qkv);
        cudaGetSymbolAddress(&p_h, g_h);
        cudaGetSymbolAddress(&p_x1, g_x1);
        cudaGetSymbolAddress(&p_a5, g_a5);
        cudaGetSymbolAddress(&p_cs1, g_cs1);
        cudaGetSymbolAddress(&p_cs3, g_cs3);
        cudaFuncSetAttribute(gemm_kernel<1, 256, 4>, cudaFuncAttributeMaxDynamicSharedMemorySize, G1::TOTAL);
        cudaFuncSetAttribute(gemm_kernel<2, 128, 5>, cudaFuncAttributeMaxDynamicSharedMemorySize, G2::TOTAL);
        cudaFuncSetAttribute(gemm_kernel<3, 224, 4>, cudaFuncAttributeMaxDynamicSharedMemorySize, G3::TOTAL);
        cudaFuncSetAttribute(gemm_kernel<5, 128, 5>, cudaFuncAttributeMaxDynamicSharedMemorySize, G2::TOTAL);
        cudaStreamCreateWithFlags(&s2, cudaStreamNonBlocking);
        cudaEventCreateWithFlags(&ev_fork, cudaEventDisableTiming);
        cudaEventCreateWithFlags(&ev_join, cudaEventDisableTiming);
        cudaFuncSetAttribute(attn_kernel, cudaFuncAttributeMaxDynamicSharedMemorySize, ATT_SMEM);
        cudaFuncSetAttribute(attn_exact_kernel, cudaFuncAttributeMaxDynamicSharedMemorySize, ATT_SMEM);
    }
    const CUtensorMapSwizzle SW128 = CU_TENSOR_MAP_SWIZZLE_128B, SW64 = CU_TENSOR_MAP_SWIZZLE_64B;
    CUtensorMap mX = make_map(enc, x, S_LEN, DM, 64, 128, SW128);
    CUtensorMap mXres = make_map(enc, x, S_LEN, DM, 64, 64, SW128);
    CUtensorMap mWqkv = make_map(enc, wqkv, DM, 3 * DM, 64, 64, SW128);
    CUtensorMap mW1 = make_map(enc, w1, DM, DM, 64, 64, SW128);
    CUtensorMap mW2 = make_map(enc, w2, DM, DM, 64, 64, SW128);
    CUtensorMap mW3 = make_map(enc, w3, DM, FF, 64, 64, SW128);
    CUtensorMap mW4 = make_map(enc, w4, FF, DM, 64, 64, SW128);
    CUtensorMap mWo = make_map(enc, wo, DM, DM, 64, 64, SW128);
    CUtensorMap mQKVst = make_map(enc, p_qkv, S_LEN, 3 * DM, 64, 64, SW128);
    CUtensorMap mKV = make_map(enc, p_qkv, S_LEN, 3 * DM, 32, 128, SW64);
    CUtensorMap mHst = make_map(enc, p_h, S_LEN, DM, 64, 64, SW128);
    CUtensorMap mHld = make_map(enc, p_h, S_LEN, DM, 64, 128, SW128);
    CUtensorMap mX1st = make_map(enc, p_x1, S_LEN, DM, 64, 64, SW128);
    CUtensorMap mX1ld = make_map(enc, p_x1, S_LEN, DM, 64, 128, SW128);
    CUtensorMap mA5st = make_map(enc, p_a5, S_LEN, A5W, 64, 64, SW128);
    CUtensorMap mA5st32 = make_map(enc, p_a5, S_LEN, A5W, 32, 64, SW64);
    CUtensorMap mA5ld = make_map(enc, p_a5, S_LEN, A5W, 64, 128, SW128);
    CUtensorMap mOut = make_map(enc, d_out, S_LEN, DM, 64, 64, SW128);

    cudaStream_t st = cudaStreamPerThread;
    prep_kernel<<<256 + 64 + 224, 256, 0, st>>>(x, gate_w, w1, w3);
    launch_ex(gemm_kernel<1, 256, 4>, 132, 384, G1::TOTAL, st, 2, 1, mX, mWqkv, mW1, mQKVst, mHst, x, 16, 16);
    cudaEventRecord(ev_fork, st);
    launch_ex(attn_kernel, ATT_GRID, ATT_THREADS, ATT_SMEM, st, 1, 1, mKV);
    launch_ex(attn_exact_kernel, ATT_NTILES, ATT_THREADS, ATT_SMEM, st, 1, 1, mKV);
    cudaStreamWaitEvent(s2, ev_fork, 0);
    launch_ex(gemm_kernel<2, 128, 5>, 128, 384, G2::TOTAL, s2, 2, 0, mHld, mW2, mW2, mX1st, mXres, x, 8, 16);
    launch_ex(gemm_kernel<3, 224, 4>, 132, 384, G3::TOTAL, s2, 2, 1, mX1ld, mW3, mW3, mA5st, mA5st32, x, 16, 16);
    cudaEventRecord(ev_join, s2);
    cudaStreamWaitEvent(st, ev_join, 0);
    launch_ex(gemm_kernel<5, 128, 5>, 128, 384, G2::TOTAL, st, 2, 0, mA5ld, mWo, mW4, mOut, mX1st, (const bf16*)p_x1, 8, 72);
}
```

```cpp
#include <cuda_runtime.h>
#include <cuda_bf16.h>
#include <cuda.h>
#include <stdint.h>

typedef __nv_bfloat16 bf16;

constexpr int S_LEN = 2048;
constexpr int DM = 1024;
constexpr int FF = 3584;
constexpr int NH = 32;
constexpr int DH = 32;
constexpr int A5W = DM + FF;

__device__ __align__(1024) bf16 g_qkv[S_LEN * 3 * DM];
__device__ __align__(1024) bf16 g_h[S_LEN * DM];
__device__ __align__(1024) bf16 g_x1[S_LEN * DM];
__device__ __align__(1024) bf16 g_a5[S_LEN * A5W];
__device__ __align__(16) float g_mean1[S_LEN];
__device__ __align__(16) float g_rstd1[S_LEN];
__device__ __align__(16) float g_gate[S_LEN];
__device__ __align__(16) float g_omg[S_LEN];
__device__ __align__(16) float g_cs1[4 * DM];
__device__ __align__(16) float g_cs3[4 * FF];
__device__ __align__(16) float2 g_stat2[S_LEN * 8];
__device__ int g_bad[NH * 16];
__device__ int g_tile_ctr;

#define TL_START(k)
#define PH(i)
#define TL_END(k)

__device__ __forceinline__ uint32_t smem_u32(const void* p) { return (uint32_t)__cvta_generic_to_shared(p); }

__device__ __forceinline__ void mbar_init(uint32_t bar, uint32_t count) {
    asm volatile("mbarrier.init.shared::cta.b64 [%0], %1;" ::"r"(bar), "r"(count));
}
__device__ __forceinline__ void mbar_expect_tx(uint32_t bar, uint32_t bytes) {
    asm volatile("mbarrier.arrive.expect_tx.shared::cta.b64 _, [%0], %1;" ::"r"(bar), "r"(bytes) : "memory");
}
__device__ __forceinline__ void mbar_arrive(uint32_t bar) {
    asm volatile("mbarrier.arrive.shared::cta.b64 _, [%0];" ::"r"(bar) : "memory");
}
__device__ __forceinline__ bool mbar_try_wait(uint32_t bar, uint32_t parity) {
    uint32_t ok;
    asm volatile(
        "{\n.reg .pred p;\n"
        "mbarrier.try_wait.parity.shared::cta.b64 p, [%1], %2;\n"
        "selp.u32 %0, 1, 0, p;\n}\n"
        : "=r"(ok)
        : "r"(bar), "r"(parity)
        : "memory");
    return ok != 0;
}
__device__ __forceinline__ void mbar_wait(uint32_t bar, uint32_t parity) {
    uint32_t spins = 0;
    while (!mbar_try_wait(bar, parity)) {
        if (++spins > (1u << 24)) __trap();
    }
}
__device__ __forceinline__ void tma_load_2d(uint32_t dst, const CUtensorMap* map, int c0, int c1, uint32_t bar) {
    asm volatile(
        "cp.async.bulk.tensor.2d.shared::cluster.global.mbarrier::complete_tx::bytes [%0], [%1, {%3, %4}], [%2];"
        ::"r"(dst), "l"(map), "r"(bar), "r"(c0), "r"(c1)
        : "memory");
}
__device__ __forceinline__ void tma_store_2d(const CUtensorMap* map, uint32_t src, int c0, int c1) {
    asm volatile("cp.async.bulk.tensor.2d.global.shared::cta.bulk_group [%0, {%2, %3}], [%1];"
                 ::"l"(map), "r"(src), "r"(c0), "r"(c1)
                 : "memory");
}
__device__ __forceinline__ void tma_load_2d_mc(uint32_t dst, const CUtensorMap* map, int c0, int c1, uint32_t bar, uint16_t mask) {
    asm volatile(
        "cp.async.bulk.tensor.2d.shared::cluster.global.mbarrier::complete_tx::bytes.multicast::cluster [%0], [%1, {%3, %4}], [%2], %5;"
        ::"r"(dst), "l"(map), "r"(bar), "r"(c0), "r"(c1), "h"(mask)
        : "memory");
}
__device__ __forceinline__ void mbar_arrive_cluster(uint32_t bar, uint32_t cta) {
    asm volatile(
        "{\n.reg .b32 ra;\nmapa.shared::cluster.u32 ra, %0, %1;\n"
        "mbarrier.arrive.shared::cluster.b64 _, [ra];\n}\n" ::"r"(bar), "r"(cta)
        : "memory");
}
__device__ __forceinline__ void cluster_sync_all() {
    asm volatile("barrier.cluster.arrive.release.aligned;\nbarrier.cluster.wait.acquire.aligned;" ::: "memory");
}
__device__ __forceinline__ uint32_t cluster_rank() { uint32_t r; asm volatile("mov.u32 %0, %%cluster_ctarank;" : "=r"(r)); return r; }
__device__ __forceinline__ void pdl_wait() { asm volatile("griddepcontrol.wait;" ::: "memory"); }
__device__ __forceinline__ void pdl_launch() { asm volatile("griddepcontrol.launch_dependents;" ::: "memory"); }
__device__ __forceinline__ void bulk_commit() { asm volatile("cp.async.bulk.commit_group;" ::: "memory"); }
__device__ __forceinline__ void bulk_wait_read0() { asm volatile("cp.async.bulk.wait_group.read 0;" ::: "memory"); }
__device__ __forceinline__ void bulk_wait0() { asm volatile("cp.async.bulk.wait_group 0;" ::: "memory"); }
__device__ __forceinline__ void fence_proxy_async() { asm volatile("fence.proxy.async.shared::cta;" ::: "memory"); }
__device__ __forceinline__ void named_bar_sync(int id, int n) { asm volatile("bar.sync %0, %1;" ::"r"(id), "r"(n) : "memory"); }
__device__ __forceinline__ void named_bar_arrive(int id, int n) { asm volatile("bar.arrive %0, %1;" ::"r"(id), "r"(n) : "memory"); }
__device__ __forceinline__ void wgmma_fence() { asm volatile("wgmma.fence.sync.aligned;" ::: "memory"); }
__device__ __forceinline__ void wgmma_commit() { asm volatile("wgmma.commit_group.sync.aligned;" ::: "memory"); }
template <int N>
__device__ __forceinline__ void wgmma_wait() { asm volatile("wgmma.wait_group.sync.aligned %0;" ::"n"(N) : "memory"); }
__device__ __forceinline__ void prefetch_tmap(const CUtensorMap* m) {
    asm volatile("prefetch.tensormap [%0];" ::"l"(m) : "memory");
}
template <int R>
__device__ __forceinline__ void reg_alloc() { asm volatile("setmaxnreg.inc.sync.aligned.u32 %0;" ::"n"(R)); }
template <int R>
__device__ __forceinline__ void reg_dealloc() { asm volatile("setmaxnreg.dec.sync.aligned.u32 %0;" ::"n"(R)); }
__device__ __forceinline__ void stmatrix_x4(uint32_t addr, uint32_t r0, uint32_t r1, uint32_t r2, uint32_t r3) {
    asm volatile("stmatrix.sync.aligned.m8n8.x4.shared.b16 [%0], {%1, %2, %3, %4};"
                 ::"r"(addr), "r"(r0), "r"(r1), "r"(r2), "r"(r3)
                 : "memory");
}
__device__ __forceinline__ uint32_t pack_bf16(float lo, float hi) {
    uint32_t r;
    asm("cvt.rn.bf16x2.f32 %0, %1, %2;" : "=r"(r) : "f"(hi), "f"(lo));
    return r;
}
__device__ __forceinline__ float bf16_round(float v) { return __bfloat162float(__float2bfloat16_rn(v)); }
__device__ __forceinline__ float ex2(float x) {
    float y;
    asm volatile("ex2.approx.ftz.f32 %0, %1;" : "=f"(y) : "f"(x));
    return y;
}
__device__ __forceinline__ float tanh_fast(float x) {
    float y;
    asm("tanh.approx.f32 %0, %1;" : "=f"(y) : "f"(x));
    return y;
}
__device__ __forceinline__ float gelu_tanh(float v) {
    float u = 0.7978845608028654f * (v + 0.044715f * v * v * v);
    float hv = 0.5f * v;
    return fmaf(hv, tanh_fast(u), hv);
}
__device__ __forceinline__ uint32_t desc_lo(uint32_t addr, uint32_t lbo_bytes) {
    return ((addr & 0x3FFFF) >> 4) | (((lbo_bytes >> 4) & 0x3FFF) << 16);
}
__host__ __device__ constexpr uint32_t desc_hi(uint32_t sbo_bytes, uint32_t swz) {
    return ((sbo_bytes >> 4) & 0x3FFF) | (swz << 30);
}

__device__ __forceinline__ void wgmma_ss_n128_tb1(float (&d)[64], uint32_t alo, uint32_t ahi, uint32_t blo, uint32_t bhi, int scale_d) {
    asm volatile("{\n.reg .pred p;\n.reg .b64 da, db;\nsetp.ne.b32 p, %68, 0;\nmov.b64 da, {%64, %65};\nmov.b64 db, {%66, %67};\n"
        "wgmma.mma_async.sync.aligned.m64n128k16.f32.bf16.bf16 {%0, %1, %2, %3, %4, %5, %6, %7, %8, %9, %10, %11, %12, %13, %14, %15, %16, %17, %18, %19, %20, %21, %22, %23, %24, %25, %26, %27, %28, %29, %30, %31, %32, %33, %34, %35, %36, %37, %38, %39, %40, %41, %42, %43, %44, %45, %46, %47, %48, %49, %50, %51, %52, %53, %54, %55, %56, %57, %58, %59, %60, %61, %62, %63}, da, db, p, 1, 1, 0, 1;\n}\n"
        : "+f"(d[0]), "+f"(d[1]), "+f"(d[2]), "+f"(d[3]), "+f"(d[4]), "+f"(d[5]), "+f"(d[6]), "+f"(d[7]), "+f"(d[8]), "+f"(d[9]), "+f"(d[10]), "+f"(d[11]), "+f"(d[12]), "+f"(d[13]), "+f"(d[14]), "+f"(d[15]), "+f"(d[16]), "+f"(d[17]), "+f"(d[18]), "+f"(d[19]), "+f"(d[20]), "+f"(d[21]), "+f"(d[22]), "+f"(d[23]), "+f"(d[24]), "+f"(d[25]), "+f"(d[26]), "+f"(d[27]), "+f"(d[28]), "+f"(d[29]), "+f"(d[30]), "+f"(d[31]), "+f"(d[32]), "+f"(d[33]), "+f"(d[34]), "+f"(d[35]), "+f"(d[36]), "+f"(d[37]), "+f"(d[38]), "+f"(d[39]), "+f"(d[40]), "+f"(d[41]), "+f"(d[42]), "+f"(d[43]), "+f"(d[44]), "+f"(d[45]), "+f"(d[46]), "+f"(d[47]), "+f"(d[48]), "+f"(d[49]), "+f"(d[50]), "+f"(d[51]), "+f"(d[52]), "+f"(d[53]), "+f"(d[54]), "+f"(d[55]), "+f"(d[56]), "+f"(d[57]), "+f"(d[58]), "+f"(d[59]), "+f"(d[60]), "+f"(d[61]), "+f"(d[62]), "+f"(d[63])
        : "r"(alo), "r"(ahi), "r"(blo), "r"(bhi), "r"(scale_d));
}

__device__ __forceinline__ void wgmma_ss_n192_tb1(float (&d)[96], uint32_t alo, uint32_t ahi, uint32_t blo, uint32_t bhi, int scale_d) {
    asm volatile("{\n.reg .pred p;\n.reg .b64 da, db;\nsetp.ne.b32 p, %100, 0;\nmov.b64 da, {%96, %97};\nmov.b64 db, {%98, %99};\n"
        "wgmma.mma_async.sync.aligned.m64n192k16.f32.bf16.bf16 {%0, %1, %2, %3, %4, %5, %6, %7, %8, %9, %10, %11, %12, %13, %14, %15, %16, %17, %18, %19, %20, %21, %22, %23, %24, %25, %26, %27, %28, %29, %30, %31, %32, %33, %34, %35, %36, %37, %38, %39, %40, %41, %42, %43, %44, %45, %46, %47, %48, %49, %50, %51, %52, %53, %54, %55, %56, %57, %58, %59, %60, %61, %62, %63, %64, %65, %66, %67, %68, %69, %70, %71, %72, %73, %74, %75, %76, %77, %78, %79, %80, %81, %82, %83, %84, %85, %86, %87, %88, %89, %90, %91, %92, %93, %94, %95}, da, db, p, 1, 1, 0, 1;\n}\n"
        : "+f"(d[0]), "+f"(d[1]), "+f"(d[2]), "+f"(d[3]), "+f"(d[4]), "+f"(d[5]), "+f"(d[6]), "+f"(d[7]), "+f"(d[8]), "+f"(d[9]), "+f"(d[10]), "+f"(d[11]), "+f"(d[12]), "+f"(d[13]), "+f"(d[14]), "+f"(d[15]), "+f"(d[16]), "+f"(d[17]), "+f"(d[18]), "+f"(d[19]), "+f"(d[20]), "+f"(d[21]), "+f"(d[22]), "+f"(d[23]), "+f"(d[24]), "+f"(d[25]), "+f"(d[26]), "+f"(d[27]), "+f"(d[28]), "+f"(d[29]), "+f"(d[30]), "+f"(d[31]), "+f"(d[32]), "+f"(d[33]), "+f"(d[34]), "+f"(d[35]), "+f"(d[36]), "+f"(d[37]), "+f"(d[38]), "+f"(d[39]), "+f"(d[40]), "+f"(d[41]), "+f"(d[42]), "+f"(d[43]), "+f"(d[44]), "+f"(d[45]), "+f"(d[46]), "+f"(d[47]), "+f"(d[48]), "+f"(d[49]), "+f"(d[50]), "+f"(d[51]), "+f"(d[52]), "+f"(d[53]), "+f"(d[54]), "+f"(d[55]), "+f"(d[56]), "+f"(d[57]), "+f"(d[58]), "+f"(d[59]), "+f"(d[60]), "+f"(d[61]), "+f"(d[62]), "+f"(d[63]), "+f"(d[64]), "+f"(d[65]), "+f"(d[66]), "+f"(d[67]), "+f"(d[68]), "+f"(d[69]), "+f"(d[70]), "+f"(d[71]), "+f"(d[72]), "+f"(d[73]), "+f"(d[74]), "+f"(d[75]), "+f"(d[76]), "+f"(d[77]), "+f"(d[78]), "+f"(d[79]), "+f"(d[80]), "+f"(d[81]), "+f"(d[82]), "+f"(d[83]), "+f"(d[84]), "+f"(d[85]), "+f"(d[86]), "+f"(d[87]), "+f"(d[88]), "+f"(d[89]), "+f"(d[90]), "+f"(d[91]), "+f"(d[92]), "+f"(d[93]), "+f"(d[94]), "+f"(d[95])
        : "r"(alo), "r"(ahi), "r"(blo), "r"(bhi), "r"(scale_d));
}

__device__ __forceinline__ void wgmma_ss_n224_tb1(float (&d)[112], uint32_t alo, uint32_t ahi, uint32_t blo, uint32_t bhi, int scale_d) {
    asm volatile("{\n.reg .pred p;\n.reg .b64 da, db;\nsetp.ne.b32 p, %116, 0;\nmov.b64 da, {%112, %113};\nmov.b64 db, {%114, %115};\n"
        "wgmma.mma_async.sync.aligned.m64n224k16.f32.bf16.bf16 {%0, %1, %2, %3, %4, %5, %6, %7, %8, %9, %10, %11, %12, %13, %14, %15, %16, %17, %18, %19, %20, %21, %22, %23, %24, %25, %26, %27, %28, %29, %30, %31, %32, %33, %34, %35, %36, %37, %38, %39, %40, %41, %42, %43, %44, %45, %46, %47, %48, %49, %50, %51, %52, %53, %54, %55, %56, %57, %58, %59, %60, %61, %62, %63, %64, %65, %66, %67, %68, %69, %70, %71, %72, %73, %74, %75, %76, %77, %78, %79, %80, %81, %82, %83, %84, %85, %86, %87, %88, %89, %90, %91, %92, %93, %94, %95, %96, %97, %98, %99, %100, %101, %102, %103, %104, %105, %106, %107, %108, %109, %110, %111}, da, db, p, 1, 1, 0, 1;\n}\n"
        : "+f"(d[0]), "+f"(d[1]), "+f"(d[2]), "+f"(d[3]), "+f"(d[4]), "+f"(d[5]), "+f"(d[6]), "+f"(d[7]), "+f"(d[8]), "+f"(d[9]), "+f"(d[10]), "+f"(d[11]), "+f"(d[12]), "+f"(d[13]), "+f"(d[14]), "+f"(d[15]), "+f"(d[16]), "+f"(d[17]), "+f"(d[18]), "+f"(d[19]), "+f"(d[20]), "+f"(d[21]), "+f"(d[22]), "+f"(d[23]), "+f"(d[24]), "+f"(d[25]), "+f"(d[26]), "+f"(d[27]), "+f"(d[28]), "+f"(d[29]), "+f"(d[30]), "+f"(d[31]), "+f"(d[32]), "+f"(d[33]), "+f"(d[34]), "+f"(d[35]), "+f"(d[36]), "+f"(d[37]), "+f"(d[38]), "+f"(d[39]), "+f"(d[40]), "+f"(d[41]), "+f"(d[42]), "+f"(d[43]), "+f"(d[44]), "+f"(d[45]), "+f"(d[46]), "+f"(d[47]), "+f"(d[48]), "+f"(d[49]), "+f"(d[50]), "+f"(d[51]), "+f"(d[52]), "+f"(d[53]), "+f"(d[54]), "+f"(d[55]), "+f"(d[56]), "+f"(d[57]), "+f"(d[58]), "+f"(d[59]), "+f"(d[60]), "+f"(d[61]), "+f"(d[62]), "+f"(d[63]), "+f"(d[64]), "+f"(d[65]), "+f"(d[66]), "+f"(d[67]), "+f"(d[68]), "+f"(d[69]), "+f"(d[70]), "+f"(d[71]), "+f"(d[72]), "+f"(d[73]), "+f"(d[74]), "+f"(d[75]), "+f"(d[76]), "+f"(d[77]), "+f"(d[78]), "+f"(d[79]), "+f"(d[80]), "+f"(d[81]), "+f"(d[82]), "+f"(d[83]), "+f"(d[84]), "+f"(d[85]), "+f"(d[86]), "+f"(d[87]), "+f"(d[88]), "+f"(d[89]), "+f"(d[90]), "+f"(d[91]), "+f"(d[92]), "+f"(d[93]), "+f"(d[94]), "+f"(d[95]), "+f"(d[96]), "+f"(d[97]), "+f"(d[98]), "+f"(d[99]), "+f"(d[100]), "+f"(d[101]), "+f"(d[102]), "+f"(d[103]), "+f"(d[104]), "+f"(d[105]), "+f"(d[106]), "+f"(d[107]), "+f"(d[108]), "+f"(d[109]), "+f"(d[110]), "+f"(d[111])
        : "r"(alo), "r"(ahi), "r"(blo), "r"(bhi), "r"(scale_d));
}

__device__ __forceinline__ void wgmma_ss_n256_tb1(float (&d)[128], uint32_t alo, uint32_t ahi, uint32_t blo, uint32_t bhi, int scale_d) {
    asm volatile("{\n.reg .pred p;\n.reg .b64 da, db;\nsetp.ne.b32 p, %132, 0;\nmov.b64 da, {%128, %129};\nmov.b64 db, {%130, %131};\n"
        "wgmma.mma_async.sync.aligned.m64n256k16.f32.bf16.bf16 {%0, %1, %2, %3, %4, %5, %6, %7, %8, %9, %10, %11, %12, %13, %14, %15, %16, %17, %18, %19, %20, %21, %22, %23, %24, %25, %26, %27, %28, %29, %30, %31, %32, %33, %34, %35, %36, %37, %38, %39, %40, %41, %42, %43, %44, %45, %46, %47, %48, %49, %50, %51, %52, %53, %54, %55, %56, %57, %58, %59, %60, %61, %62, %63, %64, %65, %66, %67, %68, %69, %70, %71, %72, %73, %74, %75, %76, %77, %78, %79, %80, %81, %82, %83, %84, %85, %86, %87, %88, %89, %90, %91, %92, %93, %94, %95, %96, %97, %98, %99, %100, %101, %102, %103, %104, %105, %106, %107, %108, %109, %110, %111, %112, %113, %114, %115, %116, %117, %118, %119, %120, %121, %122, %123, %124, %125, %126, %127}, da, db, p, 1, 1, 0, 1;\n}\n"
        : "+f"(d[0]), "+f"(d[1]), "+f"(d[2]), "+f"(d[3]), "+f"(d[4]), "+f"(d[5]), "+f"(d[6]), "+f"(d[7]), "+f"(d[8]), "+f"(d[9]), "+f"(d[10]), "+f"(d[11]), "+f"(d[12]), "+f"(d[13]), "+f"(d[14]), "+f"(d[15]), "+f"(d[16]), "+f"(d[17]), "+f"(d[18]), "+f"(d[19]), "+f"(d[20]), "+f"(d[21]), "+f"(d[22]), "+f"(d[23]), "+f"(d[24]), "+f"(d[25]), "+f"(d[26]), "+f"(d[27]), "+f"(d[28]), "+f"(d[29]), "+f"(d[30]), "+f"(d[31]), "+f"(d[32]), "+f"(d[33]), "+f"(d[34]), "+f"(d[35]), "+f"(d[36]), "+f"(d[37]), "+f"(d[38]), "+f"(d[39]), "+f"(d[40]), "+f"(d[41]), "+f"(d[42]), "+f"(d[43]), "+f"(d[44]), "+f"(d[45]), "+f"(d[46]), "+f"(d[47]), "+f"(d[48]), "+f"(d[49]), "+f"(d[50]), "+f"(d[51]), "+f"(d[52]), "+f"(d[53]), "+f"(d[54]), "+f"(d[55]), "+f"(d[56]), "+f"(d[57]), "+f"(d[58]), "+f"(d[59]), "+f"(d[60]), "+f"(d[61]), "+f"(d[62]), "+f"(d[63]), "+f"(d[64]), "+f"(d[65]), "+f"(d[66]), "+f"(d[67]), "+f"(d[68]), "+f"(d[69]), "+f"(d[70]), "+f"(d[71]), "+f"(d[72]), "+f"(d[73]), "+f"(d[74]), "+f"(d[75]), "+f"(d[76]), "+f"(d[77]), "+f"(d[78]), "+f"(d[79]), "+f"(d[80]), "+f"(d[81]), "+f"(d[82]), "+f"(d[83]), "+f"(d[84]), "+f"(d[85]), "+f"(d[86]), "+f"(d[87]), "+f"(d[88]), "+f"(d[89]), "+f"(d[90]), "+f"(d[91]), "+f"(d[92]), "+f"(d[93]), "+f"(d[94]), "+f"(d[95]), "+f"(d[96]), "+f"(d[97]), "+f"(d[98]), "+f"(d[99]), "+f"(d[100]), "+f"(d[101]), "+f"(d[102]), "+f"(d[103]), "+f"(d[104]), "+f"(d[105]), "+f"(d[106]), "+f"(d[107]), "+f"(d[108]), "+f"(d[109]), "+f"(d[110]), "+f"(d[111]), "+f"(d[112]), "+f"(d[113]), "+f"(d[114]), "+f"(d[115]), "+f"(d[116]), "+f"(d[117]), "+f"(d[118]), "+f"(d[119]), "+f"(d[120]), "+f"(d[121]), "+f"(d[122]), "+f"(d[123]), "+f"(d[124]), "+f"(d[125]), "+f"(d[126]), "+f"(d[127])
        : "r"(alo), "r"(ahi), "r"(blo), "r"(bhi), "r"(scale_d));
}

__device__ __forceinline__ void wgmma_ss_n64_tb0(float (&d)[32], uint32_t alo, uint32_t ahi, uint32_t blo, uint32_t bhi, int scale_d) {
    asm volatile("{\n.reg .pred p;\n.reg .b64 da, db;\nsetp.ne.b32 p, %36, 0;\nmov.b64 da, {%32, %33};\nmov.b64 db, {%34, %35};\n"
        "wgmma.mma_async.sync.aligned.m64n64k16.f32.bf16.bf16 {%0, %1, %2, %3, %4, %5, %6, %7, %8, %9, %10, %11, %12, %13, %14, %15, %16, %17, %18, %19, %20, %21, %22, %23, %24, %25, %26, %27, %28, %29, %30, %31}, da, db, p, 1, 1, 0, 0;\n}\n"
        : "+f"(d[0]), "+f"(d[1]), "+f"(d[2]), "+f"(d[3]), "+f"(d[4]), "+f"(d[5]), "+f"(d[6]), "+f"(d[7]), "+f"(d[8]), "+f"(d[9]), "+f"(d[10]), "+f"(d[11]), "+f"(d[12]), "+f"(d[13]), "+f"(d[14]), "+f"(d[15]), "+f"(d[16]), "+f"(d[17]), "+f"(d[18]), "+f"(d[19]), "+f"(d[20]), "+f"(d[21]), "+f"(d[22]), "+f"(d[23]), "+f"(d[24]), "+f"(d[25]), "+f"(d[26]), "+f"(d[27]), "+f"(d[28]), "+f"(d[29]), "+f"(d[30]), "+f"(d[31])
        : "r"(alo), "r"(ahi), "r"(blo), "r"(bhi), "r"(scale_d));
}

__device__ __forceinline__ void wgmma_rs_n128_tb0(float (&d)[64], uint32_t a0, uint32_t a1, uint32_t a2, uint32_t a3, uint32_t blo, uint32_t bhi, int scale_d) {
    asm volatile("{\n.reg .pred p;\n.reg .b64 db;\nsetp.ne.b32 p, %70, 0;\nmov.b64 db, {%68, %69};\n"
        "wgmma.mma_async.sync.aligned.m64n128k16.f32.bf16.bf16 {%0, %1, %2, %3, %4, %5, %6, %7, %8, %9, %10, %11, %12, %13, %14, %15, %16, %17, %18, %19, %20, %21, %22, %23, %24, %25, %26, %27, %28, %29, %30, %31, %32, %33, %34, %35, %36, %37, %38, %39, %40, %41, %42, %43, %44, %45, %46, %47, %48, %49, %50, %51, %52, %53, %54, %55, %56, %57, %58, %59, %60, %61, %62, %63}, {%64, %65, %66, %67}, db, p, 1, 1, 0;\n}\n"
        : "+f"(d[0]), "+f"(d[1]), "+f"(d[2]), "+f"(d[3]), "+f"(d[4]), "+f"(d[5]), "+f"(d[6]), "+f"(d[7]), "+f"(d[8]), "+f"(d[9]), "+f"(d[10]), "+f"(d[11]), "+f"(d[12]), "+f"(d[13]), "+f"(d[14]), "+f"(d[15]), "+f"(d[16]), "+f"(d[17]), "+f"(d[18]), "+f"(d[19]), "+f"(d[20]), "+f"(d[21]), "+f"(d[22]), "+f"(d[23]), "+f"(d[24]), "+f"(d[25]), "+f"(d[26]), "+f"(d[27]), "+f"(d[28]), "+f"(d[29]), "+f"(d[30]), "+f"(d[31]), "+f"(d[32]), "+f"(d[33]), "+f"(d[34]), "+f"(d[35]), "+f"(d[36]), "+f"(d[37]), "+f"(d[38]), "+f"(d[39]), "+f"(d[40]), "+f"(d[41]), "+f"(d[42]), "+f"(d[43]), "+f"(d[44]), "+f"(d[45]), "+f"(d[46]), "+f"(d[47]), "+f"(d[48]), "+f"(d[49]), "+f"(d[50]), "+f"(d[51]), "+f"(d[52]), "+f"(d[53]), "+f"(d[54]), "+f"(d[55]), "+f"(d[56]), "+f"(d[57]), "+f"(d[58]), "+f"(d[59]), "+f"(d[60]), "+f"(d[61]), "+f"(d[62]), "+f"(d[63])
        : "r"(a0), "r"(a1), "r"(a2), "r"(a3), "r"(blo), "r"(bhi), "r"(scale_d));
}

__device__ __forceinline__ void wgmma_rs_n64_tb0(float (&d)[32], uint32_t a0, uint32_t a1, uint32_t a2, uint32_t a3, uint32_t blo, uint32_t bhi, int scale_d) {
    asm volatile("{\n.reg .pred p;\n.reg .b64 db;\nsetp.ne.b32 p, %38, 0;\nmov.b64 db, {%36, %37};\n"
        "wgmma.mma_async.sync.aligned.m64n64k16.f32.bf16.bf16 {%0, %1, %2, %3, %4, %5, %6, %7, %8, %9, %10, %11, %12, %13, %14, %15, %16, %17, %18, %19, %20, %21, %22, %23, %24, %25, %26, %27, %28, %29, %30, %31}, {%32, %33, %34, %35}, db, p, 1, 1, 0;\n}\n"
        : "+f"(d[0]), "+f"(d[1]), "+f"(d[2]), "+f"(d[3]), "+f"(d[4]), "+f"(d[5]), "+f"(d[6]), "+f"(d[7]), "+f"(d[8]), "+f"(d[9]), "+f"(d[10]), "+f"(d[11]), "+f"(d[12]), "+f"(d[13]), "+f"(d[14]), "+f"(d[15]), "+f"(d[16]), "+f"(d[17]), "+f"(d[18]), "+f"(d[19]), "+f"(d[20]), "+f"(d[21]), "+f"(d[22]), "+f"(d[23]), "+f"(d[24]), "+f"(d[25]), "+f"(d[26]), "+f"(d[27]), "+f"(d[28]), "+f"(d[29]), "+f"(d[30]), "+f"(d[31])
        : "r"(a0), "r"(a1), "r"(a2), "r"(a3), "r"(blo), "r"(bhi), "r"(scale_d));
}

__device__ __forceinline__ void wgmma_rs_n32_tb1(float (&d)[16], uint32_t a0, uint32_t a1, uint32_t a2, uint32_t a3, uint32_t blo, uint32_t bhi, int scale_d) {
    asm volatile("{\n.reg .pred p;\n.reg .b64 db;\nsetp.ne.b32 p, %22, 0;\nmov.b64 db, {%20, %21};\n"
        "wgmma.mma_async.sync.aligned.m64n32k16.f32.bf16.bf16 {%0, %1, %2, %3, %4, %5, %6, %7, %8, %9, %10, %11, %12, %13, %14, %15}, {%16, %17, %18, %19}, db, p, 1, 1, 1;\n}\n"
        : "+f"(d[0]), "+f"(d[1]), "+f"(d[2]), "+f"(d[3]), "+f"(d[4]), "+f"(d[5]), "+f"(d[6]), "+f"(d[7]), "+f"(d[8]), "+f"(d[9]), "+f"(d[10]), "+f"(d[11]), "+f"(d[12]), "+f"(d[13]), "+f"(d[14]), "+f"(d[15])
        : "r"(a0), "r"(a1), "r"(a2), "r"(a3), "r"(blo), "r"(bhi), "r"(scale_d));
}

__device__ __forceinline__ void wgmma_rs_n40_tb1(float (&d)[20], uint32_t a0, uint32_t a1, uint32_t a2, uint32_t a3, uint32_t blo, uint32_t bhi, int scale_d) {
    asm volatile("{\n.reg .pred p;\n.reg .b64 db;\nsetp.ne.b32 p, %26, 0;\nmov.b64 db, {%24, %25};\n"
        "wgmma.mma_async.sync.aligned.m64n40k16.f32.bf16.bf16 {%0, %1, %2, %3, %4, %5, %6, %7, %8, %9, %10, %11, %12, %13, %14, %15, %16, %17, %18, %19}, {%20, %21, %22, %23}, db, p, 1, 1, 1;\n}\n"
        : "+f"(d[0]), "+f"(d[1]), "+f"(d[2]), "+f"(d[3]), "+f"(d[4]), "+f"(d[5]), "+f"(d[6]), "+f"(d[7]), "+f"(d[8]), "+f"(d[9]), "+f"(d[10]), "+f"(d[11]), "+f"(d[12]), "+f"(d[13]), "+f"(d[14]), "+f"(d[15]), "+f"(d[16]), "+f"(d[17]), "+f"(d[18]), "+f"(d[19])
        : "r"(a0), "r"(a1), "r"(a2), "r"(a3), "r"(blo), "r"(bhi), "r"(scale_d));
}

template <int BN>
__device__ __forceinline__ void wgmma_tile(float (&d)[BN / 2], uint32_t da, uint32_t db, int sd) {
    constexpr uint32_t HI = desc_hi(1024, 1);
    if constexpr (BN == 128) wgmma_ss_n128_tb1(d, da, HI, db, HI, sd);
    else if constexpr (BN == 192) wgmma_ss_n192_tb1(d, da, HI, db, HI, sd);
    else if constexpr (BN == 224) wgmma_ss_n224_tb1(d, da, HI, db, HI, sd);
    else wgmma_ss_n256_tb1(d, da, HI, db, HI, sd);
}

__global__ void __launch_bounds__(256) prep_kernel(const bf16* __restrict__ x, const bf16* __restrict__ gate_w,
                                                   const bf16* __restrict__ w1, const bf16* __restrict__ w3) {
    constexpr int row_blocks = 256;
    if (blockIdx.x == 0 && threadIdx.x == 0) g_tile_ctr = 0;
    const int tid = threadIdx.x;
    TL_START(0)
    pdl_launch();
    if ((int)blockIdx.x < row_blocks) {
        const int row = blockIdx.x * 8 + (tid >> 5);
        const int lane = tid & 31;
        const uint4* xr = reinterpret_cast<const uint4*>(x + (size_t)row * DM);
        const uint4* gw = reinterpret_cast<const uint4*>(gate_w);
        float v[32];
        float gsum = 0.f, sum = 0.f;
#pragma unroll
        for (int i = 0; i < 4; i++) {
            uint4 a = xr[lane + 32 * i];
            uint4 b = gw[lane + 32 * i];
            const uint32_t aa[4] = {a.x, a.y, a.z, a.w};
            const uint32_t bb[4] = {b.x, b.y, b.z, b.w};
#pragma unroll
            for (int j = 0; j < 4; j++) {
                float x0 = __uint_as_float(aa[j] << 16), x1 = __uint_as_float(aa[j] & 0xFFFF0000u);
                float g0 = __uint_as_float(bb[j] << 16), g1 = __uint_as_float(bb[j] & 0xFFFF0000u);
                v[i * 8 + j * 2] = x0;
                v[i * 8 + j * 2 + 1] = x1;
                sum += x0 + x1;
                gsum += bf16_round(x0 * g0) + bf16_round(x1 * g1);
            }
        }
#pragma unroll
        for (int o = 16; o > 0; o >>= 1) {
            sum += __shfl_xor_sync(0xffffffffu, sum, o);
            gsum += __shfl_xor_sync(0xffffffffu, gsum, o);
        }
        const float mean = sum * (1.0f / DM);
        float m2 = 0.f;
#pragma unroll
        for (int i = 0; i < 32; i++) {
            float d = v[i] - mean;
            m2 += d * d;
        }
#pragma unroll
        for (int o = 16; o > 0; o >>= 1) m2 += __shfl_xor_sync(0xffffffffu, m2, o);
        if (lane == 0) {
            g_mean1[row] = mean;
            g_rstd1[row] = rsqrtf(m2 * (1.0f / DM) + 1e-5f);
            float logit = bf16_round(gsum);
            float g = bf16_round(1.0f / (1.0f + __expf(-logit)));
            g_gate[row] = g;
            g_omg[row] = bf16_round(1.0f - g);
        }
    } else {
        __shared__ float red[32][65];
        int blk = blockIdx.x - row_blocks;
        const bf16* w = w1;
        int ld = DM;
        float* cs_out = g_cs1;
        if (blk >= 64) { blk -= 64; w = w3; ld = FF; cs_out = g_cs3; }
        const int chunk = blk & 3;
        const int col0 = (blk >> 2) * 64;
        const int cg = tid & 7;
        const int rg = tid >> 3;
        uint4 a[8];
#pragma unroll
        for (int r = 0; r < 8; r++)
            a[r] = *reinterpret_cast<const uint4*>(w + (size_t)(chunk * 256 + r * 32 + rg) * ld + col0 + cg * 8);
        float acc[8];
#pragma unroll
        for (int j = 0; j < 8; j++) acc[j] = 0.f;
#pragma unroll
        for (int r = 0; r < 8; r++) {
            const uint32_t aa[4] = {a[r].x, a[r].y, a[r].z, a[r].w};
#pragma unroll
            for (int j = 0; j < 4; j++) {
                acc[2 * j] += __uint_as_float(aa[j] << 16);
                acc[2 * j + 1] += __uint_as_float(aa[j] & 0xFFFF0000u);
            }
        }
#pragma unroll
        for (int j = 0; j < 8; j++) red[rg][cg * 8 + j] = acc[j];
        __syncthreads();
        if (tid < 64) {
            float s = 0.f;
#pragma unroll
            for (int r = 0; r < 32; r++) s += red[r][tid];
            cs_out[chunk * ld + col0 + tid] = s;
        }
    }
    TL_END(0)
}

#define RELEASE_STAGE(b) if (tid_wg == 0) mbar_arrive(b)
template <int BN, int STAGES>
struct GemmSmem {
    static constexpr int A_BYTES = 128 * 64 * 2;
    static constexpr int B_BOXES = (BN + 63) / 64;
    static constexpr int B_BYTES = B_BOXES * 64 * 64 * 2;
    static constexpr int STAGE_BYTES = A_BYTES + B_BYTES;
    static constexpr int STG_OFF = STAGES * STAGE_BYTES;
    static constexpr int CS_OFF = STAGES * STAGE_BYTES + 2 * 16384;
    static constexpr int BAR_OFF = CS_OFF + 1024;
    static constexpr int TOTAL = BAR_OFF + 192 + 512;
};

template <int MODE, int BN, int STAGES>
__global__ void __launch_bounds__(384, 1)
gemm_kernel(const __grid_constant__ CUtensorMap mA, const __grid_constant__ CUtensorMap mB0,
            const __grid_constant__ CUtensorMap mB1, const __grid_constant__ CUtensorMap mC0,
            const __grid_constant__ CUtensorMap mC1, const bf16* __restrict__ xin, int n_tiles_n, int kblocks) {
    using L = GemmSmem<BN, STAGES>;
    extern __shared__ uint8_t smem_raw[];
    const uint32_t sbase = (smem_u32(smem_raw) + 1023u) & ~1023u;
    const uint32_t bar_full = sbase + L::BAR_OFF;
    const uint32_t bar_empty = bar_full + 8 * STAGES;
    const uint32_t bar_res = bar_empty + 8 * STAGES;
    const int wg = threadIdx.x >> 7;
    const int ntiles = 16 * n_tiles_n;
    constexpr bool DYN = (MODE == 3);
    const uint32_t bar_tfull = bar_res + 8;
    const uint32_t bar_tempty = bar_tfull + 16;
    const uint32_t tile_slot = bar_tempty + 16;
    TL_START(MODE)
    pdl_launch();

    if (threadIdx.x == 0) {
        for (int s = 0; s < STAGES; s++) {
            mbar_init(bar_full + 8 * s, 1);
            mbar_init(bar_empty + 8 * s, 2);
        }
        for (int s = 0; s < 2; s++) {
            mbar_init(bar_tfull + 8 * s, 1);
            mbar_init(bar_tempty + 8 * s, 2);
        }
        mbar_init(bar_res, 1);
        asm volatile("fence.mbarrier_init.release.cluster;" ::: "memory");
        prefetch_tmap(&mA);
        prefetch_tmap(&mB0);
        if (MODE == 1 || MODE == 5) prefetch_tmap(&mB1);
        if (MODE == 2 || MODE == 5) prefetch_tmap(&mC1);
        prefetch_tmap(&mC0);
    }
    __syncthreads();

    if (wg == 0) {
        reg_dealloc<40>();
        if (threadIdx.x == 0) {
            if (MODE != 1) pdl_wait();
            int stage = 0;
            uint32_t phase = 1;
            for (int it = 0;; it++) {
                int tile;
                if (DYN) {
                    tile = atomicAdd(&g_tile_ctr, 1);
                    mbar_wait(bar_tempty + 8 * (it & 1), ((it >> 1) & 1) ^ 1);
                    asm volatile("st.shared.b32 [%0], %1;" ::"r"(tile_slot + 4 * (it & 1)), "r"(tile) : "memory");
                    mbar_arrive(bar_tfull + 8 * (it & 1));
                } else {
                    tile = blockIdx.x + it * gridDim.x;
                }
                if (tile >= ntiles) break;
                const int m0 = (tile & 15) * 128;
                const int n0 = (tile >> 4) * BN;
                for (int kb = 0; kb < kblocks; kb++) {
                    mbar_wait(bar_empty + 8 * stage, phase);
                    const uint32_t sa = sbase + stage * L::STAGE_BYTES;
                    const uint32_t sb = sa + L::A_BYTES;
                    const uint32_t fb = bar_full + 8 * stage;
                    mbar_expect_tx(fb, L::STAGE_BYTES);
                    int arow = m0;
                    if (MODE == 2) {
                        const int grp = kb >> 2;
                        arow += (grp == 0) ? -1 : (grp == 1) ? 1 : (grp == 2) ? -2 : 2;
                    }
                    tma_load_2d(sa, &mA, kb * 64, arow, fb);
                    const CUtensorMap* mb = &mB0;
                    int bc = n0, br = kb * 64;
                    if (MODE == 1 && n0 >= 3 * DM) { mb = &mB1; bc = n0 - 3 * DM; }
                    if (MODE == 5 && kb >= 16) { mb = &mB1; br = (kb - 16) * 64; }
#pragma unroll
                    for (int b = 0; b < L::B_BOXES; b++) tma_load_2d(sb + b * 8192, mb, bc + b * 64, br, fb);
                    if ((MODE == 2 || MODE == 5) && kb == STAGES - 1) {
                        mbar_expect_tx(bar_res, 32768);
#pragma unroll
                        for (int q = 0; q < 4; q++)
                            tma_load_2d(sbase + L::STG_OFF + q * 8192, &mC1, n0 + (q & 1) * 64, m0 + (q >> 1) * 64, bar_res);
                    }
                    if (++stage == STAGES) { stage = 0; phase ^= 1; }
                }
            }
        }
    } else {
        reg_alloc<232>();
        const int c = wg - 1;
        const int warp = (threadIdx.x >> 5) & 3;
        const int lane = threadIdx.x & 31;
        const int tid_wg = threadIdx.x & 127;
        const uint32_t stg = sbase + L::STG_OFF + c * 16384;
        int stage = 0;
        uint32_t phase = 0;
        float acc[BN / 2];
        bool first = true;
        PH(0)
        if (MODE != 1) pdl_wait();
        for (int it = 0;; it++) {
            int tile;
            if (DYN) {
                mbar_wait(bar_tfull + 8 * (it & 1), (it >> 1) & 1);
                asm volatile("ld.shared.b32 %0, [%1];" : "=r"(tile) : "r"(tile_slot + 4 * (it & 1)) : "memory");
                named_bar_sync(1 + c, 128);
                if (tid_wg == 0) mbar_arrive(bar_tempty + 8 * (it & 1));
            } else {
                tile = blockIdx.x + it * gridDim.x;
            }
            if (tile >= ntiles) break;
            const int m0 = (tile & 15) * 128;
            const int n0 = (tile >> 4) * BN;
            const int r0 = m0 + c * 64 + warp * 16 + (lane >> 2);
            const int r1 = r0 + 8;
            float mu[2], rs[2], og[2];
            if (MODE == 3) {
                const int t = threadIdx.x - 128;
                if (t < BN) {
                    const float v = (g_cs3[n0 + t] + g_cs3[FF + n0 + t]) + (g_cs3[2 * FF + n0 + t] + g_cs3[3 * FF + n0 + t]);
                    asm volatile("st.shared.f32 [%0], %1;" ::"r"(sbase + L::CS_OFF + t * 4), "f"(v) : "memory");
                }
#pragma unroll
                for (int h = 0; h < 2; h++) {
                    const float4* sp = reinterpret_cast<const float4*>(&g_stat2[(h ? r1 : r0) * 8]);
                    float4 p[4];
                    float s = 0.f;
#pragma unroll
                    for (int i = 0; i < 4; i++) { p[i] = sp[i]; s += p[i].x + p[i].z; }
                    const float mean = s * (1.0f / DM);
                    float m2 = 0.f;
#pragma unroll
                    for (int i = 0; i < 4; i++) {
                        float d0 = p[i].x * (1.0f / 128) - mean, d1 = p[i].z * (1.0f / 128) - mean;
                        m2 += p[i].y + p[i].w + 128.0f * (d0 * d0 + d1 * d1);
                    }
                    mu[h] = mean;
                    rs[h] = rsqrtf(m2 * (1.0f / DM) + 1e-5f);
                }
            }
            if (MODE == 3 || MODE == 5) { og[0] = g_omg[r0]; og[1] = g_omg[r1]; }
            int prev_stage = 0;
            for (int kb = 0; kb < kblocks; kb++) {
                mbar_wait(bar_full + 8 * stage, phase);
                const uint32_t sa = sbase + stage * L::STAGE_BYTES + c * 8192;
                const uint32_t sb = sbase + stage * L::STAGE_BYTES + L::A_BYTES;
                const uint32_t da = desc_lo(sa, 16);
                const uint32_t db = desc_lo(sb, 8192);
                wgmma_fence();
#pragma unroll
                for (int k = 0; k < 4; k++) wgmma_tile<BN>(acc, da + k * 2, db + k * 128, (kb | k) != 0);
                wgmma_commit();
                if (kb > 0) {
                    wgmma_wait<1>();
                    RELEASE_STAGE(bar_empty + 8 * prev_stage);
                }
                prev_stage = stage;
                if (++stage == STAGES) { stage = 0; phase ^= 1; }
            }
            wgmma_wait<0>();
            RELEASE_STAGE(bar_empty + 8 * prev_stage);
            PH(1)
            if (MODE == 1 && first) { pdl_wait(); first = false; }

            const int cq = (lane & 3) * 2;
            const CUtensorMap* mc = &mC0;
            const uint32_t rrow = warp * 16 + (lane >> 2);
            const uint32_t res0 = stg + rrow * 128 + cq * 2;
            int out_c0 = n0;
            if (MODE == 1) {
                if (n0 < DM) {
                    const float qs = 0.17677669529663687f * 1.4426950408889634f;
#pragma unroll
                    for (int j = 0; j < BN / 2; j++) acc[j] *= qs;
                } else if (n0 >= 3 * DM) {
                    mc = &mC1;
                    out_c0 = n0 - 3 * DM;
                    const float mu0 = g_mean1[r0], mu1 = g_mean1[r1];
                    const float rs0 = g_rstd1[r0], rs1 = g_rstd1[r1];
                    {
                        const int t = threadIdx.x - 128;
                        const float v = (g_cs1[out_c0 + t] + g_cs1[DM + out_c0 + t]) + (g_cs1[2 * DM + out_c0 + t] + g_cs1[3 * DM + out_c0 + t]);
                        asm volatile("st.shared.f32 [%0], %1;" ::"r"(sbase + L::CS_OFF + t * 4), "f"(v) : "memory");
                    }
                    named_bar_sync(3, 256);
#pragma unroll
                    for (int j = 0; j < BN / 8; j++) {
                        float2 cs;
                        asm volatile("ld.shared.v2.f32 {%0, %1}, [%2];" : "=f"(cs.x), "=f"(cs.y) : "r"(sbase + L::CS_OFF + (8 * j + cq) * 4));
                        acc[4 * j + 0] = gelu_tanh(rs0 * fmaf(-mu0, cs.x, acc[4 * j + 0]));
                        acc[4 * j + 1] = gelu_tanh(rs0 * fmaf(-mu0, cs.y, acc[4 * j + 1]));
                        acc[4 * j + 2] = gelu_tanh(rs1 * fmaf(-mu1, cs.x, acc[4 * j + 2]));
                        acc[4 * j + 3] = gelu_tanh(rs1 * fmaf(-mu1, cs.y, acc[4 * j + 3]));
                    }
                    named_bar_sync(3, 256);
                }
            } else if (MODE == 2) {
                float s0 = 0.f, s1 = 0.f;
                mbar_wait(bar_res, 0);
#pragma unroll
                for (int j = 0; j < BN / 8; j++) {
                    uint32_t xa, xb;
                    const uint32_t ra = res0 + (j >> 3) * 8192 + (((j & 7) ^ (rrow & 7)) << 4);
                    asm volatile("ld.shared.b32 %0, [%1];" : "=r"(xa) : "r"(ra));
                    asm volatile("ld.shared.b32 %0, [%1];" : "=r"(xb) : "r"(ra + 1024));
                    acc[4 * j + 0] = bf16_round(bf16_round(acc[4 * j + 0]) + __uint_as_float(xa << 16));
                    acc[4 * j + 1] = bf16_round(bf16_round(acc[4 * j + 1]) + __uint_as_float(xa & 0xFFFF0000u));
                    acc[4 * j + 2] = bf16_round(bf16_round(acc[4 * j + 2]) + __uint_as_float(xb << 16));
                    acc[4 * j + 3] = bf16_round(bf16_round(acc[4 * j + 3]) + __uint_as_float(xb & 0xFFFF0000u));
                    s0 += acc[4 * j + 0] + acc[4 * j + 1];
                    s1 += acc[4 * j + 2] + acc[4 * j + 3];
                }
                s0 += __shfl_xor_sync(0xffffffffu, s0, 1);
                s0 += __shfl_xor_sync(0xffffffffu, s0, 2);
                s1 += __shfl_xor_sync(0xffffffffu, s1, 1);
                s1 += __shfl_xor_sync(0xffffffffu, s1, 2);
                const float mu0 = s0 * (1.0f / BN), mu1 = s1 * (1.0f / BN);
                float q0 = 0.f, q1 = 0.f;
#pragma unroll
                for (int j = 0; j < BN / 8; j++) {
                    float d;
                    d = acc[4 * j + 0] - mu0; q0 += d * d;
                    d = acc[4 * j + 1] - mu0; q0 += d * d;
                    d = acc[4 * j + 2] - mu1; q1 += d * d;
                    d = acc[4 * j + 3] - mu1; q1 += d * d;
                }
                q0 += __shfl_xor_sync(0xffffffffu, q0, 1);
                q0 += __shfl_xor_sync(0xffffffffu, q0, 2);
                q1 += __shfl_xor_sync(0xffffffffu, q1, 1);
                q1 += __shfl_xor_sync(0xffffffffu, q1, 2);
                if ((lane & 3) == 0) {
                    static_assert(MODE != 2 || BN == 128, "stats layout assumes BN=128");
                    g_stat2[r0 * 8 + (n0 >> 7)] = make_float2(s0, q0);
                    g_stat2[r1 * 8 + (n0 >> 7)] = make_float2(s1, q1);
                }
            } else if (MODE == 3) {
                out_c0 = n0 + DM;
                named_bar_sync(3, 256);
#pragma unroll
                for (int j = 0; j < BN / 8; j++) {
                    float2 cs;
                    asm volatile("ld.shared.v2.f32 {%0, %1}, [%2];" : "=f"(cs.x), "=f"(cs.y) : "r"(sbase + L::CS_OFF + (8 * j + cq) * 4));
                    acc[4 * j + 0] = og[0] * gelu_tanh(rs[0] * fmaf(-mu[0], cs.x, acc[4 * j + 0]));
                    acc[4 * j + 1] = og[0] * gelu_tanh(rs[0] * fmaf(-mu[0], cs.y, acc[4 * j + 1]));
                    acc[4 * j + 2] = og[1] * gelu_tanh(rs[1] * fmaf(-mu[1], cs.x, acc[4 * j + 2]));
                    acc[4 * j + 3] = og[1] * gelu_tanh(rs[1] * fmaf(-mu[1], cs.y, acc[4 * j + 3]));
                }
                named_bar_sync(3, 256);
            } else {
                const float og0 = og[0], og1 = og[1];
                mbar_wait(bar_res, 0);
#pragma unroll
                for (int j = 0; j < BN / 8; j++) {
                    uint32_t xa, xb;
                    const uint32_t ra = res0 + (j >> 3) * 8192 + (((j & 7) ^ (rrow & 7)) << 4);
                    asm volatile("ld.shared.b32 %0, [%1];" : "=r"(xa) : "r"(ra));
                    asm volatile("ld.shared.b32 %0, [%1];" : "=r"(xb) : "r"(ra + 1024));
                    acc[4 * j + 0] = fmaf(og0, __uint_as_float(xa << 16), acc[4 * j + 0]);
                    acc[4 * j + 1] = fmaf(og0, __uint_as_float(xa & 0xFFFF0000u), acc[4 * j + 1]);
                    acc[4 * j + 2] = fmaf(og1, __uint_as_float(xb << 16), acc[4 * j + 2]);
                    acc[4 * j + 3] = fmaf(og1, __uint_as_float(xb & 0xFFFF0000u), acc[4 * j + 3]);
                }
            }
            PH(3)
            const int srow = warp * 16 + (lane & 7) + ((lane >> 3) & 1) * 8;
#pragma unroll
            for (int rnd = 0; rnd < (BN + 127) / 128; rnd++) {
                if (tid_wg == 0) bulk_wait_read0();
                named_bar_sync(1 + c, 128);
#pragma unroll
                for (int jj = 0; jj < 8; jj++) {
                    const int j = rnd * 16 + jj * 2;
                    if (j * 8 < BN) {
                        const int jb = jj * 2 + (lane >> 4);
                        uint32_t addr = stg + (jb >> 3) * 8192 + srow * 128 + (((jb & 7) ^ (srow & 7)) << 4);
                        if (rnd * 128 + 128 > BN && jj >= 4)
                            addr = stg + 8192 + srow * 64 + (((jb & 3) ^ ((srow >> 1) & 3)) << 4);
                        stmatrix_x4(addr, pack_bf16(acc[4 * j + 0], acc[4 * j + 1]), pack_bf16(acc[4 * j + 2], acc[4 * j + 3]),
                                    pack_bf16(acc[4 * j + 4], acc[4 * j + 5]), pack_bf16(acc[4 * j + 6], acc[4 * j + 7]));
                    }
                }
                fence_proxy_async();
                named_bar_sync(1 + c, 128);
                if (tid_wg == 0) {
                    tma_store_2d(mc, stg, out_c0 + rnd * 128, m0 + c * 64);
                    if (rnd * 128 + 64 < BN)
                        tma_store_2d((rnd * 128 + 128 > BN) ? &mC1 : mc, stg + 8192, out_c0 + rnd * 128 + 64, m0 + c * 64);
                    bulk_commit();
                }
            }
        }
        PH(4)
        if (tid_wg == 0) bulk_wait0();
        PH(5)
        TL_END(MODE)
    }
}

#define ATT_SPLIT 16
constexpr int ATT_NTILES = NH * 16;
#define ATT_GRID_N 512
constexpr int ATT_GRID = ATT_GRID_N;
constexpr int ATT_THREADS = 256;
constexpr int ATT_STAGES = 4;
constexpr int ATT_DIST = 2;
constexpr int ATT_Q_OFF = ATT_STAGES * 16384;
constexpr int ATT_ONES_OFF = ATT_Q_OFF + 8192;
constexpr int ATT_KEXT_OFF = ATT_ONES_OFF + 4096;
constexpr int ATT_QEXT_OFF = ATT_KEXT_OFF + 4096;
constexpr int ATT_BAR_OFF = ATT_QEXT_OFF + 8192;
constexpr int ATT_SMEM = ATT_BAR_OFF + 256 + 1024;

__device__ __forceinline__ void row_max(const float (&s)[32], float& m0, float& m1) {
    float a0[8], a1[8];
#pragma unroll
    for (int i = 0; i < 8; i++) {
        a0[i] = fmaxf(s[4 * i], s[4 * i + 1]);
        a1[i] = fmaxf(s[4 * i + 2], s[4 * i + 3]);
    }
#pragma unroll
    for (int w = 4; w > 0; w >>= 1)
#pragma unroll
        for (int i = 0; i < w; i++) { a0[i] = fmaxf(a0[i], a0[i + w]); a1[i] = fmaxf(a1[i], a1[i + w]); }
    float mx0 = a0[0], mx1 = a1[0];
    mx0 = fmaxf(mx0, __shfl_xor_sync(0xffffffffu, mx0, 1));
    mx1 = fmaxf(mx1, __shfl_xor_sync(0xffffffffu, mx1, 1));
    mx0 = fmaxf(mx0, __shfl_xor_sync(0xffffffffu, mx0, 2));
    mx1 = fmaxf(mx1, __shfl_xor_sync(0xffffffffu, mx1, 2));
    m0 = fmaxf(m0, mx0);
    m1 = fmaxf(m1, mx1);
}

__device__ __forceinline__ void attn_step(float (&s)[32], float (&o)[20], uint32_t dq, uint32_t dke, uint32_t dk_next,
                                          uint32_t dv_cur, uint32_t release_bar) {
    constexpr uint32_t HI = desc_hi(512, 2);
    uint32_t p[16];
#pragma unroll
    for (int i = 0; i < 16; i++) p[i] = pack_bf16(ex2(s[2 * i]), ex2(s[2 * i + 1]));
    wgmma_fence();
    wgmma_ss_n64_tb0(s, dq, HI, dk_next, HI, 0);
    wgmma_ss_n64_tb0(s, dq + 2, HI, dk_next + 2, HI, 1);
    wgmma_ss_n64_tb0(s, dq + ((ATT_QEXT_OFF - ATT_Q_OFF) >> 4), HI, dke, HI, 1);
#pragma unroll
    for (int t = 0; t < 4; t++)
        wgmma_rs_n40_tb1(o, p[4 * t], p[4 * t + 1], p[4 * t + 2], p[4 * t + 3], dv_cur + t * 64, HI, 1);
    wgmma_commit();
    wgmma_wait<0>();
    if (release_bar != 0 && (threadIdx.x & 127) == 0) mbar_arrive(release_bar);
}

__global__ void __launch_bounds__(256, 1)
attn_exact_kernel(const __grid_constant__ CUtensorMap mKV) {
    extern __shared__ uint8_t smem_raw[];
    pdl_launch();
    pdl_wait();
    const int tile = blockIdx.x;
    if (g_bad[tile] == 0) return;
    constexpr int NBLK = S_LEN / 128;
    constexpr uint32_t HI = desc_hi(512, 2);
    const uint32_t sbase = (smem_u32(smem_raw) + 1023u) & ~1023u;
    const uint32_t bar = sbase + ATT_BAR_OFF;
    const int warp_id = threadIdx.x >> 5;
    const int lane = threadIdx.x & 31;
    const int cq = (lane & 3) * 2;
    const uint32_t dk0 = desc_lo(sbase, 16);
    const uint32_t dv0 = desc_lo(sbase + 8192, ATT_ONES_OFF - 8192);
    if (threadIdx.x == 0) {
        mbar_init(bar, 1);
        asm volatile("fence.mbarrier_init.release.cluster;" ::: "memory");
    }
    asm volatile("st.shared.v4.b32 [%0], {%1, %1, %1, %1};" ::"r"(sbase + ATT_ONES_OFF + threadIdx.x * 16), "r"(0x3F803F80u) : "memory");
    fence_proxy_async();
    __syncthreads();
    const int head = tile >> 4;
    const int row0 = (tile & 15) * 128 + warp_id * 16 + (lane >> 2);
    const uint32_t dq = desc_lo(sbase + ATT_Q_OFF + (threadIdx.x >> 7) * 4096, 16);
    float o[20];
#pragma unroll
    for (int i = 0; i < 20; i++) o[i] = 0.f;
    float m0 = -INFINITY, m1 = -INFINITY;
#pragma unroll 1
    for (int j = 0; j < NBLK; j++) {
        if (threadIdx.x == 0) {
            mbar_expect_tx(bar, j == 0 ? 3 * 8192 : 2 * 8192);
            if (j == 0) tma_load_2d(sbase + ATT_Q_OFF, &mKV, head * DH, (tile & 15) * 128, bar);
            tma_load_2d(sbase, &mKV, DM + head * DH, j * 128, bar);
            tma_load_2d(sbase + 8192, &mKV, 2 * DM + head * DH, j * 128, bar);
        }
        __syncwarp();
        mbar_wait(bar, j & 1);
#pragma unroll 1
        for (int hf = 0; hf < 2; hf++) {
            float s[32];
            wgmma_fence();
            wgmma_ss_n64_tb0(s, dq, HI, dk0 + hf * 256, HI, 0);
            wgmma_ss_n64_tb0(s, dq + 2, HI, dk0 + hf * 256 + 2, HI, 1);
            wgmma_commit();
            wgmma_wait<0>();
            const float mo0 = m0, mo1 = m1;
            row_max(s, m0, m1);
            const float a0 = ex2(mo0 - m0), a1 = ex2(mo1 - m1);
            uint32_t p[16];
#pragma unroll
            for (int i = 0; i < 8; i++) {
                p[2 * i] = pack_bf16(ex2(s[4 * i + 0] - m0), ex2(s[4 * i + 1] - m0));
                p[2 * i + 1] = pack_bf16(ex2(s[4 * i + 2] - m1), ex2(s[4 * i + 3] - m1));
            }
#pragma unroll
            for (int i = 0; i < 5; i++) {
                o[4 * i + 0] *= a0; o[4 * i + 1] *= a0;
                o[4 * i + 2] *= a1; o[4 * i + 3] *= a1;
            }
            wgmma_fence();
            const uint32_t dv = dv0 + hf * 256 - ((uint32_t)(hf * 256) << 16);
#pragma unroll
            for (int t = 0; t < 4; t++)
                wgmma_rs_n40_tb1(o, p[4 * t], p[4 * t + 1], p[4 * t + 2], p[4 * t + 3], dv + t * 64, HI, 1);
            wgmma_commit();
            wgmma_wait<0>();
        }
        __syncthreads();
    }
    const float f0 = g_gate[row0] / o[16], f1 = g_gate[row0 + 8] / o[18];
    bf16* op0 = g_a5 + (size_t)row0 * A5W + head * DH + cq;
    bf16* op1 = op0 + 8 * A5W;
#pragma unroll
    for (int i = 0; i < 4; i++) {
        *reinterpret_cast<uint32_t*>(op0 + 8 * i) = pack_bf16(o[4 * i] * f0, o[4 * i + 1] * f0);
        *reinterpret_cast<uint32_t*>(op1 + 8 * i) = pack_bf16(o[4 * i + 2] * f1, o[4 * i + 3] * f1);
    }
}

#define ATT_MINB 2
__global__ void __launch_bounds__(256, ATT_MINB)
attn_kernel(const __grid_constant__ CUtensorMap mKV) {
    extern __shared__ uint8_t smem_raw[];
    const uint32_t sbase = (smem_u32(smem_raw) + 1023u) & ~1023u;
    const uint32_t bar_kfull = sbase + ATT_BAR_OFF;
    const uint32_t bar_vfull = bar_kfull + 8 * ATT_STAGES;
    const uint32_t bar_empty = bar_vfull + 8 * ATT_STAGES;
    const int tile = blockIdx.x;
    const int head = tile >> 4;
    const int lane = threadIdx.x & 31;
    constexpr int NBLK = S_LEN / 128;
    TL_START(6)
    pdl_launch();

    auto issue_kv = [&](int g) {
        const int sn = g % ATT_STAGES;
        if (g >= ATT_STAGES) mbar_wait(bar_empty + 8 * sn, ((g / ATT_STAGES) - 1) & 1);
        const uint32_t skn = sbase + sn * 16384;
        mbar_expect_tx(bar_kfull + 8 * sn, g == 0 ? 16384 : 8192);
        if (g == 0) tma_load_2d(sbase + ATT_Q_OFF, &mKV, head * DH, (tile & 15) * 128, bar_kfull);
        tma_load_2d(skn, &mKV, DM + head * DH, g * 128, bar_kfull + 8 * sn);
        mbar_expect_tx(bar_vfull + 8 * sn, 8192);
        tma_load_2d(skn + 8192, &mKV, 2 * DM + head * DH, g * 128, bar_vfull + 8 * sn);
    };

    if (threadIdx.x == 0) {
        for (int s = 0; s < ATT_STAGES; s++) {
            mbar_init(bar_kfull + 8 * s, 1);
            mbar_init(bar_vfull + 8 * s, 1);
            mbar_init(bar_empty + 8 * s, 2);
        }
        asm volatile("fence.mbarrier_init.release.cluster;" ::: "memory");
        prefetch_tmap(&mKV);
        pdl_wait();
#pragma unroll
        for (int j = 0; j < ATT_DIST; j++) issue_kv(j);
    }
    {
        asm volatile("st.shared.v4.b32 [%0], {%1, %1, %1, %1};" ::"r"(sbase + ATT_ONES_OFF + threadIdx.x * 16), "r"(0x3F803F80u) : "memory");
        const int r = threadIdx.x >> 2, ch = threadIdx.x & 3;
        const uint32_t w0 = (ch == ((r >> 1) & 3)) ? 0x00003F80u : 0u;
        asm volatile("st.shared.v4.b32 [%0], {%1, %2, %2, %2};" ::"r"(sbase + ATT_KEXT_OFF + threadIdx.x * 16), "r"(w0), "r"(0u) : "memory");
        asm volatile("st.shared.v4.b32 [%0], {%1, %1, %1, %1};" ::"r"(sbase + ATT_QEXT_OFF + threadIdx.x * 16), "r"(0u) : "memory");
        asm volatile("st.shared.v4.b32 [%0], {%1, %1, %1, %1};" ::"r"(sbase + ATT_QEXT_OFF + 4096 + threadIdx.x * 16), "r"(0u) : "memory");
    }
    fence_proxy_async();
    __syncthreads();

    constexpr uint32_t HI = desc_hi(512, 2);
    const uint32_t dk0 = desc_lo(sbase, 16);
    const uint32_t dv0 = desc_lo(sbase + 8192, ATT_ONES_OFF - 8192);
    const uint32_t dke = dk0 + (ATT_KEXT_OFF >> 4);
    const uint32_t dq = dk0 + ((ATT_Q_OFF + (threadIdx.x >> 7) * 4096) >> 4);
    float o[20];
#pragma unroll
    for (int i = 0; i < 20; i++) o[i] = 0.f;
    float s0[32];
    mbar_wait(bar_kfull, 0);
    wgmma_fence();
    wgmma_ss_n64_tb0(s0, dq, HI, dk0, HI, 0);
    wgmma_ss_n64_tb0(s0, dq + 2, HI, dk0 + 2, HI, 1);
    wgmma_commit();
    wgmma_wait<0>();
    float m0 = -INFINITY, m1 = -INFINITY;
    row_max(s0, m0, m1);
    if ((lane & 3) == 0) {
        const int r = ((threadIdx.x >> 5) & 3) * 16 + (lane >> 2);
        const uint32_t qe = sbase + ATT_QEXT_OFF + (threadIdx.x >> 7) * 4096;
        asm volatile("st.shared.b16 [%0], %1;" ::"r"(qe + r * 64 + (((r >> 1) & 3) << 4)), "h"((uint16_t)(pack_bf16(-m0, 0.f) & 0xFFFFu)) : "memory");
        asm volatile("st.shared.b16 [%0], %1;" ::"r"(qe + (r + 8) * 64 + ((((r + 8) >> 1) & 3) << 4)), "h"((uint16_t)(pack_bf16(-m1, 0.f) & 0xFFFFu)) : "memory");
    }
    fence_proxy_async();
    named_bar_sync(1 + (threadIdx.x >> 7), 128);
    wgmma_fence();
    wgmma_ss_n64_tb0(s0, dq + ((ATT_QEXT_OFF - ATT_Q_OFF) >> 4), HI, dke, HI, 1);
    wgmma_commit();
    wgmma_wait<0>();
#pragma unroll 1
    for (int j = 0; j < NBLK; j++) {
        if (threadIdx.x == 0 && j + ATT_DIST < NBLK) issue_kv(j + ATT_DIST);
        __syncwarp();
        const uint32_t stage = j & (ATT_STAGES - 1), nstage = (j + 1) & (ATT_STAGES - 1);
        const uint32_t dk = dk0 + stage * 1024;
        const uint32_t dv = dv0 + stage * 1024 - (stage << 26);
        mbar_wait(bar_vfull + 8 * stage, (j / ATT_STAGES) & 1);
        attn_step(s0, o, dq, dke, dk + 256, dv, 0u);
        uint32_t dkn = dk;
        if (j + 1 < NBLK) {
            mbar_wait(bar_kfull + 8 * nstage, ((j + 1) / ATT_STAGES) & 1);
            dkn = dk0 + nstage * 1024;
        }
        attn_step(s0, o, dq, dke, dkn, dv + 256 - (256u << 16), bar_empty + 8 * stage);
    }
    bool ok = (o[16] <= 1.8446744e19f) && (o[18] <= 1.8446744e19f);
#pragma unroll
    for (int i = 0; i < 16; i++) ok = ok && (fabsf(o[i]) <= 3.0e38f);
    const int row0 = (tile & 15) * 128 + (threadIdx.x >> 5) * 16 + (lane >> 2);
    const float f0 = g_gate[row0] / o[16], f1 = g_gate[row0 + 8] / o[18];
    bf16* op0 = g_a5 + (size_t)row0 * A5W + head * DH + (lane & 3) * 2;
    bf16* op1 = op0 + 8 * A5W;
#pragma unroll
    for (int i = 0; i < 4; i++) {
        *reinterpret_cast<uint32_t*>(op0 + 8 * i) = pack_bf16(o[4 * i] * f0, o[4 * i + 1] * f0);
        *reinterpret_cast<uint32_t*>(op1 + 8 * i) = pack_bf16(o[4 * i + 2] * f1, o[4 * i + 3] * f1);
    }
    const int bad = __syncthreads_or(!ok);
    if (threadIdx.x == 0) g_bad[tile] = bad;
    TL_END(6)
}

typedef CUresult (*EncodeFn)(CUtensorMap*, CUtensorMapDataType, cuuint32_t, void*, const cuuint64_t*, const cuuint64_t*,
                             const cuuint32_t*, const cuuint32_t*, CUtensorMapInterleave, CUtensorMapSwizzle,
                             CUtensorMapL2promotion, CUtensorMapFloatOOBfill);

static CUtensorMap make_map(EncodeFn fn, const void* ptr, int rows, int cols, int box_cols, int box_rows,
                            CUtensorMapSwizzle swz) {
    CUtensorMap m;
    cuuint64_t dims[2] = {(cuuint64_t)cols, (cuuint64_t)rows};
    cuuint64_t strides[1] = {(cuuint64_t)cols * 2};
    cuuint32_t box[2] = {(cuuint32_t)box_cols, (cuuint32_t)box_rows};
    cuuint32_t es[2] = {1, 1};
    fn(&m, CU_TENSOR_MAP_DATA_TYPE_BFLOAT16, 2, const_cast<void*>(ptr), dims, strides, box, es,
       CU_TENSOR_MAP_INTERLEAVE_NONE, swz, CU_TENSOR_MAP_L2_PROMOTION_L2_256B, CU_TENSOR_MAP_FLOAT_OOB_FILL_NONE);
    return m;
}

template <typename... KArgs, typename... Args>
static void launch_ex(void (*kern)(KArgs...), int grid, int block, int smem, cudaStream_t st, int cluster, int pdl, Args... args) {
    cudaLaunchConfig_t cfg = {};
    cfg.gridDim = dim3(grid);
    cfg.blockDim = dim3(block);
    cfg.dynamicSmemBytes = smem;
    cfg.stream = st;
    cudaLaunchAttribute at[2];
    at[0].id = cudaLaunchAttributeProgrammaticStreamSerialization;
    at[0].val.programmaticStreamSerializationAllowed = pdl;
    at[1].id = cudaLaunchAttributeClusterDimension;
    at[1].val.clusterDim.x = cluster;
    at[1].val.clusterDim.y = 1;
    at[1].val.clusterDim.z = 1;
    cfg.attrs = at;
    cfg.numAttrs = cluster > 1 ? 2 : 1;
    cudaLaunchKernelEx(&cfg, kern, KArgs(args)...);
}

extern "C" void kernel_launch(void* const* d_in, const int* in_sizes, int n_in, void* d_out, int out_size) {
    const bf16* x = (const bf16*)d_in[0];
    const bf16* wqkv = (const bf16*)d_in[1];
    const bf16* wo = (const bf16*)d_in[2];
    const bf16* w1 = (const bf16*)d_in[4];
    const bf16* w2 = (const bf16*)d_in[5];
    const bf16* w3 = (const bf16*)d_in[6];
    const bf16* w4 = (const bf16*)d_in[7];
    const bf16* gate_w = (const bf16*)d_in[8];

    static EncodeFn enc = nullptr;
    static void *p_qkv, *p_h, *p_x1, *p_a5, *p_cs1, *p_cs3;
    static cudaStream_t s2;
    static cudaEvent_t ev_fork, ev_join;
    using G1 = GemmSmem<256, 4>;
    using G2 = GemmSmem<128, 5>;
    using G3 = GemmSmem<224, 4>;
    if (!enc) {
        void* fn = nullptr;
        cudaDriverEntryPointQueryResult qres;
        cudaGetDriverEntryPoint("cuTensorMapEncodeTiled", &fn, cudaEnableDefault, &qres);
        enc = (EncodeFn)fn;
        cudaGetSymbolAddress(&p_qkv, g_qkv);
        cudaGetSymbolAddress(&p_h, g_h);
        cudaGetSymbolAddress(&p_x1, g_x1);
        cudaGetSymbolAddress(&p_a5, g_a5);
        cudaGetSymbolAddress(&p_cs1, g_cs1);
        cudaGetSymbolAddress(&p_cs3, g_cs3);
        cudaFuncSetAttribute(gemm_kernel<1, 256, 4>, cudaFuncAttributeMaxDynamicSharedMemorySize, G1::TOTAL);
        cudaFuncSetAttribute(gemm_kernel<2, 128, 5>, cudaFuncAttributeMaxDynamicSharedMemorySize, G2::TOTAL);
        cudaFuncSetAttribute(gemm_kernel<3, 224, 4>, cudaFuncAttributeMaxDynamicSharedMemorySize, G3::TOTAL);
        cudaFuncSetAttribute(gemm_kernel<5, 128, 5>, cudaFuncAttributeMaxDynamicSharedMemorySize, G2::TOTAL);
        cudaStreamCreateWithFlags(&s2, cudaStreamNonBlocking);
        cudaEventCreateWithFlags(&ev_fork, cudaEventDisableTiming);
        cudaEventCreateWithFlags(&ev_join, cudaEventDisableTiming);
        cudaFuncSetAttribute(attn_kernel, cudaFuncAttributeMaxDynamicSharedMemorySize, ATT_SMEM);
        cudaFuncSetAttribute(attn_exact_kernel, cudaFuncAttributeMaxDynamicSharedMemorySize, ATT_SMEM);
    }
    const CUtensorMapSwizzle SW128 = CU_TENSOR_MAP_SWIZZLE_128B, SW64 = CU_TENSOR_MAP_SWIZZLE_64B;
    CUtensorMap mX = make_map(enc, x, S_LEN, DM, 64, 128, SW128);
    CUtensorMap mXres = make_map(enc, x, S_LEN, DM, 64, 64, SW128);
    CUtensorMap mWqkv = make_map(enc, wqkv, DM, 3 * DM, 64, 64, SW128);
    CUtensorMap mW1 = make_map(enc, w1, DM, DM, 64, 64, SW128);
    CUtensorMap mW2 = make_map(enc, w2, DM, DM, 64, 64, SW128);
    CUtensorMap mW3 = make_map(enc, w3, DM, FF, 64, 64, SW128);
    CUtensorMap mW4 = make_map(enc, w4, FF, DM, 64, 64, SW128);
    CUtensorMap mWo = make_map(enc, wo, DM, DM, 64, 64, SW128);
    CUtensorMap mQKVst = make_map(enc, p_qkv, S_LEN, 3 * DM, 64, 64, SW128);
    CUtensorMap mKV = make_map(enc, p_qkv, S_LEN, 3 * DM, 32, 128, SW64);
    CUtensorMap mHst = make_map(enc, p_h, S_LEN, DM, 64, 64, SW128);
    CUtensorMap mHld = make_map(enc, p_h, S_LEN, DM, 64, 128, SW128);
    CUtensorMap mX1st = make_map(enc, p_x1, S_LEN, DM, 64, 64, SW128);
    CUtensorMap mX1ld = make_map(enc, p_x1, S_LEN, DM, 64, 128, SW128);
    CUtensorMap mA5st = make_map(enc, p_a5, S_LEN, A5W, 64, 64, SW128);
    CUtensorMap mA5st32 = make_map(enc, p_a5, S_LEN, A5W, 32, 64, SW64);
    CUtensorMap mA5ld = make_map(enc, p_a5, S_LEN, A5W, 64, 128, SW128);
    CUtensorMap mOut = make_map(enc, d_out, S_LEN, DM, 64, 64, SW128);

    cudaStream_t st = cudaStreamPerThread;
    prep_kernel<<<256 + 64 + 224, 256, 0, st>>>(x, gate_w, w1, w3);
    launch_ex(gemm_kernel<1, 256, 4>, 132, 384, G1::TOTAL, st, 1, 1, mX, mWqkv, mW1, mQKVst, mHst, x, 16, 16);
    launch_ex(gemm_kernel<2, 128, 5>, 128, 384, G2::TOTAL, st, 1, 1, mHld, mW2, mW2, mX1st, mXres, x, 8, 16);
    cudaEventRecord(ev_fork, st);
    launch_ex(attn_kernel, ATT_GRID, ATT_THREADS, ATT_SMEM, st, 1, 1, mKV);
    launch_ex(attn_exact_kernel, ATT_NTILES, ATT_THREADS, ATT_SMEM, st, 1, 1, mKV);
    cudaStreamWaitEvent(s2, ev_fork, 0);
    launch_ex(gemm_kernel<3, 224, 4>, 132, 384, G3::TOTAL, s2, 1, 0, mX1ld, mW3, mW3, mA5st, mA5st32, x, 16, 16);
    cudaEventRecord(ev_join, s2);
    cudaStreamWaitEvent(st, ev_join, 0);
    launch_ex(gemm_kernel<5, 128, 5>, 128, 384, G2::TOTAL, st, 1, 0, mA5ld, mWo, mW4, mOut, mX1st, (const bf16*)p_x1, 8, 72);
}
```

```cpp
#include <cuda_runtime.h>
#include <cuda_bf16.h>
#include <cuda.h>
#include <stdint.h>

typedef __nv_bfloat16 bf16;

constexpr int S_LEN = 2048;
constexpr int DM = 1024;
constexpr int FF = 3584;
constexpr int NH = 32;
constexpr int DH = 32;
constexpr int A5W = DM + FF;

__device__ __align__(1024) bf16 g_qkv[S_LEN * 3 * DM];
__device__ __align__(1024) bf16 g_h[S_LEN * DM];
__device__ __align__(1024) bf16 g_x1[S_LEN * DM];
__device__ __align__(1024) bf16 g_a5[S_LEN * A5W];
__device__ __align__(16) float g_mean1[S_LEN];
__device__ __align__(16) float g_rstd1[S_LEN];
__device__ __align__(16) float g_gate[S_LEN];
__device__ __align__(16) float g_omg[S_LEN];
__device__ __align__(16) float g_cs1[4 * DM];
__device__ __align__(16) float g_cs3[4 * FF];
__device__ __align__(16) float2 g_stat2[S_LEN * 8];
__device__ int g_bad[NH * 16];
__device__ int g_tile_ctr;

#define TL_START(k)
#define PH(i)
#define TL_END(k)

__device__ __forceinline__ uint32_t smem_u32(const void* p) { return (uint32_t)__cvta_generic_to_shared(p); }

__device__ __forceinline__ void mbar_init(uint32_t bar, uint32_t count) {
    asm volatile("mbarrier.init.shared::cta.b64 [%0], %1;" ::"r"(bar), "r"(count));
}
__device__ __forceinline__ void mbar_expect_tx(uint32_t bar, uint32_t bytes) {
    asm volatile("mbarrier.arrive.expect_tx.shared::cta.b64 _, [%0], %1;" ::"r"(bar), "r"(bytes) : "memory");
}
__device__ __forceinline__ void mbar_arrive(uint32_t bar) {
    asm volatile("mbarrier.arrive.shared::cta.b64 _, [%0];" ::"r"(bar) : "memory");
}
__device__ __forceinline__ bool mbar_try_wait(uint32_t bar, uint32_t parity) {
    uint32_t ok;
    asm volatile(
        "{\n.reg .pred p;\n"
        "mbarrier.try_wait.parity.shared::cta.b64 p, [%1], %2;\n"
        "selp.u32 %0, 1, 0, p;\n}\n"
        : "=r"(ok)
        : "r"(bar), "r"(parity)
        : "memory");
    return ok != 0;
}
__device__ __forceinline__ void mbar_wait(uint32_t bar, uint32_t parity) {
    uint32_t spins = 0;
    while (!mbar_try_wait(bar, parity)) {
        if (++spins > (1u << 24)) __trap();
    }
}
__device__ __forceinline__ void tma_load_2d(uint32_t dst, const CUtensorMap* map, int c0, int c1, uint32_t bar) {
    asm volatile(
        "cp.async.bulk.tensor.2d.shared::cluster.global.mbarrier::complete_tx::bytes [%0], [%1, {%3, %4}], [%2];"
        ::"r"(dst), "l"(map), "r"(bar), "r"(c0), "r"(c1)
        : "memory");
}
__device__ __forceinline__ void tma_store_2d(const CUtensorMap* map, uint32_t src, int c0, int c1) {
    asm volatile("cp.async.bulk.tensor.2d.global.shared::cta.bulk_group [%0, {%2, %3}], [%1];"
                 ::"l"(map), "r"(src), "r"(c0), "r"(c1)
                 : "memory");
}
__device__ __forceinline__ void tma_load_2d_mc(uint32_t dst, const CUtensorMap* map, int c0, int c1, uint32_t bar, uint16_t mask) {
    asm volatile(
        "cp.async.bulk.tensor.2d.shared::cluster.global.mbarrier::complete_tx::bytes.multicast::cluster [%0], [%1, {%3, %4}], [%2], %5;"
        ::"r"(dst), "l"(map), "r"(bar), "r"(c0), "r"(c1), "h"(mask)
        : "memory");
}
__device__ __forceinline__ void mbar_arrive_cluster(uint32_t bar, uint32_t cta) {
    asm volatile(
        "{\n.reg .b32 ra;\nmapa.shared::cluster.u32 ra, %0, %1;\n"
        "mbarrier.arrive.shared::cluster.b64 _, [ra];\n}\n" ::"r"(bar), "r"(cta)
        : "memory");
}
__device__ __forceinline__ void cluster_sync_all() {
    asm volatile("barrier.cluster.arrive.release.aligned;\nbarrier.cluster.wait.acquire.aligned;" ::: "memory");
}
__device__ __forceinline__ uint32_t cluster_rank() { uint32_t r; asm volatile("mov.u32 %0, %%cluster_ctarank;" : "=r"(r)); return r; }
__device__ __forceinline__ void pdl_wait() { asm volatile("griddepcontrol.wait;" ::: "memory"); }
__device__ __forceinline__ void pdl_launch() { asm volatile("griddepcontrol.launch_dependents;" ::: "memory"); }
__device__ __forceinline__ void bulk_commit() { asm volatile("cp.async.bulk.commit_group;" ::: "memory"); }
__device__ __forceinline__ void bulk_wait_read0() { asm volatile("cp.async.bulk.wait_group.read 0;" ::: "memory"); }
__device__ __forceinline__ void bulk_wait0() { asm volatile("cp.async.bulk.wait_group 0;" ::: "memory"); }
__device__ __forceinline__ void fence_proxy_async() { asm volatile("fence.proxy.async.shared::cta;" ::: "memory"); }
__device__ __forceinline__ void named_bar_sync(int id, int n) { asm volatile("bar.sync %0, %1;" ::"r"(id), "r"(n) : "memory"); }
__device__ __forceinline__ void named_bar_arrive(int id, int n) { asm volatile("bar.arrive %0, %1;" ::"r"(id), "r"(n) : "memory"); }
__device__ __forceinline__ void wgmma_fence() { asm volatile("wgmma.fence.sync.aligned;" ::: "memory"); }
__device__ __forceinline__ void wgmma_commit() { asm volatile("wgmma.commit_group.sync.aligned;" ::: "memory"); }
template <int N>
__device__ __forceinline__ void wgmma_wait() { asm volatile("wgmma.wait_group.sync.aligned %0;" ::"n"(N) : "memory"); }
__device__ __forceinline__ void prefetch_tmap(const CUtensorMap* m) {
    asm volatile("prefetch.tensormap [%0];" ::"l"(m) : "memory");
}
template <int R>
__device__ __forceinline__ void reg_alloc() { asm volatile("setmaxnreg.inc.sync.aligned.u32 %0;" ::"n"(R)); }
template <int R>
__device__ __forceinline__ void reg_dealloc() { asm volatile("setmaxnreg.dec.sync.aligned.u32 %0;" ::"n"(R)); }
__device__ __forceinline__ void stmatrix_x4(uint32_t addr, uint32_t r0, uint32_t r1, uint32_t r2, uint32_t r3) {
    asm volatile("stmatrix.sync.aligned.m8n8.x4.shared.b16 [%0], {%1, %2, %3, %4};"
                 ::"r"(addr), "r"(r0), "r"(r1), "r"(r2), "r"(r3)
                 : "memory");
}
__device__ __forceinline__ uint32_t pack_bf16(float lo, float hi) {
    uint32_t r;
    asm("cvt.rn.bf16x2.f32 %0, %1, %2;" : "=r"(r) : "f"(hi), "f"(lo));
    return r;
}
__device__ __forceinline__ float bf16_round(float v) { return __bfloat162float(__float2bfloat16_rn(v)); }
__device__ __forceinline__ float ex2(float x) {
    float y;
    asm volatile("ex2.approx.ftz.f32 %0, %1;" : "=f"(y) : "f"(x));
    return y;
}
__device__ __forceinline__ float tanh_fast(float x) {
    float y;
    asm("tanh.approx.f32 %0, %1;" : "=f"(y) : "f"(x));
    return y;
}
__device__ __forceinline__ float gelu_tanh(float v) {
    float u = 0.7978845608028654f * (v + 0.044715f * v * v * v);
    float hv = 0.5f * v;
    return fmaf(hv, tanh_fast(u), hv);
}
__device__ __forceinline__ uint32_t desc_lo(uint32_t addr, uint32_t lbo_bytes) {
    return ((addr & 0x3FFFF) >> 4) | (((lbo_bytes >> 4) & 0x3FFF) << 16);
}
__host__ __device__ constexpr uint32_t desc_hi(uint32_t sbo_bytes, uint32_t swz) {
    return ((sbo_bytes >> 4) & 0x3FFF) | (swz << 30);
}

__device__ __forceinline__ void wgmma_ss_n128_tb1(float (&d)[64], uint32_t alo, uint32_t ahi, uint32_t blo, uint32_t bhi, int scale_d) {
    asm volatile("{\n.reg .pred p;\n.reg .b64 da, db;\nsetp.ne.b32 p, %68, 0;\nmov.b64 da, {%64, %65};\nmov.b64 db, {%66, %67};\n"
        "wgmma.mma_async.sync.aligned.m64n128k16.f32.bf16.bf16 {%0, %1, %2, %3, %4, %5, %6, %7, %8, %9, %10, %11, %12, %13, %14, %15, %16, %17, %18, %19, %20, %21, %22, %23, %24, %25, %26, %27, %28, %29, %30, %31, %32, %33, %34, %35, %36, %37, %38, %39, %40, %41, %42, %43, %44, %45, %46, %47, %48, %49, %50, %51, %52, %53, %54, %55, %56, %57, %58, %59, %60, %61, %62, %63}, da, db, p, 1, 1, 0, 1;\n}\n"
        : "+f"(d[0]), "+f"(d[1]), "+f"(d[2]), "+f"(d[3]), "+f"(d[4]), "+f"(d[5]), "+f"(d[6]), "+f"(d[7]), "+f"(d[8]), "+f"(d[9]), "+f"(d[10]), "+f"(d[11]), "+f"(d[12]), "+f"(d[13]), "+f"(d[14]), "+f"(d[15]), "+f"(d[16]), "+f"(d[17]), "+f"(d[18]), "+f"(d[19]), "+f"(d[20]), "+f"(d[21]), "+f"(d[22]), "+f"(d[23]), "+f"(d[24]), "+f"(d[25]), "+f"(d[26]), "+f"(d[27]), "+f"(d[28]), "+f"(d[29]), "+f"(d[30]), "+f"(d[31]), "+f"(d[32]), "+f"(d[33]), "+f"(d[34]), "+f"(d[35]), "+f"(d[36]), "+f"(d[37]), "+f"(d[38]), "+f"(d[39]), "+f"(d[40]), "+f"(d[41]), "+f"(d[42]), "+f"(d[43]), "+f"(d[44]), "+f"(d[45]), "+f"(d[46]), "+f"(d[47]), "+f"(d[48]), "+f"(d[49]), "+f"(d[50]), "+f"(d[51]), "+f"(d[52]), "+f"(d[53]), "+f"(d[54]), "+f"(d[55]), "+f"(d[56]), "+f"(d[57]), "+f"(d[58]), "+f"(d[59]), "+f"(d[60]), "+f"(d[61]), "+f"(d[62]), "+f"(d[63])
        : "r"(alo), "r"(ahi), "r"(blo), "r"(bhi), "r"(scale_d));
}

__device__ __forceinline__ void wgmma_ss_n192_tb1(float (&d)[96], uint32_t alo, uint32_t ahi, uint32_t blo, uint32_t bhi, int scale_d) {
    asm volatile("{\n.reg .pred p;\n.reg .b64 da, db;\nsetp.ne.b32 p, %100, 0;\nmov.b64 da, {%96, %97};\nmov.b64 db, {%98, %99};\n"
        "wgmma.mma_async.sync.aligned.m64n192k16.f32.bf16.bf16 {%0, %1, %2, %3, %4, %5, %6, %7, %8, %9, %10, %11, %12, %13, %14, %15, %16, %17, %18, %19, %20, %21, %22, %23, %24, %25, %26, %27, %28, %29, %30, %31, %32, %33, %34, %35, %36, %37, %38, %39, %40, %41, %42, %43, %44, %45, %46, %47, %48, %49, %50, %51, %52, %53, %54, %55, %56, %57, %58, %59, %60, %61, %62, %63, %64, %65, %66, %67, %68, %69, %70, %71, %72, %73, %74, %75, %76, %77, %78, %79, %80, %81, %82, %83, %84, %85, %86, %87, %88, %89, %90, %91, %92, %93, %94, %95}, da, db, p, 1, 1, 0, 1;\n}\n"
        : "+f"(d[0]), "+f"(d[1]), "+f"(d[2]), "+f"(d[3]), "+f"(d[4]), "+f"(d[5]), "+f"(d[6]), "+f"(d[7]), "+f"(d[8]), "+f"(d[9]), "+f"(d[10]), "+f"(d[11]), "+f"(d[12]), "+f"(d[13]), "+f"(d[14]), "+f"(d[15]), "+f"(d[16]), "+f"(d[17]), "+f"(d[18]), "+f"(d[19]), "+f"(d[20]), "+f"(d[21]), "+f"(d[22]), "+f"(d[23]), "+f"(d[24]), "+f"(d[25]), "+f"(d[26]), "+f"(d[27]), "+f"(d[28]), "+f"(d[29]), "+f"(d[30]), "+f"(d[31]), "+f"(d[32]), "+f"(d[33]), "+f"(d[34]), "+f"(d[35]), "+f"(d[36]), "+f"(d[37]), "+f"(d[38]), "+f"(d[39]), "+f"(d[40]), "+f"(d[41]), "+f"(d[42]), "+f"(d[43]), "+f"(d[44]), "+f"(d[45]), "+f"(d[46]), "+f"(d[47]), "+f"(d[48]), "+f"(d[49]), "+f"(d[50]), "+f"(d[51]), "+f"(d[52]), "+f"(d[53]), "+f"(d[54]), "+f"(d[55]), "+f"(d[56]), "+f"(d[57]), "+f"(d[58]), "+f"(d[59]), "+f"(d[60]), "+f"(d[61]), "+f"(d[62]), "+f"(d[63]), "+f"(d[64]), "+f"(d[65]), "+f"(d[66]), "+f"(d[67]), "+f"(d[68]), "+f"(d[69]), "+f"(d[70]), "+f"(d[71]), "+f"(d[72]), "+f"(d[73]), "+f"(d[74]), "+f"(d[75]), "+f"(d[76]), "+f"(d[77]), "+f"(d[78]), "+f"(d[79]), "+f"(d[80]), "+f"(d[81]), "+f"(d[82]), "+f"(d[83]), "+f"(d[84]), "+f"(d[85]), "+f"(d[86]), "+f"(d[87]), "+f"(d[88]), "+f"(d[89]), "+f"(d[90]), "+f"(d[91]), "+f"(d[92]), "+f"(d[93]), "+f"(d[94]), "+f"(d[95])
        : "r"(alo), "r"(ahi), "r"(blo), "r"(bhi), "r"(scale_d));
}

__device__ __forceinline__ void wgmma_ss_n224_tb1(float (&d)[112], uint32_t alo, uint32_t ahi, uint32_t blo, uint32_t bhi, int scale_d) {
    asm volatile("{\n.reg .pred p;\n.reg .b64 da, db;\nsetp.ne.b32 p, %116, 0;\nmov.b64 da, {%112, %113};\nmov.b64 db, {%114, %115};\n"
        "wgmma.mma_async.sync.aligned.m64n224k16.f32.bf16.bf16 {%0, %1, %2, %3, %4, %5, %6, %7, %8, %9, %10, %11, %12, %13, %14, %15, %16, %17, %18, %19, %20, %21, %22, %23, %24, %25, %26, %27, %28, %29, %30, %31, %32, %33, %34, %35, %36, %37, %38, %39, %40, %41, %42, %43, %44, %45, %46, %47, %48, %49, %50, %51, %52, %53, %54, %55, %56, %57, %58, %59, %60, %61, %62, %63, %64, %65, %66, %67, %68, %69, %70, %71, %72, %73, %74, %75, %76, %77, %78, %79, %80, %81, %82, %83, %84, %85, %86, %87, %88, %89, %90, %91, %92, %93, %94, %95, %96, %97, %98, %99, %100, %101, %102, %103, %104, %105, %106, %107, %108, %109, %110, %111}, da, db, p, 1, 1, 0, 1;\n}\n"
        : "+f"(d[0]), "+f"(d[1]), "+f"(d[2]), "+f"(d[3]), "+f"(d[4]), "+f"(d[5]), "+f"(d[6]), "+f"(d[7]), "+f"(d[8]), "+f"(d[9]), "+f"(d[10]), "+f"(d[11]), "+f"(d[12]), "+f"(d[13]), "+f"(d[14]), "+f"(d[15]), "+f"(d[16]), "+f"(d[17]), "+f"(d[18]), "+f"(d[19]), "+f"(d[20]), "+f"(d[21]), "+f"(d[22]), "+f"(d[23]), "+f"(d[24]), "+f"(d[25]), "+f"(d[26]), "+f"(d[27]), "+f"(d[28]), "+f"(d[29]), "+f"(d[30]), "+f"(d[31]), "+f"(d[32]), "+f"(d[33]), "+f"(d[34]), "+f"(d[35]), "+f"(d[36]), "+f"(d[37]), "+f"(d[38]), "+f"(d[39]), "+f"(d[40]), "+f"(d[41]), "+f"(d[42]), "+f"(d[43]), "+f"(d[44]), "+f"(d[45]), "+f"(d[46]), "+f"(d[47]), "+f"(d[48]), "+f"(d[49]), "+f"(d[50]), "+f"(d[51]), "+f"(d[52]), "+f"(d[53]), "+f"(d[54]), "+f"(d[55]), "+f"(d[56]), "+f"(d[57]), "+f"(d[58]), "+f"(d[59]), "+f"(d[60]), "+f"(d[61]), "+f"(d[62]), "+f"(d[63]), "+f"(d[64]), "+f"(d[65]), "+f"(d[66]), "+f"(d[67]), "+f"(d[68]), "+f"(d[69]), "+f"(d[70]), "+f"(d[71]), "+f"(d[72]), "+f"(d[73]), "+f"(d[74]), "+f"(d[75]), "+f"(d[76]), "+f"(d[77]), "+f"(d[78]), "+f"(d[79]), "+f"(d[80]), "+f"(d[81]), "+f"(d[82]), "+f"(d[83]), "+f"(d[84]), "+f"(d[85]), "+f"(d[86]), "+f"(d[87]), "+f"(d[88]), "+f"(d[89]), "+f"(d[90]), "+f"(d[91]), "+f"(d[92]), "+f"(d[93]), "+f"(d[94]), "+f"(d[95]), "+f"(d[96]), "+f"(d[97]), "+f"(d[98]), "+f"(d[99]), "+f"(d[100]), "+f"(d[101]), "+f"(d[102]), "+f"(d[103]), "+f"(d[104]), "+f"(d[105]), "+f"(d[106]), "+f"(d[107]), "+f"(d[108]), "+f"(d[109]), "+f"(d[110]), "+f"(d[111])
        : "r"(alo), "r"(ahi), "r"(blo), "r"(bhi), "r"(scale_d));
}

__device__ __forceinline__ void wgmma_ss_n256_tb1(float (&d)[128], uint32_t alo, uint32_t ahi, uint32_t blo, uint32_t bhi, int scale_d) {
    asm volatile("{\n.reg .pred p;\n.reg .b64 da, db;\nsetp.ne.b32 p, %132, 0;\nmov.b64 da, {%128, %129};\nmov.b64 db, {%130, %131};\n"
        "wgmma.mma_async.sync.aligned.m64n256k16.f32.bf16.bf16 {%0, %1, %2, %3, %4, %5, %6, %7, %8, %9, %10, %11, %12, %13, %14, %15, %16, %17, %18, %19, %20, %21, %22, %23, %24, %25, %26, %27, %28, %29, %30, %31, %32, %33, %34, %35, %36, %37, %38, %39, %40, %41, %42, %43, %44, %45, %46, %47, %48, %49, %50, %51, %52, %53, %54, %55, %56, %57, %58, %59, %60, %61, %62, %63, %64, %65, %66, %67, %68, %69, %70, %71, %72, %73, %74, %75, %76, %77, %78, %79, %80, %81, %82, %83, %84, %85, %86, %87, %88, %89, %90, %91, %92, %93, %94, %95, %96, %97, %98, %99, %100, %101, %102, %103, %104, %105, %106, %107, %108, %109, %110, %111, %112, %113, %114, %115, %116, %117, %118, %119, %120, %121, %122, %123, %124, %125, %126, %127}, da, db, p, 1, 1, 0, 1;\n}\n"
        : "+f"(d[0]), "+f"(d[1]), "+f"(d[2]), "+f"(d[3]), "+f"(d[4]), "+f"(d[5]), "+f"(d[6]), "+f"(d[7]), "+f"(d[8]), "+f"(d[9]), "+f"(d[10]), "+f"(d[11]), "+f"(d[12]), "+f"(d[13]), "+f"(d[14]), "+f"(d[15]), "+f"(d[16]), "+f"(d[17]), "+f"(d[18]), "+f"(d[19]), "+f"(d[20]), "+f"(d[21]), "+f"(d[22]), "+f"(d[23]), "+f"(d[24]), "+f"(d[25]), "+f"(d[26]), "+f"(d[27]), "+f"(d[28]), "+f"(d[29]), "+f"(d[30]), "+f"(d[31]), "+f"(d[32]), "+f"(d[33]), "+f"(d[34]), "+f"(d[35]), "+f"(d[36]), "+f"(d[37]), "+f"(d[38]), "+f"(d[39]), "+f"(d[40]), "+f"(d[41]), "+f"(d[42]), "+f"(d[43]), "+f"(d[44]), "+f"(d[45]), "+f"(d[46]), "+f"(d[47]), "+f"(d[48]), "+f"(d[49]), "+f"(d[50]), "+f"(d[51]), "+f"(d[52]), "+f"(d[53]), "+f"(d[54]), "+f"(d[55]), "+f"(d[56]), "+f"(d[57]), "+f"(d[58]), "+f"(d[59]), "+f"(d[60]), "+f"(d[61]), "+f"(d[62]), "+f"(d[63]), "+f"(d[64]), "+f"(d[65]), "+f"(d[66]), "+f"(d[67]), "+f"(d[68]), "+f"(d[69]), "+f"(d[70]), "+f"(d[71]), "+f"(d[72]), "+f"(d[73]), "+f"(d[74]), "+f"(d[75]), "+f"(d[76]), "+f"(d[77]), "+f"(d[78]), "+f"(d[79]), "+f"(d[80]), "+f"(d[81]), "+f"(d[82]), "+f"(d[83]), "+f"(d[84]), "+f"(d[85]), "+f"(d[86]), "+f"(d[87]), "+f"(d[88]), "+f"(d[89]), "+f"(d[90]), "+f"(d[91]), "+f"(d[92]), "+f"(d[93]), "+f"(d[94]), "+f"(d[95]), "+f"(d[96]), "+f"(d[97]), "+f"(d[98]), "+f"(d[99]), "+f"(d[100]), "+f"(d[101]), "+f"(d[102]), "+f"(d[103]), "+f"(d[104]), "+f"(d[105]), "+f"(d[106]), "+f"(d[107]), "+f"(d[108]), "+f"(d[109]), "+f"(d[110]), "+f"(d[111]), "+f"(d[112]), "+f"(d[113]), "+f"(d[114]), "+f"(d[115]), "+f"(d[116]), "+f"(d[117]), "+f"(d[118]), "+f"(d[119]), "+f"(d[120]), "+f"(d[121]), "+f"(d[122]), "+f"(d[123]), "+f"(d[124]), "+f"(d[125]), "+f"(d[126]), "+f"(d[127])
        : "r"(alo), "r"(ahi), "r"(blo), "r"(bhi), "r"(scale_d));
}

__device__ __forceinline__ void wgmma_ss_n64_tb0(float (&d)[32], uint32_t alo, uint32_t ahi, uint32_t blo, uint32_t bhi, int scale_d) {
    asm volatile("{\n.reg .pred p;\n.reg .b64 da, db;\nsetp.ne.b32 p, %36, 0;\nmov.b64 da, {%32, %33};\nmov.b64 db, {%34, %35};\n"
        "wgmma.mma_async.sync.aligned.m64n64k16.f32.bf16.bf16 {%0, %1, %2, %3, %4, %5, %6, %7, %8, %9, %10, %11, %12, %13, %14, %15, %16, %17, %18, %19, %20, %21, %22, %23, %24, %25, %26, %27, %28, %29, %30, %31}, da, db, p, 1, 1, 0, 0;\n}\n"
        : "+f"(d[0]), "+f"(d[1]), "+f"(d[2]), "+f"(d[3]), "+f"(d[4]), "+f"(d[5]), "+f"(d[6]), "+f"(d[7]), "+f"(d[8]), "+f"(d[9]), "+f"(d[10]), "+f"(d[11]), "+f"(d[12]), "+f"(d[13]), "+f"(d[14]), "+f"(d[15]), "+f"(d[16]), "+f"(d[17]), "+f"(d[18]), "+f"(d[19]), "+f"(d[20]), "+f"(d[21]), "+f"(d[22]), "+f"(d[23]), "+f"(d[24]), "+f"(d[25]), "+f"(d[26]), "+f"(d[27]), "+f"(d[28]), "+f"(d[29]), "+f"(d[30]), "+f"(d[31])
        : "r"(alo), "r"(ahi), "r"(blo), "r"(bhi), "r"(scale_d));
}

__device__ __forceinline__ void wgmma_rs_n128_tb0(float (&d)[64], uint32_t a0, uint32_t a1, uint32_t a2, uint32_t a3, uint32_t blo, uint32_t bhi, int scale_d) {
    asm volatile("{\n.reg .pred p;\n.reg .b64 db;\nsetp.ne.b32 p, %70, 0;\nmov.b64 db, {%68, %69};\n"
        "wgmma.mma_async.sync.aligned.m64n128k16.f32.bf16.bf16 {%0, %1, %2, %3, %4, %5, %6, %7, %8, %9, %10, %11, %12, %13, %14, %15, %16, %17, %18, %19, %20, %21, %22, %23, %24, %25, %26, %27, %28, %29, %30, %31, %32, %33, %34, %35, %36, %37, %38, %39, %40, %41, %42, %43, %44, %45, %46, %47, %48, %49, %50, %51, %52, %53, %54, %55, %56, %57, %58, %59, %60, %61, %62, %63}, {%64, %65, %66, %67}, db, p, 1, 1, 0;\n}\n"
        : "+f"(d[0]), "+f"(d[1]), "+f"(d[2]), "+f"(d[3]), "+f"(d[4]), "+f"(d[5]), "+f"(d[6]), "+f"(d[7]), "+f"(d[8]), "+f"(d[9]), "+f"(d[10]), "+f"(d[11]), "+f"(d[12]), "+f"(d[13]), "+f"(d[14]), "+f"(d[15]), "+f"(d[16]), "+f"(d[17]), "+f"(d[18]), "+f"(d[19]), "+f"(d[20]), "+f"(d[21]), "+f"(d[22]), "+f"(d[23]), "+f"(d[24]), "+f"(d[25]), "+f"(d[26]), "+f"(d[27]), "+f"(d[28]), "+f"(d[29]), "+f"(d[30]), "+f"(d[31]), "+f"(d[32]), "+f"(d[33]), "+f"(d[34]), "+f"(d[35]), "+f"(d[36]), "+f"(d[37]), "+f"(d[38]), "+f"(d[39]), "+f"(d[40]), "+f"(d[41]), "+f"(d[42]), "+f"(d[43]), "+f"(d[44]), "+f"(d[45]), "+f"(d[46]), "+f"(d[47]), "+f"(d[48]), "+f"(d[49]), "+f"(d[50]), "+f"(d[51]), "+f"(d[52]), "+f"(d[53]), "+f"(d[54]), "+f"(d[55]), "+f"(d[56]), "+f"(d[57]), "+f"(d[58]), "+f"(d[59]), "+f"(d[60]), "+f"(d[61]), "+f"(d[62]), "+f"(d[63])
        : "r"(a0), "r"(a1), "r"(a2), "r"(a3), "r"(blo), "r"(bhi), "r"(scale_d));
}

__device__ __forceinline__ void wgmma_rs_n64_tb0(float (&d)[32], uint32_t a0, uint32_t a1, uint32_t a2, uint32_t a3, uint32_t blo, uint32_t bhi, int scale_d) {
    asm volatile("{\n.reg .pred p;\n.reg .b64 db;\nsetp.ne.b32 p, %38, 0;\nmov.b64 db, {%36, %37};\n"
        "wgmma.mma_async.sync.aligned.m64n64k16.f32.bf16.bf16 {%0, %1, %2, %3, %4, %5, %6, %7, %8, %9, %10, %11, %12, %13, %14, %15, %16, %17, %18, %19, %20, %21, %22, %23, %24, %25, %26, %27, %28, %29, %30, %31}, {%32, %33, %34, %35}, db, p, 1, 1, 0;\n}\n"
        : "+f"(d[0]), "+f"(d[1]), "+f"(d[2]), "+f"(d[3]), "+f"(d[4]), "+f"(d[5]), "+f"(d[6]), "+f"(d[7]), "+f"(d[8]), "+f"(d[9]), "+f"(d[10]), "+f"(d[11]), "+f"(d[12]), "+f"(d[13]), "+f"(d[14]), "+f"(d[15]), "+f"(d[16]), "+f"(d[17]), "+f"(d[18]), "+f"(d[19]), "+f"(d[20]), "+f"(d[21]), "+f"(d[22]), "+f"(d[23]), "+f"(d[24]), "+f"(d[25]), "+f"(d[26]), "+f"(d[27]), "+f"(d[28]), "+f"(d[29]), "+f"(d[30]), "+f"(d[31])
        : "r"(a0), "r"(a1), "r"(a2), "r"(a3), "r"(blo), "r"(bhi), "r"(scale_d));
}

__device__ __forceinline__ void wgmma_rs_n32_tb1(float (&d)[16], uint32_t a0, uint32_t a1, uint32_t a2, uint32_t a3, uint32_t blo, uint32_t bhi, int scale_d) {
    asm volatile("{\n.reg .pred p;\n.reg .b64 db;\nsetp.ne.b32 p, %22, 0;\nmov.b64 db, {%20, %21};\n"
        "wgmma.mma_async.sync.aligned.m64n32k16.f32.bf16.bf16 {%0, %1, %2, %3, %4, %5, %6, %7, %8, %9, %10, %11, %12, %13, %14, %15}, {%16, %17, %18, %19}, db, p, 1, 1, 1;\n}\n"
        : "+f"(d[0]), "+f"(d[1]), "+f"(d[2]), "+f"(d[3]), "+f"(d[4]), "+f"(d[5]), "+f"(d[6]), "+f"(d[7]), "+f"(d[8]), "+f"(d[9]), "+f"(d[10]), "+f"(d[11]), "+f"(d[12]), "+f"(d[13]), "+f"(d[14]), "+f"(d[15])
        : "r"(a0), "r"(a1), "r"(a2), "r"(a3), "r"(blo), "r"(bhi), "r"(scale_d));
}

__device__ __forceinline__ void wgmma_rs_n40_tb1(float (&d)[20], uint32_t a0, uint32_t a1, uint32_t a2, uint32_t a3, uint32_t blo, uint32_t bhi, int scale_d) {
    asm volatile("{\n.reg .pred p;\n.reg .b64 db;\nsetp.ne.b32 p, %26, 0;\nmov.b64 db, {%24, %25};\n"
        "wgmma.mma_async.sync.aligned.m64n40k16.f32.bf16.bf16 {%0, %1, %2, %3, %4, %5, %6, %7, %8, %9, %10, %11, %12, %13, %14, %15, %16, %17, %18, %19}, {%20, %21, %22, %23}, db, p, 1, 1, 1;\n}\n"
        : "+f"(d[0]), "+f"(d[1]), "+f"(d[2]), "+f"(d[3]), "+f"(d[4]), "+f"(d[5]), "+f"(d[6]), "+f"(d[7]), "+f"(d[8]), "+f"(d[9]), "+f"(d[10]), "+f"(d[11]), "+f"(d[12]), "+f"(d[13]), "+f"(d[14]), "+f"(d[15]), "+f"(d[16]), "+f"(d[17]), "+f"(d[18]), "+f"(d[19])
        : "r"(a0), "r"(a1), "r"(a2), "r"(a3), "r"(blo), "r"(bhi), "r"(scale_d));
}

template <int BN>
__device__ __forceinline__ void wgmma_tile(float (&d)[BN / 2], uint32_t da, uint32_t db, int sd) {
    constexpr uint32_t HI = desc_hi(1024, 1);
    if constexpr (BN == 128) wgmma_ss_n128_tb1(d, da, HI, db, HI, sd);
    else if constexpr (BN == 192) wgmma_ss_n192_tb1(d, da, HI, db, HI, sd);
    else if constexpr (BN == 224) wgmma_ss_n224_tb1(d, da, HI, db, HI, sd);
    else wgmma_ss_n256_tb1(d, da, HI, db, HI, sd);
}

__global__ void __launch_bounds__(256) prep_kernel(const bf16* __restrict__ x, const bf16* __restrict__ gate_w,
                                                   const bf16* __restrict__ w1, const bf16* __restrict__ w3) {
    constexpr int row_blocks = 256;
    if (blockIdx.x == 0 && threadIdx.x == 0) g_tile_ctr = 0;
    const int tid = threadIdx.x;
    TL_START(0)
    pdl_launch();
    if ((int)blockIdx.x < row_blocks) {
        const int row = blockIdx.x * 8 + (tid >> 5);
        const int lane = tid & 31;
        const uint4* xr = reinterpret_cast<const uint4*>(x + (size_t)row * DM);
        const uint4* gw = reinterpret_cast<const uint4*>(gate_w);
        float v[32];
        float gsum = 0.f, sum = 0.f;
#pragma unroll
        for (int i = 0; i < 4; i++) {
            uint4 a = xr[lane + 32 * i];
            uint4 b = gw[lane + 32 * i];
            const uint32_t aa[4] = {a.x, a.y, a.z, a.w};
            const uint32_t bb[4] = {b.x, b.y, b.z, b.w};
#pragma unroll
            for (int j = 0; j < 4; j++) {
                float x0 = __uint_as_float(aa[j] << 16), x1 = __uint_as_float(aa[j] & 0xFFFF0000u);
                float g0 = __uint_as_float(bb[j] << 16), g1 = __uint_as_float(bb[j] & 0xFFFF0000u);
                v[i * 8 + j * 2] = x0;
                v[i * 8 + j * 2 + 1] = x1;
                sum += x0 + x1;
                gsum += bf16_round(x0 * g0) + bf16_round(x1 * g1);
            }
        }
#pragma unroll
        for (int o = 16; o > 0; o >>= 1) {
            sum += __shfl_xor_sync(0xffffffffu, sum, o);
            gsum += __shfl_xor_sync(0xffffffffu, gsum, o);
        }
        const float mean = sum * (1.0f / DM);
        float m2 = 0.f;
#pragma unroll
        for (int i = 0; i < 32; i++) {
            float d = v[i] - mean;
            m2 += d * d;
        }
#pragma unroll
        for (int o = 16; o > 0; o >>= 1) m2 += __shfl_xor_sync(0xffffffffu, m2, o);
        if (lane == 0) {
            g_mean1[row] = mean;
            g_rstd1[row] = rsqrtf(m2 * (1.0f / DM) + 1e-5f);
            float logit = bf16_round(gsum);
            float g = bf16_round(1.0f / (1.0f + __expf(-logit)));
            g_gate[row] = g;
            g_omg[row] = bf16_round(1.0f - g);
        }
    } else {
        __shared__ float red[32][65];
        int blk = blockIdx.x - row_blocks;
        const bf16* w = w1;
        int ld = DM;
        float* cs_out = g_cs1;
        if (blk >= 64) { blk -= 64; w = w3; ld = FF; cs_out = g_cs3; }
        const int chunk = blk & 3;
        const int col0 = (blk >> 2) * 64;
        const int cg = tid & 7;
        const int rg = tid >> 3;
        uint4 a[8];
#pragma unroll
        for (int r = 0; r < 8; r++)
            a[r] = *reinterpret_cast<const uint4*>(w + (size_t)(chunk * 256 + r * 32 + rg) * ld + col0 + cg * 8);
        float acc[8];
#pragma unroll
        for (int j = 0; j < 8; j++) acc[j] = 0.f;
#pragma unroll
        for (int r = 0; r < 8; r++) {
            const uint32_t aa[4] = {a[r].x, a[r].y, a[r].z, a[r].w};
#pragma unroll
            for (int j = 0; j < 4; j++) {
                acc[2 * j] += __uint_as_float(aa[j] << 16);
                acc[2 * j + 1] += __uint_as_float(aa[j] & 0xFFFF0000u);
            }
        }
#pragma unroll
        for (int j = 0; j < 8; j++) red[rg][cg * 8 + j] = acc[j];
        __syncthreads();
        if (tid < 64) {
            float s = 0.f;
#pragma unroll
            for (int r = 0; r < 32; r++) s += red[r][tid];
            cs_out[chunk * ld + col0 + tid] = s;
        }
    }
    TL_END(0)
}

#define RELEASE_STAGE(b) if (tid_wg == 0) mbar_arrive(b)
template <int BN, int STAGES>
struct GemmSmem {
    static constexpr int A_BYTES = 128 * 64 * 2;
    static constexpr int B_BOXES = (BN + 63) / 64;
    static constexpr int B_BYTES = B_BOXES * 64 * 64 * 2;
    static constexpr int STAGE_BYTES = A_BYTES + B_BYTES;
    static constexpr int STG_OFF = STAGES * STAGE_BYTES;
    static constexpr int CS_OFF = STAGES * STAGE_BYTES + 2 * 16384;
    static constexpr int BAR_OFF = CS_OFF + 1024;
    static constexpr int TOTAL = BAR_OFF + 192 + 512;
};

template <int MODE, int BN, int STAGES>
__global__ void __launch_bounds__(384, 1)
gemm_kernel(const __grid_constant__ CUtensorMap mA, const __grid_constant__ CUtensorMap mB0,
            const __grid_constant__ CUtensorMap mB1, const __grid_constant__ CUtensorMap mC0,
            const __grid_constant__ CUtensorMap mC1, const bf16* __restrict__ xin, int n_tiles_n, int kblocks) {
    using L = GemmSmem<BN, STAGES>;
    extern __shared__ uint8_t smem_raw[];
    const uint32_t sbase = (smem_u32(smem_raw) + 1023u) & ~1023u;
    const uint32_t bar_full = sbase + L::BAR_OFF;
    const uint32_t bar_empty = bar_full + 8 * STAGES;
    const uint32_t bar_res = bar_empty + 8 * STAGES;
    const int wg = threadIdx.x >> 7;
    const int ntiles = 16 * n_tiles_n;
    constexpr bool DYN = (MODE == 3);
    const uint32_t bar_tfull = bar_res + 8;
    const uint32_t bar_tempty = bar_tfull + 16;
    const uint32_t tile_slot = bar_tempty + 16;
    TL_START(MODE)
    pdl_launch();

    if (threadIdx.x == 0) {
        for (int s = 0; s < STAGES; s++) {
            mbar_init(bar_full + 8 * s, 1);
            mbar_init(bar_empty + 8 * s, 2);
        }
        for (int s = 0; s < 2; s++) {
            mbar_init(bar_tfull + 8 * s, 1);
            mbar_init(bar_tempty + 8 * s, 2);
        }
        mbar_init(bar_res, 1);
        asm volatile("fence.mbarrier_init.release.cluster;" ::: "memory");
        prefetch_tmap(&mA);
        prefetch_tmap(&mB0);
        if (MODE == 1 || MODE == 5) prefetch_tmap(&mB1);
        if (MODE == 2 || MODE == 5) prefetch_tmap(&mC1);
        prefetch_tmap(&mC0);
    }
    __syncthreads();

    if (wg == 0) {
        reg_dealloc<40>();
        if (threadIdx.x == 0) {
            if (MODE != 1) pdl_wait();
            int stage = 0;
            uint32_t phase = 1;
            for (int it = 0;; it++) {
                int tile;
                if (DYN) {
                    tile = atomicAdd(&g_tile_ctr, 1);
                    mbar_wait(bar_tempty + 8 * (it & 1), ((it >> 1) & 1) ^ 1);
                    asm volatile("st.shared.b32 [%0], %1;" ::"r"(tile_slot + 4 * (it & 1)), "r"(tile) : "memory");
                    mbar_arrive(bar_tfull + 8 * (it & 1));
                } else {
                    tile = blockIdx.x + it * gridDim.x;
                }
                if (tile >= ntiles) break;
                if (MODE == 1) tile = (tile + 192) & 255;
                const int m0 = (tile & 15) * 128;
                const int n0 = (tile >> 4) * BN;
                for (int kb = 0; kb < kblocks; kb++) {
                    mbar_wait(bar_empty + 8 * stage, phase);
                    const uint32_t sa = sbase + stage * L::STAGE_BYTES;
                    const uint32_t sb = sa + L::A_BYTES;
                    const uint32_t fb = bar_full + 8 * stage;
                    mbar_expect_tx(fb, L::STAGE_BYTES);
                    int arow = m0;
                    if (MODE == 2) {
                        const int grp = kb >> 2;
                        arow += (grp == 0) ? -1 : (grp == 1) ? 1 : (grp == 2) ? -2 : 2;
                    }
                    tma_load_2d(sa, &mA, kb * 64, arow, fb);
                    const CUtensorMap* mb = &mB0;
                    int bc = n0, br = kb * 64;
                    if (MODE == 1 && n0 >= 3 * DM) { mb = &mB1; bc = n0 - 3 * DM; }
                    if (MODE == 5 && kb >= 16) { mb = &mB1; br = (kb - 16) * 64; }
#pragma unroll
                    for (int b = 0; b < L::B_BOXES; b++) tma_load_2d(sb + b * 8192, mb, bc + b * 64, br, fb);
                    if ((MODE == 2 || MODE == 5) && kb == STAGES - 1) {
                        mbar_expect_tx(bar_res, 32768);
#pragma unroll
                        for (int q = 0; q < 4; q++)
                            tma_load_2d(sbase + L::STG_OFF + q * 8192, &mC1, n0 + (q & 1) * 64, m0 + (q >> 1) * 64, bar_res);
                    }
                    if (++stage == STAGES) { stage = 0; phase ^= 1; }
                }
            }
        }
    } else {
        reg_alloc<232>();
        const int c = wg - 1;
        const int warp = (threadIdx.x >> 5) & 3;
        const int lane = threadIdx.x & 31;
        const int tid_wg = threadIdx.x & 127;
        const uint32_t stg = sbase + L::STG_OFF + c * 16384;
        int stage = 0;
        uint32_t phase = 0;
        float acc[BN / 2];
        bool first = true;
        PH(0)
        if (MODE != 1) pdl_wait();
        for (int it = 0;; it++) {
            int tile;
            if (DYN) {
                mbar_wait(bar_tfull + 8 * (it & 1), (it >> 1) & 1);
                asm volatile("ld.shared.b32 %0, [%1];" : "=r"(tile) : "r"(tile_slot + 4 * (it & 1)) : "memory");
                named_bar_sync(1 + c, 128);
                if (tid_wg == 0) mbar_arrive(bar_tempty + 8 * (it & 1));
            } else {
                tile = blockIdx.x + it * gridDim.x;
            }
            if (tile >= ntiles) break;
            if (MODE == 1) tile = (tile + 192) & 255;
            const int m0 = (tile & 15) * 128;
            const int n0 = (tile >> 4) * BN;
            const int r0 = m0 + c * 64 + warp * 16 + (lane >> 2);
            const int r1 = r0 + 8;
            float mu[2], rs[2], og[2];
            if (MODE == 3) {
                const int t = threadIdx.x - 128;
                if (t < BN) {
                    const float v = (g_cs3[n0 + t] + g_cs3[FF + n0 + t]) + (g_cs3[2 * FF + n0 + t] + g_cs3[3 * FF + n0 + t]);
                    asm volatile("st.shared.f32 [%0], %1;" ::"r"(sbase + L::CS_OFF + t * 4), "f"(v) : "memory");
                }
#pragma unroll
                for (int h = 0; h < 2; h++) {
                    const float4* sp = reinterpret_cast<const float4*>(&g_stat2[(h ? r1 : r0) * 8]);
                    float4 p[4];
                    float s = 0.f;
#pragma unroll
                    for (int i = 0; i < 4; i++) { p[i] = sp[i]; s += p[i].x + p[i].z; }
                    const float mean = s * (1.0f / DM);
                    float m2 = 0.f;
#pragma unroll
                    for (int i = 0; i < 4; i++) {
                        float d0 = p[i].x * (1.0f / 128) - mean, d1 = p[i].z * (1.0f / 128) - mean;
                        m2 += p[i].y + p[i].w + 128.0f * (d0 * d0 + d1 * d1);
                    }
                    mu[h] = mean;
                    rs[h] = rsqrtf(m2 * (1.0f / DM) + 1e-5f);
                }
            }
            if (MODE == 3 || MODE == 5) { og[0] = g_omg[r0]; og[1] = g_omg[r1]; }
            int prev_stage = 0;
            for (int kb = 0; kb < kblocks; kb++) {
                mbar_wait(bar_full + 8 * stage, phase);
                const uint32_t sa = sbase + stage * L::STAGE_BYTES + c * 8192;
                const uint32_t sb = sbase + stage * L::STAGE_BYTES + L::A_BYTES;
                const uint32_t da = desc_lo(sa, 16);
                const uint32_t db = desc_lo(sb, 8192);
                wgmma_fence();
#pragma unroll
                for (int k = 0; k < 4; k++) wgmma_tile<BN>(acc, da + k * 2, db + k * 128, (kb | k) != 0);
                wgmma_commit();
                if (kb > 0) {
                    wgmma_wait<1>();
                    RELEASE_STAGE(bar_empty + 8 * prev_stage);
                }
                prev_stage = stage;
                if (++stage == STAGES) { stage = 0; phase ^= 1; }
            }
            wgmma_wait<0>();
            RELEASE_STAGE(bar_empty + 8 * prev_stage);
            PH(1)
            if (MODE == 1 && first) { pdl_wait(); first = false; }

            const int cq = (lane & 3) * 2;
            const CUtensorMap* mc = &mC0;
            const uint32_t rrow = warp * 16 + (lane >> 2);
            const uint32_t res0 = stg + rrow * 128 + cq * 2;
            int out_c0 = n0;
            if (MODE == 1) {
                if (n0 < DM) {
                    const float qs = 0.17677669529663687f * 1.4426950408889634f;
#pragma unroll
                    for (int j = 0; j < BN / 2; j++) acc[j] *= qs;
                } else if (n0 >= 3 * DM) {
                    mc = &mC1;
                    out_c0 = n0 - 3 * DM;
                    const float mu0 = g_mean1[r0], mu1 = g_mean1[r1];
                    const float rs0 = g_rstd1[r0], rs1 = g_rstd1[r1];
                    {
                        const int t = threadIdx.x - 128;
                        const float v = (g_cs1[out_c0 + t] + g_cs1[DM + out_c0 + t]) + (g_cs1[2 * DM + out_c0 + t] + g_cs1[3 * DM + out_c0 + t]);
                        asm volatile("st.shared.f32 [%0], %1;" ::"r"(sbase + L::CS_OFF + t * 4), "f"(v) : "memory");
                    }
                    named_bar_sync(3, 256);
#pragma unroll
                    for (int j = 0; j < BN / 8; j++) {
                        float2 cs;
                        asm volatile("ld.shared.v2.f32 {%0, %1}, [%2];" : "=f"(cs.x), "=f"(cs.y) : "r"(sbase + L::CS_OFF + (8 * j + cq) * 4));
                        acc[4 * j + 0] = gelu_tanh(rs0 * fmaf(-mu0, cs.x, acc[4 * j + 0]));
                        acc[4 * j + 1] = gelu_tanh(rs0 * fmaf(-mu0, cs.y, acc[4 * j + 1]));
                        acc[4 * j + 2] = gelu_tanh(rs1 * fmaf(-mu1, cs.x, acc[4 * j + 2]));
                        acc[4 * j + 3] = gelu_tanh(rs1 * fmaf(-mu1, cs.y, acc[4 * j + 3]));
                    }
                    named_bar_sync(3, 256);
                }
            } else if (MODE == 2) {
                float s0 = 0.f, s1 = 0.f;
                mbar_wait(bar_res, 0);
#pragma unroll
                for (int j = 0; j < BN / 8; j++) {
                    uint32_t xa, xb;
                    const uint32_t ra = res0 + (j >> 3) * 8192 + (((j & 7) ^ (rrow & 7)) << 4);
                    asm volatile("ld.shared.b32 %0, [%1];" : "=r"(xa) : "r"(ra));
                    asm volatile("ld.shared.b32 %0, [%1];" : "=r"(xb) : "r"(ra + 1024));
                    acc[4 * j + 0] = bf16_round(bf16_round(acc[4 * j + 0]) + __uint_as_float(xa << 16));
                    acc[4 * j + 1] = bf16_round(bf16_round(acc[4 * j + 1]) + __uint_as_float(xa & 0xFFFF0000u));
                    acc[4 * j + 2] = bf16_round(bf16_round(acc[4 * j + 2]) + __uint_as_float(xb << 16));
                    acc[4 * j + 3] = bf16_round(bf16_round(acc[4 * j + 3]) + __uint_as_float(xb & 0xFFFF0000u));
                    s0 += acc[4 * j + 0] + acc[4 * j + 1];
                    s1 += acc[4 * j + 2] + acc[4 * j + 3];
                }
                s0 += __shfl_xor_sync(0xffffffffu, s0, 1);
                s0 += __shfl_xor_sync(0xffffffffu, s0, 2);
                s1 += __shfl_xor_sync(0xffffffffu, s1, 1);
                s1 += __shfl_xor_sync(0xffffffffu, s1, 2);
                const float mu0 = s0 * (1.0f / BN), mu1 = s1 * (1.0f / BN);
                float q0 = 0.f, q1 = 0.f;
#pragma unroll
                for (int j = 0; j < BN / 8; j++) {
                    float d;
                    d = acc[4 * j + 0] - mu0; q0 += d * d;
                    d = acc[4 * j + 1] - mu0; q0 += d * d;
                    d = acc[4 * j + 2] - mu1; q1 += d * d;
                    d = acc[4 * j + 3] - mu1; q1 += d * d;
                }
                q0 += __shfl_xor_sync(0xffffffffu, q0, 1);
                q0 += __shfl_xor_sync(0xffffffffu, q0, 2);
                q1 += __shfl_xor_sync(0xffffffffu, q1, 1);
                q1 += __shfl_xor_sync(0xffffffffu, q1, 2);
                if ((lane & 3) == 0) {
                    static_assert(MODE != 2 || BN == 128, "stats layout assumes BN=128");
                    g_stat2[r0 * 8 + (n0 >> 7)] = make_float2(s0, q0);
                    g_stat2[r1 * 8 + (n0 >> 7)] = make_float2(s1, q1);
                }
            } else if (MODE == 3) {
                out_c0 = n0 + DM;
                named_bar_sync(3, 256);
#pragma unroll
                for (int j = 0; j < BN / 8; j++) {
                    float2 cs;
                    asm volatile("ld.shared.v2.f32 {%0, %1}, [%2];" : "=f"(cs.x), "=f"(cs.y) : "r"(sbase + L::CS_OFF + (8 * j + cq) * 4));
                    acc[4 * j + 0] = og[0] * gelu_tanh(rs[0] * fmaf(-mu[0], cs.x, acc[4 * j + 0]));
                    acc[4 * j + 1] = og[0] * gelu_tanh(rs[0] * fmaf(-mu[0], cs.y, acc[4 * j + 1]));
                    acc[4 * j + 2] = og[1] * gelu_tanh(rs[1] * fmaf(-mu[1], cs.x, acc[4 * j + 2]));
                    acc[4 * j + 3] = og[1] * gelu_tanh(rs[1] * fmaf(-mu[1], cs.y, acc[4 * j + 3]));
                }
                named_bar_sync(3, 256);
            } else {
                const float og0 = og[0], og1 = og[1];
                mbar_wait(bar_res, 0);
#pragma unroll
                for (int j = 0; j < BN / 8; j++) {
                    uint32_t xa, xb;
                    const uint32_t ra = res0 + (j >> 3) * 8192 + (((j & 7) ^ (rrow & 7)) << 4);
                    asm volatile("ld.shared.b32 %0, [%1];" : "=r"(xa) : "r"(ra));
                    asm volatile("ld.shared.b32 %0, [%1];" : "=r"(xb) : "r"(ra + 1024));
                    acc[4 * j + 0] = fmaf(og0, __uint_as_float(xa << 16), acc[4 * j + 0]);
                    acc[4 * j + 1] = fmaf(og0, __uint_as_float(xa & 0xFFFF0000u), acc[4 * j + 1]);
                    acc[4 * j + 2] = fmaf(og1, __uint_as_float(xb << 16), acc[4 * j + 2]);
                    acc[4 * j + 3] = fmaf(og1, __uint_as_float(xb & 0xFFFF0000u), acc[4 * j + 3]);
                }
            }
            PH(3)
            const int srow = warp * 16 + (lane & 7) + ((lane >> 3) & 1) * 8;
#pragma unroll
            for (int rnd = 0; rnd < (BN + 127) / 128; rnd++) {
                if (tid_wg == 0) bulk_wait_read0();
                named_bar_sync(1 + c, 128);
#pragma unroll
                for (int jj = 0; jj < 8; jj++) {
                    const int j = rnd * 16 + jj * 2;
                    if (j * 8 < BN) {
                        const int jb = jj * 2 + (lane >> 4);
                        uint32_t addr = stg + (jb >> 3) * 8192 + srow * 128 + (((jb & 7) ^ (srow & 7)) << 4);
                        if (rnd * 128 + 128 > BN && jj >= 4)
                            addr = stg + 8192 + srow * 64 + (((jb & 3) ^ ((srow >> 1) & 3)) << 4);
                        stmatrix_x4(addr, pack_bf16(acc[4 * j + 0], acc[4 * j + 1]), pack_bf16(acc[4 * j + 2], acc[4 * j + 3]),
                                    pack_bf16(acc[4 * j + 4], acc[4 * j + 5]), pack_bf16(acc[4 * j + 6], acc[4 * j + 7]));
                    }
                }
                fence_proxy_async();
                named_bar_sync(1 + c, 128);
                if (tid_wg == 0) {
                    tma_store_2d(mc, stg, out_c0 + rnd * 128, m0 + c * 64);
                    if (rnd * 128 + 64 < BN)
                        tma_store_2d((rnd * 128 + 128 > BN) ? &mC1 : mc, stg + 8192, out_c0 + rnd * 128 + 64, m0 + c * 64);
                    bulk_commit();
                }
            }
        }
        PH(4)
        if (tid_wg == 0) bulk_wait0();
        PH(5)
        TL_END(MODE)
    }
}

#define ATT_SPLIT 16
constexpr int ATT_NTILES = NH * 16;
#define ATT_GRID_N 512
constexpr int ATT_GRID = ATT_GRID_N;
constexpr int ATT_THREADS = 256;
constexpr int ATT_STAGES = 4;
constexpr int ATT_DIST = 2;
constexpr int ATT_Q_OFF = ATT_STAGES * 16384;
constexpr int ATT_ONES_OFF = ATT_Q_OFF + 8192;
constexpr int ATT_KEXT_OFF = ATT_ONES_OFF + 4096;
constexpr int ATT_QEXT_OFF = ATT_KEXT_OFF + 4096;
constexpr int ATT_BAR_OFF = ATT_QEXT_OFF + 8192;
constexpr int ATT_SMEM = ATT_BAR_OFF + 256 + 1024;

__device__ __forceinline__ void row_max(const float (&s)[32], float& m0, float& m1) {
    float a0[8], a1[8];
#pragma unroll
    for (int i = 0; i < 8; i++) {
        a0[i] = fmaxf(s[4 * i], s[4 * i + 1]);
        a1[i] = fmaxf(s[4 * i + 2], s[4 * i + 3]);
    }
#pragma unroll
    for (int w = 4; w > 0; w >>= 1)
#pragma unroll
        for (int i = 0; i < w; i++) { a0[i] = fmaxf(a0[i], a0[i + w]); a1[i] = fmaxf(a1[i], a1[i + w]); }
    float mx0 = a0[0], mx1 = a1[0];
    mx0 = fmaxf(mx0, __shfl_xor_sync(0xffffffffu, mx0, 1));
    mx1 = fmaxf(mx1, __shfl_xor_sync(0xffffffffu, mx1, 1));
    mx0 = fmaxf(mx0, __shfl_xor_sync(0xffffffffu, mx0, 2));
    mx1 = fmaxf(mx1, __shfl_xor_sync(0xffffffffu, mx1, 2));
    m0 = fmaxf(m0, mx0);
    m1 = fmaxf(m1, mx1);
}

__device__ __forceinline__ void attn_step(float (&s)[32], float (&o)[20], uint32_t dq, uint32_t dke, uint32_t dk_next,
                                          uint32_t dv_cur, uint32_t release_bar) {
    constexpr uint32_t HI = desc_hi(512, 2);
    uint32_t p[16];
#pragma unroll
    for (int i = 0; i < 16; i++) p[i] = pack_bf16(ex2(s[2 * i]), ex2(s[2 * i + 1]));
    wgmma_fence();
    wgmma_ss_n64_tb0(s, dq, HI, dk_next, HI, 0);
    wgmma_ss_n64_tb0(s, dq + 2, HI, dk_next + 2, HI, 1);
    wgmma_ss_n64_tb0(s, dq + ((ATT_QEXT_OFF - ATT_Q_OFF) >> 4), HI, dke, HI, 1);
#pragma unroll
    for (int t = 0; t < 4; t++)
        wgmma_rs_n40_tb1(o, p[4 * t], p[4 * t + 1], p[4 * t + 2], p[4 * t + 3], dv_cur + t * 64, HI, 1);
    wgmma_commit();
    wgmma_wait<0>();
    if (release_bar != 0 && (threadIdx.x & 127) == 0) mbar_arrive(release_bar);
}

__global__ void __launch_bounds__(256, 1)
attn_exact_kernel(const __grid_constant__ CUtensorMap mKV) {
    extern __shared__ uint8_t smem_raw[];
    pdl_launch();
    pdl_wait();
    int any = 0;
    for (int t = blockIdx.x; t < ATT_NTILES; t += gridDim.x) any |= g_bad[t];
    if (!any) return;
    constexpr int NBLK = S_LEN / 128;
    constexpr uint32_t HI = desc_hi(512, 2);
    const uint32_t sbase = (smem_u32(smem_raw) + 1023u) & ~1023u;
    const uint32_t bar = sbase + ATT_BAR_OFF;
    const int warp_id = threadIdx.x >> 5;
    const int lane = threadIdx.x & 31;
    const int cq = (lane & 3) * 2;
    const uint32_t dk0 = desc_lo(sbase, 16);
    const uint32_t dv0 = desc_lo(sbase + 8192, ATT_ONES_OFF - 8192);
    if (threadIdx.x == 0) {
        mbar_init(bar, 1);
        asm volatile("fence.mbarrier_init.release.cluster;" ::: "memory");
    }
    asm volatile("st.shared.v4.b32 [%0], {%1, %1, %1, %1};" ::"r"(sbase + ATT_ONES_OFF + threadIdx.x * 16), "r"(0x3F803F80u) : "memory");
    fence_proxy_async();
    __syncthreads();
#pragma unroll 1
    for (int tile = blockIdx.x; tile < ATT_NTILES; tile += gridDim.x) {
    if (g_bad[tile] == 0) continue;
    const int head = tile >> 4;
    const int row0 = (tile & 15) * 128 + warp_id * 16 + (lane >> 2);
    const uint32_t dq = desc_lo(sbase + ATT_Q_OFF + (threadIdx.x >> 7) * 4096, 16);
    float o[20];
#pragma unroll
    for (int i = 0; i < 20; i++) o[i] = 0.f;
    float m0 = -INFINITY, m1 = -INFINITY;
#pragma unroll 1
    for (int j = 0; j < NBLK; j++) {
        if (threadIdx.x == 0) {
            mbar_expect_tx(bar, j == 0 ? 3 * 8192 : 2 * 8192);
            if (j == 0) tma_load_2d(sbase + ATT_Q_OFF, &mKV, head * DH, (tile & 15) * 128, bar);
            tma_load_2d(sbase, &mKV, DM + head * DH, j * 128, bar);
            tma_load_2d(sbase + 8192, &mKV, 2 * DM + head * DH, j * 128, bar);
        }
        __syncwarp();
        mbar_wait(bar, j & 1);
#pragma unroll 1
        for (int hf = 0; hf < 2; hf++) {
            float s[32];
            wgmma_fence();
            wgmma_ss_n64_tb0(s, dq, HI, dk0 + hf * 256, HI, 0);
            wgmma_ss_n64_tb0(s, dq + 2, HI, dk0 + hf * 256 + 2, HI, 1);
            wgmma_commit();
            wgmma_wait<0>();
            const float mo0 = m0, mo1 = m1;
            row_max(s, m0, m1);
            const float a0 = ex2(mo0 - m0), a1 = ex2(mo1 - m1);
            uint32_t p[16];
#pragma unroll
            for (int i = 0; i < 8; i++) {
                p[2 * i] = pack_bf16(ex2(s[4 * i + 0] - m0), ex2(s[4 * i + 1] - m0));
                p[2 * i + 1] = pack_bf16(ex2(s[4 * i + 2] - m1), ex2(s[4 * i + 3] - m1));
            }
#pragma unroll
            for (int i = 0; i < 5; i++) {
                o[4 * i + 0] *= a0; o[4 * i + 1] *= a0;
                o[4 * i + 2] *= a1; o[4 * i + 3] *= a1;
            }
            wgmma_fence();
            const uint32_t dv = dv0 + hf * 256 - ((uint32_t)(hf * 256) << 16);
#pragma unroll
            for (int t = 0; t < 4; t++)
                wgmma_rs_n40_tb1(o, p[4 * t], p[4 * t + 1], p[4 * t + 2], p[4 * t + 3], dv + t * 64, HI, 1);
            wgmma_commit();
            wgmma_wait<0>();
        }
        __syncthreads();
    }
    const float f0 = g_gate[row0] / o[16], f1 = g_gate[row0 + 8] / o[18];
    bf16* op0 = g_a5 + (size_t)row0 * A5W + head * DH + cq;
    bf16* op1 = op0 + 8 * A5W;
#pragma unroll
    for (int i = 0; i < 4; i++) {
        *reinterpret_cast<uint32_t*>(op0 + 8 * i) = pack_bf16(o[4 * i] * f0, o[4 * i + 1] * f0);
        *reinterpret_cast<uint32_t*>(op1 + 8 * i) = pack_bf16(o[4 * i + 2] * f1, o[4 * i + 3] * f1);
    }
    }
}

#define ATT_MINB 2
__global__ void __launch_bounds__(256, ATT_MINB)
attn_kernel(const __grid_constant__ CUtensorMap mKV) {
    extern __shared__ uint8_t smem_raw[];
    const uint32_t sbase = (smem_u32(smem_raw) + 1023u) & ~1023u;
    const uint32_t bar_kfull = sbase + ATT_BAR_OFF;
    const uint32_t bar_vfull = bar_kfull + 8 * ATT_STAGES;
    const uint32_t bar_empty = bar_vfull + 8 * ATT_STAGES;
    const int tile = blockIdx.x;
    const int head = tile >> 4;
    const int lane = threadIdx.x & 31;
    constexpr int NBLK = S_LEN / 128;
    TL_START(6)
    pdl_launch();

    auto issue_kv = [&](int g) {
        const int sn = g % ATT_STAGES;
        if (g >= ATT_STAGES) mbar_wait(bar_empty + 8 * sn, ((g / ATT_STAGES) - 1) & 1);
        const uint32_t skn = sbase + sn * 16384;
        mbar_expect_tx(bar_kfull + 8 * sn, g == 0 ? 16384 : 8192);
        if (g == 0) tma_load_2d(sbase + ATT_Q_OFF, &mKV, head * DH, (tile & 15) * 128, bar_kfull);
        tma_load_2d(skn, &mKV, DM + head * DH, g * 128, bar_kfull + 8 * sn);
        mbar_expect_tx(bar_vfull + 8 * sn, 8192);
        tma_load_2d(skn + 8192, &mKV, 2 * DM + head * DH, g * 128, bar_vfull + 8 * sn);
    };

    if (threadIdx.x == 0) {
        for (int s = 0; s < ATT_STAGES; s++) {
            mbar_init(bar_kfull + 8 * s, 1);
            mbar_init(bar_vfull + 8 * s, 1);
            mbar_init(bar_empty + 8 * s, 2);
        }
        asm volatile("fence.mbarrier_init.release.cluster;" ::: "memory");
        prefetch_tmap(&mKV);
        pdl_wait();
#pragma unroll
        for (int j = 0; j < ATT_DIST; j++) issue_kv(j);
    }
    {
        asm volatile("st.shared.v4.b32 [%0], {%1, %1, %1, %1};" ::"r"(sbase + ATT_ONES_OFF + threadIdx.x * 16), "r"(0x3F803F80u) : "memory");
        const int r = threadIdx.x >> 2, ch = threadIdx.x & 3;
        const uint32_t w0 = (ch == ((r >> 1) & 3)) ? 0x00003F80u : 0u;
        asm volatile("st.shared.v4.b32 [%0], {%1, %2, %2, %2};" ::"r"(sbase + ATT_KEXT_OFF + threadIdx.x * 16), "r"(w0), "r"(0u) : "memory");
        asm volatile("st.shared.v4.b32 [%0], {%1, %1, %1, %1};" ::"r"(sbase + ATT_QEXT_OFF + threadIdx.x * 16), "r"(0u) : "memory");
        asm volatile("st.shared.v4.b32 [%0], {%1, %1, %1, %1};" ::"r"(sbase + ATT_QEXT_OFF + 4096 + threadIdx.x * 16), "r"(0u) : "memory");
    }
    fence_proxy_async();
    __syncthreads();

    constexpr uint32_t HI = desc_hi(512, 2);
    const uint32_t dk0 = desc_lo(sbase, 16);
    const uint32_t dv0 = desc_lo(sbase + 8192, ATT_ONES_OFF - 8192);
    const uint32_t dke = dk0 + (ATT_KEXT_OFF >> 4);
    const uint32_t dq = dk0 + ((ATT_Q_OFF + (threadIdx.x >> 7) * 4096) >> 4);
    float o[20];
#pragma unroll
    for (int i = 0; i < 20; i++) o[i] = 0.f;
    float s0[32];
    mbar_wait(bar_kfull, 0);
    wgmma_fence();
    wgmma_ss_n64_tb0(s0, dq, HI, dk0, HI, 0);
    wgmma_ss_n64_tb0(s0, dq + 2, HI, dk0 + 2, HI, 1);
    wgmma_commit();
    wgmma_wait<0>();
    float m0 = -INFINITY, m1 = -INFINITY;
    row_max(s0, m0, m1);
    if ((lane & 3) == 0) {
        const int r = ((threadIdx.x >> 5) & 3) * 16 + (lane >> 2);
        const uint32_t qe = sbase + ATT_QEXT_OFF + (threadIdx.x >> 7) * 4096;
        asm volatile("st.shared.b16 [%0], %1;" ::"r"(qe + r * 64 + (((r >> 1) & 3) << 4)), "h"((uint16_t)(pack_bf16(-m0, 0.f) & 0xFFFFu)) : "memory");
        asm volatile("st.shared.b16 [%0], %1;" ::"r"(qe + (r + 8) * 64 + ((((r + 8) >> 1) & 3) << 4)), "h"((uint16_t)(pack_bf16(-m1, 0.f) & 0xFFFFu)) : "memory");
    }
    fence_proxy_async();
    named_bar_sync(1 + (threadIdx.x >> 7), 128);
    wgmma_fence();
    wgmma_ss_n64_tb0(s0, dq + ((ATT_QEXT_OFF - ATT_Q_OFF) >> 4), HI, dke, HI, 1);
    wgmma_commit();
    wgmma_wait<0>();
#pragma unroll 1
    for (int j = 0; j < NBLK; j++) {
        if (threadIdx.x == 0 && j + ATT_DIST < NBLK) issue_kv(j + ATT_DIST);
        __syncwarp();
        const uint32_t stage = j & (ATT_STAGES - 1), nstage = (j + 1) & (ATT_STAGES - 1);
        const uint32_t dk = dk0 + stage * 1024;
        const uint32_t dv = dv0 + stage * 1024 - (stage << 26);
        mbar_wait(bar_vfull + 8 * stage, (j / ATT_STAGES) & 1);
        attn_step(s0, o, dq, dke, dk + 256, dv, 0u);
        uint32_t dkn = dk;
        if (j + 1 < NBLK) {
            mbar_wait(bar_kfull + 8 * nstage, ((j + 1) / ATT_STAGES) & 1);
            dkn = dk0 + nstage * 1024;
        }
        attn_step(s0, o, dq, dke, dkn, dv + 256 - (256u << 16), bar_empty + 8 * stage);
    }
    bool ok = (o[16] <= 1.8446744e19f) && (o[18] <= 1.8446744e19f);
#pragma unroll
    for (int i = 0; i < 16; i++) ok = ok && (fabsf(o[i]) <= 3.0e38f);
    const int row0 = (tile & 15) * 128 + (threadIdx.x >> 5) * 16 + (lane >> 2);
    const float f0 = g_gate[row0] / o[16], f1 = g_gate[row0 + 8] / o[18];
    bf16* op0 = g_a5 + (size_t)row0 * A5W + head * DH + (lane & 3) * 2;
    bf16* op1 = op0 + 8 * A5W;
#pragma unroll
    for (int i = 0; i < 4; i++) {
        *reinterpret_cast<uint32_t*>(op0 + 8 * i) = pack_bf16(o[4 * i] * f0, o[4 * i + 1] * f0);
        *reinterpret_cast<uint32_t*>(op1 + 8 * i) = pack_bf16(o[4 * i + 2] * f1, o[4 * i + 3] * f1);
    }
    const int bad = __syncthreads_or(!ok);
    if (threadIdx.x == 0) g_bad[tile] = bad;
    TL_END(6)
}

typedef CUresult (*EncodeFn)(CUtensorMap*, CUtensorMapDataType, cuuint32_t, void*, const cuuint64_t*, const cuuint64_t*,
                             const cuuint32_t*, const cuuint32_t*, CUtensorMapInterleave, CUtensorMapSwizzle,
                             CUtensorMapL2promotion, CUtensorMapFloatOOBfill);

static CUtensorMap make_map(EncodeFn fn, const void* ptr, int rows, int cols, int box_cols, int box_rows,
                            CUtensorMapSwizzle swz) {
    CUtensorMap m;
    cuuint64_t dims[2] = {(cuuint64_t)cols, (cuuint64_t)rows};
    cuuint64_t strides[1] = {(cuuint64_t)cols * 2};
    cuuint32_t box[2] = {(cuuint32_t)box_cols, (cuuint32_t)box_rows};
    cuuint32_t es[2] = {1, 1};
    fn(&m, CU_TENSOR_MAP_DATA_TYPE_BFLOAT16, 2, const_cast<void*>(ptr), dims, strides, box, es,
       CU_TENSOR_MAP_INTERLEAVE_NONE, swz, CU_TENSOR_MAP_L2_PROMOTION_L2_256B, CU_TENSOR_MAP_FLOAT_OOB_FILL_NONE);
    return m;
}

template <typename... KArgs, typename... Args>
static void launch_ex(void (*kern)(KArgs...), int grid, int block, int smem, cudaStream_t st, int cluster, int pdl, Args... args) {
    cudaLaunchConfig_t cfg = {};
    cfg.gridDim = dim3(grid);
    cfg.blockDim = dim3(block);
    cfg.dynamicSmemBytes = smem;
    cfg.stream = st;
    cudaLaunchAttribute at[2];
    at[0].id = cudaLaunchAttributeProgrammaticStreamSerialization;
    at[0].val.programmaticStreamSerializationAllowed = pdl;
    at[1].id = cudaLaunchAttributeClusterDimension;
    at[1].val.clusterDim.x = cluster;
    at[1].val.clusterDim.y = 1;
    at[1].val.clusterDim.z = 1;
    cfg.attrs = at;
    cfg.numAttrs = cluster > 1 ? 2 : 1;
    cudaLaunchKernelEx(&cfg, kern, KArgs(args)...);
}

extern "C" void kernel_launch(void* const* d_in, const int* in_sizes, int n_in, void* d_out, int out_size) {
    const bf16* x = (const bf16*)d_in[0];
    const bf16* wqkv = (const bf16*)d_in[1];
    const bf16* wo = (const bf16*)d_in[2];
    const bf16* w1 = (const bf16*)d_in[4];
    const bf16* w2 = (const bf16*)d_in[5];
    const bf16* w3 = (const bf16*)d_in[6];
    const bf16* w4 = (const bf16*)d_in[7];
    const bf16* gate_w = (const bf16*)d_in[8];

    static EncodeFn enc = nullptr;
    static void *p_qkv, *p_h, *p_x1, *p_a5, *p_cs1, *p_cs3;
    static cudaStream_t s2;
    static cudaEvent_t ev_fork, ev_join;
    using G1 = GemmSmem<256, 4>;
    using G2 = GemmSmem<128, 5>;
#define G3BN 256
    using G3 = GemmSmem<G3BN, 4>;
    if (!enc) {
        void* fn = nullptr;
        cudaDriverEntryPointQueryResult qres;
        cudaGetDriverEntryPoint("cuTensorMapEncodeTiled", &fn, cudaEnableDefault, &qres);
        enc = (EncodeFn)fn;
        cudaGetSymbolAddress(&p_qkv, g_qkv);
        cudaGetSymbolAddress(&p_h, g_h);
        cudaGetSymbolAddress(&p_x1, g_x1);
        cudaGetSymbolAddress(&p_a5, g_a5);
        cudaGetSymbolAddress(&p_cs1, g_cs1);
        cudaGetSymbolAddress(&p_cs3, g_cs3);
        cudaFuncSetAttribute(gemm_kernel<1, 256, 4>, cudaFuncAttributeMaxDynamicSharedMemorySize, G1::TOTAL);
        cudaFuncSetAttribute(gemm_kernel<2, 128, 5>, cudaFuncAttributeMaxDynamicSharedMemorySize, G2::TOTAL);
        cudaFuncSetAttribute(gemm_kernel<3, G3BN, 4>, cudaFuncAttributeMaxDynamicSharedMemorySize, G3::TOTAL);
        cudaFuncSetAttribute(gemm_kernel<5, 128, 5>, cudaFuncAttributeMaxDynamicSharedMemorySize, G2::TOTAL);
        cudaStreamCreateWithFlags(&s2, cudaStreamNonBlocking);
        cudaEventCreateWithFlags(&ev_fork, cudaEventDisableTiming);
        cudaEventCreateWithFlags(&ev_join, cudaEventDisableTiming);
        cudaFuncSetAttribute(attn_kernel, cudaFuncAttributeMaxDynamicSharedMemorySize, ATT_SMEM);
        cudaFuncSetAttribute(attn_exact_kernel, cudaFuncAttributeMaxDynamicSharedMemorySize, ATT_SMEM);
    }
    const CUtensorMapSwizzle SW128 = CU_TENSOR_MAP_SWIZZLE_128B, SW64 = CU_TENSOR_MAP_SWIZZLE_64B;
    CUtensorMap mX = make_map(enc, x, S_LEN, DM, 64, 128, SW128);
    CUtensorMap mXres = make_map(enc, x, S_LEN, DM, 64, 64, SW128);
    CUtensorMap mWqkv = make_map(enc, wqkv, DM, 3 * DM, 64, 64, SW128);
    CUtensorMap mW1 = make_map(enc, w1, DM, DM, 64, 64, SW128);
    CUtensorMap mW2 = make_map(enc, w2, DM, DM, 64, 64, SW128);
    CUtensorMap mW3 = make_map(enc, w3, DM, FF, 64, 64, SW128);
    CUtensorMap mW4 = make_map(enc, w4, FF, DM, 64, 64, SW128);
    CUtensorMap mWo = make_map(enc, wo, DM, DM, 64, 64, SW128);
    CUtensorMap mQKVst = make_map(enc, p_qkv, S_LEN, 3 * DM, 64, 64, SW128);
    CUtensorMap mKV = make_map(enc, p_qkv, S_LEN, 3 * DM, 32, 128, SW64);
    CUtensorMap mHst = make_map(enc, p_h, S_LEN, DM, 64, 64, SW128);
    CUtensorMap mHld = make_map(enc, p_h, S_LEN, DM, 64, 128, SW128);
    CUtensorMap mX1st = make_map(enc, p_x1, S_LEN, DM, 64, 64, SW128);
    CUtensorMap mX1ld = make_map(enc, p_x1, S_LEN, DM, 64, 128, SW128);
    CUtensorMap mA5st = make_map(enc, p_a5, S_LEN, A5W, 64, 64, SW128);
    CUtensorMap mA5st32 = make_map(enc, p_a5, S_LEN, A5W, 32, 64, SW64);
    CUtensorMap mA5ld = make_map(enc, p_a5, S_LEN, A5W, 64, 128, SW128);
    CUtensorMap mOut = make_map(enc, d_out, S_LEN, DM, 64, 64, SW128);

    cudaStream_t st = cudaStreamPerThread;
    prep_kernel<<<256 + 64 + 224, 256, 0, st>>>(x, gate_w, w1, w3);
    launch_ex(gemm_kernel<1, 256, 4>, 132, 384, G1::TOTAL, st, 1, 1, mX, mWqkv, mW1, mQKVst, mHst, x, 16, 16);
    launch_ex(gemm_kernel<2, 128, 5>, 128, 384, G2::TOTAL, st, 1, 1, mHld, mW2, mW2, mX1st, mXres, x, 8, 16);
    cudaEventRecord(ev_fork, st);
    launch_ex(attn_kernel, ATT_GRID, ATT_THREADS, ATT_SMEM, st, 1, 1, mKV);
    launch_ex(attn_exact_kernel, 32, ATT_THREADS, ATT_SMEM, st, 1, 1, mKV);
    cudaStreamWaitEvent(s2, ev_fork, 0);
    launch_ex(gemm_kernel<3, G3BN, 4>, 132, 384, G3::TOTAL, s2, 1, 0, mX1ld, mW3, mW3, mA5st, mA5st32, x, FF / G3BN, 16);
    cudaEventRecord(ev_join, s2);
    cudaStreamWaitEvent(st, ev_join, 0);
    launch_ex(gemm_kernel<5, 128, 5>, 128, 384, G2::TOTAL, st, 1, 0, mA5ld, mWo, mW4, mOut, mX1st, (const bf16*)p_x1, 8, 72);
}
```

```cpp
#include <cuda_runtime.h>
#include <cuda_bf16.h>
#include <cuda.h>
#include <stdint.h>

typedef __nv_bfloat16 bf16;

constexpr int S_LEN = 2048;
constexpr int DM = 1024;
constexpr int FF = 3584;
constexpr int NH = 32;
constexpr int DH = 32;
constexpr int A5W = DM + FF;

__device__ __align__(1024) bf16 g_qkv[S_LEN * 3 * DM];
__device__ __align__(1024) bf16 g_h[S_LEN * DM];
__device__ __align__(1024) bf16 g_x1[S_LEN * DM];
__device__ __align__(1024) bf16 g_a5[S_LEN * A5W];
__device__ __align__(16) float g_mean1[S_LEN];
__device__ __align__(16) float g_rstd1[S_LEN];
__device__ __align__(16) float g_gate[S_LEN];
__device__ __align__(16) float g_omg[S_LEN];
__device__ __align__(16) float g_cs1[4 * DM];
__device__ __align__(16) float g_cs3[4 * FF];
__device__ __align__(16) float2 g_stat2[S_LEN * 8];
__device__ int g_bad[NH * 16];
__device__ int g_tile_ctr;

#define TL_START(k)
#define PH(i)
#define TL_END(k)

__device__ __forceinline__ uint32_t smem_u32(const void* p) { return (uint32_t)__cvta_generic_to_shared(p); }

__device__ __forceinline__ void mbar_init(uint32_t bar, uint32_t count) {
    asm volatile("mbarrier.init.shared::cta.b64 [%0], %1;" ::"r"(bar), "r"(count));
}
__device__ __forceinline__ void mbar_expect_tx(uint32_t bar, uint32_t bytes) {
    asm volatile("mbarrier.arrive.expect_tx.shared::cta.b64 _, [%0], %1;" ::"r"(bar), "r"(bytes) : "memory");
}
__device__ __forceinline__ void mbar_arrive(uint32_t bar) {
    asm volatile("mbarrier.arrive.shared::cta.b64 _, [%0];" ::"r"(bar) : "memory");
}
__device__ __forceinline__ bool mbar_try_wait(uint32_t bar, uint32_t parity) {
    uint32_t ok;
    asm volatile(
        "{\n.reg .pred p;\n"
        "mbarrier.try_wait.parity.shared::cta.b64 p, [%1], %2;\n"
        "selp.u32 %0, 1, 0, p;\n}\n"
        : "=r"(ok)
        : "r"(bar), "r"(parity)
        : "memory");
    return ok != 0;
}
__device__ __forceinline__ void mbar_wait(uint32_t bar, uint32_t parity) {
    uint32_t spins = 0;
    while (!mbar_try_wait(bar, parity)) {
        if (++spins > (1u << 24)) __trap();
    }
}
__device__ __forceinline__ void tma_load_2d(uint32_t dst, const CUtensorMap* map, int c0, int c1, uint32_t bar) {
    asm volatile(
        "cp.async.bulk.tensor.2d.shared::cluster.global.mbarrier::complete_tx::bytes [%0], [%1, {%3, %4}], [%2];"
        ::"r"(dst), "l"(map), "r"(bar), "r"(c0), "r"(c1)
        : "memory");
}
__device__ __forceinline__ void tma_store_2d(const CUtensorMap* map, uint32_t src, int c0, int c1) {
    asm volatile("cp.async.bulk.tensor.2d.global.shared::cta.bulk_group [%0, {%2, %3}], [%1];"
                 ::"l"(map), "r"(src), "r"(c0), "r"(c1)
                 : "memory");
}
__device__ __forceinline__ void tma_load_2d_mc(uint32_t dst, const CUtensorMap* map, int c0, int c1, uint32_t bar, uint16_t mask) {
    asm volatile(
        "cp.async.bulk.tensor.2d.shared::cluster.global.mbarrier::complete_tx::bytes.multicast::cluster [%0], [%1, {%3, %4}], [%2], %5;"
        ::"r"(dst), "l"(map), "r"(bar), "r"(c0), "r"(c1), "h"(mask)
        : "memory");
}
__device__ __forceinline__ void mbar_arrive_cluster(uint32_t bar, uint32_t cta) {
    asm volatile(
        "{\n.reg .b32 ra;\nmapa.shared::cluster.u32 ra, %0, %1;\n"
        "mbarrier.arrive.shared::cluster.b64 _, [ra];\n}\n" ::"r"(bar), "r"(cta)
        : "memory");
}
__device__ __forceinline__ void cluster_sync_all() {
    asm volatile("barrier.cluster.arrive.release.aligned;\nbarrier.cluster.wait.acquire.aligned;" ::: "memory");
}
__device__ __forceinline__ uint32_t cluster_rank() { uint32_t r; asm volatile("mov.u32 %0, %%cluster_ctarank;" : "=r"(r)); return r; }
__device__ __forceinline__ void pdl_wait() { asm volatile("griddepcontrol.wait;" ::: "memory"); }
__device__ __forceinline__ void pdl_launch() { asm volatile("griddepcontrol.launch_dependents;" ::: "memory"); }
__device__ __forceinline__ void bulk_commit() { asm volatile("cp.async.bulk.commit_group;" ::: "memory"); }
__device__ __forceinline__ void bulk_wait_read0() { asm volatile("cp.async.bulk.wait_group.read 0;" ::: "memory"); }
__device__ __forceinline__ void bulk_wait0() { asm volatile("cp.async.bulk.wait_group 0;" ::: "memory"); }
__device__ __forceinline__ void fence_proxy_async() { asm volatile("fence.proxy.async.shared::cta;" ::: "memory"); }
__device__ __forceinline__ void named_bar_sync(int id, int n) { asm volatile("bar.sync %0, %1;" ::"r"(id), "r"(n) : "memory"); }
__device__ __forceinline__ void named_bar_arrive(int id, int n) { asm volatile("bar.arrive %0, %1;" ::"r"(id), "r"(n) : "memory"); }
__device__ __forceinline__ void wgmma_fence() { asm volatile("wgmma.fence.sync.aligned;" ::: "memory"); }
__device__ __forceinline__ void wgmma_commit() { asm volatile("wgmma.commit_group.sync.aligned;" ::: "memory"); }
template <int N>
__device__ __forceinline__ void wgmma_wait() { asm volatile("wgmma.wait_group.sync.aligned %0;" ::"n"(N) : "memory"); }
__device__ __forceinline__ void prefetch_tmap(const CUtensorMap* m) {
    asm volatile("prefetch.tensormap [%0];" ::"l"(m) : "memory");
}
template <int R>
__device__ __forceinline__ void reg_alloc() { asm volatile("setmaxnreg.inc.sync.aligned.u32 %0;" ::"n"(R)); }
template <int R>
__device__ __forceinline__ void reg_dealloc() { asm volatile("setmaxnreg.dec.sync.aligned.u32 %0;" ::"n"(R)); }
__device__ __forceinline__ void stmatrix_x4(uint32_t addr, uint32_t r0, uint32_t r1, uint32_t r2, uint32_t r3) {
    asm volatile("stmatrix.sync.aligned.m8n8.x4.shared.b16 [%0], {%1, %2, %3, %4};"
                 ::"r"(addr), "r"(r0), "r"(r1), "r"(r2), "r"(r3)
                 : "memory");
}
__device__ __forceinline__ uint32_t pack_bf16(float lo, float hi) {
    uint32_t r;
    asm("cvt.rn.bf16x2.f32 %0, %1, %2;" : "=r"(r) : "f"(hi), "f"(lo));
    return r;
}
__device__ __forceinline__ float bf16_round(float v) { return __bfloat162float(__float2bfloat16_rn(v)); }
__device__ __forceinline__ float ex2(float x) {
    float y;
    asm volatile("ex2.approx.ftz.f32 %0, %1;" : "=f"(y) : "f"(x));
    return y;
}
__device__ __forceinline__ float tanh_fast(float x) {
    float y;
    asm("tanh.approx.f32 %0, %1;" : "=f"(y) : "f"(x));
    return y;
}
__device__ __forceinline__ float gelu_tanh(float v) {
    float u = 0.7978845608028654f * (v + 0.044715f * v * v * v);
    float hv = 0.5f * v;
    return fmaf(hv, tanh_fast(u), hv);
}
__device__ __forceinline__ uint32_t desc_lo(uint32_t addr, uint32_t lbo_bytes) {
    return ((addr & 0x3FFFF) >> 4) | (((lbo_bytes >> 4) & 0x3FFF) << 16);
}
__host__ __device__ constexpr uint32_t desc_hi(uint32_t sbo_bytes, uint32_t swz) {
    return ((sbo_bytes >> 4) & 0x3FFF) | (swz << 30);
}

__device__ __forceinline__ void wgmma_ss_n128_tb1(float (&d)[64], uint32_t alo, uint32_t ahi, uint32_t blo, uint32_t bhi, int scale_d) {
    asm volatile("{\n.reg .pred p;\n.reg .b64 da, db;\nsetp.ne.b32 p, %68, 0;\nmov.b64 da, {%64, %65};\nmov.b64 db, {%66, %67};\n"
        "wgmma.mma_async.sync.aligned.m64n128k16.f32.bf16.bf16 {%0, %1, %2, %3, %4, %5, %6, %7, %8, %9, %10, %11, %12, %13, %14, %15, %16, %17, %18, %19, %20, %21, %22, %23, %24, %25, %26, %27, %28, %29, %30, %31, %32, %33, %34, %35, %36, %37, %38, %39, %40, %41, %42, %43, %44, %45, %46, %47, %48, %49, %50, %51, %52, %53, %54, %55, %56, %57, %58, %59, %60, %61, %62, %63}, da, db, p, 1, 1, 0, 1;\n}\n"
        : "+f"(d[0]), "+f"(d[1]), "+f"(d[2]), "+f"(d[3]), "+f"(d[4]), "+f"(d[5]), "+f"(d[6]), "+f"(d[7]), "+f"(d[8]), "+f"(d[9]), "+f"(d[10]), "+f"(d[11]), "+f"(d[12]), "+f"(d[13]), "+f"(d[14]), "+f"(d[15]), "+f"(d[16]), "+f"(d[17]), "+f"(d[18]), "+f"(d[19]), "+f"(d[20]), "+f"(d[21]), "+f"(d[22]), "+f"(d[23]), "+f"(d[24]), "+f"(d[25]), "+f"(d[26]), "+f"(d[27]), "+f"(d[28]), "+f"(d[29]), "+f"(d[30]), "+f"(d[31]), "+f"(d[32]), "+f"(d[33]), "+f"(d[34]), "+f"(d[35]), "+f"(d[36]), "+f"(d[37]), "+f"(d[38]), "+f"(d[39]), "+f"(d[40]), "+f"(d[41]), "+f"(d[42]), "+f"(d[43]), "+f"(d[44]), "+f"(d[45]), "+f"(d[46]), "+f"(d[47]), "+f"(d[48]), "+f"(d[49]), "+f"(d[50]), "+f"(d[51]), "+f"(d[52]), "+f"(d[53]), "+f"(d[54]), "+f"(d[55]), "+f"(d[56]), "+f"(d[57]), "+f"(d[58]), "+f"(d[59]), "+f"(d[60]), "+f"(d[61]), "+f"(d[62]), "+f"(d[63])
        : "r"(alo), "r"(ahi), "r"(blo), "r"(bhi), "r"(scale_d));
}

__device__ __forceinline__ void wgmma_ss_n192_tb1(float (&d)[96], uint32_t alo, uint32_t ahi, uint32_t blo, uint32_t bhi, int scale_d) {
    asm volatile("{\n.reg .pred p;\n.reg .b64 da, db;\nsetp.ne.b32 p, %100, 0;\nmov.b64 da, {%96, %97};\nmov.b64 db, {%98, %99};\n"
        "wgmma.mma_async.sync.aligned.m64n192k16.f32.bf16.bf16 {%0, %1, %2, %3, %4, %5, %6, %7, %8, %9, %10, %11, %12, %13, %14, %15, %16, %17, %18, %19, %20, %21, %22, %23, %24, %25, %26, %27, %28, %29, %30, %31, %32, %33, %34, %35, %36, %37, %38, %39, %40, %41, %42, %43, %44, %45, %46, %47, %48, %49, %50, %51, %52, %53, %54, %55, %56, %57, %58, %59, %60, %61, %62, %63, %64, %65, %66, %67, %68, %69, %70, %71, %72, %73, %74, %75, %76, %77, %78, %79, %80, %81, %82, %83, %84, %85, %86, %87, %88, %89, %90, %91, %92, %93, %94, %95}, da, db, p, 1, 1, 0, 1;\n}\n"
        : "+f"(d[0]), "+f"(d[1]), "+f"(d[2]), "+f"(d[3]), "+f"(d[4]), "+f"(d[5]), "+f"(d[6]), "+f"(d[7]), "+f"(d[8]), "+f"(d[9]), "+f"(d[10]), "+f"(d[11]), "+f"(d[12]), "+f"(d[13]), "+f"(d[14]), "+f"(d[15]), "+f"(d[16]), "+f"(d[17]), "+f"(d[18]), "+f"(d[19]), "+f"(d[20]), "+f"(d[21]), "+f"(d[22]), "+f"(d[23]), "+f"(d[24]), "+f"(d[25]), "+f"(d[26]), "+f"(d[27]), "+f"(d[28]), "+f"(d[29]), "+f"(d[30]), "+f"(d[31]), "+f"(d[32]), "+f"(d[33]), "+f"(d[34]), "+f"(d[35]), "+f"(d[36]), "+f"(d[37]), "+f"(d[38]), "+f"(d[39]), "+f"(d[40]), "+f"(d[41]), "+f"(d[42]), "+f"(d[43]), "+f"(d[44]), "+f"(d[45]), "+f"(d[46]), "+f"(d[47]), "+f"(d[48]), "+f"(d[49]), "+f"(d[50]), "+f"(d[51]), "+f"(d[52]), "+f"(d[53]), "+f"(d[54]), "+f"(d[55]), "+f"(d[56]), "+f"(d[57]), "+f"(d[58]), "+f"(d[59]), "+f"(d[60]), "+f"(d[61]), "+f"(d[62]), "+f"(d[63]), "+f"(d[64]), "+f"(d[65]), "+f"(d[66]), "+f"(d[67]), "+f"(d[68]), "+f"(d[69]), "+f"(d[70]), "+f"(d[71]), "+f"(d[72]), "+f"(d[73]), "+f"(d[74]), "+f"(d[75]), "+f"(d[76]), "+f"(d[77]), "+f"(d[78]), "+f"(d[79]), "+f"(d[80]), "+f"(d[81]), "+f"(d[82]), "+f"(d[83]), "+f"(d[84]), "+f"(d[85]), "+f"(d[86]), "+f"(d[87]), "+f"(d[88]), "+f"(d[89]), "+f"(d[90]), "+f"(d[91]), "+f"(d[92]), "+f"(d[93]), "+f"(d[94]), "+f"(d[95])
        : "r"(alo), "r"(ahi), "r"(blo), "r"(bhi), "r"(scale_d));
}

__device__ __forceinline__ void wgmma_ss_n224_tb1(float (&d)[112], uint32_t alo, uint32_t ahi, uint32_t blo, uint32_t bhi, int scale_d) {
    asm volatile("{\n.reg .pred p;\n.reg .b64 da, db;\nsetp.ne.b32 p, %116, 0;\nmov.b64 da, {%112, %113};\nmov.b64 db, {%114, %115};\n"
        "wgmma.mma_async.sync.aligned.m64n224k16.f32.bf16.bf16 {%0, %1, %2, %3, %4, %5, %6, %7, %8, %9, %10, %11, %12, %13, %14, %15, %16, %17, %18, %19, %20, %21, %22, %23, %24, %25, %26, %27, %28, %29, %30, %31, %32, %33, %34, %35, %36, %37, %38, %39, %40, %41, %42, %43, %44, %45, %46, %47, %48, %49, %50, %51, %52, %53, %54, %55, %56, %57, %58, %59, %60, %61, %62, %63, %64, %65, %66, %67, %68, %69, %70, %71, %72, %73, %74, %75, %76, %77, %78, %79, %80, %81, %82, %83, %84, %85, %86, %87, %88, %89, %90, %91, %92, %93, %94, %95, %96, %97, %98, %99, %100, %101, %102, %103, %104, %105, %106, %107, %108, %109, %110, %111}, da, db, p, 1, 1, 0, 1;\n}\n"
        : "+f"(d[0]), "+f"(d[1]), "+f"(d[2]), "+f"(d[3]), "+f"(d[4]), "+f"(d[5]), "+f"(d[6]), "+f"(d[7]), "+f"(d[8]), "+f"(d[9]), "+f"(d[10]), "+f"(d[11]), "+f"(d[12]), "+f"(d[13]), "+f"(d[14]), "+f"(d[15]), "+f"(d[16]), "+f"(d[17]), "+f"(d[18]), "+f"(d[19]), "+f"(d[20]), "+f"(d[21]), "+f"(d[22]), "+f"(d[23]), "+f"(d[24]), "+f"(d[25]), "+f"(d[26]), "+f"(d[27]), "+f"(d[28]), "+f"(d[29]), "+f"(d[30]), "+f"(d[31]), "+f"(d[32]), "+f"(d[33]), "+f"(d[34]), "+f"(d[35]), "+f"(d[36]), "+f"(d[37]), "+f"(d[38]), "+f"(d[39]), "+f"(d[40]), "+f"(d[41]), "+f"(d[42]), "+f"(d[43]), "+f"(d[44]), "+f"(d[45]), "+f"(d[46]), "+f"(d[47]), "+f"(d[48]), "+f"(d[49]), "+f"(d[50]), "+f"(d[51]), "+f"(d[52]), "+f"(d[53]), "+f"(d[54]), "+f"(d[55]), "+f"(d[56]), "+f"(d[57]), "+f"(d[58]), "+f"(d[59]), "+f"(d[60]), "+f"(d[61]), "+f"(d[62]), "+f"(d[63]), "+f"(d[64]), "+f"(d[65]), "+f"(d[66]), "+f"(d[67]), "+f"(d[68]), "+f"(d[69]), "+f"(d[70]), "+f"(d[71]), "+f"(d[72]), "+f"(d[73]), "+f"(d[74]), "+f"(d[75]), "+f"(d[76]), "+f"(d[77]), "+f"(d[78]), "+f"(d[79]), "+f"(d[80]), "+f"(d[81]), "+f"(d[82]), "+f"(d[83]), "+f"(d[84]), "+f"(d[85]), "+f"(d[86]), "+f"(d[87]), "+f"(d[88]), "+f"(d[89]), "+f"(d[90]), "+f"(d[91]), "+f"(d[92]), "+f"(d[93]), "+f"(d[94]), "+f"(d[95]), "+f"(d[96]), "+f"(d[97]), "+f"(d[98]), "+f"(d[99]), "+f"(d[100]), "+f"(d[101]), "+f"(d[102]), "+f"(d[103]), "+f"(d[104]), "+f"(d[105]), "+f"(d[106]), "+f"(d[107]), "+f"(d[108]), "+f"(d[109]), "+f"(d[110]), "+f"(d[111])
        : "r"(alo), "r"(ahi), "r"(blo), "r"(bhi), "r"(scale_d));
}

__device__ __forceinline__ void wgmma_ss_n256_tb1(float (&d)[128], uint32_t alo, uint32_t ahi, uint32_t blo, uint32_t bhi, int scale_d) {
    asm volatile("{\n.reg .pred p;\n.reg .b64 da, db;\nsetp.ne.b32 p, %132, 0;\nmov.b64 da, {%128, %129};\nmov.b64 db, {%130, %131};\n"
        "wgmma.mma_async.sync.aligned.m64n256k16.f32.bf16.bf16 {%0, %1, %2, %3, %4, %5, %6, %7, %8, %9, %10, %11, %12, %13, %14, %15, %16, %17, %18, %19, %20, %21, %22, %23, %24, %25, %26, %27, %28, %29, %30, %31, %32, %33, %34, %35, %36, %37, %38, %39, %40, %41, %42, %43, %44, %45, %46, %47, %48, %49, %50, %51, %52, %53, %54, %55, %56, %57, %58, %59, %60, %61, %62, %63, %64, %65, %66, %67, %68, %69, %70, %71, %72, %73, %74, %75, %76, %77, %78, %79, %80, %81, %82, %83, %84, %85, %86, %87, %88, %89, %90, %91, %92, %93, %94, %95, %96, %97, %98, %99, %100, %101, %102, %103, %104, %105, %106, %107, %108, %109, %110, %111, %112, %113, %114, %115, %116, %117, %118, %119, %120, %121, %122, %123, %124, %125, %126, %127}, da, db, p, 1, 1, 0, 1;\n}\n"
        : "+f"(d[0]), "+f"(d[1]), "+f"(d[2]), "+f"(d[3]), "+f"(d[4]), "+f"(d[5]), "+f"(d[6]), "+f"(d[7]), "+f"(d[8]), "+f"(d[9]), "+f"(d[10]), "+f"(d[11]), "+f"(d[12]), "+f"(d[13]), "+f"(d[14]), "+f"(d[15]), "+f"(d[16]), "+f"(d[17]), "+f"(d[18]), "+f"(d[19]), "+f"(d[20]), "+f"(d[21]), "+f"(d[22]), "+f"(d[23]), "+f"(d[24]), "+f"(d[25]), "+f"(d[26]), "+f"(d[27]), "+f"(d[28]), "+f"(d[29]), "+f"(d[30]), "+f"(d[31]), "+f"(d[32]), "+f"(d[33]), "+f"(d[34]), "+f"(d[35]), "+f"(d[36]), "+f"(d[37]), "+f"(d[38]), "+f"(d[39]), "+f"(d[40]), "+f"(d[41]), "+f"(d[42]), "+f"(d[43]), "+f"(d[44]), "+f"(d[45]), "+f"(d[46]), "+f"(d[47]), "+f"(d[48]), "+f"(d[49]), "+f"(d[50]), "+f"(d[51]), "+f"(d[52]), "+f"(d[53]), "+f"(d[54]), "+f"(d[55]), "+f"(d[56]), "+f"(d[57]), "+f"(d[58]), "+f"(d[59]), "+f"(d[60]), "+f"(d[61]), "+f"(d[62]), "+f"(d[63]), "+f"(d[64]), "+f"(d[65]), "+f"(d[66]), "+f"(d[67]), "+f"(d[68]), "+f"(d[69]), "+f"(d[70]), "+f"(d[71]), "+f"(d[72]), "+f"(d[73]), "+f"(d[74]), "+f"(d[75]), "+f"(d[76]), "+f"(d[77]), "+f"(d[78]), "+f"(d[79]), "+f"(d[80]), "+f"(d[81]), "+f"(d[82]), "+f"(d[83]), "+f"(d[84]), "+f"(d[85]), "+f"(d[86]), "+f"(d[87]), "+f"(d[88]), "+f"(d[89]), "+f"(d[90]), "+f"(d[91]), "+f"(d[92]), "+f"(d[93]), "+f"(d[94]), "+f"(d[95]), "+f"(d[96]), "+f"(d[97]), "+f"(d[98]), "+f"(d[99]), "+f"(d[100]), "+f"(d[101]), "+f"(d[102]), "+f"(d[103]), "+f"(d[104]), "+f"(d[105]), "+f"(d[106]), "+f"(d[107]), "+f"(d[108]), "+f"(d[109]), "+f"(d[110]), "+f"(d[111]), "+f"(d[112]), "+f"(d[113]), "+f"(d[114]), "+f"(d[115]), "+f"(d[116]), "+f"(d[117]), "+f"(d[118]), "+f"(d[119]), "+f"(d[120]), "+f"(d[121]), "+f"(d[122]), "+f"(d[123]), "+f"(d[124]), "+f"(d[125]), "+f"(d[126]), "+f"(d[127])
        : "r"(alo), "r"(ahi), "r"(blo), "r"(bhi), "r"(scale_d));
}

__device__ __forceinline__ void wgmma_ss_n64_tb0(float (&d)[32], uint32_t alo, uint32_t ahi, uint32_t blo, uint32_t bhi, int scale_d) {
    asm volatile("{\n.reg .pred p;\n.reg .b64 da, db;\nsetp.ne.b32 p, %36, 0;\nmov.b64 da, {%32, %33};\nmov.b64 db, {%34, %35};\n"
        "wgmma.mma_async.sync.aligned.m64n64k16.f32.bf16.bf16 {%0, %1, %2, %3, %4, %5, %6, %7, %8, %9, %10, %11, %12, %13, %14, %15, %16, %17, %18, %19, %20, %21, %22, %23, %24, %25, %26, %27, %28, %29, %30, %31}, da, db, p, 1, 1, 0, 0;\n}\n"
        : "+f"(d[0]), "+f"(d[1]), "+f"(d[2]), "+f"(d[3]), "+f"(d[4]), "+f"(d[5]), "+f"(d[6]), "+f"(d[7]), "+f"(d[8]), "+f"(d[9]), "+f"(d[10]), "+f"(d[11]), "+f"(d[12]), "+f"(d[13]), "+f"(d[14]), "+f"(d[15]), "+f"(d[16]), "+f"(d[17]), "+f"(d[18]), "+f"(d[19]), "+f"(d[20]), "+f"(d[21]), "+f"(d[22]), "+f"(d[23]), "+f"(d[24]), "+f"(d[25]), "+f"(d[26]), "+f"(d[27]), "+f"(d[28]), "+f"(d[29]), "+f"(d[30]), "+f"(d[31])
        : "r"(alo), "r"(ahi), "r"(blo), "r"(bhi), "r"(scale_d));
}

__device__ __forceinline__ void wgmma_rs_n128_tb0(float (&d)[64], uint32_t a0, uint32_t a1, uint32_t a2, uint32_t a3, uint32_t blo, uint32_t bhi, int scale_d) {
    asm volatile("{\n.reg .pred p;\n.reg .b64 db;\nsetp.ne.b32 p, %70, 0;\nmov.b64 db, {%68, %69};\n"
        "wgmma.mma_async.sync.aligned.m64n128k16.f32.bf16.bf16 {%0, %1, %2, %3, %4, %5, %6, %7, %8, %9, %10, %11, %12, %13, %14, %15, %16, %17, %18, %19, %20, %21, %22, %23, %24, %25, %26, %27, %28, %29, %30, %31, %32, %33, %34, %35, %36, %37, %38, %39, %40, %41, %42, %43, %44, %45, %46, %47, %48, %49, %50, %51, %52, %53, %54, %55, %56, %57, %58, %59, %60, %61, %62, %63}, {%64, %65, %66, %67}, db, p, 1, 1, 0;\n}\n"
        : "+f"(d[0]), "+f"(d[1]), "+f"(d[2]), "+f"(d[3]), "+f"(d[4]), "+f"(d[5]), "+f"(d[6]), "+f"(d[7]), "+f"(d[8]), "+f"(d[9]), "+f"(d[10]), "+f"(d[11]), "+f"(d[12]), "+f"(d[13]), "+f"(d[14]), "+f"(d[15]), "+f"(d[16]), "+f"(d[17]), "+f"(d[18]), "+f"(d[19]), "+f"(d[20]), "+f"(d[21]), "+f"(d[22]), "+f"(d[23]), "+f"(d[24]), "+f"(d[25]), "+f"(d[26]), "+f"(d[27]), "+f"(d[28]), "+f"(d[29]), "+f"(d[30]), "+f"(d[31]), "+f"(d[32]), "+f"(d[33]), "+f"(d[34]), "+f"(d[35]), "+f"(d[36]), "+f"(d[37]), "+f"(d[38]), "+f"(d[39]), "+f"(d[40]), "+f"(d[41]), "+f"(d[42]), "+f"(d[43]), "+f"(d[44]), "+f"(d[45]), "+f"(d[46]), "+f"(d[47]), "+f"(d[48]), "+f"(d[49]), "+f"(d[50]), "+f"(d[51]), "+f"(d[52]), "+f"(d[53]), "+f"(d[54]), "+f"(d[55]), "+f"(d[56]), "+f"(d[57]), "+f"(d[58]), "+f"(d[59]), "+f"(d[60]), "+f"(d[61]), "+f"(d[62]), "+f"(d[63])
        : "r"(a0), "r"(a1), "r"(a2), "r"(a3), "r"(blo), "r"(bhi), "r"(scale_d));
}

__device__ __forceinline__ void wgmma_rs_n64_tb0(float (&d)[32], uint32_t a0, uint32_t a1, uint32_t a2, uint32_t a3, uint32_t blo, uint32_t bhi, int scale_d) {
    asm volatile("{\n.reg .pred p;\n.reg .b64 db;\nsetp.ne.b32 p, %38, 0;\nmov.b64 db, {%36, %37};\n"
        "wgmma.mma_async.sync.aligned.m64n64k16.f32.bf16.bf16 {%0, %1, %2, %3, %4, %5, %6, %7, %8, %9, %10, %11, %12, %13, %14, %15, %16, %17, %18, %19, %20, %21, %22, %23, %24, %25, %26, %27, %28, %29, %30, %31}, {%32, %33, %34, %35}, db, p, 1, 1, 0;\n}\n"
        : "+f"(d[0]), "+f"(d[1]), "+f"(d[2]), "+f"(d[3]), "+f"(d[4]), "+f"(d[5]), "+f"(d[6]), "+f"(d[7]), "+f"(d[8]), "+f"(d[9]), "+f"(d[10]), "+f"(d[11]), "+f"(d[12]), "+f"(d[13]), "+f"(d[14]), "+f"(d[15]), "+f"(d[16]), "+f"(d[17]), "+f"(d[18]), "+f"(d[19]), "+f"(d[20]), "+f"(d[21]), "+f"(d[22]), "+f"(d[23]), "+f"(d[24]), "+f"(d[25]), "+f"(d[26]), "+f"(d[27]), "+f"(d[28]), "+f"(d[29]), "+f"(d[30]), "+f"(d[31])
        : "r"(a0), "r"(a1), "r"(a2), "r"(a3), "r"(blo), "r"(bhi), "r"(scale_d));
}

__device__ __forceinline__ void wgmma_rs_n32_tb1(float (&d)[16], uint32_t a0, uint32_t a1, uint32_t a2, uint32_t a3, uint32_t blo, uint32_t bhi, int scale_d) {
    asm volatile("{\n.reg .pred p;\n.reg .b64 db;\nsetp.ne.b32 p, %22, 0;\nmov.b64 db, {%20, %21};\n"
        "wgmma.mma_async.sync.aligned.m64n32k16.f32.bf16.bf16 {%0, %1, %2, %3, %4, %5, %6, %7, %8, %9, %10, %11, %12, %13, %14, %15}, {%16, %17, %18, %19}, db, p, 1, 1, 1;\n}\n"
        : "+f"(d[0]), "+f"(d[1]), "+f"(d[2]), "+f"(d[3]), "+f"(d[4]), "+f"(d[5]), "+f"(d[6]), "+f"(d[7]), "+f"(d[8]), "+f"(d[9]), "+f"(d[10]), "+f"(d[11]), "+f"(d[12]), "+f"(d[13]), "+f"(d[14]), "+f"(d[15])
        : "r"(a0), "r"(a1), "r"(a2), "r"(a3), "r"(blo), "r"(bhi), "r"(scale_d));
}

__device__ __forceinline__ void wgmma_rs_n40_tb1(float (&d)[20], uint32_t a0, uint32_t a1, uint32_t a2, uint32_t a3, uint32_t blo, uint32_t bhi, int scale_d) {
    asm volatile("{\n.reg .pred p;\n.reg .b64 db;\nsetp.ne.b32 p, %26, 0;\nmov.b64 db, {%24, %25};\n"
        "wgmma.mma_async.sync.aligned.m64n40k16.f32.bf16.bf16 {%0, %1, %2, %3, %4, %5, %6, %7, %8, %9, %10, %11, %12, %13, %14, %15, %16, %17, %18, %19}, {%20, %21, %22, %23}, db, p, 1, 1, 1;\n}\n"
        : "+f"(d[0]), "+f"(d[1]), "+f"(d[2]), "+f"(d[3]), "+f"(d[4]), "+f"(d[5]), "+f"(d[6]), "+f"(d[7]), "+f"(d[8]), "+f"(d[9]), "+f"(d[10]), "+f"(d[11]), "+f"(d[12]), "+f"(d[13]), "+f"(d[14]), "+f"(d[15]), "+f"(d[16]), "+f"(d[17]), "+f"(d[18]), "+f"(d[19])
        : "r"(a0), "r"(a1), "r"(a2), "r"(a3), "r"(blo), "r"(bhi), "r"(scale_d));
}

template <int BN>
__device__ __forceinline__ void wgmma_tile(float (&d)[BN / 2], uint32_t da, uint32_t db, int sd) {
    constexpr uint32_t HI = desc_hi(1024, 1);
    if constexpr (BN == 128) wgmma_ss_n128_tb1(d, da, HI, db, HI, sd);
    else if constexpr (BN == 192) wgmma_ss_n192_tb1(d, da, HI, db, HI, sd);
    else if constexpr (BN == 224) wgmma_ss_n224_tb1(d, da, HI, db, HI, sd);
    else wgmma_ss_n256_tb1(d, da, HI, db, HI, sd);
}

__global__ void __launch_bounds__(256) prep_kernel(const bf16* __restrict__ x, const bf16* __restrict__ gate_w,
                                                   const bf16* __restrict__ w1, const bf16* __restrict__ w3) {
    constexpr int row_blocks = 256;
    if (blockIdx.x == 0 && threadIdx.x == 0) g_tile_ctr = 0;
    const int tid = threadIdx.x;
    TL_START(0)
    pdl_launch();
    if ((int)blockIdx.x < row_blocks) {
        const int row = blockIdx.x * 8 + (tid >> 5);
        const int lane = tid & 31;
        const uint4* xr = reinterpret_cast<const uint4*>(x + (size_t)row * DM);
        const uint4* gw = reinterpret_cast<const uint4*>(gate_w);
        float v[32];
        float gsum = 0.f, sum = 0.f;
#pragma unroll
        for (int i = 0; i < 4; i++) {
            uint4 a = xr[lane + 32 * i];
            uint4 b = gw[lane + 32 * i];
            const uint32_t aa[4] = {a.x, a.y, a.z, a.w};
            const uint32_t bb[4] = {b.x, b.y, b.z, b.w};
#pragma unroll
            for (int j = 0; j < 4; j++) {
                float x0 = __uint_as_float(aa[j] << 16), x1 = __uint_as_float(aa[j] & 0xFFFF0000u);
                float g0 = __uint_as_float(bb[j] << 16), g1 = __uint_as_float(bb[j] & 0xFFFF0000u);
                v[i * 8 + j * 2] = x0;
                v[i * 8 + j * 2 + 1] = x1;
                sum += x0 + x1;
                gsum += bf16_round(x0 * g0) + bf16_round(x1 * g1);
            }
        }
#pragma unroll
        for (int o = 16; o > 0; o >>= 1) {
            sum += __shfl_xor_sync(0xffffffffu, sum, o);
            gsum += __shfl_xor_sync(0xffffffffu, gsum, o);
        }
        const float mean = sum * (1.0f / DM);
        float m2 = 0.f;
#pragma unroll
        for (int i = 0; i < 32; i++) {
            float d = v[i] - mean;
            m2 += d * d;
        }
#pragma unroll
        for (int o = 16; o > 0; o >>= 1) m2 += __shfl_xor_sync(0xffffffffu, m2, o);
        if (lane == 0) {
            g_mean1[row] = mean;
            g_rstd1[row] = rsqrtf(m2 * (1.0f / DM) + 1e-5f);
            float logit = bf16_round(gsum);
            float g = bf16_round(1.0f / (1.0f + __expf(-logit)));
            g_gate[row] = g;
            g_omg[row] = bf16_round(1.0f - g);
        }
    } else {
        __shared__ float red[32][65];
        int blk = blockIdx.x - row_blocks;
        const bf16* w = w1;
        int ld = DM;
        float* cs_out = g_cs1;
        if (blk >= 64) { blk -= 64; w = w3; ld = FF; cs_out = g_cs3; }
        const int chunk = blk & 3;
        const int col0 = (blk >> 2) * 64;
        const int cg = tid & 7;
        const int rg = tid >> 3;
        uint4 a[8];
#pragma unroll
        for (int r = 0; r < 8; r++)
            a[r] = *reinterpret_cast<const uint4*>(w + (size_t)(chunk * 256 + r * 32 + rg) * ld + col0 + cg * 8);
        float acc[8];
#pragma unroll
        for (int j = 0; j < 8; j++) acc[j] = 0.f;
#pragma unroll
        for (int r = 0; r < 8; r++) {
            const uint32_t aa[4] = {a[r].x, a[r].y, a[r].z, a[r].w};
#pragma unroll
            for (int j = 0; j < 4; j++) {
                acc[2 * j] += __uint_as_float(aa[j] << 16);
                acc[2 * j + 1] += __uint_as_float(aa[j] & 0xFFFF0000u);
            }
        }
#pragma unroll
        for (int j = 0; j < 8; j++) red[rg][cg * 8 + j] = acc[j];
        __syncthreads();
        if (tid < 64) {
            float s = 0.f;
#pragma unroll
            for (int r = 0; r < 32; r++) s += red[r][tid];
            cs_out[chunk * ld + col0 + tid] = s;
        }
    }
    TL_END(0)
}

#define RELEASE_STAGE(b) if (tid_wg == 0) mbar_arrive(b)
template <int BN, int STAGES>
struct GemmSmem {
    static constexpr int A_BYTES = 128 * 64 * 2;
    static constexpr int B_BOXES = (BN + 63) / 64;
    static constexpr int B_BYTES = B_BOXES * 64 * 64 * 2;
    static constexpr int STAGE_BYTES = A_BYTES + B_BYTES;
    static constexpr int STG_OFF = STAGES * STAGE_BYTES;
    static constexpr int CS_OFF = STAGES * STAGE_BYTES + 2 * 16384;
    static constexpr int BAR_OFF = CS_OFF + 1024;
    static constexpr int TOTAL = BAR_OFF + 192 + 512;
};

template <int MODE, int BN, int STAGES>
__global__ void __launch_bounds__(384, 1)
gemm_kernel(const __grid_constant__ CUtensorMap mA, const __grid_constant__ CUtensorMap mB0,
            const __grid_constant__ CUtensorMap mB1, const __grid_constant__ CUtensorMap mC0,
            const __grid_constant__ CUtensorMap mC1, const bf16* __restrict__ xin, int n_tiles_n, int kblocks) {
    using L = GemmSmem<BN, STAGES>;
    extern __shared__ uint8_t smem_raw[];
    const uint32_t sbase = (smem_u32(smem_raw) + 1023u) & ~1023u;
    const uint32_t bar_full = sbase + L::BAR_OFF;
    const uint32_t bar_empty = bar_full + 8 * STAGES;
    const uint32_t bar_res = bar_empty + 8 * STAGES;
    const int wg = threadIdx.x >> 7;
    const int ntiles = 16 * n_tiles_n;
    constexpr bool DYN = (MODE == 3);
    const uint32_t bar_tfull = bar_res + 8;
    const uint32_t bar_tempty = bar_tfull + 16;
    const uint32_t tile_slot = bar_tempty + 16;
    TL_START(MODE)
    pdl_launch();

    if (threadIdx.x == 0) {
        for (int s = 0; s < STAGES; s++) {
            mbar_init(bar_full + 8 * s, 1);
            mbar_init(bar_empty + 8 * s, 2);
        }
        for (int s = 0; s < 2; s++) {
            mbar_init(bar_tfull + 8 * s, 1);
            mbar_init(bar_tempty + 8 * s, 2);
        }
        mbar_init(bar_res, 1);
        asm volatile("fence.mbarrier_init.release.cluster;" ::: "memory");
        prefetch_tmap(&mA);
        prefetch_tmap(&mB0);
        if (MODE == 1 || MODE == 5) prefetch_tmap(&mB1);
        if (MODE == 2 || MODE == 5) prefetch_tmap(&mC1);
        prefetch_tmap(&mC0);
    }
    __syncthreads();

    if (wg == 0) {
        reg_dealloc<40>();
        if (threadIdx.x == 0) {
            if (MODE != 1) pdl_wait();
            int stage = 0;
            uint32_t phase = 1;
            for (int it = 0;; it++) {
                int tile;
                if (DYN) {
                    tile = atomicAdd(&g_tile_ctr, 1);
                    mbar_wait(bar_tempty + 8 * (it & 1), ((it >> 1) & 1) ^ 1);
                    asm volatile("st.shared.b32 [%0], %1;" ::"r"(tile_slot + 4 * (it & 1)), "r"(tile) : "memory");
                    mbar_arrive(bar_tfull + 8 * (it & 1));
                } else {
                    tile = blockIdx.x + it * gridDim.x;
                }
                if (tile >= ntiles) break;
                if (MODE == 1) tile = (tile + 192) & 255;
                const int m0 = (tile & 15) * 128;
                const int n0 = (tile >> 4) * BN;
                for (int kb = 0; kb < kblocks; kb++) {
                    mbar_wait(bar_empty + 8 * stage, phase);
                    const uint32_t sa = sbase + stage * L::STAGE_BYTES;
                    const uint32_t sb = sa + L::A_BYTES;
                    const uint32_t fb = bar_full + 8 * stage;
                    mbar_expect_tx(fb, L::STAGE_BYTES);
                    int arow = m0;
                    if (MODE == 2) {
                        const int grp = kb >> 2;
                        arow += (grp == 0) ? -1 : (grp == 1) ? 1 : (grp == 2) ? -2 : 2;
                    }
                    tma_load_2d(sa, &mA, kb * 64, arow, fb);
                    const CUtensorMap* mb = &mB0;
                    int bc = n0, br = kb * 64;
                    if (MODE == 1 && n0 >= 3 * DM) { mb = &mB1; bc = n0 - 3 * DM; }
                    if (MODE == 5 && kb >= 16) { mb = &mB1; br = (kb - 16) * 64; }
#pragma unroll
                    for (int b = 0; b < L::B_BOXES; b++) tma_load_2d(sb + b * 8192, mb, bc + b * 64, br, fb);
                    if ((MODE == 2 || MODE == 5) && kb == STAGES - 1) {
                        mbar_expect_tx(bar_res, 32768);
#pragma unroll
                        for (int q = 0; q < 4; q++)
                            tma_load_2d(sbase + L::STG_OFF + q * 8192, &mC1, n0 + (q & 1) * 64, m0 + (q >> 1) * 64, bar_res);
                    }
                    if (++stage == STAGES) { stage = 0; phase ^= 1; }
                }
            }
        }
    } else {
        reg_alloc<232>();
        const int c = wg - 1;
        const int warp = (threadIdx.x >> 5) & 3;
        const int lane = threadIdx.x & 31;
        const int tid_wg = threadIdx.x & 127;
        const uint32_t stg = sbase + L::STG_OFF + c * 16384;
        int stage = 0;
        uint32_t phase = 0;
        float acc[BN / 2];
        bool first = true;
        PH(0)
        if (MODE != 1) pdl_wait();
        for (int it = 0;; it++) {
            int tile;
            if (DYN) {
                mbar_wait(bar_tfull + 8 * (it & 1), (it >> 1) & 1);
                asm volatile("ld.shared.b32 %0, [%1];" : "=r"(tile) : "r"(tile_slot + 4 * (it & 1)) : "memory");
                named_bar_sync(1 + c, 128);
                if (tid_wg == 0) mbar_arrive(bar_tempty + 8 * (it & 1));
            } else {
                tile = blockIdx.x + it * gridDim.x;
            }
            if (tile >= ntiles) break;
            if (MODE == 1) tile = (tile + 192) & 255;
            const int m0 = (tile & 15) * 128;
            const int n0 = (tile >> 4) * BN;
            const int r0 = m0 + c * 64 + warp * 16 + (lane >> 2);
            const int r1 = r0 + 8;
            float mu[2], rs[2], og[2];
            if (MODE == 3) {
                const int t = threadIdx.x - 128;
                if (t < BN) {
                    const float v = (g_cs3[n0 + t] + g_cs3[FF + n0 + t]) + (g_cs3[2 * FF + n0 + t] + g_cs3[3 * FF + n0 + t]);
                    asm volatile("st.shared.f32 [%0], %1;" ::"r"(sbase + L::CS_OFF + t * 4), "f"(v) : "memory");
                }
#pragma unroll
                for (int h = 0; h < 2; h++) {
                    const float4* sp = reinterpret_cast<const float4*>(&g_stat2[(h ? r1 : r0) * 8]);
                    float4 p[4];
                    float s = 0.f;
#pragma unroll
                    for (int i = 0; i < 4; i++) { p[i] = sp[i]; s += p[i].x + p[i].z; }
                    const float mean = s * (1.0f / DM);
                    float m2 = 0.f;
#pragma unroll
                    for (int i = 0; i < 4; i++) {
                        float d0 = p[i].x * (1.0f / 128) - mean, d1 = p[i].z * (1.0f / 128) - mean;
                        m2 += p[i].y + p[i].w + 128.0f * (d0 * d0 + d1 * d1);
                    }
                    mu[h] = mean;
                    rs[h] = rsqrtf(m2 * (1.0f / DM) + 1e-5f);
                }
            }
            if (MODE == 3 || MODE == 5) { og[0] = g_omg[r0]; og[1] = g_omg[r1]; }
            int prev_stage = 0;
            for (int kb = 0; kb < kblocks; kb++) {
                mbar_wait(bar_full + 8 * stage, phase);
                const uint32_t sa = sbase + stage * L::STAGE_BYTES + c * 8192;
                const uint32_t sb = sbase + stage * L::STAGE_BYTES + L::A_BYTES;
                const uint32_t da = desc_lo(sa, 16);
                const uint32_t db = desc_lo(sb, 8192);
                wgmma_fence();
#pragma unroll
                for (int k = 0; k < 4; k++) wgmma_tile<BN>(acc, da + k * 2, db + k * 128, (kb | k) != 0);
                wgmma_commit();
                if (kb > 0) {
                    wgmma_wait<1>();
                    RELEASE_STAGE(bar_empty + 8 * prev_stage);
                }
                prev_stage = stage;
                if (++stage == STAGES) { stage = 0; phase ^= 1; }
            }
            wgmma_wait<0>();
            RELEASE_STAGE(bar_empty + 8 * prev_stage);
            PH(1)
            if (MODE == 1 && first) { pdl_wait(); first = false; }

            const int cq = (lane & 3) * 2;
            const CUtensorMap* mc = &mC0;
            const uint32_t rrow = warp * 16 + (lane >> 2);
            const uint32_t res0 = stg + rrow * 128 + cq * 2;
            int out_c0 = n0;
            if (MODE == 1) {
                if (n0 < DM) {
                    const float qs = 0.17677669529663687f * 1.4426950408889634f;
#pragma unroll
                    for (int j = 0; j < BN / 2; j++) acc[j] *= qs;
                } else if (n0 >= 3 * DM) {
                    mc = &mC1;
                    out_c0 = n0 - 3 * DM;
                    const float mu0 = g_mean1[r0], mu1 = g_mean1[r1];
                    const float rs0 = g_rstd1[r0], rs1 = g_rstd1[r1];
                    {
                        const int t = threadIdx.x - 128;
                        const float v = (g_cs1[out_c0 + t] + g_cs1[DM + out_c0 + t]) + (g_cs1[2 * DM + out_c0 + t] + g_cs1[3 * DM + out_c0 + t]);
                        asm volatile("st.shared.f32 [%0], %1;" ::"r"(sbase + L::CS_OFF + t * 4), "f"(v) : "memory");
                    }
                    named_bar_sync(3, 256);
#pragma unroll
                    for (int j = 0; j < BN / 8; j++) {
                        float2 cs;
                        asm volatile("ld.shared.v2.f32 {%0, %1}, [%2];" : "=f"(cs.x), "=f"(cs.y) : "r"(sbase + L::CS_OFF + (8 * j + cq) * 4));
                        acc[4 * j + 0] = gelu_tanh(rs0 * fmaf(-mu0, cs.x, acc[4 * j + 0]));
                        acc[4 * j + 1] = gelu_tanh(rs0 * fmaf(-mu0, cs.y, acc[4 * j + 1]));
                        acc[4 * j + 2] = gelu_tanh(rs1 * fmaf(-mu1, cs.x, acc[4 * j + 2]));
                        acc[4 * j + 3] = gelu_tanh(rs1 * fmaf(-mu1, cs.y, acc[4 * j + 3]));
                    }
                    named_bar_sync(3, 256);
                }
            } else if (MODE == 2) {
                float s0 = 0.f, s1 = 0.f;
                mbar_wait(bar_res, 0);
#pragma unroll
                for (int j = 0; j < BN / 8; j++) {
                    uint32_t xa, xb;
                    const uint32_t ra = res0 + (j >> 3) * 8192 + (((j & 7) ^ (rrow & 7)) << 4);
                    asm volatile("ld.shared.b32 %0, [%1];" : "=r"(xa) : "r"(ra));
                    asm volatile("ld.shared.b32 %0, [%1];" : "=r"(xb) : "r"(ra + 1024));
                    acc[4 * j + 0] = bf16_round(bf16_round(acc[4 * j + 0]) + __uint_as_float(xa << 16));
                    acc[4 * j + 1] = bf16_round(bf16_round(acc[4 * j + 1]) + __uint_as_float(xa & 0xFFFF0000u));
                    acc[4 * j + 2] = bf16_round(bf16_round(acc[4 * j + 2]) + __uint_as_float(xb << 16));
                    acc[4 * j + 3] = bf16_round(bf16_round(acc[4 * j + 3]) + __uint_as_float(xb & 0xFFFF0000u));
                    s0 += acc[4 * j + 0] + acc[4 * j + 1];
                    s1 += acc[4 * j + 2] + acc[4 * j + 3];
                }
                s0 += __shfl_xor_sync(0xffffffffu, s0, 1);
                s0 += __shfl_xor_sync(0xffffffffu, s0, 2);
                s1 += __shfl_xor_sync(0xffffffffu, s1, 1);
                s1 += __shfl_xor_sync(0xffffffffu, s1, 2);
                const float mu0 = s0 * (1.0f / BN), mu1 = s1 * (1.0f / BN);
                float q0 = 0.f, q1 = 0.f;
#pragma unroll
                for (int j = 0; j < BN / 8; j++) {
                    float d;
                    d = acc[4 * j + 0] - mu0; q0 += d * d;
                    d = acc[4 * j + 1] - mu0; q0 += d * d;
                    d = acc[4 * j + 2] - mu1; q1 += d * d;
                    d = acc[4 * j + 3] - mu1; q1 += d * d;
                }
                q0 += __shfl_xor_sync(0xffffffffu, q0, 1);
                q0 += __shfl_xor_sync(0xffffffffu, q0, 2);
                q1 += __shfl_xor_sync(0xffffffffu, q1, 1);
                q1 += __shfl_xor_sync(0xffffffffu, q1, 2);
                if ((lane & 3) == 0) {
                    static_assert(MODE != 2 || BN == 128, "stats layout assumes BN=128");
                    g_stat2[r0 * 8 + (n0 >> 7)] = make_float2(s0, q0);
                    g_stat2[r1 * 8 + (n0 >> 7)] = make_float2(s1, q1);
                }
            } else if (MODE == 3) {
                out_c0 = n0 + DM;
                named_bar_sync(3, 256);
#pragma unroll
                for (int j = 0; j < BN / 8; j++) {
                    float2 cs;
                    asm volatile("ld.shared.v2.f32 {%0, %1}, [%2];" : "=f"(cs.x), "=f"(cs.y) : "r"(sbase + L::CS_OFF + (8 * j + cq) * 4));
                    acc[4 * j + 0] = og[0] * gelu_tanh(rs[0] * fmaf(-mu[0], cs.x, acc[4 * j + 0]));
                    acc[4 * j + 1] = og[0] * gelu_tanh(rs[0] * fmaf(-mu[0], cs.y, acc[4 * j + 1]));
                    acc[4 * j + 2] = og[1] * gelu_tanh(rs[1] * fmaf(-mu[1], cs.x, acc[4 * j + 2]));
                    acc[4 * j + 3] = og[1] * gelu_tanh(rs[1] * fmaf(-mu[1], cs.y, acc[4 * j + 3]));
                }
                named_bar_sync(3, 256);
            } else {
                const float og0 = og[0], og1 = og[1];
                mbar_wait(bar_res, 0);
#pragma unroll
                for (int j = 0; j < BN / 8; j++) {
                    uint32_t xa, xb;
                    const uint32_t ra = res0 + (j >> 3) * 8192 + (((j & 7) ^ (rrow & 7)) << 4);
                    asm volatile("ld.shared.b32 %0, [%1];" : "=r"(xa) : "r"(ra));
                    asm volatile("ld.shared.b32 %0, [%1];" : "=r"(xb) : "r"(ra + 1024));
                    acc[4 * j + 0] = fmaf(og0, __uint_as_float(xa << 16), acc[4 * j + 0]);
                    acc[4 * j + 1] = fmaf(og0, __uint_as_float(xa & 0xFFFF0000u), acc[4 * j + 1]);
                    acc[4 * j + 2] = fmaf(og1, __uint_as_float(xb << 16), acc[4 * j + 2]);
                    acc[4 * j + 3] = fmaf(og1, __uint_as_float(xb & 0xFFFF0000u), acc[4 * j + 3]);
                }
            }
            PH(3)
            const int srow = warp * 16 + (lane & 7) + ((lane >> 3) & 1) * 8;
#pragma unroll
            for (int rnd = 0; rnd < (BN + 127) / 128; rnd++) {
                if (tid_wg == 0) bulk_wait_read0();
                named_bar_sync(1 + c, 128);
#pragma unroll
                for (int jj = 0; jj < 8; jj++) {
                    const int j = rnd * 16 + jj * 2;
                    if (j * 8 < BN) {
                        const int jb = jj * 2 + (lane >> 4);
                        uint32_t addr = stg + (jb >> 3) * 8192 + srow * 128 + (((jb & 7) ^ (srow & 7)) << 4);
                        if (rnd * 128 + 128 > BN && jj >= 4)
                            addr = stg + 8192 + srow * 64 + (((jb & 3) ^ ((srow >> 1) & 3)) << 4);
                        stmatrix_x4(addr, pack_bf16(acc[4 * j + 0], acc[4 * j + 1]), pack_bf16(acc[4 * j + 2], acc[4 * j + 3]),
                                    pack_bf16(acc[4 * j + 4], acc[4 * j + 5]), pack_bf16(acc[4 * j + 6], acc[4 * j + 7]));
                    }
                }
                fence_proxy_async();
                named_bar_sync(1 + c, 128);
                if (tid_wg == 0) {
                    tma_store_2d(mc, stg, out_c0 + rnd * 128, m0 + c * 64);
                    if (rnd * 128 + 64 < BN)
                        tma_store_2d((rnd * 128 + 128 > BN) ? &mC1 : mc, stg + 8192, out_c0 + rnd * 128 + 64, m0 + c * 64);
                    bulk_commit();
                }
            }
        }
        PH(4)
        if (tid_wg == 0) bulk_wait0();
        PH(5)
        TL_END(MODE)
    }
}

#define ATT_SPLIT 16
#define ATT_NWG 4
constexpr int ATT_NTILES = NH * 16;
constexpr int ATT_TPH = S_LEN / (64 * ATT_NWG);
constexpr int ATT_GRID = NH * ATT_TPH;
constexpr int ATT_THREADS = 128 * ATT_NWG;
constexpr int ATT_STAGES = 4;
constexpr int ATT_DIST = 2;
constexpr int ATT_Q_OFF = ATT_STAGES * 16384;
constexpr int ATT_ONES_OFF = ATT_Q_OFF + 4096 * ATT_NWG;
constexpr int ATT_KEXT_OFF = ATT_ONES_OFF + 4096;
constexpr int ATT_QEXT_OFF = ATT_KEXT_OFF + 4096;
constexpr int ATT_BAR_OFF = ATT_QEXT_OFF + 4096 * ATT_NWG;
constexpr int ATT_SMEM = ATT_BAR_OFF + 256 + 1024;

__device__ __forceinline__ void row_max(const float (&s)[32], float& m0, float& m1) {
    float a0[8], a1[8];
#pragma unroll
    for (int i = 0; i < 8; i++) {
        a0[i] = fmaxf(s[4 * i], s[4 * i + 1]);
        a1[i] = fmaxf(s[4 * i + 2], s[4 * i + 3]);
    }
#pragma unroll
    for (int w = 4; w > 0; w >>= 1)
#pragma unroll
        for (int i = 0; i < w; i++) { a0[i] = fmaxf(a0[i], a0[i + w]); a1[i] = fmaxf(a1[i], a1[i + w]); }
    float mx0 = a0[0], mx1 = a1[0];
    mx0 = fmaxf(mx0, __shfl_xor_sync(0xffffffffu, mx0, 1));
    mx1 = fmaxf(mx1, __shfl_xor_sync(0xffffffffu, mx1, 1));
    mx0 = fmaxf(mx0, __shfl_xor_sync(0xffffffffu, mx0, 2));
    mx1 = fmaxf(mx1, __shfl_xor_sync(0xffffffffu, mx1, 2));
    m0 = fmaxf(m0, mx0);
    m1 = fmaxf(m1, mx1);
}

__device__ __forceinline__ void attn_step(float (&s)[32], float (&o)[20], uint32_t dq, uint32_t dke, uint32_t dk_next,
                                          uint32_t dv_cur, uint32_t release_bar) {
    constexpr uint32_t HI = desc_hi(512, 2);
    uint32_t p[16];
#pragma unroll
    for (int i = 0; i < 16; i++) p[i] = pack_bf16(ex2(s[2 * i]), ex2(s[2 * i + 1]));
    wgmma_fence();
    wgmma_ss_n64_tb0(s, dq, HI, dk_next, HI, 0);
    wgmma_ss_n64_tb0(s, dq + 2, HI, dk_next + 2, HI, 1);
    wgmma_ss_n64_tb0(s, dq + ((ATT_QEXT_OFF - ATT_Q_OFF) >> 4), HI, dke, HI, 1);
#pragma unroll
    for (int t = 0; t < 4; t++)
        wgmma_rs_n40_tb1(o, p[4 * t], p[4 * t + 1], p[4 * t + 2], p[4 * t + 3], dv_cur + t * 64, HI, 1);
    wgmma_commit();
    wgmma_wait<0>();
    if (release_bar != 0 && (threadIdx.x & 127) == 0) mbar_arrive(release_bar);
}

__global__ void __launch_bounds__(256, 1)
attn_exact_kernel(const __grid_constant__ CUtensorMap mKV) {
    extern __shared__ uint8_t smem_raw[];
    pdl_launch();
    pdl_wait();
    int any = 0;
    for (int t = blockIdx.x; t < ATT_NTILES; t += gridDim.x) any |= g_bad[t];
    if (!any) return;
    constexpr int NBLK = S_LEN / 128;
    constexpr uint32_t HI = desc_hi(512, 2);
    const uint32_t sbase = (smem_u32(smem_raw) + 1023u) & ~1023u;
    const uint32_t bar = sbase + ATT_BAR_OFF;
    const int warp_id = threadIdx.x >> 5;
    const int lane = threadIdx.x & 31;
    const int cq = (lane & 3) * 2;
    const uint32_t dk0 = desc_lo(sbase, 16);
    const uint32_t dv0 = desc_lo(sbase + 8192, ATT_ONES_OFF - 8192);
    if (threadIdx.x == 0) {
        mbar_init(bar, 1);
        asm volatile("fence.mbarrier_init.release.cluster;" ::: "memory");
    }
    asm volatile("st.shared.v4.b32 [%0], {%1, %1, %1, %1};" ::"r"(sbase + ATT_ONES_OFF + threadIdx.x * 16), "r"(0x3F803F80u) : "memory");
    fence_proxy_async();
    __syncthreads();
#pragma unroll 1
    for (int tile = blockIdx.x; tile < ATT_NTILES; tile += gridDim.x) {
    if (g_bad[tile] == 0) continue;
    const int head = tile >> 4;
    const int row0 = (tile & 15) * 128 + warp_id * 16 + (lane >> 2);
    const uint32_t dq = desc_lo(sbase + ATT_Q_OFF + (threadIdx.x >> 7) * 4096, 16);
    float o[20];
#pragma unroll
    for (int i = 0; i < 20; i++) o[i] = 0.f;
    float m0 = -INFINITY, m1 = -INFINITY;
#pragma unroll 1
    for (int j = 0; j < NBLK; j++) {
        if (threadIdx.x == 0) {
            mbar_expect_tx(bar, j == 0 ? 3 * 8192 : 2 * 8192);
            if (j == 0) tma_load_2d(sbase + ATT_Q_OFF, &mKV, head * DH, (tile & 15) * 128, bar);
            tma_load_2d(sbase, &mKV, DM + head * DH, j * 128, bar);
            tma_load_2d(sbase + 8192, &mKV, 2 * DM + head * DH, j * 128, bar);
        }
        __syncwarp();
        mbar_wait(bar, j & 1);
#pragma unroll 1
        for (int hf = 0; hf < 2; hf++) {
            float s[32];
            wgmma_fence();
            wgmma_ss_n64_tb0(s, dq, HI, dk0 + hf * 256, HI, 0);
            wgmma_ss_n64_tb0(s, dq + 2, HI, dk0 + hf * 256 + 2, HI, 1);
            wgmma_commit();
            wgmma_wait<0>();
            const float mo0 = m0, mo1 = m1;
            row_max(s, m0, m1);
            const float a0 = ex2(mo0 - m0), a1 = ex2(mo1 - m1);
            uint32_t p[16];
#pragma unroll
            for (int i = 0; i < 8; i++) {
                p[2 * i] = pack_bf16(ex2(s[4 * i + 0] - m0), ex2(s[4 * i + 1] - m0));
                p[2 * i + 1] = pack_bf16(ex2(s[4 * i + 2] - m1), ex2(s[4 * i + 3] - m1));
            }
#pragma unroll
            for (int i = 0; i < 5; i++) {
                o[4 * i + 0] *= a0; o[4 * i + 1] *= a0;
                o[4 * i + 2] *= a1; o[4 * i + 3] *= a1;
            }
            wgmma_fence();
            const uint32_t dv = dv0 + hf * 256 - ((uint32_t)(hf * 256) << 16);
#pragma unroll
            for (int t = 0; t < 4; t++)
                wgmma_rs_n40_tb1(o, p[4 * t], p[4 * t + 1], p[4 * t + 2], p[4 * t + 3], dv + t * 64, HI, 1);
            wgmma_commit();
            wgmma_wait<0>();
        }
        __syncthreads();
    }
    const float f0 = g_gate[row0] / o[16], f1 = g_gate[row0 + 8] / o[18];
    bf16* op0 = g_a5 + (size_t)row0 * A5W + head * DH + cq;
    bf16* op1 = op0 + 8 * A5W;
#pragma unroll
    for (int i = 0; i < 4; i++) {
        *reinterpret_cast<uint32_t*>(op0 + 8 * i) = pack_bf16(o[4 * i] * f0, o[4 * i + 1] * f0);
        *reinterpret_cast<uint32_t*>(op1 + 8 * i) = pack_bf16(o[4 * i + 2] * f1, o[4 * i + 3] * f1);
    }
    }
}

#define ATT_MINB 2
__global__ void __launch_bounds__(ATT_THREADS, 4 / ATT_NWG)
attn_kernel(const __grid_constant__ CUtensorMap mKV) {
    extern __shared__ uint8_t smem_raw[];
    const uint32_t sbase = (smem_u32(smem_raw) + 1023u) & ~1023u;
    const uint32_t bar_kfull = sbase + ATT_BAR_OFF;
    const uint32_t bar_vfull = bar_kfull + 8 * ATT_STAGES;
    const uint32_t bar_empty = bar_vfull + 8 * ATT_STAGES;
    const int tile = blockIdx.x;
    const int head = tile / ATT_TPH;
    const int q0 = (tile % ATT_TPH) * (64 * ATT_NWG);
    const int lane = threadIdx.x & 31;
    constexpr int NBLK = S_LEN / 128;
    TL_START(6)
    pdl_launch();

    auto issue_kv = [&](int g) {
        const int sn = g % ATT_STAGES;
        if (g >= ATT_STAGES) mbar_wait(bar_empty + 8 * sn, ((g / ATT_STAGES) - 1) & 1);
        const uint32_t skn = sbase + sn * 16384;
        mbar_expect_tx(bar_kfull + 8 * sn, g == 0 ? 8192 + 4096 * ATT_NWG : 8192);
        if (g == 0) {
#pragma unroll
            for (int qq = 0; qq < ATT_NWG / 2; qq++)
                tma_load_2d(sbase + ATT_Q_OFF + qq * 8192, &mKV, head * DH, q0 + qq * 128, bar_kfull);
        }
        tma_load_2d(skn, &mKV, DM + head * DH, g * 128, bar_kfull + 8 * sn);
        mbar_expect_tx(bar_vfull + 8 * sn, 8192);
        tma_load_2d(skn + 8192, &mKV, 2 * DM + head * DH, g * 128, bar_vfull + 8 * sn);
    };

    if (threadIdx.x == 0) {
        for (int s = 0; s < ATT_STAGES; s++) {
            mbar_init(bar_kfull + 8 * s, 1);
            mbar_init(bar_vfull + 8 * s, 1);
            mbar_init(bar_empty + 8 * s, ATT_NWG);
        }
        asm volatile("fence.mbarrier_init.release.cluster;" ::: "memory");
        prefetch_tmap(&mKV);
        pdl_wait();
#pragma unroll
        for (int j = 0; j < ATT_DIST; j++) issue_kv(j);
    }
    {
        if (threadIdx.x < 256) {
            asm volatile("st.shared.v4.b32 [%0], {%1, %1, %1, %1};" ::"r"(sbase + ATT_ONES_OFF + threadIdx.x * 16), "r"(0x3F803F80u) : "memory");
            const int r = threadIdx.x >> 2, ch = threadIdx.x & 3;
            const uint32_t w0 = (ch == ((r >> 1) & 3)) ? 0x00003F80u : 0u;
            asm volatile("st.shared.v4.b32 [%0], {%1, %2, %2, %2};" ::"r"(sbase + ATT_KEXT_OFF + threadIdx.x * 16), "r"(w0), "r"(0u) : "memory");
        }
        asm volatile("st.shared.v4.b32 [%0], {%1, %1, %1, %1};" ::"r"(sbase + ATT_QEXT_OFF + threadIdx.x * 32), "r"(0u) : "memory");
        asm volatile("st.shared.v4.b32 [%0], {%1, %1, %1, %1};" ::"r"(sbase + ATT_QEXT_OFF + threadIdx.x * 32 + 16), "r"(0u) : "memory");
    }
    fence_proxy_async();
    __syncthreads();

    constexpr uint32_t HI = desc_hi(512, 2);
    const uint32_t dk0 = desc_lo(sbase, 16);
    const uint32_t dv0 = desc_lo(sbase + 8192, ATT_ONES_OFF - 8192);
    const uint32_t dke = dk0 + (ATT_KEXT_OFF >> 4);
    const uint32_t dq = dk0 + ((ATT_Q_OFF + (threadIdx.x >> 7) * 4096) >> 4);
    float o[20];
#pragma unroll
    for (int i = 0; i < 20; i++) o[i] = 0.f;
    float s0[32];
    mbar_wait(bar_kfull, 0);
    wgmma_fence();
    wgmma_ss_n64_tb0(s0, dq, HI, dk0, HI, 0);
    wgmma_ss_n64_tb0(s0, dq + 2, HI, dk0 + 2, HI, 1);
    wgmma_commit();
    wgmma_wait<0>();
    float m0 = -INFINITY, m1 = -INFINITY;
    row_max(s0, m0, m1);
    if ((lane & 3) == 0) {
        const int r = ((threadIdx.x >> 5) & 3) * 16 + (lane >> 2);
        const uint32_t qe = sbase + ATT_QEXT_OFF + (threadIdx.x >> 7) * 4096;
        asm volatile("st.shared.b16 [%0], %1;" ::"r"(qe + r * 64 + (((r >> 1) & 3) << 4)), "h"((uint16_t)(pack_bf16(-m0, 0.f) & 0xFFFFu)) : "memory");
        asm volatile("st.shared.b16 [%0], %1;" ::"r"(qe + (r + 8) * 64 + ((((r + 8) >> 1) & 3) << 4)), "h"((uint16_t)(pack_bf16(-m1, 0.f) & 0xFFFFu)) : "memory");
    }
    fence_proxy_async();
    named_bar_sync(1 + (threadIdx.x >> 7), 128);
    wgmma_fence();
    wgmma_ss_n64_tb0(s0, dq + ((ATT_QEXT_OFF - ATT_Q_OFF) >> 4), HI, dke, HI, 1);
    wgmma_commit();
    wgmma_wait<0>();
#pragma unroll 1
    for (int j = 0; j < NBLK; j++) {
        if (threadIdx.x == 0 && j + ATT_DIST < NBLK) issue_kv(j + ATT_DIST);
        __syncwarp();
        const uint32_t stage = j & (ATT_STAGES - 1), nstage = (j + 1) & (ATT_STAGES - 1);
        const uint32_t dk = dk0 + stage * 1024;
        const uint32_t dv = dv0 + stage * 1024 - (stage << 26);
        mbar_wait(bar_vfull + 8 * stage, (j / ATT_STAGES) & 1);
        attn_step(s0, o, dq, dke, dk + 256, dv, 0u);
        uint32_t dkn = dk;
        if (j + 1 < NBLK) {
            mbar_wait(bar_kfull + 8 * nstage, ((j + 1) / ATT_STAGES) & 1);
            dkn = dk0 + nstage * 1024;
        }
        attn_step(s0, o, dq, dke, dkn, dv + 256 - (256u << 16), bar_empty + 8 * stage);
    }
    bool ok = (o[16] <= 1.8446744e19f) && (o[18] <= 1.8446744e19f);
#pragma unroll
    for (int i = 0; i < 16; i++) ok = ok && (fabsf(o[i]) <= 3.0e38f);
    const int row0 = q0 + (threadIdx.x >> 5) * 16 + (lane >> 2);
    const float f0 = g_gate[row0] / o[16], f1 = g_gate[row0 + 8] / o[18];
    bf16* op0 = g_a5 + (size_t)row0 * A5W + head * DH + (lane & 3) * 2;
    bf16* op1 = op0 + 8 * A5W;
#pragma unroll
    for (int i = 0; i < 4; i++) {
        *reinterpret_cast<uint32_t*>(op0 + 8 * i) = pack_bf16(o[4 * i] * f0, o[4 * i + 1] * f0);
        *reinterpret_cast<uint32_t*>(op1 + 8 * i) = pack_bf16(o[4 * i + 2] * f1, o[4 * i + 3] * f1);
    }
    const int bad = __syncthreads_or(!ok);
    if (threadIdx.x < ATT_NWG / 2) g_bad[tile * (ATT_NWG / 2) + threadIdx.x] = bad;
    TL_END(6)
}

typedef CUresult (*EncodeFn)(CUtensorMap*, CUtensorMapDataType, cuuint32_t, void*, const cuuint64_t*, const cuuint64_t*,
                             const cuuint32_t*, const cuuint32_t*, CUtensorMapInterleave, CUtensorMapSwizzle,
                             CUtensorMapL2promotion, CUtensorMapFloatOOBfill);

static CUtensorMap make_map(EncodeFn fn, const void* ptr, int rows, int cols, int box_cols, int box_rows,
                            CUtensorMapSwizzle swz) {
    CUtensorMap m;
    cuuint64_t dims[2] = {(cuuint64_t)cols, (cuuint64_t)rows};
    cuuint64_t strides[1] = {(cuuint64_t)cols * 2};
    cuuint32_t box[2] = {(cuuint32_t)box_cols, (cuuint32_t)box_rows};
    cuuint32_t es[2] = {1, 1};
    fn(&m, CU_TENSOR_MAP_DATA_TYPE_BFLOAT16, 2, const_cast<void*>(ptr), dims, strides, box, es,
       CU_TENSOR_MAP_INTERLEAVE_NONE, swz, CU_TENSOR_MAP_L2_PROMOTION_L2_256B, CU_TENSOR_MAP_FLOAT_OOB_FILL_NONE);
    return m;
}

template <typename... KArgs, typename... Args>
static void launch_ex(void (*kern)(KArgs...), int grid, int block, int smem, cudaStream_t st, int cluster, int pdl, Args... args) {
    cudaLaunchConfig_t cfg = {};
    cfg.gridDim = dim3(grid);
    cfg.blockDim = dim3(block);
    cfg.dynamicSmemBytes = smem;
    cfg.stream = st;
    cudaLaunchAttribute at[2];
    at[0].id = cudaLaunchAttributeProgrammaticStreamSerialization;
    at[0].val.programmaticStreamSerializationAllowed = pdl;
    at[1].id = cudaLaunchAttributeClusterDimension;
    at[1].val.clusterDim.x = cluster;
    at[1].val.clusterDim.y = 1;
    at[1].val.clusterDim.z = 1;
    cfg.attrs = at;
    cfg.numAttrs = cluster > 1 ? 2 : 1;
    cudaLaunchKernelEx(&cfg, kern, KArgs(args)...);
}

extern "C" void kernel_launch(void* const* d_in, const int* in_sizes, int n_in, void* d_out, int out_size) {
    const bf16* x = (const bf16*)d_in[0];
    const bf16* wqkv = (const bf16*)d_in[1];
    const bf16* wo = (const bf16*)d_in[2];
    const bf16* w1 = (const bf16*)d_in[4];
    const bf16* w2 = (const bf16*)d_in[5];
    const bf16* w3 = (const bf16*)d_in[6];
    const bf16* w4 = (const bf16*)d_in[7];
    const bf16* gate_w = (const bf16*)d_in[8];

    static EncodeFn enc = nullptr;
    static void *p_qkv, *p_h, *p_x1, *p_a5, *p_cs1, *p_cs3;
    static cudaStream_t s2;
    static cudaEvent_t ev_fork, ev_join;
    using G1 = GemmSmem<256, 4>;
    using G2 = GemmSmem<128, 5>;
#define G3BN 256
    using G3 = GemmSmem<G3BN, 4>;
    if (!enc) {
        void* fn = nullptr;
        cudaDriverEntryPointQueryResult qres;
        cudaGetDriverEntryPoint("cuTensorMapEncodeTiled", &fn, cudaEnableDefault, &qres);
        enc = (EncodeFn)fn;
        cudaGetSymbolAddress(&p_qkv, g_qkv);
        cudaGetSymbolAddress(&p_h, g_h);
        cudaGetSymbolAddress(&p_x1, g_x1);
        cudaGetSymbolAddress(&p_a5, g_a5);
        cudaGetSymbolAddress(&p_cs1, g_cs1);
        cudaGetSymbolAddress(&p_cs3, g_cs3);
        cudaFuncSetAttribute(gemm_kernel<1, 256, 4>, cudaFuncAttributeMaxDynamicSharedMemorySize, G1::TOTAL);
        cudaFuncSetAttribute(gemm_kernel<2, 128, 5>, cudaFuncAttributeMaxDynamicSharedMemorySize, G2::TOTAL);
        cudaFuncSetAttribute(gemm_kernel<3, G3BN, 4>, cudaFuncAttributeMaxDynamicSharedMemorySize, G3::TOTAL);
        cudaFuncSetAttribute(gemm_kernel<5, 128, 5>, cudaFuncAttributeMaxDynamicSharedMemorySize, G2::TOTAL);
        cudaStreamCreateWithFlags(&s2, cudaStreamNonBlocking);
        cudaEventCreateWithFlags(&ev_fork, cudaEventDisableTiming);
        cudaEventCreateWithFlags(&ev_join, cudaEventDisableTiming);
        cudaFuncSetAttribute(attn_kernel, cudaFuncAttributeMaxDynamicSharedMemorySize, ATT_SMEM);
        cudaFuncSetAttribute(attn_exact_kernel, cudaFuncAttributeMaxDynamicSharedMemorySize, ATT_SMEM);
    }
    const CUtensorMapSwizzle SW128 = CU_TENSOR_MAP_SWIZZLE_128B, SW64 = CU_TENSOR_MAP_SWIZZLE_64B;
    CUtensorMap mX = make_map(enc, x, S_LEN, DM, 64, 128, SW128);
    CUtensorMap mXres = make_map(enc, x, S_LEN, DM, 64, 64, SW128);
    CUtensorMap mWqkv = make_map(enc, wqkv, DM, 3 * DM, 64, 64, SW128);
    CUtensorMap mW1 = make_map(enc, w1, DM, DM, 64, 64, SW128);
    CUtensorMap mW2 = make_map(enc, w2, DM, DM, 64, 64, SW128);
    CUtensorMap mW3 = make_map(enc, w3, DM, FF, 64, 64, SW128);
    CUtensorMap mW4 = make_map(enc, w4, FF, DM, 64, 64, SW128);
    CUtensorMap mWo = make_map(enc, wo, DM, DM, 64, 64, SW128);
    CUtensorMap mQKVst = make_map(enc, p_qkv, S_LEN, 3 * DM, 64, 64, SW128);
    CUtensorMap mKV = make_map(enc, p_qkv, S_LEN, 3 * DM, 32, 128, SW64);
    CUtensorMap mHst = make_map(enc, p_h, S_LEN, DM, 64, 64, SW128);
    CUtensorMap mHld = make_map(enc, p_h, S_LEN, DM, 64, 128, SW128);
    CUtensorMap mX1st = make_map(enc, p_x1, S_LEN, DM, 64, 64, SW128);
    CUtensorMap mX1ld = make_map(enc, p_x1, S_LEN, DM, 64, 128, SW128);
    CUtensorMap mA5st = make_map(enc, p_a5, S_LEN, A5W, 64, 64, SW128);
    CUtensorMap mA5st32 = make_map(enc, p_a5, S_LEN, A5W, 32, 64, SW64);
    CUtensorMap mA5ld = make_map(enc, p_a5, S_LEN, A5W, 64, 128, SW128);
    CUtensorMap mOut = make_map(enc, d_out, S_LEN, DM, 64, 64, SW128);

    cudaStream_t st = cudaStreamPerThread;
    prep_kernel<<<256 + 64 + 224, 256, 0, st>>>(x, gate_w, w1, w3);
    launch_ex(gemm_kernel<1, 256, 4>, 132, 384, G1::TOTAL, st, 1, 1, mX, mWqkv, mW1, mQKVst, mHst, x, 16, 16);
    launch_ex(gemm_kernel<2, 128, 5>, 128, 384, G2::TOTAL, st, 1, 1, mHld, mW2, mW2, mX1st, mXres, x, 8, 16);
    cudaEventRecord(ev_fork, st);
    launch_ex(attn_kernel, ATT_GRID, ATT_THREADS, ATT_SMEM, st, 1, 1, mKV);
    launch_ex(attn_exact_kernel, 32, 256, ATT_SMEM, st, 1, 1, mKV);
    cudaStreamWaitEvent(s2, ev_fork, 0);
    launch_ex(gemm_kernel<3, G3BN, 4>, 132, 384, G3::TOTAL, s2, 1, 0, mX1ld, mW3, mW3, mA5st, mA5st32, x, FF / G3BN, 16);
    cudaEventRecord(ev_join, s2);
    cudaStreamWaitEvent(st, ev_join, 0);
    launch_ex(gemm_kernel<5, 128, 5>, 128, 384, G2::TOTAL, st, 1, 0, mA5ld, mWo, mW4, mOut, mX1st, (const bf16*)p_x1, 8, 72);
}
```

```cpp
#include <cuda_runtime.h>
#include <cuda_bf16.h>
#include <cuda.h>
#include <stdint.h>

typedef __nv_bfloat16 bf16;

constexpr int S_LEN = 2048;
constexpr int DM = 1024;
constexpr int FF = 3584;
constexpr int NH = 32;
constexpr int DH = 32;
constexpr int A5W = DM + FF;

__device__ __align__(1024) bf16 g_qkv[S_LEN * 3 * DM];
__device__ __align__(1024) bf16 g_h[S_LEN * DM];
__device__ __align__(1024) bf16 g_x1[S_LEN * DM];
__device__ __align__(1024) bf16 g_a5[S_LEN * A5W];
__device__ __align__(16) float g_mean1[S_LEN];
__device__ __align__(16) float g_rstd1[S_LEN];
__device__ __align__(16) float g_gate[S_LEN];
__device__ __align__(16) float g_omg[S_LEN];
__device__ __align__(16) float g_cs1[4 * DM];
__device__ __align__(16) float g_cs3[4 * FF];
__device__ __align__(16) float2 g_stat2[S_LEN * 8];
__device__ int g_bad[NH * 16];
__device__ int g_tile_ctr;

#define TL_START(k)
#define PH(i)
#define TL_END(k)

__device__ __forceinline__ uint32_t smem_u32(const void* p) { return (uint32_t)__cvta_generic_to_shared(p); }

__device__ __forceinline__ void mbar_init(uint32_t bar, uint32_t count) {
    asm volatile("mbarrier.init.shared::cta.b64 [%0], %1;" ::"r"(bar), "r"(count));
}
__device__ __forceinline__ void mbar_expect_tx(uint32_t bar, uint32_t bytes) {
    asm volatile("mbarrier.arrive.expect_tx.shared::cta.b64 _, [%0], %1;" ::"r"(bar), "r"(bytes) : "memory");
}
__device__ __forceinline__ void mbar_arrive(uint32_t bar) {
    asm volatile("mbarrier.arrive.shared::cta.b64 _, [%0];" ::"r"(bar) : "memory");
}
__device__ __forceinline__ bool mbar_try_wait(uint32_t bar, uint32_t parity) {
    uint32_t ok;
    asm volatile(
        "{\n.reg .pred p;\n"
        "mbarrier.try_wait.parity.shared::cta.b64 p, [%1], %2;\n"
        "selp.u32 %0, 1, 0, p;\n}\n"
        : "=r"(ok)
        : "r"(bar), "r"(parity)
        : "memory");
    return ok != 0;
}
__device__ __forceinline__ void mbar_wait(uint32_t bar, uint32_t parity) {
    uint32_t spins = 0;
    while (!mbar_try_wait(bar, parity)) {
        if (++spins > (1u << 24)) __trap();
    }
}
__device__ __forceinline__ void tma_load_2d(uint32_t dst, const CUtensorMap* map, int c0, int c1, uint32_t bar) {
    asm volatile(
        "cp.async.bulk.tensor.2d.shared::cluster.global.mbarrier::complete_tx::bytes [%0], [%1, {%3, %4}], [%2];"
        ::"r"(dst), "l"(map), "r"(bar), "r"(c0), "r"(c1)
        : "memory");
}
__device__ __forceinline__ void tma_store_2d(const CUtensorMap* map, uint32_t src, int c0, int c1) {
    asm volatile("cp.async.bulk.tensor.2d.global.shared::cta.bulk_group [%0, {%2, %3}], [%1];"
                 ::"l"(map), "r"(src), "r"(c0), "r"(c1)
                 : "memory");
}
__device__ __forceinline__ void pdl_wait() { asm volatile("griddepcontrol.wait;" ::: "memory"); }
__device__ __forceinline__ void pdl_launch() { asm volatile("griddepcontrol.launch_dependents;" ::: "memory"); }
__device__ __forceinline__ void bulk_commit() { asm volatile("cp.async.bulk.commit_group;" ::: "memory"); }
__device__ __forceinline__ void bulk_wait_read0() { asm volatile("cp.async.bulk.wait_group.read 0;" ::: "memory"); }
__device__ __forceinline__ void bulk_wait0() { asm volatile("cp.async.bulk.wait_group 0;" ::: "memory"); }
__device__ __forceinline__ void fence_proxy_async() { asm volatile("fence.proxy.async.shared::cta;" ::: "memory"); }
__device__ __forceinline__ void named_bar_sync(int id, int n) { asm volatile("bar.sync %0, %1;" ::"r"(id), "r"(n) : "memory"); }
__device__ __forceinline__ void named_bar_arrive(int id, int n) { asm volatile("bar.arrive %0, %1;" ::"r"(id), "r"(n) : "memory"); }
__device__ __forceinline__ void wgmma_fence() { asm volatile("wgmma.fence.sync.aligned;" ::: "memory"); }
__device__ __forceinline__ void wgmma_commit() { asm volatile("wgmma.commit_group.sync.aligned;" ::: "memory"); }
template <int N>
__device__ __forceinline__ void wgmma_wait() { asm volatile("wgmma.wait_group.sync.aligned %0;" ::"n"(N) : "memory"); }
__device__ __forceinline__ void prefetch_tmap(const CUtensorMap* m) {
    asm volatile("prefetch.tensormap [%0];" ::"l"(m) : "memory");
}
template <int R>
__device__ __forceinline__ void reg_alloc() { asm volatile("setmaxnreg.inc.sync.aligned.u32 %0;" ::"n"(R)); }
template <int R>
__device__ __forceinline__ void reg_dealloc() { asm volatile("setmaxnreg.dec.sync.aligned.u32 %0;" ::"n"(R)); }
__device__ __forceinline__ void stmatrix_x4(uint32_t addr, uint32_t r0, uint32_t r1, uint32_t r2, uint32_t r3) {
    asm volatile("stmatrix.sync.aligned.m8n8.x4.shared.b16 [%0], {%1, %2, %3, %4};"
                 ::"r"(addr), "r"(r0), "r"(r1), "r"(r2), "r"(r3)
                 : "memory");
}
__device__ __forceinline__ uint32_t pack_bf16(float lo, float hi) {
    uint32_t r;
    asm("cvt.rn.bf16x2.f32 %0, %1, %2;" : "=r"(r) : "f"(hi), "f"(lo));
    return r;
}
__device__ __forceinline__ float bf16_round(float v) { return __bfloat162float(__float2bfloat16_rn(v)); }
__device__ __forceinline__ float ex2(float x) {
    float y;
    asm volatile("ex2.approx.ftz.f32 %0, %1;" : "=f"(y) : "f"(x));
    return y;
}
__device__ __forceinline__ float tanh_fast(float x) {
    float y;
    asm("tanh.approx.f32 %0, %1;" : "=f"(y) : "f"(x));
    return y;
}
__device__ __forceinline__ float gelu_tanh(float v) {
    float u = 0.7978845608028654f * (v + 0.044715f * v * v * v);
    float hv = 0.5f * v;
    return fmaf(hv, tanh_fast(u), hv);
}
__device__ __forceinline__ uint32_t desc_lo(uint32_t addr, uint32_t lbo_bytes) {
    return ((addr & 0x3FFFF) >> 4) | (((lbo_bytes >> 4) & 0x3FFF) << 16);
}
__host__ __device__ constexpr uint32_t desc_hi(uint32_t sbo_bytes, uint32_t swz) {
    return ((sbo_bytes >> 4) & 0x3FFF) | (swz << 30);
}

__device__ __forceinline__ void wgmma_ss_n128_tb1(float (&d)[64], uint32_t alo, uint32_t ahi, uint32_t blo, uint32_t bhi, int scale_d) {
    asm volatile("{\n.reg .pred p;\n.reg .b64 da, db;\nsetp.ne.b32 p, %68, 0;\nmov.b64 da, {%64, %65};\nmov.b64 db, {%66, %67};\n"
        "wgmma.mma_async.sync.aligned.m64n128k16.f32.bf16.bf16 {%0, %1, %2, %3, %4, %5, %6, %7, %8, %9, %10, %11, %12, %13, %14, %15, %16, %17, %18, %19, %20, %21, %22, %23, %24, %25, %26, %27, %28, %29, %30, %31, %32, %33, %34, %35, %36, %37, %38, %39, %40, %41, %42, %43, %44, %45, %46, %47, %48, %49, %50, %51, %52, %53, %54, %55, %56, %57, %58, %59, %60, %61, %62, %63}, da, db, p, 1, 1, 0, 1;\n}\n"
        : "+f"(d[0]), "+f"(d[1]), "+f"(d[2]), "+f"(d[3]), "+f"(d[4]), "+f"(d[5]), "+f"(d[6]), "+f"(d[7]), "+f"(d[8]), "+f"(d[9]), "+f"(d[10]), "+f"(d[11]), "+f"(d[12]), "+f"(d[13]), "+f"(d[14]), "+f"(d[15]), "+f"(d[16]), "+f"(d[17]), "+f"(d[18]), "+f"(d[19]), "+f"(d[20]), "+f"(d[21]), "+f"(d[22]), "+f"(d[23]), "+f"(d[24]), "+f"(d[25]), "+f"(d[26]), "+f"(d[27]), "+f"(d[28]), "+f"(d[29]), "+f"(d[30]), "+f"(d[31]), "+f"(d[32]), "+f"(d[33]), "+f"(d[34]), "+f"(d[35]), "+f"(d[36]), "+f"(d[37]), "+f"(d[38]), "+f"(d[39]), "+f"(d[40]), "+f"(d[41]), "+f"(d[42]), "+f"(d[43]), "+f"(d[44]), "+f"(d[45]), "+f"(d[46]), "+f"(d[47]), "+f"(d[48]), "+f"(d[49]), "+f"(d[50]), "+f"(d[51]), "+f"(d[52]), "+f"(d[53]), "+f"(d[54]), "+f"(d[55]), "+f"(d[56]), "+f"(d[57]), "+f"(d[58]), "+f"(d[59]), "+f"(d[60]), "+f"(d[61]), "+f"(d[62]), "+f"(d[63])
        : "r"(alo), "r"(ahi), "r"(blo), "r"(bhi), "r"(scale_d));
}

__device__ __forceinline__ void wgmma_ss_n192_tb1(float (&d)[96], uint32_t alo, uint32_t ahi, uint32_t blo, uint32_t bhi, int scale_d) {
    asm volatile("{\n.reg .pred p;\n.reg .b64 da, db;\nsetp.ne.b32 p, %100, 0;\nmov.b64 da, {%96, %97};\nmov.b64 db, {%98, %99};\n"
        "wgmma.mma_async.sync.aligned.m64n192k16.f32.bf16.bf16 {%0, %1, %2, %3, %4, %5, %6, %7, %8, %9, %10, %11, %12, %13, %14, %15, %16, %17, %18, %19, %20, %21, %22, %23, %24, %25, %26, %27, %28, %29, %30, %31, %32, %33, %34, %35, %36, %37, %38, %39, %40, %41, %42, %43, %44, %45, %46, %47, %48, %49, %50, %51, %52, %53, %54, %55, %56, %57, %58, %59, %60, %61, %62, %63, %64, %65, %66, %67, %68, %69, %70, %71, %72, %73, %74, %75, %76, %77, %78, %79, %80, %81, %82, %83, %84, %85, %86, %87, %88, %89, %90, %91, %92, %93, %94, %95}, da, db, p, 1, 1, 0, 1;\n}\n"
        : "+f"(d[0]), "+f"(d[1]), "+f"(d[2]), "+f"(d[3]), "+f"(d[4]), "+f"(d[5]), "+f"(d[6]), "+f"(d[7]), "+f"(d[8]), "+f"(d[9]), "+f"(d[10]), "+f"(d[11]), "+f"(d[12]), "+f"(d[13]), "+f"(d[14]), "+f"(d[15]), "+f"(d[16]), "+f"(d[17]), "+f"(d[18]), "+f"(d[19]), "+f"(d[20]), "+f"(d[21]), "+f"(d[22]), "+f"(d[23]), "+f"(d[24]), "+f"(d[25]), "+f"(d[26]), "+f"(d[27]), "+f"(d[28]), "+f"(d[29]), "+f"(d[30]), "+f"(d[31]), "+f"(d[32]), "+f"(d[33]), "+f"(d[34]), "+f"(d[35]), "+f"(d[36]), "+f"(d[37]), "+f"(d[38]), "+f"(d[39]), "+f"(d[40]), "+f"(d[41]), "+f"(d[42]), "+f"(d[43]), "+f"(d[44]), "+f"(d[45]), "+f"(d[46]), "+f"(d[47]), "+f"(d[48]), "+f"(d[49]), "+f"(d[50]), "+f"(d[51]), "+f"(d[52]), "+f"(d[53]), "+f"(d[54]), "+f"(d[55]), "+f"(d[56]), "+f"(d[57]), "+f"(d[58]), "+f"(d[59]), "+f"(d[60]), "+f"(d[61]), "+f"(d[62]), "+f"(d[63]), "+f"(d[64]), "+f"(d[65]), "+f"(d[66]), "+f"(d[67]), "+f"(d[68]), "+f"(d[69]), "+f"(d[70]), "+f"(d[71]), "+f"(d[72]), "+f"(d[73]), "+f"(d[74]), "+f"(d[75]), "+f"(d[76]), "+f"(d[77]), "+f"(d[78]), "+f"(d[79]), "+f"(d[80]), "+f"(d[81]), "+f"(d[82]), "+f"(d[83]), "+f"(d[84]), "+f"(d[85]), "+f"(d[86]), "+f"(d[87]), "+f"(d[88]), "+f"(d[89]), "+f"(d[90]), "+f"(d[91]), "+f"(d[92]), "+f"(d[93]), "+f"(d[94]), "+f"(d[95])
        : "r"(alo), "r"(ahi), "r"(blo), "r"(bhi), "r"(scale_d));
}

__device__ __forceinline__ void wgmma_ss_n224_tb1(float (&d)[112], uint32_t alo, uint32_t ahi, uint32_t blo, uint32_t bhi, int scale_d) {
    asm volatile("{\n.reg .pred p;\n.reg .b64 da, db;\nsetp.ne.b32 p, %116, 0;\nmov.b64 da, {%112, %113};\nmov.b64 db, {%114, %115};\n"
        "wgmma.mma_async.sync.aligned.m64n224k16.f32.bf16.bf16 {%0, %1, %2, %3, %4, %5, %6, %7, %8, %9, %10, %11, %12, %13, %14, %15, %16, %17, %18, %19, %20, %21, %22, %23, %24, %25, %26, %27, %28, %29, %30, %31, %32, %33, %34, %35, %36, %37, %38, %39, %40, %41, %42, %43, %44, %45, %46, %47, %48, %49, %50, %51, %52, %53, %54, %55, %56, %57, %58, %59, %60, %61, %62, %63, %64, %65, %66, %67, %68, %69, %70, %71, %72, %73, %74, %75, %76, %77, %78, %79, %80, %81, %82, %83, %84, %85, %86, %87, %88, %89, %90, %91, %92, %93, %94, %95, %96, %97, %98, %99, %100, %101, %102, %103, %104, %105, %106, %107, %108, %109, %110, %111}, da, db, p, 1, 1, 0, 1;\n}\n"
        : "+f"(d[0]), "+f"(d[1]), "+f"(d[2]), "+f"(d[3]), "+f"(d[4]), "+f"(d[5]), "+f"(d[6]), "+f"(d[7]), "+f"(d[8]), "+f"(d[9]), "+f"(d[10]), "+f"(d[11]), "+f"(d[12]), "+f"(d[13]), "+f"(d[14]), "+f"(d[15]), "+f"(d[16]), "+f"(d[17]), "+f"(d[18]), "+f"(d[19]), "+f"(d[20]), "+f"(d[21]), "+f"(d[22]), "+f"(d[23]), "+f"(d[24]), "+f"(d[25]), "+f"(d[26]), "+f"(d[27]), "+f"(d[28]), "+f"(d[29]), "+f"(d[30]), "+f"(d[31]), "+f"(d[32]), "+f"(d[33]), "+f"(d[34]), "+f"(d[35]), "+f"(d[36]), "+f"(d[37]), "+f"(d[38]), "+f"(d[39]), "+f"(d[40]), "+f"(d[41]), "+f"(d[42]), "+f"(d[43]), "+f"(d[44]), "+f"(d[45]), "+f"(d[46]), "+f"(d[47]), "+f"(d[48]), "+f"(d[49]), "+f"(d[50]), "+f"(d[51]), "+f"(d[52]), "+f"(d[53]), "+f"(d[54]), "+f"(d[55]), "+f"(d[56]), "+f"(d[57]), "+f"(d[58]), "+f"(d[59]), "+f"(d[60]), "+f"(d[61]), "+f"(d[62]), "+f"(d[63]), "+f"(d[64]), "+f"(d[65]), "+f"(d[66]), "+f"(d[67]), "+f"(d[68]), "+f"(d[69]), "+f"(d[70]), "+f"(d[71]), "+f"(d[72]), "+f"(d[73]), "+f"(d[74]), "+f"(d[75]), "+f"(d[76]), "+f"(d[77]), "+f"(d[78]), "+f"(d[79]), "+f"(d[80]), "+f"(d[81]), "+f"(d[82]), "+f"(d[83]), "+f"(d[84]), "+f"(d[85]), "+f"(d[86]), "+f"(d[87]), "+f"(d[88]), "+f"(d[89]), "+f"(d[90]), "+f"(d[91]), "+f"(d[92]), "+f"(d[93]), "+f"(d[94]), "+f"(d[95]), "+f"(d[96]), "+f"(d[97]), "+f"(d[98]), "+f"(d[99]), "+f"(d[100]), "+f"(d[101]), "+f"(d[102]), "+f"(d[103]), "+f"(d[104]), "+f"(d[105]), "+f"(d[106]), "+f"(d[107]), "+f"(d[108]), "+f"(d[109]), "+f"(d[110]), "+f"(d[111])
        : "r"(alo), "r"(ahi), "r"(blo), "r"(bhi), "r"(scale_d));
}

__device__ __forceinline__ void wgmma_ss_n256_tb1(float (&d)[128], uint32_t alo, uint32_t ahi, uint32_t blo, uint32_t bhi, int scale_d) {
    asm volatile("{\n.reg .pred p;\n.reg .b64 da, db;\nsetp.ne.b32 p, %132, 0;\nmov.b64 da, {%128, %129};\nmov.b64 db, {%130, %131};\n"
        "wgmma.mma_async.sync.aligned.m64n256k16.f32.bf16.bf16 {%0, %1, %2, %3, %4, %5, %6, %7, %8, %9, %10, %11, %12, %13, %14, %15, %16, %17, %18, %19, %20, %21, %22, %23, %24, %25, %26, %27, %28, %29, %30, %31, %32, %33, %34, %35, %36, %37, %38, %39, %40, %41, %42, %43, %44, %45, %46, %47, %48, %49, %50, %51, %52, %53, %54, %55, %56, %57, %58, %59, %60, %61, %62, %63, %64, %65, %66, %67, %68, %69, %70, %71, %72, %73, %74, %75, %76, %77, %78, %79, %80, %81, %82, %83, %84, %85, %86, %87, %88, %89, %90, %91, %92, %93, %94, %95, %96, %97, %98, %99, %100, %101, %102, %103, %104, %105, %106, %107, %108, %109, %110, %111, %112, %113, %114, %115, %116, %117, %118, %119, %120, %121, %122, %123, %124, %125, %126, %127}, da, db, p, 1, 1, 0, 1;\n}\n"
        : "+f"(d[0]), "+f"(d[1]), "+f"(d[2]), "+f"(d[3]), "+f"(d[4]), "+f"(d[5]), "+f"(d[6]), "+f"(d[7]), "+f"(d[8]), "+f"(d[9]), "+f"(d[10]), "+f"(d[11]), "+f"(d[12]), "+f"(d[13]), "+f"(d[14]), "+f"(d[15]), "+f"(d[16]), "+f"(d[17]), "+f"(d[18]), "+f"(d[19]), "+f"(d[20]), "+f"(d[21]), "+f"(d[22]), "+f"(d[23]), "+f"(d[24]), "+f"(d[25]), "+f"(d[26]), "+f"(d[27]), "+f"(d[28]), "+f"(d[29]), "+f"(d[30]), "+f"(d[31]), "+f"(d[32]), "+f"(d[33]), "+f"(d[34]), "+f"(d[35]), "+f"(d[36]), "+f"(d[37]), "+f"(d[38]), "+f"(d[39]), "+f"(d[40]), "+f"(d[41]), "+f"(d[42]), "+f"(d[43]), "+f"(d[44]), "+f"(d[45]), "+f"(d[46]), "+f"(d[47]), "+f"(d[48]), "+f"(d[49]), "+f"(d[50]), "+f"(d[51]), "+f"(d[52]), "+f"(d[53]), "+f"(d[54]), "+f"(d[55]), "+f"(d[56]), "+f"(d[57]), "+f"(d[58]), "+f"(d[59]), "+f"(d[60]), "+f"(d[61]), "+f"(d[62]), "+f"(d[63]), "+f"(d[64]), "+f"(d[65]), "+f"(d[66]), "+f"(d[67]), "+f"(d[68]), "+f"(d[69]), "+f"(d[70]), "+f"(d[71]), "+f"(d[72]), "+f"(d[73]), "+f"(d[74]), "+f"(d[75]), "+f"(d[76]), "+f"(d[77]), "+f"(d[78]), "+f"(d[79]), "+f"(d[80]), "+f"(d[81]), "+f"(d[82]), "+f"(d[83]), "+f"(d[84]), "+f"(d[85]), "+f"(d[86]), "+f"(d[87]), "+f"(d[88]), "+f"(d[89]), "+f"(d[90]), "+f"(d[91]), "+f"(d[92]), "+f"(d[93]), "+f"(d[94]), "+f"(d[95]), "+f"(d[96]), "+f"(d[97]), "+f"(d[98]), "+f"(d[99]), "+f"(d[100]), "+f"(d[101]), "+f"(d[102]), "+f"(d[103]), "+f"(d[104]), "+f"(d[105]), "+f"(d[106]), "+f"(d[107]), "+f"(d[108]), "+f"(d[109]), "+f"(d[110]), "+f"(d[111]), "+f"(d[112]), "+f"(d[113]), "+f"(d[114]), "+f"(d[115]), "+f"(d[116]), "+f"(d[117]), "+f"(d[118]), "+f"(d[119]), "+f"(d[120]), "+f"(d[121]), "+f"(d[122]), "+f"(d[123]), "+f"(d[124]), "+f"(d[125]), "+f"(d[126]), "+f"(d[127])
        : "r"(alo), "r"(ahi), "r"(blo), "r"(bhi), "r"(scale_d));
}

__device__ __forceinline__ void wgmma_ss_n64_tb0(float (&d)[32], uint32_t alo, uint32_t ahi, uint32_t blo, uint32_t bhi, int scale_d) {
    asm volatile("{\n.reg .pred p;\n.reg .b64 da, db;\nsetp.ne.b32 p, %36, 0;\nmov.b64 da, {%32, %33};\nmov.b64 db, {%34, %35};\n"
        "wgmma.mma_async.sync.aligned.m64n64k16.f32.bf16.bf16 {%0, %1, %2, %3, %4, %5, %6, %7, %8, %9, %10, %11, %12, %13, %14, %15, %16, %17, %18, %19, %20, %21, %22, %23, %24, %25, %26, %27, %28, %29, %30, %31}, da, db, p, 1, 1, 0, 0;\n}\n"
        : "+f"(d[0]), "+f"(d[1]), "+f"(d[2]), "+f"(d[3]), "+f"(d[4]), "+f"(d[5]), "+f"(d[6]), "+f"(d[7]), "+f"(d[8]), "+f"(d[9]), "+f"(d[10]), "+f"(d[11]), "+f"(d[12]), "+f"(d[13]), "+f"(d[14]), "+f"(d[15]), "+f"(d[16]), "+f"(d[17]), "+f"(d[18]), "+f"(d[19]), "+f"(d[20]), "+f"(d[21]), "+f"(d[22]), "+f"(d[23]), "+f"(d[24]), "+f"(d[25]), "+f"(d[26]), "+f"(d[27]), "+f"(d[28]), "+f"(d[29]), "+f"(d[30]), "+f"(d[31])
        : "r"(alo), "r"(ahi), "r"(blo), "r"(bhi), "r"(scale_d));
}

__device__ __forceinline__ void wgmma_rs_n128_tb0(float (&d)[64], uint32_t a0, uint32_t a1, uint32_t a2, uint32_t a3, uint32_t blo, uint32_t bhi, int scale_d) {
    asm volatile("{\n.reg .pred p;\n.reg .b64 db;\nsetp.ne.b32 p, %70, 0;\nmov.b64 db, {%68, %69};\n"
        "wgmma.mma_async.sync.aligned.m64n128k16.f32.bf16.bf16 {%0, %1, %2, %3, %4, %5, %6, %7, %8, %9, %10, %11, %12, %13, %14, %15, %16, %17, %18, %19, %20, %21, %22, %23, %24, %25, %26, %27, %28, %29, %30, %31, %32, %33, %34, %35, %36, %37, %38, %39, %40, %41, %42, %43, %44, %45, %46, %47, %48, %49, %50, %51, %52, %53, %54, %55, %56, %57, %58, %59, %60, %61, %62, %63}, {%64, %65, %66, %67}, db, p, 1, 1, 0;\n}\n"
        : "+f"(d[0]), "+f"(d[1]), "+f"(d[2]), "+f"(d[3]), "+f"(d[4]), "+f"(d[5]), "+f"(d[6]), "+f"(d[7]), "+f"(d[8]), "+f"(d[9]), "+f"(d[10]), "+f"(d[11]), "+f"(d[12]), "+f"(d[13]), "+f"(d[14]), "+f"(d[15]), "+f"(d[16]), "+f"(d[17]), "+f"(d[18]), "+f"(d[19]), "+f"(d[20]), "+f"(d[21]), "+f"(d[22]), "+f"(d[23]), "+f"(d[24]), "+f"(d[25]), "+f"(d[26]), "+f"(d[27]), "+f"(d[28]), "+f"(d[29]), "+f"(d[30]), "+f"(d[31]), "+f"(d[32]), "+f"(d[33]), "+f"(d[34]), "+f"(d[35]), "+f"(d[36]), "+f"(d[37]), "+f"(d[38]), "+f"(d[39]), "+f"(d[40]), "+f"(d[41]), "+f"(d[42]), "+f"(d[43]), "+f"(d[44]), "+f"(d[45]), "+f"(d[46]), "+f"(d[47]), "+f"(d[48]), "+f"(d[49]), "+f"(d[50]), "+f"(d[51]), "+f"(d[52]), "+f"(d[53]), "+f"(d[54]), "+f"(d[55]), "+f"(d[56]), "+f"(d[57]), "+f"(d[58]), "+f"(d[59]), "+f"(d[60]), "+f"(d[61]), "+f"(d[62]), "+f"(d[63])
        : "r"(a0), "r"(a1), "r"(a2), "r"(a3), "r"(blo), "r"(bhi), "r"(scale_d));
}

__device__ __forceinline__ void wgmma_rs_n64_tb0(float (&d)[32], uint32_t a0, uint32_t a1, uint32_t a2, uint32_t a3, uint32_t blo, uint32_t bhi, int scale_d) {
    asm volatile("{\n.reg .pred p;\n.reg .b64 db;\nsetp.ne.b32 p, %38, 0;\nmov.b64 db, {%36, %37};\n"
        "wgmma.mma_async.sync.aligned.m64n64k16.f32.bf16.bf16 {%0, %1, %2, %3, %4, %5, %6, %7, %8, %9, %10, %11, %12, %13, %14, %15, %16, %17, %18, %19, %20, %21, %22, %23, %24, %25, %26, %27, %28, %29, %30, %31}, {%32, %33, %34, %35}, db, p, 1, 1, 0;\n}\n"
        : "+f"(d[0]), "+f"(d[1]), "+f"(d[2]), "+f"(d[3]), "+f"(d[4]), "+f"(d[5]), "+f"(d[6]), "+f"(d[7]), "+f"(d[8]), "+f"(d[9]), "+f"(d[10]), "+f"(d[11]), "+f"(d[12]), "+f"(d[13]), "+f"(d[14]), "+f"(d[15]), "+f"(d[16]), "+f"(d[17]), "+f"(d[18]), "+f"(d[19]), "+f"(d[20]), "+f"(d[21]), "+f"(d[22]), "+f"(d[23]), "+f"(d[24]), "+f"(d[25]), "+f"(d[26]), "+f"(d[27]), "+f"(d[28]), "+f"(d[29]), "+f"(d[30]), "+f"(d[31])
        : "r"(a0), "r"(a1), "r"(a2), "r"(a3), "r"(blo), "r"(bhi), "r"(scale_d));
}

__device__ __forceinline__ void wgmma_rs_n32_tb1(float (&d)[16], uint32_t a0, uint32_t a1, uint32_t a2, uint32_t a3, uint32_t blo, uint32_t bhi, int scale_d) {
    asm volatile("{\n.reg .pred p;\n.reg .b64 db;\nsetp.ne.b32 p, %22, 0;\nmov.b64 db, {%20, %21};\n"
        "wgmma.mma_async.sync.aligned.m64n32k16.f32.bf16.bf16 {%0, %1, %2, %3, %4, %5, %6, %7, %8, %9, %10, %11, %12, %13, %14, %15}, {%16, %17, %18, %19}, db, p, 1, 1, 1;\n}\n"
        : "+f"(d[0]), "+f"(d[1]), "+f"(d[2]), "+f"(d[3]), "+f"(d[4]), "+f"(d[5]), "+f"(d[6]), "+f"(d[7]), "+f"(d[8]), "+f"(d[9]), "+f"(d[10]), "+f"(d[11]), "+f"(d[12]), "+f"(d[13]), "+f"(d[14]), "+f"(d[15])
        : "r"(a0), "r"(a1), "r"(a2), "r"(a3), "r"(blo), "r"(bhi), "r"(scale_d));
}

__device__ __forceinline__ void wgmma_rs_n40_tb1(float (&d)[20], uint32_t a0, uint32_t a1, uint32_t a2, uint32_t a3, uint32_t blo, uint32_t bhi, int scale_d) {
    asm volatile("{\n.reg .pred p;\n.reg .b64 db;\nsetp.ne.b32 p, %26, 0;\nmov.b64 db, {%24, %25};\n"
        "wgmma.mma_async.sync.aligned.m64n40k16.f32.bf16.bf16 {%0, %1, %2, %3, %4, %5, %6, %7, %8, %9, %10, %11, %12, %13, %14, %15, %16, %17, %18, %19}, {%20, %21, %22, %23}, db, p, 1, 1, 1;\n}\n"
        : "+f"(d[0]), "+f"(d[1]), "+f"(d[2]), "+f"(d[3]), "+f"(d[4]), "+f"(d[5]), "+f"(d[6]), "+f"(d[7]), "+f"(d[8]), "+f"(d[9]), "+f"(d[10]), "+f"(d[11]), "+f"(d[12]), "+f"(d[13]), "+f"(d[14]), "+f"(d[15]), "+f"(d[16]), "+f"(d[17]), "+f"(d[18]), "+f"(d[19])
        : "r"(a0), "r"(a1), "r"(a2), "r"(a3), "r"(blo), "r"(bhi), "r"(scale_d));
}

template <int BN>
__device__ __forceinline__ void wgmma_tile(float (&d)[BN / 2], uint32_t da, uint32_t db, int sd) {
    constexpr uint32_t HI = desc_hi(1024, 1);
    if constexpr (BN == 128) wgmma_ss_n128_tb1(d, da, HI, db, HI, sd);
    else if constexpr (BN == 192) wgmma_ss_n192_tb1(d, da, HI, db, HI, sd);
    else if constexpr (BN == 224) wgmma_ss_n224_tb1(d, da, HI, db, HI, sd);
    else wgmma_ss_n256_tb1(d, da, HI, db, HI, sd);
}

__global__ void __launch_bounds__(256) prep_kernel(const bf16* __restrict__ x, const bf16* __restrict__ gate_w,
                                                   const bf16* __restrict__ w1, const bf16* __restrict__ w3) {
    constexpr int row_blocks = 256;
    if (blockIdx.x == 0 && threadIdx.x == 0) g_tile_ctr = 0;
    const int tid = threadIdx.x;
    TL_START(0)
    pdl_launch();
    if ((int)blockIdx.x < row_blocks) {
        const int row = blockIdx.x * 8 + (tid >> 5);
        const int lane = tid & 31;
        const uint4* xr = reinterpret_cast<const uint4*>(x + (size_t)row * DM);
        const uint4* gw = reinterpret_cast<const uint4*>(gate_w);
        float v[32];
        float gsum = 0.f, sum = 0.f;
#pragma unroll
        for (int i = 0; i < 4; i++) {
            uint4 a = xr[lane + 32 * i];
            uint4 b = gw[lane + 32 * i];
            const uint32_t aa[4] = {a.x, a.y, a.z, a.w};
            const uint32_t bb[4] = {b.x, b.y, b.z, b.w};
#pragma unroll
            for (int j = 0; j < 4; j++) {
                float x0 = __uint_as_float(aa[j] << 16), x1 = __uint_as_float(aa[j] & 0xFFFF0000u);
                float g0 = __uint_as_float(bb[j] << 16), g1 = __uint_as_float(bb[j] & 0xFFFF0000u);
                v[i * 8 + j * 2] = x0;
                v[i * 8 + j * 2 + 1] = x1;
                sum += x0 + x1;
                gsum += bf16_round(x0 * g0) + bf16_round(x1 * g1);
            }
        }
#pragma unroll
        for (int o = 16; o > 0; o >>= 1) {
            sum += __shfl_xor_sync(0xffffffffu, sum, o);
            gsum += __shfl_xor_sync(0xffffffffu, gsum, o);
        }
        const float mean = sum * (1.0f / DM);
        float m2 = 0.f;
#pragma unroll
        for (int i = 0; i < 32; i++) {
            float d = v[i] - mean;
            m2 += d * d;
        }
#pragma unroll
        for (int o = 16; o > 0; o >>= 1) m2 += __shfl_xor_sync(0xffffffffu, m2, o);
        if (lane == 0) {
            g_mean1[row] = mean;
            g_rstd1[row] = rsqrtf(m2 * (1.0f / DM) + 1e-5f);
            float logit = bf16_round(gsum);
            float g = bf16_round(1.0f / (1.0f + __expf(-logit)));
            g_gate[row] = g;
            g_omg[row] = bf16_round(1.0f - g);
        }
    } else {
        __shared__ float red[32][65];
        int blk = blockIdx.x - row_blocks;
        const bf16* w = w1;
        int ld = DM;
        float* cs_out = g_cs1;
        if (blk >= 64) { blk -= 64; w = w3; ld = FF; cs_out = g_cs3; }
        const int chunk = blk & 3;
        const int col0 = (blk >> 2) * 64;
        const int cg = tid & 7;
        const int rg = tid >> 3;
        uint4 a[8];
#pragma unroll
        for (int r = 0; r < 8; r++)
            a[r] = *reinterpret_cast<const uint4*>(w + (size_t)(chunk * 256 + r * 32 + rg) * ld + col0 + cg * 8);
        float acc[8];
#pragma unroll
        for (int j = 0; j < 8; j++) acc[j] = 0.f;
#pragma unroll
        for (int r = 0; r < 8; r++) {
            const uint32_t aa[4] = {a[r].x, a[r].y, a[r].z, a[r].w};
#pragma unroll
            for (int j = 0; j < 4; j++) {
                acc[2 * j] += __uint_as_float(aa[j] << 16);
                acc[2 * j + 1] += __uint_as_float(aa[j] & 0xFFFF0000u);
            }
        }
#pragma unroll
        for (int j = 0; j < 8; j++) red[rg][cg * 8 + j] = acc[j];
        __syncthreads();
        if (tid < 64) {
            float s = 0.f;
#pragma unroll
            for (int r = 0; r < 32; r++) s += red[r][tid];
            cs_out[chunk * ld + col0 + tid] = s;
        }
    }
    TL_END(0)
}

#define RELEASE_STAGE(b) if (tid_wg == 0) mbar_arrive(b)
template <int BN, int STAGES>
struct GemmSmem {
    static constexpr int A_BYTES = 128 * 64 * 2;
    static constexpr int B_BOXES = (BN + 63) / 64;
    static constexpr int B_BYTES = B_BOXES * 64 * 64 * 2;
    static constexpr int STAGE_BYTES = A_BYTES + B_BYTES;
    static constexpr int STG_OFF = STAGES * STAGE_BYTES;
    static constexpr int CS_OFF = STAGES * STAGE_BYTES + 2 * 16384;
    static constexpr int BAR_OFF = CS_OFF + 1024;
    static constexpr int TOTAL = BAR_OFF + 192 + 512;
};

template <int MODE, int BN, int STAGES>
__global__ void __launch_bounds__(384, 1)
gemm_kernel(const __grid_constant__ CUtensorMap mA, const __grid_constant__ CUtensorMap mB0,
            const __grid_constant__ CUtensorMap mB1, const __grid_constant__ CUtensorMap mC0,
            const __grid_constant__ CUtensorMap mC1, const bf16* __restrict__ xin, int n_tiles_n, int kblocks) {
    using L = GemmSmem<BN, STAGES>;
    extern __shared__ uint8_t smem_raw[];
    const uint32_t sbase = (smem_u32(smem_raw) + 1023u) & ~1023u;
    const uint32_t bar_full = sbase + L::BAR_OFF;
    const uint32_t bar_empty = bar_full + 8 * STAGES;
    const uint32_t bar_res = bar_empty + 8 * STAGES;
    const int wg = threadIdx.x >> 7;
    const int ntiles = 16 * n_tiles_n;
    constexpr bool DYN = (MODE == 3);
    const uint32_t bar_tfull = bar_res + 8;
    const uint32_t bar_tempty = bar_tfull + 16;
    const uint32_t tile_slot = bar_tempty + 16;
    TL_START(MODE)
    pdl_launch();

    if (threadIdx.x == 0) {
        for (int s = 0; s < STAGES; s++) {
            mbar_init(bar_full + 8 * s, 1);
            mbar_init(bar_empty + 8 * s, 2);
        }
        for (int s = 0; s < 2; s++) {
            mbar_init(bar_tfull + 8 * s, 1);
            mbar_init(bar_tempty + 8 * s, 2);
        }
        mbar_init(bar_res, 1);
        asm volatile("fence.mbarrier_init.release.cluster;" ::: "memory");
        prefetch_tmap(&mA);
        prefetch_tmap(&mB0);
        if (MODE == 1 || MODE == 5) prefetch_tmap(&mB1);
        if (MODE == 2 || MODE == 5) prefetch_tmap(&mC1);
        prefetch_tmap(&mC0);
    }
    __syncthreads();

    if (wg == 0) {
        reg_dealloc<40>();
        if (threadIdx.x == 0) {
            if (MODE != 1) pdl_wait();
            int stage = 0;
            uint32_t phase = 1;
            for (int it = 0;; it++) {
                int tile;
                if (DYN) {
                    tile = atomicAdd(&g_tile_ctr, 1);
                    mbar_wait(bar_tempty + 8 * (it & 1), ((it >> 1) & 1) ^ 1);
                    asm volatile("st.shared.b32 [%0], %1;" ::"r"(tile_slot + 4 * (it & 1)), "r"(tile) : "memory");
                    mbar_arrive(bar_tfull + 8 * (it & 1));
                } else {
                    tile = blockIdx.x + it * gridDim.x;
                }
                if (tile >= ntiles) break;
                if (MODE == 1) tile = (tile + 192) & 255;
                const int m0 = (tile & 15) * 128;
                const int n0 = (tile >> 4) * BN;
                for (int kb = 0; kb < kblocks; kb++) {
                    mbar_wait(bar_empty + 8 * stage, phase);
                    const uint32_t sa = sbase + stage * L::STAGE_BYTES;
                    const uint32_t sb = sa + L::A_BYTES;
                    const uint32_t fb = bar_full + 8 * stage;
                    mbar_expect_tx(fb, L::STAGE_BYTES);
                    int arow = m0;
                    if (MODE == 2) {
                        const int grp = kb >> 2;
                        arow += (grp == 0) ? -1 : (grp == 1) ? 1 : (grp == 2) ? -2 : 2;
                    }
                    tma_load_2d(sa, &mA, kb * 64, arow, fb);
                    const CUtensorMap* mb = &mB0;
                    int bc = n0, br = kb * 64;
                    if (MODE == 1 && n0 >= 3 * DM) { mb = &mB1; bc = n0 - 3 * DM; }
                    if (MODE == 5 && kb >= 16) { mb = &mB1; br = (kb - 16) * 64; }
#pragma unroll
                    for (int b = 0; b < L::B_BOXES; b++) tma_load_2d(sb + b * 8192, mb, bc + b * 64, br, fb);
                    if ((MODE == 2 || MODE == 5) && kb == STAGES - 1) {
                        mbar_expect_tx(bar_res, 32768);
#pragma unroll
                        for (int q = 0; q < 4; q++)
                            tma_load_2d(sbase + L::STG_OFF + q * 8192, &mC1, n0 + (q & 1) * 64, m0 + (q >> 1) * 64, bar_res);
                    }
                    if (++stage == STAGES) { stage = 0; phase ^= 1; }
                }
            }
        }
    } else {
        reg_alloc<232>();
        const int c = wg - 1;
        const int warp = (threadIdx.x >> 5) & 3;
        const int lane = threadIdx.x & 31;
        const int tid_wg = threadIdx.x & 127;
        const uint32_t stg = sbase + L::STG_OFF + c * 16384;
        int stage = 0;
        uint32_t phase = 0;
        float acc[BN / 2];
        bool first = true;
        PH(0)
        if (MODE != 1) pdl_wait();
        for (int it = 0;; it++) {
            int tile;
            if (DYN) {
                mbar_wait(bar_tfull + 8 * (it & 1), (it >> 1) & 1);
                asm volatile("ld.shared.b32 %0, [%1];" : "=r"(tile) : "r"(tile_slot + 4 * (it & 1)) : "memory");
                named_bar_sync(1 + c, 128);
                if (tid_wg == 0) mbar_arrive(bar_tempty + 8 * (it & 1));
            } else {
                tile = blockIdx.x + it * gridDim.x;
            }
            if (tile >= ntiles) break;
            if (MODE == 1) tile = (tile + 192) & 255;
            const int m0 = (tile & 15) * 128;
            const int n0 = (tile >> 4) * BN;
            const int r0 = m0 + c * 64 + warp * 16 + (lane >> 2);
            const int r1 = r0 + 8;
            float mu[2], rs[2], og[2];
            if (MODE == 3) {
                const int t = threadIdx.x - 128;
                if (t < BN) {
                    const float v = (g_cs3[n0 + t] + g_cs3[FF + n0 + t]) + (g_cs3[2 * FF + n0 + t] + g_cs3[3 * FF + n0 + t]);
                    asm volatile("st.shared.f32 [%0], %1;" ::"r"(sbase + L::CS_OFF + t * 4), "f"(v) : "memory");
                }
#pragma unroll
                for (int h = 0; h < 2; h++) {
                    const float4* sp = reinterpret_cast<const float4*>(&g_stat2[(h ? r1 : r0) * 8]);
                    float4 p[4];
                    float s = 0.f;
#pragma unroll
                    for (int i = 0; i < 4; i++) { p[i] = sp[i]; s += p[i].x + p[i].z; }
                    const float mean = s * (1.0f / DM);
                    float m2 = 0.f;
#pragma unroll
                    for (int i = 0; i < 4; i++) {
                        float d0 = p[i].x * (1.0f / 128) - mean, d1 = p[i].z * (1.0f / 128) - mean;
                        m2 += p[i].y + p[i].w + 128.0f * (d0 * d0 + d1 * d1);
                    }
                    mu[h] = mean;
                    rs[h] = rsqrtf(m2 * (1.0f / DM) + 1e-5f);
                }
            }
            if (MODE == 3 || MODE == 5) { og[0] = g_omg[r0]; og[1] = g_omg[r1]; }
            int prev_stage = 0;
            for (int kb = 0; kb < kblocks; kb++) {
                mbar_wait(bar_full + 8 * stage, phase);
                const uint32_t sa = sbase + stage * L::STAGE_BYTES + c * 8192;
                const uint32_t sb = sbase + stage * L::STAGE_BYTES + L::A_BYTES;
                const uint32_t da = desc_lo(sa, 16);
                const uint32_t db = desc_lo(sb, 8192);
                wgmma_fence();
#pragma unroll
                for (int k = 0; k < 4; k++) wgmma_tile<BN>(acc, da + k * 2, db + k * 128, (kb | k) != 0);
                wgmma_commit();
                if (kb > 0) {
                    wgmma_wait<1>();
                    RELEASE_STAGE(bar_empty + 8 * prev_stage);
                }
                prev_stage = stage;
                if (++stage == STAGES) { stage = 0; phase ^= 1; }
            }
            wgmma_wait<0>();
            RELEASE_STAGE(bar_empty + 8 * prev_stage);
            PH(1)
            if (MODE == 1 && first) { pdl_wait(); first = false; }

            const int cq = (lane & 3) * 2;
            const CUtensorMap* mc = &mC0;
            const uint32_t rrow = warp * 16 + (lane >> 2);
            const uint32_t res0 = stg + rrow * 128 + cq * 2;
            int out_c0 = n0;
            if (MODE == 1) {
                if (n0 < DM) {
                    const float qs = 0.17677669529663687f * 1.4426950408889634f;
#pragma unroll
                    for (int j = 0; j < BN / 2; j++) acc[j] *= qs;
                } else if (n0 >= 3 * DM) {
                    mc = &mC1;
                    out_c0 = n0 - 3 * DM;
                    const float mu0 = g_mean1[r0], mu1 = g_mean1[r1];
                    const float rs0 = g_rstd1[r0], rs1 = g_rstd1[r1];
                    {
                        const int t = threadIdx.x - 128;
                        const float v = (g_cs1[out_c0 + t] + g_cs1[DM + out_c0 + t]) + (g_cs1[2 * DM + out_c0 + t] + g_cs1[3 * DM + out_c0 + t]);
                        asm volatile("st.shared.f32 [%0], %1;" ::"r"(sbase + L::CS_OFF + t * 4), "f"(v) : "memory");
                    }
                    named_bar_sync(3, 256);
#pragma unroll
                    for (int j = 0; j < BN / 8; j++) {
                        float2 cs;
                        asm volatile("ld.shared.v2.f32 {%0, %1}, [%2];" : "=f"(cs.x), "=f"(cs.y) : "r"(sbase + L::CS_OFF + (8 * j + cq) * 4));
                        acc[4 * j + 0] = gelu_tanh(rs0 * fmaf(-mu0, cs.x, acc[4 * j + 0]));
                        acc[4 * j + 1] = gelu_tanh(rs0 * fmaf(-mu0, cs.y, acc[4 * j + 1]));
                        acc[4 * j + 2] = gelu_tanh(rs1 * fmaf(-mu1, cs.x, acc[4 * j + 2]));
                        acc[4 * j + 3] = gelu_tanh(rs1 * fmaf(-mu1, cs.y, acc[4 * j + 3]));
                    }
                    named_bar_sync(3, 256);
                }
            } else if (MODE == 2) {
                float s0 = 0.f, s1 = 0.f;
                mbar_wait(bar_res, 0);
#pragma unroll
                for (int j = 0; j < BN / 8; j++) {
                    uint32_t xa, xb;
                    const uint32_t ra = res0 + (j >> 3) * 8192 + (((j & 7) ^ (rrow & 7)) << 4);
                    asm volatile("ld.shared.b32 %0, [%1];" : "=r"(xa) : "r"(ra));
                    asm volatile("ld.shared.b32 %0, [%1];" : "=r"(xb) : "r"(ra + 1024));
                    acc[4 * j + 0] = bf16_round(bf16_round(acc[4 * j + 0]) + __uint_as_float(xa << 16));
                    acc[4 * j + 1] = bf16_round(bf16_round(acc[4 * j + 1]) + __uint_as_float(xa & 0xFFFF0000u));
                    acc[4 * j + 2] = bf16_round(bf16_round(acc[4 * j + 2]) + __uint_as_float(xb << 16));
                    acc[4 * j + 3] = bf16_round(bf16_round(acc[4 * j + 3]) + __uint_as_float(xb & 0xFFFF0000u));
                    s0 += acc[4 * j + 0] + acc[4 * j + 1];
                    s1 += acc[4 * j + 2] + acc[4 * j + 3];
                }
                s0 += __shfl_xor_sync(0xffffffffu, s0, 1);
                s0 += __shfl_xor_sync(0xffffffffu, s0, 2);
                s1 += __shfl_xor_sync(0xffffffffu, s1, 1);
                s1 += __shfl_xor_sync(0xffffffffu, s1, 2);
                const float mu0 = s0 * (1.0f / BN), mu1 = s1 * (1.0f / BN);
                float q0 = 0.f, q1 = 0.f;
#pragma unroll
                for (int j = 0; j < BN / 8; j++) {
                    float d;
                    d = acc[4 * j + 0] - mu0; q0 += d * d;
                    d = acc[4 * j + 1] - mu0; q0 += d * d;
                    d = acc[4 * j + 2] - mu1; q1 += d * d;
                    d = acc[4 * j + 3] - mu1; q1 += d * d;
                }
                q0 += __shfl_xor_sync(0xffffffffu, q0, 1);
                q0 += __shfl_xor_sync(0xffffffffu, q0, 2);
                q1 += __shfl_xor_sync(0xffffffffu, q1, 1);
                q1 += __shfl_xor_sync(0xffffffffu, q1, 2);
                if ((lane & 3) == 0) {
                    static_assert(MODE != 2 || BN == 128, "stats layout assumes BN=128");
                    g_stat2[r0 * 8 + (n0 >> 7)] = make_float2(s0, q0);
                    g_stat2[r1 * 8 + (n0 >> 7)] = make_float2(s1, q1);
                }
            } else if (MODE == 3) {
                out_c0 = n0 + DM;
                named_bar_sync(3, 256);
#pragma unroll
                for (int j = 0; j < BN / 8; j++) {
                    float2 cs;
                    asm volatile("ld.shared.v2.f32 {%0, %1}, [%2];" : "=f"(cs.x), "=f"(cs.y) : "r"(sbase + L::CS_OFF + (8 * j + cq) * 4));
                    acc[4 * j + 0] = og[0] * gelu_tanh(rs[0] * fmaf(-mu[0], cs.x, acc[4 * j + 0]));
                    acc[4 * j + 1] = og[0] * gelu_tanh(rs[0] * fmaf(-mu[0], cs.y, acc[4 * j + 1]));
                    acc[4 * j + 2] = og[1] * gelu_tanh(rs[1] * fmaf(-mu[1], cs.x, acc[4 * j + 2]));
                    acc[4 * j + 3] = og[1] * gelu_tanh(rs[1] * fmaf(-mu[1], cs.y, acc[4 * j + 3]));
                }
                named_bar_sync(3, 256);
            } else {
                const float og0 = og[0], og1 = og[1];
                mbar_wait(bar_res, 0);
#pragma unroll
                for (int j = 0; j < BN / 8; j++) {
                    uint32_t xa, xb;
                    const uint32_t ra = res0 + (j >> 3) * 8192 + (((j & 7) ^ (rrow & 7)) << 4);
                    asm volatile("ld.shared.b32 %0, [%1];" : "=r"(xa) : "r"(ra));
                    asm volatile("ld.shared.b32 %0, [%1];" : "=r"(xb) : "r"(ra + 1024));
                    acc[4 * j + 0] = fmaf(og0, __uint_as_float(xa << 16), acc[4 * j + 0]);
                    acc[4 * j + 1] = fmaf(og0, __uint_as_float(xa & 0xFFFF0000u), acc[4 * j + 1]);
                    acc[4 * j + 2] = fmaf(og1, __uint_as_float(xb << 16), acc[4 * j + 2]);
                    acc[4 * j + 3] = fmaf(og1, __uint_as_float(xb & 0xFFFF0000u), acc[4 * j + 3]);
                }
            }
            PH(3)
            const int srow = warp * 16 + (lane & 7) + ((lane >> 3) & 1) * 8;
#pragma unroll
            for (int rnd = 0; rnd < (BN + 127) / 128; rnd++) {
                if (tid_wg == 0) bulk_wait_read0();
                named_bar_sync(1 + c, 128);
#pragma unroll
                for (int jj = 0; jj < 8; jj++) {
                    const int j = rnd * 16 + jj * 2;
                    if (j * 8 < BN) {
                        const int jb = jj * 2 + (lane >> 4);
                        uint32_t addr = stg + (jb >> 3) * 8192 + srow * 128 + (((jb & 7) ^ (srow & 7)) << 4);
                        if (rnd * 128 + 128 > BN && jj >= 4)
                            addr = stg + 8192 + srow * 64 + (((jb & 3) ^ ((srow >> 1) & 3)) << 4);
                        stmatrix_x4(addr, pack_bf16(acc[4 * j + 0], acc[4 * j + 1]), pack_bf16(acc[4 * j + 2], acc[4 * j + 3]),
                                    pack_bf16(acc[4 * j + 4], acc[4 * j + 5]), pack_bf16(acc[4 * j + 6], acc[4 * j + 7]));
                    }
                }
                fence_proxy_async();
                named_bar_sync(1 + c, 128);
                if (tid_wg == 0) {
                    tma_store_2d(mc, stg, out_c0 + rnd * 128, m0 + c * 64);
                    if (rnd * 128 + 64 < BN)
                        tma_store_2d((rnd * 128 + 128 > BN) ? &mC1 : mc, stg + 8192, out_c0 + rnd * 128 + 64, m0 + c * 64);
                    bulk_commit();
                }
            }
        }
        PH(4)
        if (tid_wg == 0) bulk_wait0();
        PH(5)
        TL_END(MODE)
    }
}

#define ATT_SPLIT 16
#define ATT_NWG 4
constexpr int ATT_NTILES = NH * 16;
constexpr int ATT_TPH = S_LEN / (64 * ATT_NWG);
constexpr int ATT_GRID = NH * ATT_TPH;
constexpr int ATT_THREADS = 128 * ATT_NWG;
constexpr int ATT_STAGES = 4;
constexpr int ATT_DIST = 2;
constexpr int ATT_Q_OFF = ATT_STAGES * 16384;
constexpr int ATT_ONES_OFF = ATT_Q_OFF + 4096 * ATT_NWG;
constexpr int ATT_KEXT_OFF = ATT_ONES_OFF + 4096;
constexpr int ATT_QEXT_OFF = ATT_KEXT_OFF + 4096;
constexpr int ATT_BAR_OFF = ATT_QEXT_OFF + 4096 * ATT_NWG;
constexpr int ATT_SMEM = ATT_BAR_OFF + 256 + 1024;

__device__ __forceinline__ void row_max(const float (&s)[32], float& m0, float& m1) {
    float a0[8], a1[8];
#pragma unroll
    for (int i = 0; i < 8; i++) {
        a0[i] = fmaxf(s[4 * i], s[4 * i + 1]);
        a1[i] = fmaxf(s[4 * i + 2], s[4 * i + 3]);
    }
#pragma unroll
    for (int w = 4; w > 0; w >>= 1)
#pragma unroll
        for (int i = 0; i < w; i++) { a0[i] = fmaxf(a0[i], a0[i + w]); a1[i] = fmaxf(a1[i], a1[i + w]); }
    float mx0 = a0[0], mx1 = a1[0];
    mx0 = fmaxf(mx0, __shfl_xor_sync(0xffffffffu, mx0, 1));
    mx1 = fmaxf(mx1, __shfl_xor_sync(0xffffffffu, mx1, 1));
    mx0 = fmaxf(mx0, __shfl_xor_sync(0xffffffffu, mx0, 2));
    mx1 = fmaxf(mx1, __shfl_xor_sync(0xffffffffu, mx1, 2));
    m0 = fmaxf(m0, mx0);
    m1 = fmaxf(m1, mx1);
}

__device__ __forceinline__ void attn_step(float (&s)[32], float (&o)[20], uint32_t dq, uint32_t dke, uint32_t dk_next,
                                          uint32_t dv_cur, uint32_t release_bar) {
    constexpr uint32_t HI = desc_hi(512, 2);
    uint32_t p[16];
#pragma unroll
    for (int i = 0; i < 16; i++) p[i] = pack_bf16(ex2(s[2 * i]), ex2(s[2 * i + 1]));
    wgmma_fence();
    wgmma_ss_n64_tb0(s, dq, HI, dk_next, HI, 0);
    wgmma_ss_n64_tb0(s, dq + 2, HI, dk_next + 2, HI, 1);
    wgmma_ss_n64_tb0(s, dq + ((ATT_QEXT_OFF - ATT_Q_OFF) >> 4), HI, dke, HI, 1);
#pragma unroll
    for (int t = 0; t < 4; t++)
        wgmma_rs_n40_tb1(o, p[4 * t], p[4 * t + 1], p[4 * t + 2], p[4 * t + 3], dv_cur + t * 64, HI, 1);
    wgmma_commit();
    wgmma_wait<0>();
    if (release_bar != 0 && (threadIdx.x & 127) == 0) mbar_arrive(release_bar);
}

__global__ void __launch_bounds__(256, 1)
attn_exact_kernel(const __grid_constant__ CUtensorMap mKV) {
    extern __shared__ uint8_t smem_raw[];
    pdl_launch();
    pdl_wait();
    int any = 0;
    for (int t = blockIdx.x; t < ATT_NTILES; t += gridDim.x) any |= g_bad[t];
    if (!any) return;
    constexpr int NBLK = S_LEN / 128;
    constexpr uint32_t HI = desc_hi(512, 2);
    const uint32_t sbase = (smem_u32(smem_raw) + 1023u) & ~1023u;
    const uint32_t bar = sbase + ATT_BAR_OFF;
    const int warp_id = threadIdx.x >> 5;
    const int lane = threadIdx.x & 31;
    const int cq = (lane & 3) * 2;
    const uint32_t dk0 = desc_lo(sbase, 16);
    const uint32_t dv0 = desc_lo(sbase + 8192, ATT_ONES_OFF - 8192);
    if (threadIdx.x == 0) {
        mbar_init(bar, 1);
        asm volatile("fence.mbarrier_init.release.cluster;" ::: "memory");
    }
    asm volatile("st.shared.v4.b32 [%0], {%1, %1, %1, %1};" ::"r"(sbase + ATT_ONES_OFF + threadIdx.x * 16), "r"(0x3F803F80u) : "memory");
    fence_proxy_async();
    __syncthreads();
#pragma unroll 1
    for (int tile = blockIdx.x; tile < ATT_NTILES; tile += gridDim.x) {
    if (g_bad[tile] == 0) continue;
    const int head = tile >> 4;
    const int row0 = (tile & 15) * 128 + warp_id * 16 + (lane >> 2);
    const uint32_t dq = desc_lo(sbase + ATT_Q_OFF + (threadIdx.x >> 7) * 4096, 16);
    float o[20];
#pragma unroll
    for (int i = 0; i < 20; i++) o[i] = 0.f;
    float m0 = -INFINITY, m1 = -INFINITY;
#pragma unroll 1
    for (int j = 0; j < NBLK; j++) {
        if (threadIdx.x == 0) {
            mbar_expect_tx(bar, j == 0 ? 3 * 8192 : 2 * 8192);
            if (j == 0) tma_load_2d(sbase + ATT_Q_OFF, &mKV, head * DH, (tile & 15) * 128, bar);
            tma_load_2d(sbase, &mKV, DM + head * DH, j * 128, bar);
            tma_load_2d(sbase + 8192, &mKV, 2 * DM + head * DH, j * 128, bar);
        }
        __syncwarp();
        mbar_wait(bar, j & 1);
#pragma unroll 1
        for (int hf = 0; hf < 2; hf++) {
            float s[32];
            wgmma_fence();
            wgmma_ss_n64_tb0(s, dq, HI, dk0 + hf * 256, HI, 0);
            wgmma_ss_n64_tb0(s, dq + 2, HI, dk0 + hf * 256 + 2, HI, 1);
            wgmma_commit();
            wgmma_wait<0>();
            const float mo0 = m0, mo1 = m1;
            row_max(s, m0, m1);
            const float a0 = ex2(mo0 - m0), a1 = ex2(mo1 - m1);
            uint32_t p[16];
#pragma unroll
            for (int i = 0; i < 8; i++) {
                p[2 * i] = pack_bf16(ex2(s[4 * i + 0] - m0), ex2(s[4 * i + 1] - m0));
                p[2 * i + 1] = pack_bf16(ex2(s[4 * i + 2] - m1), ex2(s[4 * i + 3] - m1));
            }
#pragma unroll
            for (int i = 0; i < 5; i++) {
                o[4 * i + 0] *= a0; o[4 * i + 1] *= a0;
                o[4 * i + 2] *= a1; o[4 * i + 3] *= a1;
            }
            wgmma_fence();
            const uint32_t dv = dv0 + hf * 256 - ((uint32_t)(hf * 256) << 16);
#pragma unroll
            for (int t = 0; t < 4; t++)
                wgmma_rs_n40_tb1(o, p[4 * t], p[4 * t + 1], p[4 * t + 2], p[4 * t + 3], dv + t * 64, HI, 1);
            wgmma_commit();
            wgmma_wait<0>();
        }
        __syncthreads();
    }
    const float f0 = g_gate[row0] / o[16], f1 = g_gate[row0 + 8] / o[18];
    bf16* op0 = g_a5 + (size_t)row0 * A5W + head * DH + cq;
    bf16* op1 = op0 + 8 * A5W;
#pragma unroll
    for (int i = 0; i < 4; i++) {
        *reinterpret_cast<uint32_t*>(op0 + 8 * i) = pack_bf16(o[4 * i] * f0, o[4 * i + 1] * f0);
        *reinterpret_cast<uint32_t*>(op1 + 8 * i) = pack_bf16(o[4 * i + 2] * f1, o[4 * i + 3] * f1);
    }
    }
}

#define ATT_MINB 2
__global__ void __launch_bounds__(ATT_THREADS, 4 / ATT_NWG)
attn_kernel(const __grid_constant__ CUtensorMap mKV) {
    extern __shared__ uint8_t smem_raw[];
    const uint32_t sbase = (smem_u32(smem_raw) + 1023u) & ~1023u;
    const uint32_t bar_kfull = sbase + ATT_BAR_OFF;
    const uint32_t bar_vfull = bar_kfull + 8 * ATT_STAGES;
    const uint32_t bar_empty = bar_vfull + 8 * ATT_STAGES;
    const int tile = blockIdx.x;
    const int head = tile / ATT_TPH;
    const int q0 = (tile % ATT_TPH) * (64 * ATT_NWG);
    const int lane = threadIdx.x & 31;
    constexpr int NBLK = S_LEN / 128;
    TL_START(6)
    pdl_launch();

    auto issue_kv = [&](int g) {
        const int sn = g % ATT_STAGES;
        if (g >= ATT_STAGES) mbar_wait(bar_empty + 8 * sn, ((g / ATT_STAGES) - 1) & 1);
        const uint32_t skn = sbase + sn * 16384;
        mbar_expect_tx(bar_kfull + 8 * sn, g == 0 ? 8192 + 4096 * ATT_NWG : 8192);
        if (g == 0) {
#pragma unroll
            for (int qq = 0; qq < ATT_NWG / 2; qq++)
                tma_load_2d(sbase + ATT_Q_OFF + qq * 8192, &mKV, head * DH, q0 + qq * 128, bar_kfull);
        }
        tma_load_2d(skn, &mKV, DM + head * DH, g * 128, bar_kfull + 8 * sn);
        mbar_expect_tx(bar_vfull + 8 * sn, 8192);
        tma_load_2d(skn + 8192, &mKV, 2 * DM + head * DH, g * 128, bar_vfull + 8 * sn);
    };

    if (threadIdx.x == 0) {
        for (int s = 0; s < ATT_STAGES; s++) {
            mbar_init(bar_kfull + 8 * s, 1);
            mbar_init(bar_vfull + 8 * s, 1);
            mbar_init(bar_empty + 8 * s, ATT_NWG);
        }
        asm volatile("fence.mbarrier_init.release.cluster;" ::: "memory");
        prefetch_tmap(&mKV);
        pdl_wait();
#pragma unroll
        for (int j = 0; j < ATT_DIST; j++) issue_kv(j);
    }
    {
        if (threadIdx.x < 256) {
            asm volatile("st.shared.v4.b32 [%0], {%1, %1, %1, %1};" ::"r"(sbase + ATT_ONES_OFF + threadIdx.x * 16), "r"(0x3F803F80u) : "memory");
            const int r = threadIdx.x >> 2, ch = threadIdx.x & 3;
            const uint32_t w0 = (ch == ((r >> 1) & 3)) ? 0x00003F80u : 0u;
            asm volatile("st.shared.v4.b32 [%0], {%1, %2, %2, %2};" ::"r"(sbase + ATT_KEXT_OFF + threadIdx.x * 16), "r"(w0), "r"(0u) : "memory");
        }
        asm volatile("st.shared.v4.b32 [%0], {%1, %1, %1, %1};" ::"r"(sbase + ATT_QEXT_OFF + threadIdx.x * 32), "r"(0u) : "memory");
        asm volatile("st.shared.v4.b32 [%0], {%1, %1, %1, %1};" ::"r"(sbase + ATT_QEXT_OFF + threadIdx.x * 32 + 16), "r"(0u) : "memory");
    }
    fence_proxy_async();
    __syncthreads();

    constexpr uint32_t HI = desc_hi(512, 2);
    const uint32_t dk0 = desc_lo(sbase, 16);
    const uint32_t dv0 = desc_lo(sbase + 8192, ATT_ONES_OFF - 8192);
    const uint32_t dke = dk0 + (ATT_KEXT_OFF >> 4);
    const uint32_t dq = dk0 + ((ATT_Q_OFF + (threadIdx.x >> 7) * 4096) >> 4);
    float o[20];
#pragma unroll
    for (int i = 0; i < 20; i++) o[i] = 0.f;
    float s0[32];
    mbar_wait(bar_kfull, 0);
    wgmma_fence();
    wgmma_ss_n64_tb0(s0, dq, HI, dk0, HI, 0);
    wgmma_ss_n64_tb0(s0, dq + 2, HI, dk0 + 2, HI, 1);
    wgmma_commit();
    wgmma_wait<0>();
    float m0 = -INFINITY, m1 = -INFINITY;
    row_max(s0, m0, m1);
    if ((lane & 3) == 0) {
        const int r = ((threadIdx.x >> 5) & 3) * 16 + (lane >> 2);
        const uint32_t qe = sbase + ATT_QEXT_OFF + (threadIdx.x >> 7) * 4096;
        asm volatile("st.shared.b16 [%0], %1;" ::"r"(qe + r * 64 + (((r >> 1) & 3) << 4)), "h"((uint16_t)(pack_bf16(-m0, 0.f) & 0xFFFFu)) : "memory");
        asm volatile("st.shared.b16 [%0], %1;" ::"r"(qe + (r + 8) * 64 + ((((r + 8) >> 1) & 3) << 4)), "h"((uint16_t)(pack_bf16(-m1, 0.f) & 0xFFFFu)) : "memory");
    }
    fence_proxy_async();
    named_bar_sync(1 + (threadIdx.x >> 7), 128);
    wgmma_fence();
    wgmma_ss_n64_tb0(s0, dq + ((ATT_QEXT_OFF - ATT_Q_OFF) >> 4), HI, dke, HI, 1);
    wgmma_commit();
    wgmma_wait<0>();
#pragma unroll 1
    for (int j = 0; j < NBLK; j++) {
        if (threadIdx.x == 0 && j + ATT_DIST < NBLK) issue_kv(j + ATT_DIST);
        __syncwarp();
        const uint32_t stage = j & (ATT_STAGES - 1), nstage = (j + 1) & (ATT_STAGES - 1);
        const uint32_t dk = dk0 + stage * 1024;
        const uint32_t dv = dv0 + stage * 1024 - (stage << 26);
        mbar_wait(bar_vfull + 8 * stage, (j / ATT_STAGES) & 1);
        attn_step(s0, o, dq, dke, dk + 256, dv, 0u);
        uint32_t dkn = dk;
        if (j + 1 < NBLK) {
            mbar_wait(bar_kfull + 8 * nstage, ((j + 1) / ATT_STAGES) & 1);
            dkn = dk0 + nstage * 1024;
        }
        attn_step(s0, o, dq, dke, dkn, dv + 256 - (256u << 16), bar_empty + 8 * stage);
    }
    bool ok = (o[16] <= 1.8446744e19f) && (o[18] <= 1.8446744e19f);
#pragma unroll
    for (int i = 0; i < 16; i++) ok = ok && (fabsf(o[i]) <= 3.0e38f);
    const int row0 = q0 + (threadIdx.x >> 5) * 16 + (lane >> 2);
    const float f0 = g_gate[row0] / o[16], f1 = g_gate[row0 + 8] / o[18];
    bf16* op0 = g_a5 + (size_t)row0 * A5W + head * DH + (lane & 3) * 2;
    bf16* op1 = op0 + 8 * A5W;
#pragma unroll
    for (int i = 0; i < 4; i++) {
        *reinterpret_cast<uint32_t*>(op0 + 8 * i) = pack_bf16(o[4 * i] * f0, o[4 * i + 1] * f0);
        *reinterpret_cast<uint32_t*>(op1 + 8 * i) = pack_bf16(o[4 * i + 2] * f1, o[4 * i + 3] * f1);
    }
    const int bad = __syncthreads_or(!ok);
    if (threadIdx.x < ATT_NWG / 2) g_bad[tile * (ATT_NWG / 2) + threadIdx.x] = bad;
    TL_END(6)
}

typedef CUresult (*EncodeFn)(CUtensorMap*, CUtensorMapDataType, cuuint32_t, void*, const cuuint64_t*, const cuuint64_t*,
                             const cuuint32_t*, const cuuint32_t*, CUtensorMapInterleave, CUtensorMapSwizzle,
                             CUtensorMapL2promotion, CUtensorMapFloatOOBfill);

static CUtensorMap make_map(EncodeFn fn, const void* ptr, int rows, int cols, int box_cols, int box_rows,
                            CUtensorMapSwizzle swz) {
    CUtensorMap m;
    cuuint64_t dims[2] = {(cuuint64_t)cols, (cuuint64_t)rows};
    cuuint64_t strides[1] = {(cuuint64_t)cols * 2};
    cuuint32_t box[2] = {(cuuint32_t)box_cols, (cuuint32_t)box_rows};
    cuuint32_t es[2] = {1, 1};
    fn(&m, CU_TENSOR_MAP_DATA_TYPE_BFLOAT16, 2, const_cast<void*>(ptr), dims, strides, box, es,
       CU_TENSOR_MAP_INTERLEAVE_NONE, swz, CU_TENSOR_MAP_L2_PROMOTION_L2_256B, CU_TENSOR_MAP_FLOAT_OOB_FILL_NONE);
    return m;
}

template <typename... KArgs, typename... Args>
static void launch_ex(void (*kern)(KArgs...), int grid, int block, int smem, cudaStream_t st, int cluster, int pdl, Args... args) {
    cudaLaunchConfig_t cfg = {};
    cfg.gridDim = dim3(grid);
    cfg.blockDim = dim3(block);
    cfg.dynamicSmemBytes = smem;
    cfg.stream = st;
    cudaLaunchAttribute at[2];
    at[0].id = cudaLaunchAttributeProgrammaticStreamSerialization;
    at[0].val.programmaticStreamSerializationAllowed = pdl;
    at[1].id = cudaLaunchAttributeClusterDimension;
    at[1].val.clusterDim.x = cluster;
    at[1].val.clusterDim.y = 1;
    at[1].val.clusterDim.z = 1;
    cfg.attrs = at;
    cfg.numAttrs = cluster > 1 ? 2 : 1;
    cudaLaunchKernelEx(&cfg, kern, KArgs(args)...);
}

extern "C" void kernel_launch(void* const* d_in, const int* in_sizes, int n_in, void* d_out, int out_size) {
    const bf16* x = (const bf16*)d_in[0];
    const bf16* wqkv = (const bf16*)d_in[1];
    const bf16* wo = (const bf16*)d_in[2];
    const bf16* w1 = (const bf16*)d_in[4];
    const bf16* w2 = (const bf16*)d_in[5];
    const bf16* w3 = (const bf16*)d_in[6];
    const bf16* w4 = (const bf16*)d_in[7];
    const bf16* gate_w = (const bf16*)d_in[8];

    static EncodeFn enc = nullptr;
    static void *p_qkv, *p_h, *p_x1, *p_a5, *p_cs1, *p_cs3;
    static cudaStream_t s2;
    static cudaEvent_t ev_fork, ev_join;
    using G1 = GemmSmem<256, 4>;
    using G2 = GemmSmem<128, 5>;
#define G3BN 256
    using G3 = GemmSmem<G3BN, 4>;
    if (!enc) {
        void* fn = nullptr;
        cudaDriverEntryPointQueryResult qres;
        cudaGetDriverEntryPoint("cuTensorMapEncodeTiled", &fn, cudaEnableDefault, &qres);
        enc = (EncodeFn)fn;
        cudaGetSymbolAddress(&p_qkv, g_qkv);
        cudaGetSymbolAddress(&p_h, g_h);
        cudaGetSymbolAddress(&p_x1, g_x1);
        cudaGetSymbolAddress(&p_a5, g_a5);
        cudaGetSymbolAddress(&p_cs1, g_cs1);
        cudaGetSymbolAddress(&p_cs3, g_cs3);
        cudaFuncSetAttribute(gemm_kernel<1, 256, 4>, cudaFuncAttributeMaxDynamicSharedMemorySize, G1::TOTAL);
        cudaFuncSetAttribute(gemm_kernel<2, 128, 5>, cudaFuncAttributeMaxDynamicSharedMemorySize, G2::TOTAL);
        cudaFuncSetAttribute(gemm_kernel<3, G3BN, 4>, cudaFuncAttributeMaxDynamicSharedMemorySize, G3::TOTAL);
        cudaFuncSetAttribute(gemm_kernel<5, 128, 5>, cudaFuncAttributeMaxDynamicSharedMemorySize, G2::TOTAL);
        cudaStreamCreateWithFlags(&s2, cudaStreamNonBlocking);
        cudaEventCreateWithFlags(&ev_fork, cudaEventDisableTiming);
        cudaEventCreateWithFlags(&ev_join, cudaEventDisableTiming);
        cudaFuncSetAttribute(attn_kernel, cudaFuncAttributeMaxDynamicSharedMemorySize, ATT_SMEM);
        cudaFuncSetAttribute(attn_exact_kernel, cudaFuncAttributeMaxDynamicSharedMemorySize, ATT_SMEM);
    }
    const CUtensorMapSwizzle SW128 = CU_TENSOR_MAP_SWIZZLE_128B, SW64 = CU_TENSOR_MAP_SWIZZLE_64B;
    CUtensorMap mX = make_map(enc, x, S_LEN, DM, 64, 128, SW128);
    CUtensorMap mXres = make_map(enc, x, S_LEN, DM, 64, 64, SW128);
    CUtensorMap mWqkv = make_map(enc, wqkv, DM, 3 * DM, 64, 64, SW128);
    CUtensorMap mW1 = make_map(enc, w1, DM, DM, 64, 64, SW128);
    CUtensorMap mW2 = make_map(enc, w2, DM, DM, 64, 64, SW128);
    CUtensorMap mW3 = make_map(enc, w3, DM, FF, 64, 64, SW128);
    CUtensorMap mW4 = make_map(enc, w4, FF, DM, 64, 64, SW128);
    CUtensorMap mWo = make_map(enc, wo, DM, DM, 64, 64, SW128);
    CUtensorMap mQKVst = make_map(enc, p_qkv, S_LEN, 3 * DM, 64, 64, SW128);
    CUtensorMap mKV = make_map(enc, p_qkv, S_LEN, 3 * DM, 32, 128, SW64);
    CUtensorMap mHst = make_map(enc, p_h, S_LEN, DM, 64, 64, SW128);
    CUtensorMap mHld = make_map(enc, p_h, S_LEN, DM, 64, 128, SW128);
    CUtensorMap mX1st = make_map(enc, p_x1, S_LEN, DM, 64, 64, SW128);
    CUtensorMap mX1ld = make_map(enc, p_x1, S_LEN, DM, 64, 128, SW128);
    CUtensorMap mA5st = make_map(enc, p_a5, S_LEN, A5W, 64, 64, SW128);
    CUtensorMap mA5st32 = make_map(enc, p_a5, S_LEN, A5W, 32, 64, SW64);
    CUtensorMap mA5ld = make_map(enc, p_a5, S_LEN, A5W, 64, 128, SW128);
    CUtensorMap mOut = make_map(enc, d_out, S_LEN, DM, 64, 64, SW128);

    cudaStream_t st = cudaStreamPerThread;
    prep_kernel<<<256 + 64 + 224, 256, 0, st>>>(x, gate_w, w1, w3);
    launch_ex(gemm_kernel<1, 256, 4>, 132, 384, G1::TOTAL, st, 1, 1, mX, mWqkv, mW1, mQKVst, mHst, x, 16, 16);
    launch_ex(gemm_kernel<2, 128, 5>, 128, 384, G2::TOTAL, st, 1, 1, mHld, mW2, mW2, mX1st, mXres, x, 8, 16);
    cudaEventRecord(ev_fork, st);
    launch_ex(attn_kernel, ATT_GRID, ATT_THREADS, ATT_SMEM, st, 1, 1, mKV);
    launch_ex(attn_exact_kernel, 32, 256, ATT_SMEM, st, 1, 1, mKV);
    cudaStreamWaitEvent(s2, ev_fork, 0);
    launch_ex(gemm_kernel<3, G3BN, 4>, 132, 384, G3::TOTAL, s2, 1, 0, mX1ld, mW3, mW3, mA5st, mA5st32, x, FF / G3BN, 16);
    cudaEventRecord(ev_join, s2);
    cudaStreamWaitEvent(st, ev_join, 0);
    launch_ex(gemm_kernel<5, 128, 5>, 128, 384, G2::TOTAL, st, 1, 0, mA5ld, mWo, mW4, mOut, mX1st, (const bf16*)p_x1, 8, 72);
}
```

```cpp
#include <cuda_runtime.h>
#include <cuda_bf16.h>
#include <cuda.h>
#include <stdint.h>

typedef __nv_bfloat16 bf16;

constexpr int S_LEN = 2048;
constexpr int DM = 1024;
constexpr int FF = 3584;
constexpr int NH = 32;
constexpr int DH = 32;
constexpr int A5W = DM + FF;

__device__ __align__(1024) bf16 g_qkv[S_LEN * 3 * DM];
__device__ __align__(1024) bf16 g_h[S_LEN * DM];
__device__ __align__(1024) bf16 g_x1[S_LEN * DM];
__device__ __align__(1024) bf16 g_a5[S_LEN * A5W];
__device__ __align__(16) float g_mean1[S_LEN];
__device__ __align__(16) float g_rstd1[S_LEN];
__device__ __align__(16) float g_gate[S_LEN];
__device__ __align__(16) float g_omg[S_LEN];
__device__ __align__(16) float g_cs1[4 * DM];
__device__ __align__(16) float g_cs3[4 * FF];
__device__ __align__(16) float2 g_stat2[S_LEN * 8];
__device__ int g_bad[NH * 16];
__device__ int g_tile_ctr;

#define TL_START(k)
#define PH(i)
#define TL_END(k)

__device__ __forceinline__ uint32_t smem_u32(const void* p) { return (uint32_t)__cvta_generic_to_shared(p); }

__device__ __forceinline__ void mbar_init(uint32_t bar, uint32_t count) {
    asm volatile("mbarrier.init.shared::cta.b64 [%0], %1;" ::"r"(bar), "r"(count));
}
__device__ __forceinline__ void mbar_expect_tx(uint32_t bar, uint32_t bytes) {
    asm volatile("mbarrier.arrive.expect_tx.shared::cta.b64 _, [%0], %1;" ::"r"(bar), "r"(bytes) : "memory");
}
__device__ __forceinline__ void mbar_arrive(uint32_t bar) {
    asm volatile("mbarrier.arrive.shared::cta.b64 _, [%0];" ::"r"(bar) : "memory");
}
__device__ __forceinline__ bool mbar_try_wait(uint32_t bar, uint32_t parity) {
    uint32_t ok;
    asm volatile(
        "{\n.reg .pred p;\n"
        "mbarrier.try_wait.parity.shared::cta.b64 p, [%1], %2;\n"
        "selp.u32 %0, 1, 0, p;\n}\n"
        : "=r"(ok)
        : "r"(bar), "r"(parity)
        : "memory");
    return ok != 0;
}
__device__ __forceinline__ void mbar_wait(uint32_t bar, uint32_t parity) {
    uint32_t spins = 0;
    while (!mbar_try_wait(bar, parity)) {
        if (++spins > (1u << 24)) __trap();
    }
}
__device__ __forceinline__ void tma_load_2d(uint32_t dst, const CUtensorMap* map, int c0, int c1, uint32_t bar) {
    asm volatile(
        "cp.async.bulk.tensor.2d.shared::cluster.global.mbarrier::complete_tx::bytes [%0], [%1, {%3, %4}], [%2];"
        ::"r"(dst), "l"(map), "r"(bar), "r"(c0), "r"(c1)
        : "memory");
}
__device__ __forceinline__ void tma_store_2d(const CUtensorMap* map, uint32_t src, int c0, int c1) {
    asm volatile("cp.async.bulk.tensor.2d.global.shared::cta.bulk_group [%0, {%2, %3}], [%1];"
                 ::"l"(map), "r"(src), "r"(c0), "r"(c1)
                 : "memory");
}
__device__ __forceinline__ void pdl_wait() { asm volatile("griddepcontrol.wait;" ::: "memory"); }
__device__ __forceinline__ void pdl_launch() { asm volatile("griddepcontrol.launch_dependents;" ::: "memory"); }
__device__ __forceinline__ void bulk_commit() { asm volatile("cp.async.bulk.commit_group;" ::: "memory"); }
__device__ __forceinline__ void bulk_wait_read0() { asm volatile("cp.async.bulk.wait_group.read 0;" ::: "memory"); }
__device__ __forceinline__ void bulk_wait0() { asm volatile("cp.async.bulk.wait_group 0;" ::: "memory"); }
__device__ __forceinline__ void fence_proxy_async() { asm volatile("fence.proxy.async.shared::cta;" ::: "memory"); }
__device__ __forceinline__ void named_bar_sync(int id, int n) { asm volatile("bar.sync %0, %1;" ::"r"(id), "r"(n) : "memory"); }
__device__ __forceinline__ void named_bar_arrive(int id, int n) { asm volatile("bar.arrive %0, %1;" ::"r"(id), "r"(n) : "memory"); }
__device__ __forceinline__ void wgmma_fence() { asm volatile("wgmma.fence.sync.aligned;" ::: "memory"); }
__device__ __forceinline__ void wgmma_commit() { asm volatile("wgmma.commit_group.sync.aligned;" ::: "memory"); }
template <int N>
__device__ __forceinline__ void wgmma_wait() { asm volatile("wgmma.wait_group.sync.aligned %0;" ::"n"(N) : "memory"); }
__device__ __forceinline__ void prefetch_tmap(const CUtensorMap* m) {
    asm volatile("prefetch.tensormap [%0];" ::"l"(m) : "memory");
}
template <int R>
__device__ __forceinline__ void reg_alloc() { asm volatile("setmaxnreg.inc.sync.aligned.u32 %0;" ::"n"(R)); }
template <int R>
__device__ __forceinline__ void reg_dealloc() { asm volatile("setmaxnreg.dec.sync.aligned.u32 %0;" ::"n"(R)); }
__device__ __forceinline__ void stmatrix_x4(uint32_t addr, uint32_t r0, uint32_t r1, uint32_t r2, uint32_t r3) {
    asm volatile("stmatrix.sync.aligned.m8n8.x4.shared.b16 [%0], {%1, %2, %3, %4};"
                 ::"r"(addr), "r"(r0), "r"(r1), "r"(r2), "r"(r3)
                 : "memory");
}
__device__ __forceinline__ uint32_t pack_bf16(float lo, float hi) {
    uint32_t r;
    asm("cvt.rn.bf16x2.f32 %0, %1, %2;" : "=r"(r) : "f"(hi), "f"(lo));
    return r;
}
__device__ __forceinline__ float bf16_round(float v) { return __bfloat162float(__float2bfloat16_rn(v)); }
__device__ __forceinline__ float ex2(float x) {
    float y;
    asm volatile("ex2.approx.ftz.f32 %0, %1;" : "=f"(y) : "f"(x));
    return y;
}
__device__ __forceinline__ float tanh_fast(float x) {
    float y;
    asm("tanh.approx.f32 %0, %1;" : "=f"(y) : "f"(x));
    return y;
}
__device__ __forceinline__ float gelu_tanh(float v) {
    float u = 0.7978845608028654f * (v + 0.044715f * v * v * v);
    float hv = 0.5f * v;
    return fmaf(hv, tanh_fast(u), hv);
}
__device__ __forceinline__ uint32_t desc_lo(uint32_t addr, uint32_t lbo_bytes) {
    return ((addr & 0x3FFFF) >> 4) | (((lbo_bytes >> 4) & 0x3FFF) << 16);
}
__host__ __device__ constexpr uint32_t desc_hi(uint32_t sbo_bytes, uint32_t swz) {
    return ((sbo_bytes >> 4) & 0x3FFF) | (swz << 30);
}

__device__ __forceinline__ void wgmma_ss_n128_tb1(float (&d)[64], uint32_t alo, uint32_t ahi, uint32_t blo, uint32_t bhi, int scale_d) {
    asm volatile("{\n.reg .pred p;\n.reg .b64 da, db;\nsetp.ne.b32 p, %68, 0;\nmov.b64 da, {%64, %65};\nmov.b64 db, {%66, %67};\n"
        "wgmma.mma_async.sync.aligned.m64n128k16.f32.bf16.bf16 {%0, %1, %2, %3, %4, %5, %6, %7, %8, %9, %10, %11, %12, %13, %14, %15, %16, %17, %18, %19, %20, %21, %22, %23, %24, %25, %26, %27, %28, %29, %30, %31, %32, %33, %34, %35, %36, %37, %38, %39, %40, %41, %42, %43, %44, %45, %46, %47, %48, %49, %50, %51, %52, %53, %54, %55, %56, %57, %58, %59, %60, %61, %62, %63}, da, db, p, 1, 1, 0, 1;\n}\n"
        : "+f"(d[0]), "+f"(d[1]), "+f"(d[2]), "+f"(d[3]), "+f"(d[4]), "+f"(d[5]), "+f"(d[6]), "+f"(d[7]), "+f"(d[8]), "+f"(d[9]), "+f"(d[10]), "+f"(d[11]), "+f"(d[12]), "+f"(d[13]), "+f"(d[14]), "+f"(d[15]), "+f"(d[16]), "+f"(d[17]), "+f"(d[18]), "+f"(d[19]), "+f"(d[20]), "+f"(d[21]), "+f"(d[22]), "+f"(d[23]), "+f"(d[24]), "+f"(d[25]), "+f"(d[26]), "+f"(d[27]), "+f"(d[28]), "+f"(d[29]), "+f"(d[30]), "+f"(d[31]), "+f"(d[32]), "+f"(d[33]), "+f"(d[34]), "+f"(d[35]), "+f"(d[36]), "+f"(d[37]), "+f"(d[38]), "+f"(d[39]), "+f"(d[40]), "+f"(d[41]), "+f"(d[42]), "+f"(d[43]), "+f"(d[44]), "+f"(d[45]), "+f"(d[46]), "+f"(d[47]), "+f"(d[48]), "+f"(d[49]), "+f"(d[50]), "+f"(d[51]), "+f"(d[52]), "+f"(d[53]), "+f"(d[54]), "+f"(d[55]), "+f"(d[56]), "+f"(d[57]), "+f"(d[58]), "+f"(d[59]), "+f"(d[60]), "+f"(d[61]), "+f"(d[62]), "+f"(d[63])
        : "r"(alo), "r"(ahi), "r"(blo), "r"(bhi), "r"(scale_d));
}

__device__ __forceinline__ void wgmma_ss_n192_tb1(float (&d)[96], uint32_t alo, uint32_t ahi, uint32_t blo, uint32_t bhi, int scale_d) {
    asm volatile("{\n.reg .pred p;\n.reg .b64 da, db;\nsetp.ne.b32 p, %100, 0;\nmov.b64 da, {%96, %97};\nmov.b64 db, {%98, %99};\n"
        "wgmma.mma_async.sync.aligned.m64n192k16.f32.bf16.bf16 {%0, %1, %2, %3, %4, %5, %6, %7, %8, %9, %10, %11, %12, %13, %14, %15, %16, %17, %18, %19, %20, %21, %22, %23, %24, %25, %26, %27, %28, %29, %30, %31, %32, %33, %34, %35, %36, %37, %38, %39, %40, %41, %42, %43, %44, %45, %46, %47, %48, %49, %50, %51, %52, %53, %54, %55, %56, %57, %58, %59, %60, %61, %62, %63, %64, %65, %66, %67, %68, %69, %70, %71, %72, %73, %74, %75, %76, %77, %78, %79, %80, %81, %82, %83, %84, %85, %86, %87, %88, %89, %90, %91, %92, %93, %94, %95}, da, db, p, 1, 1, 0, 1;\n}\n"
        : "+f"(d[0]), "+f"(d[1]), "+f"(d[2]), "+f"(d[3]), "+f"(d[4]), "+f"(d[5]), "+f"(d[6]), "+f"(d[7]), "+f"(d[8]), "+f"(d[9]), "+f"(d[10]), "+f"(d[11]), "+f"(d[12]), "+f"(d[13]), "+f"(d[14]), "+f"(d[15]), "+f"(d[16]), "+f"(d[17]), "+f"(d[18]), "+f"(d[19]), "+f"(d[20]), "+f"(d[21]), "+f"(d[22]), "+f"(d[23]), "+f"(d[24]), "+f"(d[25]), "+f"(d[26]), "+f"(d[27]), "+f"(d[28]), "+f"(d[29]), "+f"(d[30]), "+f"(d[31]), "+f"(d[32]), "+f"(d[33]), "+f"(d[34]), "+f"(d[35]), "+f"(d[36]), "+f"(d[37]), "+f"(d[38]), "+f"(d[39]), "+f"(d[40]), "+f"(d[41]), "+f"(d[42]), "+f"(d[43]), "+f"(d[44]), "+f"(d[45]), "+f"(d[46]), "+f"(d[47]), "+f"(d[48]), "+f"(d[49]), "+f"(d[50]), "+f"(d[51]), "+f"(d[52]), "+f"(d[53]), "+f"(d[54]), "+f"(d[55]), "+f"(d[56]), "+f"(d[57]), "+f"(d[58]), "+f"(d[59]), "+f"(d[60]), "+f"(d[61]), "+f"(d[62]), "+f"(d[63]), "+f"(d[64]), "+f"(d[65]), "+f"(d[66]), "+f"(d[67]), "+f"(d[68]), "+f"(d[69]), "+f"(d[70]), "+f"(d[71]), "+f"(d[72]), "+f"(d[73]), "+f"(d[74]), "+f"(d[75]), "+f"(d[76]), "+f"(d[77]), "+f"(d[78]), "+f"(d[79]), "+f"(d[80]), "+f"(d[81]), "+f"(d[82]), "+f"(d[83]), "+f"(d[84]), "+f"(d[85]), "+f"(d[86]), "+f"(d[87]), "+f"(d[88]), "+f"(d[89]), "+f"(d[90]), "+f"(d[91]), "+f"(d[92]), "+f"(d[93]), "+f"(d[94]), "+f"(d[95])
        : "r"(alo), "r"(ahi), "r"(blo), "r"(bhi), "r"(scale_d));
}

__device__ __forceinline__ void wgmma_ss_n224_tb1(float (&d)[112], uint32_t alo, uint32_t ahi, uint32_t blo, uint32_t bhi, int scale_d) {
    asm volatile("{\n.reg .pred p;\n.reg .b64 da, db;\nsetp.ne.b32 p, %116, 0;\nmov.b64 da, {%112, %113};\nmov.b64 db, {%114, %115};\n"
        "wgmma.mma_async.sync.aligned.m64n224k16.f32.bf16.bf16 {%0, %1, %2, %3, %4, %5, %6, %7, %8, %9, %10, %11, %12, %13, %14, %15, %16, %17, %18, %19, %20, %21, %22, %23, %24, %25, %26, %27, %28, %29, %30, %31, %32, %33, %34, %35, %36, %37, %38, %39, %40, %41, %42, %43, %44, %45, %46, %47, %48, %49, %50, %51, %52, %53, %54, %55, %56, %57, %58, %59, %60, %61, %62, %63, %64, %65, %66, %67, %68, %69, %70, %71, %72, %73, %74, %75, %76, %77, %78, %79, %80, %81, %82, %83, %84, %85, %86, %87, %88, %89, %90, %91, %92, %93, %94, %95, %96, %97, %98, %99, %100, %101, %102, %103, %104, %105, %106, %107, %108, %109, %110, %111}, da, db, p, 1, 1, 0, 1;\n}\n"
        : "+f"(d[0]), "+f"(d[1]), "+f"(d[2]), "+f"(d[3]), "+f"(d[4]), "+f"(d[5]), "+f"(d[6]), "+f"(d[7]), "+f"(d[8]), "+f"(d[9]), "+f"(d[10]), "+f"(d[11]), "+f"(d[12]), "+f"(d[13]), "+f"(d[14]), "+f"(d[15]), "+f"(d[16]), "+f"(d[17]), "+f"(d[18]), "+f"(d[19]), "+f"(d[20]), "+f"(d[21]), "+f"(d[22]), "+f"(d[23]), "+f"(d[24]), "+f"(d[25]), "+f"(d[26]), "+f"(d[27]), "+f"(d[28]), "+f"(d[29]), "+f"(d[30]), "+f"(d[31]), "+f"(d[32]), "+f"(d[33]), "+f"(d[34]), "+f"(d[35]), "+f"(d[36]), "+f"(d[37]), "+f"(d[38]), "+f"(d[39]), "+f"(d[40]), "+f"(d[41]), "+f"(d[42]), "+f"(d[43]), "+f"(d[44]), "+f"(d[45]), "+f"(d[46]), "+f"(d[47]), "+f"(d[48]), "+f"(d[49]), "+f"(d[50]), "+f"(d[51]), "+f"(d[52]), "+f"(d[53]), "+f"(d[54]), "+f"(d[55]), "+f"(d[56]), "+f"(d[57]), "+f"(d[58]), "+f"(d[59]), "+f"(d[60]), "+f"(d[61]), "+f"(d[62]), "+f"(d[63]), "+f"(d[64]), "+f"(d[65]), "+f"(d[66]), "+f"(d[67]), "+f"(d[68]), "+f"(d[69]), "+f"(d[70]), "+f"(d[71]), "+f"(d[72]), "+f"(d[73]), "+f"(d[74]), "+f"(d[75]), "+f"(d[76]), "+f"(d[77]), "+f"(d[78]), "+f"(d[79]), "+f"(d[80]), "+f"(d[81]), "+f"(d[82]), "+f"(d[83]), "+f"(d[84]), "+f"(d[85]), "+f"(d[86]), "+f"(d[87]), "+f"(d[88]), "+f"(d[89]), "+f"(d[90]), "+f"(d[91]), "+f"(d[92]), "+f"(d[93]), "+f"(d[94]), "+f"(d[95]), "+f"(d[96]), "+f"(d[97]), "+f"(d[98]), "+f"(d[99]), "+f"(d[100]), "+f"(d[101]), "+f"(d[102]), "+f"(d[103]), "+f"(d[104]), "+f"(d[105]), "+f"(d[106]), "+f"(d[107]), "+f"(d[108]), "+f"(d[109]), "+f"(d[110]), "+f"(d[111])
        : "r"(alo), "r"(ahi), "r"(blo), "r"(bhi), "r"(scale_d));
}

__device__ __forceinline__ void wgmma_ss_n256_tb1(float (&d)[128], uint32_t alo, uint32_t ahi, uint32_t blo, uint32_t bhi, int scale_d) {
    asm volatile("{\n.reg .pred p;\n.reg .b64 da, db;\nsetp.ne.b32 p, %132, 0;\nmov.b64 da, {%128, %129};\nmov.b64 db, {%130, %131};\n"
        "wgmma.mma_async.sync.aligned.m64n256k16.f32.bf16.bf16 {%0, %1, %2, %3, %4, %5, %6, %7, %8, %9, %10, %11, %12, %13, %14, %15, %16, %17, %18, %19, %20, %21, %22, %23, %24, %25, %26, %27, %28, %29, %30, %31, %32, %33, %34, %35, %36, %37, %38, %39, %40, %41, %42, %43, %44, %45, %46, %47, %48, %49, %50, %51, %52, %53, %54, %55, %56, %57, %58, %59, %60, %61, %62, %63, %64, %65, %66, %67, %68, %69, %70, %71, %72, %73, %74, %75, %76, %77, %78, %79, %80, %81, %82, %83, %84, %85, %86, %87, %88, %89, %90, %91, %92, %93, %94, %95, %96, %97, %98, %99, %100, %101, %102, %103, %104, %105, %106, %107, %108, %109, %110, %111, %112, %113, %114, %115, %116, %117, %118, %119, %120, %121, %122, %123, %124, %125, %126, %127}, da, db, p, 1, 1, 0, 1;\n}\n"
        : "+f"(d[0]), "+f"(d[1]), "+f"(d[2]), "+f"(d[3]), "+f"(d[4]), "+f"(d[5]), "+f"(d[6]), "+f"(d[7]), "+f"(d[8]), "+f"(d[9]), "+f"(d[10]), "+f"(d[11]), "+f"(d[12]), "+f"(d[13]), "+f"(d[14]), "+f"(d[15]), "+f"(d[16]), "+f"(d[17]), "+f"(d[18]), "+f"(d[19]), "+f"(d[20]), "+f"(d[21]), "+f"(d[22]), "+f"(d[23]), "+f"(d[24]), "+f"(d[25]), "+f"(d[26]), "+f"(d[27]), "+f"(d[28]), "+f"(d[29]), "+f"(d[30]), "+f"(d[31]), "+f"(d[32]), "+f"(d[33]), "+f"(d[34]), "+f"(d[35]), "+f"(d[36]), "+f"(d[37]), "+f"(d[38]), "+f"(d[39]), "+f"(d[40]), "+f"(d[41]), "+f"(d[42]), "+f"(d[43]), "+f"(d[44]), "+f"(d[45]), "+f"(d[46]), "+f"(d[47]), "+f"(d[48]), "+f"(d[49]), "+f"(d[50]), "+f"(d[51]), "+f"(d[52]), "+f"(d[53]), "+f"(d[54]), "+f"(d[55]), "+f"(d[56]), "+f"(d[57]), "+f"(d[58]), "+f"(d[59]), "+f"(d[60]), "+f"(d[61]), "+f"(d[62]), "+f"(d[63]), "+f"(d[64]), "+f"(d[65]), "+f"(d[66]), "+f"(d[67]), "+f"(d[68]), "+f"(d[69]), "+f"(d[70]), "+f"(d[71]), "+f"(d[72]), "+f"(d[73]), "+f"(d[74]), "+f"(d[75]), "+f"(d[76]), "+f"(d[77]), "+f"(d[78]), "+f"(d[79]), "+f"(d[80]), "+f"(d[81]), "+f"(d[82]), "+f"(d[83]), "+f"(d[84]), "+f"(d[85]), "+f"(d[86]), "+f"(d[87]), "+f"(d[88]), "+f"(d[89]), "+f"(d[90]), "+f"(d[91]), "+f"(d[92]), "+f"(d[93]), "+f"(d[94]), "+f"(d[95]), "+f"(d[96]), "+f"(d[97]), "+f"(d[98]), "+f"(d[99]), "+f"(d[100]), "+f"(d[101]), "+f"(d[102]), "+f"(d[103]), "+f"(d[104]), "+f"(d[105]), "+f"(d[106]), "+f"(d[107]), "+f"(d[108]), "+f"(d[109]), "+f"(d[110]), "+f"(d[111]), "+f"(d[112]), "+f"(d[113]), "+f"(d[114]), "+f"(d[115]), "+f"(d[116]), "+f"(d[117]), "+f"(d[118]), "+f"(d[119]), "+f"(d[120]), "+f"(d[121]), "+f"(d[122]), "+f"(d[123]), "+f"(d[124]), "+f"(d[125]), "+f"(d[126]), "+f"(d[127])
        : "r"(alo), "r"(ahi), "r"(blo), "r"(bhi), "r"(scale_d));
}

__device__ __forceinline__ void wgmma_ss_n64_tb0(float (&d)[32], uint32_t alo, uint32_t ahi, uint32_t blo, uint32_t bhi, int scale_d) {
    asm volatile("{\n.reg .pred p;\n.reg .b64 da, db;\nsetp.ne.b32 p, %36, 0;\nmov.b64 da, {%32, %33};\nmov.b64 db, {%34, %35};\n"
        "wgmma.mma_async.sync.aligned.m64n64k16.f32.bf16.bf16 {%0, %1, %2, %3, %4, %5, %6, %7, %8, %9, %10, %11, %12, %13, %14, %15, %16, %17, %18, %19, %20, %21, %22, %23, %24, %25, %26, %27, %28, %29, %30, %31}, da, db, p, 1, 1, 0, 0;\n}\n"
        : "+f"(d[0]), "+f"(d[1]), "+f"(d[2]), "+f"(d[3]), "+f"(d[4]), "+f"(d[5]), "+f"(d[6]), "+f"(d[7]), "+f"(d[8]), "+f"(d[9]), "+f"(d[10]), "+f"(d[11]), "+f"(d[12]), "+f"(d[13]), "+f"(d[14]), "+f"(d[15]), "+f"(d[16]), "+f"(d[17]), "+f"(d[18]), "+f"(d[19]), "+f"(d[20]), "+f"(d[21]), "+f"(d[22]), "+f"(d[23]), "+f"(d[24]), "+f"(d[25]), "+f"(d[26]), "+f"(d[27]), "+f"(d[28]), "+f"(d[29]), "+f"(d[30]), "+f"(d[31])
        : "r"(alo), "r"(ahi), "r"(blo), "r"(bhi), "r"(scale_d));
}

__device__ __forceinline__ void wgmma_rs_n128_tb0(float (&d)[64], uint32_t a0, uint32_t a1, uint32_t a2, uint32_t a3, uint32_t blo, uint32_t bhi, int scale_d) {
    asm volatile("{\n.reg .pred p;\n.reg .b64 db;\nsetp.ne.b32 p, %70, 0;\nmov.b64 db, {%68, %69};\n"
        "wgmma.mma_async.sync.aligned.m64n128k16.f32.bf16.bf16 {%0, %1, %2, %3, %4, %5, %6, %7, %8, %9, %10, %11, %12, %13, %14, %15, %16, %17, %18, %19, %20, %21, %22, %23, %24, %25, %26, %27, %28, %29, %30, %31, %32, %33, %34, %35, %36, %37, %38, %39, %40, %41, %42, %43, %44, %45, %46, %47, %48, %49, %50, %51, %52, %53, %54, %55, %56, %57, %58, %59, %60, %61, %62, %63}, {%64, %65, %66, %67}, db, p, 1, 1, 0;\n}\n"
        : "+f"(d[0]), "+f"(d[1]), "+f"(d[2]), "+f"(d[3]), "+f"(d[4]), "+f"(d[5]), "+f"(d[6]), "+f"(d[7]), "+f"(d[8]), "+f"(d[9]), "+f"(d[10]), "+f"(d[11]), "+f"(d[12]), "+f"(d[13]), "+f"(d[14]), "+f"(d[15]), "+f"(d[16]), "+f"(d[17]), "+f"(d[18]), "+f"(d[19]), "+f"(d[20]), "+f"(d[21]), "+f"(d[22]), "+f"(d[23]), "+f"(d[24]), "+f"(d[25]), "+f"(d[26]), "+f"(d[27]), "+f"(d[28]), "+f"(d[29]), "+f"(d[30]), "+f"(d[31]), "+f"(d[32]), "+f"(d[33]), "+f"(d[34]), "+f"(d[35]), "+f"(d[36]), "+f"(d[37]), "+f"(d[38]), "+f"(d[39]), "+f"(d[40]), "+f"(d[41]), "+f"(d[42]), "+f"(d[43]), "+f"(d[44]), "+f"(d[45]), "+f"(d[46]), "+f"(d[47]), "+f"(d[48]), "+f"(d[49]), "+f"(d[50]), "+f"(d[51]), "+f"(d[52]), "+f"(d[53]), "+f"(d[54]), "+f"(d[55]), "+f"(d[56]), "+f"(d[57]), "+f"(d[58]), "+f"(d[59]), "+f"(d[60]), "+f"(d[61]), "+f"(d[62]), "+f"(d[63])
        : "r"(a0), "r"(a1), "r"(a2), "r"(a3), "r"(blo), "r"(bhi), "r"(scale_d));
}

__device__ __forceinline__ void wgmma_rs_n64_tb0(float (&d)[32], uint32_t a0, uint32_t a1, uint32_t a2, uint32_t a3, uint32_t blo, uint32_t bhi, int scale_d) {
    asm volatile("{\n.reg .pred p;\n.reg .b64 db;\nsetp.ne.b32 p, %38, 0;\nmov.b64 db, {%36, %37};\n"
        "wgmma.mma_async.sync.aligned.m64n64k16.f32.bf16.bf16 {%0, %1, %2, %3, %4, %5, %6, %7, %8, %9, %10, %11, %12, %13, %14, %15, %16, %17, %18, %19, %20, %21, %22, %23, %24, %25, %26, %27, %28, %29, %30, %31}, {%32, %33, %34, %35}, db, p, 1, 1, 0;\n}\n"
        : "+f"(d[0]), "+f"(d[1]), "+f"(d[2]), "+f"(d[3]), "+f"(d[4]), "+f"(d[5]), "+f"(d[6]), "+f"(d[7]), "+f"(d[8]), "+f"(d[9]), "+f"(d[10]), "+f"(d[11]), "+f"(d[12]), "+f"(d[13]), "+f"(d[14]), "+f"(d[15]), "+f"(d[16]), "+f"(d[17]), "+f"(d[18]), "+f"(d[19]), "+f"(d[20]), "+f"(d[21]), "+f"(d[22]), "+f"(d[23]), "+f"(d[24]), "+f"(d[25]), "+f"(d[26]), "+f"(d[27]), "+f"(d[28]), "+f"(d[29]), "+f"(d[30]), "+f"(d[31])
        : "r"(a0), "r"(a1), "r"(a2), "r"(a3), "r"(blo), "r"(bhi), "r"(scale_d));
}

__device__ __forceinline__ void wgmma_rs_n32_tb1(float (&d)[16], uint32_t a0, uint32_t a1, uint32_t a2, uint32_t a3, uint32_t blo, uint32_t bhi, int scale_d) {
    asm volatile("{\n.reg .pred p;\n.reg .b64 db;\nsetp.ne.b32 p, %22, 0;\nmov.b64 db, {%20, %21};\n"
        "wgmma.mma_async.sync.aligned.m64n32k16.f32.bf16.bf16 {%0, %1, %2, %3, %4, %5, %6, %7, %8, %9, %10, %11, %12, %13, %14, %15}, {%16, %17, %18, %19}, db, p, 1, 1, 1;\n}\n"
        : "+f"(d[0]), "+f"(d[1]), "+f"(d[2]), "+f"(d[3]), "+f"(d[4]), "+f"(d[5]), "+f"(d[6]), "+f"(d[7]), "+f"(d[8]), "+f"(d[9]), "+f"(d[10]), "+f"(d[11]), "+f"(d[12]), "+f"(d[13]), "+f"(d[14]), "+f"(d[15])
        : "r"(a0), "r"(a1), "r"(a2), "r"(a3), "r"(blo), "r"(bhi), "r"(scale_d));
}

__device__ __forceinline__ void wgmma_rs_n40_tb1(float (&d)[20], uint32_t a0, uint32_t a1, uint32_t a2, uint32_t a3, uint32_t blo, uint32_t bhi, int scale_d) {
    asm volatile("{\n.reg .pred p;\n.reg .b64 db;\nsetp.ne.b32 p, %26, 0;\nmov.b64 db, {%24, %25};\n"
        "wgmma.mma_async.sync.aligned.m64n40k16.f32.bf16.bf16 {%0, %1, %2, %3, %4, %5, %6, %7, %8, %9, %10, %11, %12, %13, %14, %15, %16, %17, %18, %19}, {%20, %21, %22, %23}, db, p, 1, 1, 1;\n}\n"
        : "+f"(d[0]), "+f"(d[1]), "+f"(d[2]), "+f"(d[3]), "+f"(d[4]), "+f"(d[5]), "+f"(d[6]), "+f"(d[7]), "+f"(d[8]), "+f"(d[9]), "+f"(d[10]), "+f"(d[11]), "+f"(d[12]), "+f"(d[13]), "+f"(d[14]), "+f"(d[15]), "+f"(d[16]), "+f"(d[17]), "+f"(d[18]), "+f"(d[19])
        : "r"(a0), "r"(a1), "r"(a2), "r"(a3), "r"(blo), "r"(bhi), "r"(scale_d));
}

template <int BN>
__device__ __forceinline__ void wgmma_tile(float (&d)[BN / 2], uint32_t da, uint32_t db, int sd) {
    constexpr uint32_t HI = desc_hi(1024, 1);
    if constexpr (BN == 128) wgmma_ss_n128_tb1(d, da, HI, db, HI, sd);
    else if constexpr (BN == 192) wgmma_ss_n192_tb1(d, da, HI, db, HI, sd);
    else if constexpr (BN == 224) wgmma_ss_n224_tb1(d, da, HI, db, HI, sd);
    else wgmma_ss_n256_tb1(d, da, HI, db, HI, sd);
}

__global__ void __launch_bounds__(256) prep_kernel(const bf16* __restrict__ x, const bf16* __restrict__ gate_w,
                                                   const bf16* __restrict__ w1, const bf16* __restrict__ w3) {
    constexpr int row_blocks = 256;
    if (blockIdx.x == 0 && threadIdx.x == 0) g_tile_ctr = 0;
    const int tid = threadIdx.x;
    TL_START(0)
    pdl_launch();
    if ((int)blockIdx.x < row_blocks) {
        const int row = blockIdx.x * 8 + (tid >> 5);
        const int lane = tid & 31;
        const uint4* xr = reinterpret_cast<const uint4*>(x + (size_t)row * DM);
        const uint4* gw = reinterpret_cast<const uint4*>(gate_w);
        float v[32];
        float gsum = 0.f, sum = 0.f;
#pragma unroll
        for (int i = 0; i < 4; i++) {
            uint4 a = xr[lane + 32 * i];
            uint4 b = gw[lane + 32 * i];
            const uint32_t aa[4] = {a.x, a.y, a.z, a.w};
            const uint32_t bb[4] = {b.x, b.y, b.z, b.w};
#pragma unroll
            for (int j = 0; j < 4; j++) {
                float x0 = __uint_as_float(aa[j] << 16), x1 = __uint_as_float(aa[j] & 0xFFFF0000u);
                float g0 = __uint_as_float(bb[j] << 16), g1 = __uint_as_float(bb[j] & 0xFFFF0000u);
                v[i * 8 + j * 2] = x0;
                v[i * 8 + j * 2 + 1] = x1;
                sum += x0 + x1;
                gsum += bf16_round(x0 * g0) + bf16_round(x1 * g1);
            }
        }
#pragma unroll
        for (int o = 16; o > 0; o >>= 1) {
            sum += __shfl_xor_sync(0xffffffffu, sum, o);
            gsum += __shfl_xor_sync(0xffffffffu, gsum, o);
        }
        const float mean = sum * (1.0f / DM);
        float m2 = 0.f;
#pragma unroll
        for (int i = 0; i < 32; i++) {
            float d = v[i] - mean;
            m2 += d * d;
        }
#pragma unroll
        for (int o = 16; o > 0; o >>= 1) m2 += __shfl_xor_sync(0xffffffffu, m2, o);
        if (lane == 0) {
            g_mean1[row] = mean;
            g_rstd1[row] = rsqrtf(m2 * (1.0f / DM) + 1e-5f);
            float logit = bf16_round(gsum);
            float g = bf16_round(1.0f / (1.0f + __expf(-logit)));
            g_gate[row] = g;
            g_omg[row] = bf16_round(1.0f - g);
        }
    } else {
        __shared__ float red[32][65];
        int blk = blockIdx.x - row_blocks;
        const bf16* w = w1;
        int ld = DM;
        float* cs_out = g_cs1;
        const int chunk = blk & 3;
        const int col0 = (blk >> 2) * 64;
        const int cg = tid & 7;
        const int rg = tid >> 3;
        uint4 a[8];
#pragma unroll
        for (int r = 0; r < 8; r++)
            a[r] = *reinterpret_cast<const uint4*>(w + (size_t)(chunk * 256 + r * 32 + rg) * ld + col0 + cg * 8);
        float acc[8];
#pragma unroll
        for (int j = 0; j < 8; j++) acc[j] = 0.f;
#pragma unroll
        for (int r = 0; r < 8; r++) {
            const uint32_t aa[4] = {a[r].x, a[r].y, a[r].z, a[r].w};
#pragma unroll
            for (int j = 0; j < 4; j++) {
                acc[2 * j] += __uint_as_float(aa[j] << 16);
                acc[2 * j + 1] += __uint_as_float(aa[j] & 0xFFFF0000u);
            }
        }
#pragma unroll
        for (int j = 0; j < 8; j++) red[rg][cg * 8 + j] = acc[j];
        __syncthreads();
        if (tid < 64) {
            float s = 0.f;
#pragma unroll
            for (int r = 0; r < 32; r++) s += red[r][tid];
            cs_out[chunk * ld + col0 + tid] = s;
        }
    }
    TL_END(0)
}

#define RELEASE_STAGE(b) if (tid_wg == 0) mbar_arrive(b)
template <int BN, int STAGES>
struct GemmSmem {
    static constexpr int A_BYTES = 128 * 64 * 2;
    static constexpr int B_BOXES = (BN + 63) / 64;
    static constexpr int B_BYTES = B_BOXES * 64 * 64 * 2;
    static constexpr int STAGE_BYTES = A_BYTES + B_BYTES;
    static constexpr int STG_OFF = STAGES * STAGE_BYTES;
    static constexpr int CS_OFF = STAGES * STAGE_BYTES + 2 * 16384;
    static constexpr int BAR_OFF = CS_OFF + 1024;
    static constexpr int TOTAL = BAR_OFF + 192 + 512;
};

template <int MODE, int BN, int STAGES>
__global__ void __launch_bounds__(384, 1)
gemm_kernel(const __grid_constant__ CUtensorMap mA, const __grid_constant__ CUtensorMap mB0,
            const __grid_constant__ CUtensorMap mB1, const __grid_constant__ CUtensorMap mC0,
            const __grid_constant__ CUtensorMap mC1, const bf16* __restrict__ xin, int n_tiles_n, int kblocks) {
    using L = GemmSmem<BN, STAGES>;
    extern __shared__ uint8_t smem_raw[];
    const uint32_t sbase = (smem_u32(smem_raw) + 1023u) & ~1023u;
    const uint32_t bar_full = sbase + L::BAR_OFF;
    const uint32_t bar_empty = bar_full + 8 * STAGES;
    const uint32_t bar_res = bar_empty + 8 * STAGES;
    const int wg = threadIdx.x >> 7;
    const int ntiles = 16 * n_tiles_n;
    constexpr bool DYN = (MODE == 3);
    const uint32_t bar_tfull = bar_res + 8;
    const uint32_t bar_tempty = bar_tfull + 16;
    const uint32_t tile_slot = bar_tempty + 16;
    TL_START(MODE)
    pdl_launch();

    if (threadIdx.x == 0) {
        for (int s = 0; s < STAGES; s++) {
            mbar_init(bar_full + 8 * s, 1);
            mbar_init(bar_empty + 8 * s, 2);
        }
        for (int s = 0; s < 2; s++) {
            mbar_init(bar_tfull + 8 * s, 1);
            mbar_init(bar_tempty + 8 * s, 2);
        }
        mbar_init(bar_res, 1);
        asm volatile("fence.mbarrier_init.release.cluster;" ::: "memory");
        prefetch_tmap(&mA);
        prefetch_tmap(&mB0);
        if (MODE == 1 || MODE == 5) prefetch_tmap(&mB1);
        if (MODE == 2 || MODE == 5) prefetch_tmap(&mC1);
        prefetch_tmap(&mC0);
    }
    __syncthreads();

    if (wg == 0) {
        reg_dealloc<40>();
        if (MODE == 2 && threadIdx.x >= 32 && blockIdx.x < FF / 32) {
            const int t = threadIdx.x - 32;
            const int rg = t >> 2;
            const bf16* wp = xin + blockIdx.x * 32 + (t & 3) * 8;
            float a[8];
#pragma unroll
            for (int j = 0; j < 8; j++) a[j] = 0.f;
#pragma unroll 4
            for (int r = rg; r < DM; r += 24) {
                const uint4 v = *reinterpret_cast<const uint4*>(wp + (size_t)r * FF);
                const uint32_t vv[4] = {v.x, v.y, v.z, v.w};
#pragma unroll
                for (int j = 0; j < 4; j++) {
                    a[2 * j] += __uint_as_float(vv[j] << 16);
                    a[2 * j + 1] += __uint_as_float(vv[j] & 0xFFFF0000u);
                }
            }
#pragma unroll
            for (int j = 0; j < 8; j++) {
                a[j] += __shfl_xor_sync(0xffffffffu, a[j], 4);
                a[j] += __shfl_xor_sync(0xffffffffu, a[j], 8);
                a[j] += __shfl_xor_sync(0xffffffffu, a[j], 16);
            }
            if ((t & 31) < 4) {
                float* o = &g_cs3[(t >> 5) * FF + blockIdx.x * 32 + (t & 3) * 8];
                *reinterpret_cast<float4*>(o) = make_float4(a[0], a[1], a[2], a[3]);
                *reinterpret_cast<float4*>(o + 4) = make_float4(a[4], a[5], a[6], a[7]);
            }
        }
        if (threadIdx.x == 0) {
            if (MODE != 1) pdl_wait();
            int stage = 0;
            uint32_t phase = 1;
            for (int it = 0;; it++) {
                int tile;
                if (DYN) {
                    tile = atomicAdd(&g_tile_ctr, 1);
                    mbar_wait(bar_tempty + 8 * (it & 1), ((it >> 1) & 1) ^ 1);
                    asm volatile("st.shared.b32 [%0], %1;" ::"r"(tile_slot + 4 * (it & 1)), "r"(tile) : "memory");
                    mbar_arrive(bar_tfull + 8 * (it & 1));
                } else {
                    tile = blockIdx.x + it * gridDim.x;
                }
                if (tile >= ntiles) break;
                if (MODE == 1) tile = (tile + 192) & 255;
                const int m0 = (tile & 15) * 128;
                const int n0 = (tile >> 4) * BN;
                for (int kb = 0; kb < kblocks; kb++) {
                    mbar_wait(bar_empty + 8 * stage, phase);
                    const uint32_t sa = sbase + stage * L::STAGE_BYTES;
                    const uint32_t sb = sa + L::A_BYTES;
                    const uint32_t fb = bar_full + 8 * stage;
                    mbar_expect_tx(fb, L::STAGE_BYTES);
                    int arow = m0;
                    if (MODE == 2) {
                        const int grp = kb >> 2;
                        arow += (grp == 0) ? -1 : (grp == 1) ? 1 : (grp == 2) ? -2 : 2;
                    }
                    tma_load_2d(sa, &mA, kb * 64, arow, fb);
                    const CUtensorMap* mb = &mB0;
                    int bc = n0, br = kb * 64;
                    if (MODE == 1 && n0 >= 3 * DM) { mb = &mB1; bc = n0 - 3 * DM; }
                    if (MODE == 5 && kb >= 16) { mb = &mB1; br = (kb - 16) * 64; }
#pragma unroll
                    for (int b = 0; b < L::B_BOXES; b++) tma_load_2d(sb + b * 8192, mb, bc + b * 64, br, fb);
                    if ((MODE == 2 || MODE == 5) && kb == STAGES - 1) {
                        mbar_expect_tx(bar_res, 32768);
#pragma unroll
                        for (int q = 0; q < 4; q++)
                            tma_load_2d(sbase + L::STG_OFF + q * 8192, &mC1, n0 + (q & 1) * 64, m0 + (q >> 1) * 64, bar_res);
                    }
                    if (++stage == STAGES) { stage = 0; phase ^= 1; }
                }
            }
        }
    } else {
        reg_alloc<232>();
        const int c = wg - 1;
        const int warp = (threadIdx.x >> 5) & 3;
        const int lane = threadIdx.x & 31;
        const int tid_wg = threadIdx.x & 127;
        const uint32_t stg = sbase + L::STG_OFF + c * 16384;
        int stage = 0;
        uint32_t phase = 0;
        float acc[BN / 2];
        bool first = true;
        PH(0)
        if (MODE != 1) pdl_wait();
        for (int it = 0;; it++) {
            int tile;
            if (DYN) {
                mbar_wait(bar_tfull + 8 * (it & 1), (it >> 1) & 1);
                asm volatile("ld.shared.b32 %0, [%1];" : "=r"(tile) : "r"(tile_slot + 4 * (it & 1)) : "memory");
                named_bar_sync(1 + c, 128);
                if (tid_wg == 0) mbar_arrive(bar_tempty + 8 * (it & 1));
            } else {
                tile = blockIdx.x + it * gridDim.x;
            }
            if (tile >= ntiles) break;
            if (MODE == 1) tile = (tile + 192) & 255;
            const int m0 = (tile & 15) * 128;
            const int n0 = (tile >> 4) * BN;
            const int r0 = m0 + c * 64 + warp * 16 + (lane >> 2);
            const int r1 = r0 + 8;
            float mu[2], rs[2], og[2];
            if (MODE == 3) {
                const int t = threadIdx.x - 128;
                if (t < BN) {
                    const float v = (g_cs3[n0 + t] + g_cs3[FF + n0 + t]) + g_cs3[2 * FF + n0 + t];
                    asm volatile("st.shared.f32 [%0], %1;" ::"r"(sbase + L::CS_OFF + t * 4), "f"(v) : "memory");
                }
#pragma unroll
                for (int h = 0; h < 2; h++) {
                    const float4* sp = reinterpret_cast<const float4*>(&g_stat2[(h ? r1 : r0) * 8]);
                    float4 p[4];
                    float s = 0.f;
#pragma unroll
                    for (int i = 0; i < 4; i++) { p[i] = sp[i]; s += p[i].x + p[i].z; }
                    const float mean = s * (1.0f / DM);
                    float m2 = 0.f;
#pragma unroll
                    for (int i = 0; i < 4; i++) {
                        float d0 = p[i].x * (1.0f / 128) - mean, d1 = p[i].z * (1.0f / 128) - mean;
                        m2 += p[i].y + p[i].w + 128.0f * (d0 * d0 + d1 * d1);
                    }
                    mu[h] = mean;
                    rs[h] = rsqrtf(m2 * (1.0f / DM) + 1e-5f);
                }
            }
            if (MODE == 3 || MODE == 5) { og[0] = g_omg[r0]; og[1] = g_omg[r1]; }
            int prev_stage = 0;
            for (int kb = 0; kb < kblocks; kb++) {
                mbar_wait(bar_full + 8 * stage, phase);
                const uint32_t sa = sbase + stage * L::STAGE_BYTES + c * 8192;
                const uint32_t sb = sbase + stage * L::STAGE_BYTES + L::A_BYTES;
                const uint32_t da = desc_lo(sa, 16);
                const uint32_t db = desc_lo(sb, 8192);
                wgmma_fence();
#pragma unroll
                for (int k = 0; k < 4; k++) wgmma_tile<BN>(acc, da + k * 2, db + k * 128, (kb | k) != 0);
                wgmma_commit();
                if (kb > 0) {
                    wgmma_wait<1>();
                    RELEASE_STAGE(bar_empty + 8 * prev_stage);
                }
                prev_stage = stage;
                if (++stage == STAGES) { stage = 0; phase ^= 1; }
            }
            wgmma_wait<0>();
            RELEASE_STAGE(bar_empty + 8 * prev_stage);
            PH(1)
            if (MODE == 1 && first) { pdl_wait(); first = false; }

            const int cq = (lane & 3) * 2;
            const CUtensorMap* mc = &mC0;
            const uint32_t rrow = warp * 16 + (lane >> 2);
            const uint32_t res0 = stg + rrow * 128 + cq * 2;
            int out_c0 = n0;
            if (MODE == 1) {
                if (n0 < DM) {
                    const float qs = 0.17677669529663687f * 1.4426950408889634f;
#pragma unroll
                    for (int j = 0; j < BN / 2; j++) acc[j] *= qs;
                } else if (n0 >= 3 * DM) {
                    mc = &mC1;
                    out_c0 = n0 - 3 * DM;
                    const float mu0 = g_mean1[r0], mu1 = g_mean1[r1];
                    const float rs0 = g_rstd1[r0], rs1 = g_rstd1[r1];
                    {
                        const int t = threadIdx.x - 128;
                        const float v = (g_cs1[out_c0 + t] + g_cs1[DM + out_c0 + t]) + (g_cs1[2 * DM + out_c0 + t] + g_cs1[3 * DM + out_c0 + t]);
                        asm volatile("st.shared.f32 [%0], %1;" ::"r"(sbase + L::CS_OFF + t * 4), "f"(v) : "memory");
                    }
                    named_bar_sync(3, 256);
#pragma unroll
                    for (int j = 0; j < BN / 8; j++) {
                        float2 cs;
                        asm volatile("ld.shared.v2.f32 {%0, %1}, [%2];" : "=f"(cs.x), "=f"(cs.y) : "r"(sbase + L::CS_OFF + (8 * j + cq) * 4));
                        acc[4 * j + 0] = gelu_tanh(rs0 * fmaf(-mu0, cs.x, acc[4 * j + 0]));
                        acc[4 * j + 1] = gelu_tanh(rs0 * fmaf(-mu0, cs.y, acc[4 * j + 1]));
                        acc[4 * j + 2] = gelu_tanh(rs1 * fmaf(-mu1, cs.x, acc[4 * j + 2]));
                        acc[4 * j + 3] = gelu_tanh(rs1 * fmaf(-mu1, cs.y, acc[4 * j + 3]));
                    }
                    named_bar_sync(3, 256);
                }
            } else if (MODE == 2) {
                float s0 = 0.f, s1 = 0.f;
                mbar_wait(bar_res, 0);
#pragma unroll
                for (int j = 0; j < BN / 8; j++) {
                    uint32_t xa, xb;
                    const uint32_t ra = res0 + (j >> 3) * 8192 + (((j & 7) ^ (rrow & 7)) << 4);
                    asm volatile("ld.shared.b32 %0, [%1];" : "=r"(xa) : "r"(ra));
                    asm volatile("ld.shared.b32 %0, [%1];" : "=r"(xb) : "r"(ra + 1024));
                    acc[4 * j + 0] = bf16_round(bf16_round(acc[4 * j + 0]) + __uint_as_float(xa << 16));
                    acc[4 * j + 1] = bf16_round(bf16_round(acc[4 * j + 1]) + __uint_as_float(xa & 0xFFFF0000u));
                    acc[4 * j + 2] = bf16_round(bf16_round(acc[4 * j + 2]) + __uint_as_float(xb << 16));
                    acc[4 * j + 3] = bf16_round(bf16_round(acc[4 * j + 3]) + __uint_as_float(xb & 0xFFFF0000u));
                    s0 += acc[4 * j + 0] + acc[4 * j + 1];
                    s1 += acc[4 * j + 2] + acc[4 * j + 3];
                }
                s0 += __shfl_xor_sync(0xffffffffu, s0, 1);
                s0 += __shfl_xor_sync(0xffffffffu, s0, 2);
                s1 += __shfl_xor_sync(0xffffffffu, s1, 1);
                s1 += __shfl_xor_sync(0xffffffffu, s1, 2);
                const float mu0 = s0 * (1.0f / BN), mu1 = s1 * (1.0f / BN);
                float q0 = 0.f, q1 = 0.f;
#pragma unroll
                for (int j = 0; j < BN / 8; j++) {
                    float d;
                    d = acc[4 * j + 0] - mu0; q0 += d * d;
                    d = acc[4 * j + 1] - mu0; q0 += d * d;
                    d = acc[4 * j + 2] - mu1; q1 += d * d;
                    d = acc[4 * j + 3] - mu1; q1 += d * d;
                }
                q0 += __shfl_xor_sync(0xffffffffu, q0, 1);
                q0 += __shfl_xor_sync(0xffffffffu, q0, 2);
                q1 += __shfl_xor_sync(0xffffffffu, q1, 1);
                q1 += __shfl_xor_sync(0xffffffffu, q1, 2);
                if ((lane & 3) == 0) {
                    static_assert(MODE != 2 || BN == 128, "stats layout assumes BN=128");
                    g_stat2[r0 * 8 + (n0 >> 7)] = make_float2(s0, q0);
                    g_stat2[r1 * 8 + (n0 >> 7)] = make_float2(s1, q1);
                }
            } else if (MODE == 3) {
                out_c0 = n0 + DM;
                named_bar_sync(3, 256);
#pragma unroll
                for (int j = 0; j < BN / 8; j++) {
                    float2 cs;
                    asm volatile("ld.shared.v2.f32 {%0, %1}, [%2];" : "=f"(cs.x), "=f"(cs.y) : "r"(sbase + L::CS_OFF + (8 * j + cq) * 4));
                    acc[4 * j + 0] = og[0] * gelu_tanh(rs[0] * fmaf(-mu[0], cs.x, acc[4 * j + 0]));
                    acc[4 * j + 1] = og[0] * gelu_tanh(rs[0] * fmaf(-mu[0], cs.y, acc[4 * j + 1]));
                    acc[4 * j + 2] = og[1] * gelu_tanh(rs[1] * fmaf(-mu[1], cs.x, acc[4 * j + 2]));
                    acc[4 * j + 3] = og[1] * gelu_tanh(rs[1] * fmaf(-mu[1], cs.y, acc[4 * j + 3]));
                }
                named_bar_sync(3, 256);
            } else {
                const float og0 = og[0], og1 = og[1];
                mbar_wait(bar_res, 0);
#pragma unroll
                for (int j = 0; j < BN / 8; j++) {
                    uint32_t xa, xb;
                    const uint32_t ra = res0 + (j >> 3) * 8192 + (((j & 7) ^ (rrow & 7)) << 4);
                    asm volatile("ld.shared.b32 %0, [%1];" : "=r"(xa) : "r"(ra));
                    asm volatile("ld.shared.b32 %0, [%1];" : "=r"(xb) : "r"(ra + 1024));
                    acc[4 * j + 0] = fmaf(og0, __uint_as_float(xa << 16), acc[4 * j + 0]);
                    acc[4 * j + 1] = fmaf(og0, __uint_as_float(xa & 0xFFFF0000u), acc[4 * j + 1]);
                    acc[4 * j + 2] = fmaf(og1, __uint_as_float(xb << 16), acc[4 * j + 2]);
                    acc[4 * j + 3] = fmaf(og1, __uint_as_float(xb & 0xFFFF0000u), acc[4 * j + 3]);
                }
            }
            PH(3)
            const int srow = warp * 16 + (lane & 7) + ((lane >> 3) & 1) * 8;
#pragma unroll
            for (int rnd = 0; rnd < (BN + 127) / 128; rnd++) {
                if (tid_wg == 0) bulk_wait_read0();
                named_bar_sync(1 + c, 128);
#pragma unroll
                for (int jj = 0; jj < 8; jj++) {
                    const int j = rnd * 16 + jj * 2;
                    if (j * 8 < BN) {
                        const int jb = jj * 2 + (lane >> 4);
                        uint32_t addr = stg + (jb >> 3) * 8192 + srow * 128 + (((jb & 7) ^ (srow & 7)) << 4);
                        if (rnd * 128 + 128 > BN && jj >= 4)
                            addr = stg + 8192 + srow * 64 + (((jb & 3) ^ ((srow >> 1) & 3)) << 4);
                        stmatrix_x4(addr, pack_bf16(acc[4 * j + 0], acc[4 * j + 1]), pack_bf16(acc[4 * j + 2], acc[4 * j + 3]),
                                    pack_bf16(acc[4 * j + 4], acc[4 * j + 5]), pack_bf16(acc[4 * j + 6], acc[4 * j + 7]));
                    }
                }
                fence_proxy_async();
                named_bar_sync(1 + c, 128);
                if (tid_wg == 0) {
                    tma_store_2d(mc, stg, out_c0 + rnd * 128, m0 + c * 64);
                    if (rnd * 128 + 64 < BN)
                        tma_store_2d((rnd * 128 + 128 > BN) ? &mC1 : mc, stg + 8192, out_c0 + rnd * 128 + 64, m0 + c * 64);
                    bulk_commit();
                }
            }
        }
        PH(4)
        if (tid_wg == 0) bulk_wait0();
        PH(5)
        TL_END(MODE)
    }
}

#define ATT_NWG 2
constexpr int ATT_NTILES = NH * 16;
constexpr int ATT_TPH = S_LEN / (64 * ATT_NWG);
constexpr int ATT_GRID = NH * ATT_TPH;
constexpr int ATT_THREADS = 128 * ATT_NWG;
constexpr int ATT_STAGES = 4;
constexpr int ATT_DIST = 2;
constexpr int ATT_Q_OFF = ATT_STAGES * 16384;
constexpr int ATT_ONES_OFF = ATT_Q_OFF + 4096 * ATT_NWG;
constexpr int ATT_KEXT_OFF = ATT_ONES_OFF + 4096;
constexpr int ATT_QEXT_OFF = ATT_KEXT_OFF + 4096;
constexpr int ATT_BAR_OFF = ATT_QEXT_OFF + 4096 * ATT_NWG;
constexpr int ATT_SMEM = ATT_BAR_OFF + 256 + 1024;

__device__ __forceinline__ void row_max(const float (&s)[32], float& m0, float& m1) {
    float a0[8], a1[8];
#pragma unroll
    for (int i = 0; i < 8; i++) {
        a0[i] = fmaxf(s[4 * i], s[4 * i + 1]);
        a1[i] = fmaxf(s[4 * i + 2], s[4 * i + 3]);
    }
#pragma unroll
    for (int w = 4; w > 0; w >>= 1)
#pragma unroll
        for (int i = 0; i < w; i++) { a0[i] = fmaxf(a0[i], a0[i + w]); a1[i] = fmaxf(a1[i], a1[i + w]); }
    float mx0 = a0[0], mx1 = a1[0];
    mx0 = fmaxf(mx0, __shfl_xor_sync(0xffffffffu, mx0, 1));
    mx1 = fmaxf(mx1, __shfl_xor_sync(0xffffffffu, mx1, 1));
    mx0 = fmaxf(mx0, __shfl_xor_sync(0xffffffffu, mx0, 2));
    mx1 = fmaxf(mx1, __shfl_xor_sync(0xffffffffu, mx1, 2));
    m0 = fmaxf(m0, mx0);
    m1 = fmaxf(m1, mx1);
}

__device__ __forceinline__ void attn_step(float (&s)[32], float (&o)[20], uint32_t dq, uint32_t dke, uint32_t dk_next,
                                          uint32_t dv_cur, uint32_t release_bar) {
    constexpr uint32_t HI = desc_hi(512, 2);
    uint32_t p[16];
#pragma unroll
    for (int i = 0; i < 16; i++) p[i] = pack_bf16(ex2(s[2 * i]), ex2(s[2 * i + 1]));
    wgmma_fence();
    wgmma_ss_n64_tb0(s, dq, HI, dk_next, HI, 0);
    wgmma_ss_n64_tb0(s, dq + 2, HI, dk_next + 2, HI, 1);
    wgmma_ss_n64_tb0(s, dq + ((ATT_QEXT_OFF - ATT_Q_OFF) >> 4), HI, dke, HI, 1);
#pragma unroll
    for (int t = 0; t < 4; t++)
        wgmma_rs_n40_tb1(o, p[4 * t], p[4 * t + 1], p[4 * t + 2], p[4 * t + 3], dv_cur + t * 64, HI, 1);
    wgmma_commit();
    wgmma_wait<0>();
    if (release_bar != 0 && (threadIdx.x & 127) == 0) mbar_arrive(release_bar);
}

__global__ void __launch_bounds__(256, 1)
attn_exact_kernel(const __grid_constant__ CUtensorMap mKV) {
    extern __shared__ uint8_t smem_raw[];
    pdl_launch();
    pdl_wait();
    int any = 0;
    for (int t = blockIdx.x; t < ATT_NTILES; t += gridDim.x) any |= g_bad[t];
    if (!any) return;
    constexpr int NBLK = S_LEN / 128;
    constexpr uint32_t HI = desc_hi(512, 2);
    const uint32_t sbase = (smem_u32(smem_raw) + 1023u) & ~1023u;
    const uint32_t bar = sbase + ATT_BAR_OFF;
    const int warp_id = threadIdx.x >> 5;
    const int lane = threadIdx.x & 31;
    const int cq = (lane & 3) * 2;
    const uint32_t dk0 = desc_lo(sbase, 16);
    const uint32_t dv0 = desc_lo(sbase + 8192, ATT_ONES_OFF - 8192);
    if (threadIdx.x == 0) {
        mbar_init(bar, 1);
        asm volatile("fence.mbarrier_init.release.cluster;" ::: "memory");
    }
    asm volatile("st.shared.v4.b32 [%0], {%1, %1, %1, %1};" ::"r"(sbase + ATT_ONES_OFF + threadIdx.x * 16), "r"(0x3F803F80u) : "memory");
    fence_proxy_async();
    __syncthreads();
#pragma unroll 1
    for (int tile = blockIdx.x; tile < ATT_NTILES; tile += gridDim.x) {
    if (g_bad[tile] == 0) continue;
    const int head = tile >> 4;
    const int row0 = (tile & 15) * 128 + warp_id * 16 + (lane >> 2);
    const uint32_t dq = desc_lo(sbase + ATT_Q_OFF + (threadIdx.x >> 7) * 4096, 16);
    float o[20];
#pragma unroll
    for (int i = 0; i < 20; i++) o[i] = 0.f;
    float m0 = -INFINITY, m1 = -INFINITY;
#pragma unroll 1
    for (int j = 0; j < NBLK; j++) {
        if (threadIdx.x == 0) {
            mbar_expect_tx(bar, j == 0 ? 3 * 8192 : 2 * 8192);
            if (j == 0) tma_load_2d(sbase + ATT_Q_OFF, &mKV, head * DH, (tile & 15) * 128, bar);
            tma_load_2d(sbase, &mKV, DM + head * DH, j * 128, bar);
            tma_load_2d(sbase + 8192, &mKV, 2 * DM + head * DH, j * 128, bar);
        }
        __syncwarp();
        mbar_wait(bar, j & 1);
#pragma unroll 1
        for (int hf = 0; hf < 2; hf++) {
            float s[32];
            wgmma_fence();
            wgmma_ss_n64_tb0(s, dq, HI, dk0 + hf * 256, HI, 0);
            wgmma_ss_n64_tb0(s, dq + 2, HI, dk0 + hf * 256 + 2, HI, 1);
            wgmma_commit();
            wgmma_wait<0>();
            const float mo0 = m0, mo1 = m1;
            row_max(s, m0, m1);
            const float a0 = ex2(mo0 - m0), a1 = ex2(mo1 - m1);
            uint32_t p[16];
#pragma unroll
            for (int i = 0; i < 8; i++) {
                p[2 * i] = pack_bf16(ex2(s[4 * i + 0] - m0), ex2(s[4 * i + 1] - m0));
                p[2 * i + 1] = pack_bf16(ex2(s[4 * i + 2] - m1), ex2(s[4 * i + 3] - m1));
            }
#pragma unroll
            for (int i = 0; i < 5; i++) {
                o[4 * i + 0] *= a0; o[4 * i + 1] *= a0;
                o[4 * i + 2] *= a1; o[4 * i + 3] *= a1;
            }
            wgmma_fence();
            const uint32_t dv = dv0 + hf * 256 - ((uint32_t)(hf * 256) << 16);
#pragma unroll
            for (int t = 0; t < 4; t++)
                wgmma_rs_n40_tb1(o, p[4 * t], p[4 * t + 1], p[4 * t + 2], p[4 * t + 3], dv + t * 64, HI, 1);
            wgmma_commit();
            wgmma_wait<0>();
        }
        __syncthreads();
    }
    const float f0 = g_gate[row0] / o[16], f1 = g_gate[row0 + 8] / o[18];
    bf16* op0 = g_a5 + (size_t)row0 * A5W + head * DH + cq;
    bf16* op1 = op0 + 8 * A5W;
#pragma unroll
    for (int i = 0; i < 4; i++) {
        *reinterpret_cast<uint32_t*>(op0 + 8 * i) = pack_bf16(o[4 * i] * f0, o[4 * i + 1] * f0);
        *reinterpret_cast<uint32_t*>(op1 + 8 * i) = pack_bf16(o[4 * i + 2] * f1, o[4 * i + 3] * f1);
    }
    }
}

#define ATT_MINB 2
__global__ void __launch_bounds__(ATT_THREADS, 4 / ATT_NWG)
attn_kernel(const __grid_constant__ CUtensorMap mKV) {
    extern __shared__ uint8_t smem_raw[];
    const uint32_t sbase = (smem_u32(smem_raw) + 1023u) & ~1023u;
    const uint32_t bar_kfull = sbase + ATT_BAR_OFF;
    const uint32_t bar_vfull = bar_kfull + 8 * ATT_STAGES;
    const uint32_t bar_empty = bar_vfull + 8 * ATT_STAGES;
    const int tile = blockIdx.x;
    const int head = tile / ATT_TPH;
    const int q0 = (tile % ATT_TPH) * (64 * ATT_NWG);
    const int lane = threadIdx.x & 31;
    constexpr int NBLK = S_LEN / 128;
    TL_START(6)
    pdl_launch();

    auto issue_kv = [&](int g) {
        const int sn = g % ATT_STAGES;
        if (g >= ATT_STAGES) mbar_wait(bar_empty + 8 * sn, ((g / ATT_STAGES) - 1) & 1);
        const uint32_t skn = sbase + sn * 16384;
        mbar_expect_tx(bar_kfull + 8 * sn, g == 0 ? 8192 + 4096 * ATT_NWG : 8192);
        if (g == 0) {
#pragma unroll
            for (int qq = 0; qq < ATT_NWG / 2; qq++)
                tma_load_2d(sbase + ATT_Q_OFF + qq * 8192, &mKV, head * DH, q0 + qq * 128, bar_kfull);
        }
        tma_load_2d(skn, &mKV, DM + head * DH, g * 128, bar_kfull + 8 * sn);
        mbar_expect_tx(bar_vfull + 8 * sn, 8192);
        tma_load_2d(skn + 8192, &mKV, 2 * DM + head * DH, g * 128, bar_vfull + 8 * sn);
    };

    if (threadIdx.x == 0) {
        for (int s = 0; s < ATT_STAGES; s++) {
            mbar_init(bar_kfull + 8 * s, 1);
            mbar_init(bar_vfull + 8 * s, 1);
            mbar_init(bar_empty + 8 * s, ATT_NWG);
        }
        asm volatile("fence.mbarrier_init.release.cluster;" ::: "memory");
        prefetch_tmap(&mKV);
        pdl_wait();
#pragma unroll
        for (int j = 0; j < ATT_DIST; j++) issue_kv(j);
    }
    {
        if (threadIdx.x < 256) {
            asm volatile("st.shared.v4.b32 [%0], {%1, %1, %1, %1};" ::"r"(sbase + ATT_ONES_OFF + threadIdx.x * 16), "r"(0x3F803F80u) : "memory");
            const int r = threadIdx.x >> 2, ch = threadIdx.x & 3;
            const uint32_t w0 = (ch == ((r >> 1) & 3)) ? 0x00003F80u : 0u;
            asm volatile("st.shared.v4.b32 [%0], {%1, %2, %2, %2};" ::"r"(sbase + ATT_KEXT_OFF + threadIdx.x * 16), "r"(w0), "r"(0u) : "memory");
        }
        asm volatile("st.shared.v4.b32 [%0], {%1, %1, %1, %1};" ::"r"(sbase + ATT_QEXT_OFF + threadIdx.x * 32), "r"(0u) : "memory");
        asm volatile("st.shared.v4.b32 [%0], {%1, %1, %1, %1};" ::"r"(sbase + ATT_QEXT_OFF + threadIdx.x * 32 + 16), "r"(0u) : "memory");
    }
    fence_proxy_async();
    __syncthreads();

    constexpr uint32_t HI = desc_hi(512, 2);
    const uint32_t dk0 = desc_lo(sbase, 16);
    const uint32_t dv0 = desc_lo(sbase + 8192, ATT_ONES_OFF - 8192);
    const uint32_t dke = dk0 + (ATT_KEXT_OFF >> 4);
    const uint32_t dq = dk0 + ((ATT_Q_OFF + (threadIdx.x >> 7) * 4096) >> 4);
    float o[20];
#pragma unroll
    for (int i = 0; i < 20; i++) o[i] = 0.f;
    float s0[32];
    mbar_wait(bar_kfull, 0);
    wgmma_fence();
    wgmma_ss_n64_tb0(s0, dq, HI, dk0, HI, 0);
    wgmma_ss_n64_tb0(s0, dq + 2, HI, dk0 + 2, HI, 1);
    wgmma_commit();
    wgmma_wait<0>();
    float m0 = -INFINITY, m1 = -INFINITY;
    row_max(s0, m0, m1);
    if ((lane & 3) == 0) {
        const int r = ((threadIdx.x >> 5) & 3) * 16 + (lane >> 2);
        const uint32_t qe = sbase + ATT_QEXT_OFF + (threadIdx.x >> 7) * 4096;
        asm volatile("st.shared.b16 [%0], %1;" ::"r"(qe + r * 64 + (((r >> 1) & 3) << 4)), "h"((uint16_t)(pack_bf16(-m0, 0.f) & 0xFFFFu)) : "memory");
        asm volatile("st.shared.b16 [%0], %1;" ::"r"(qe + (r + 8) * 64 + ((((r + 8) >> 1) & 3) << 4)), "h"((uint16_t)(pack_bf16(-m1, 0.f) & 0xFFFFu)) : "memory");
    }
    fence_proxy_async();
    named_bar_sync(1 + (threadIdx.x >> 7), 128);
    wgmma_fence();
    wgmma_ss_n64_tb0(s0, dq + ((ATT_QEXT_OFF - ATT_Q_OFF) >> 4), HI, dke, HI, 1);
    wgmma_commit();
    wgmma_wait<0>();
#pragma unroll 1
    for (int j = 0; j < NBLK; j++) {
        if (threadIdx.x == 0 && j + ATT_DIST < NBLK) issue_kv(j + ATT_DIST);
        __syncwarp();
        const uint32_t stage = j & (ATT_STAGES - 1), nstage = (j + 1) & (ATT_STAGES - 1);
        const uint32_t dk = dk0 + stage * 1024;
        const uint32_t dv = dv0 + stage * 1024 - (stage << 26);
        mbar_wait(bar_vfull + 8 * stage, (j / ATT_STAGES) & 1);
        attn_step(s0, o, dq, dke, dk + 256, dv, 0u);
        uint32_t dkn = dk;
        if (j + 1 < NBLK) {
            mbar_wait(bar_kfull + 8 * nstage, ((j + 1) / ATT_STAGES) & 1);
            dkn = dk0 + nstage * 1024;
        }
        attn_step(s0, o, dq, dke, dkn, dv + 256 - (256u << 16), bar_empty + 8 * stage);
    }
    bool ok = (o[16] <= 1.2676506e30f) && (o[18] <= 1.2676506e30f);
#pragma unroll
    for (int i = 0; i < 16; i++) ok = ok && (fabsf(o[i]) <= 3.0e38f);
    const int row0 = q0 + (threadIdx.x >> 5) * 16 + (lane >> 2);
    const float f0 = g_gate[row0] / o[16], f1 = g_gate[row0 + 8] / o[18];
    bf16* op0 = g_a5 + (size_t)row0 * A5W + head * DH + (lane & 3) * 2;
    bf16* op1 = op0 + 8 * A5W;
#pragma unroll
    for (int i = 0; i < 4; i++) {
        *reinterpret_cast<uint32_t*>(op0 + 8 * i) = pack_bf16(o[4 * i] * f0, o[4 * i + 1] * f0);
        *reinterpret_cast<uint32_t*>(op1 + 8 * i) = pack_bf16(o[4 * i + 2] * f1, o[4 * i + 3] * f1);
    }
    const int bad = __syncthreads_or(!ok);
    if (threadIdx.x < ATT_NWG / 2) g_bad[tile * (ATT_NWG / 2) + threadIdx.x] = bad;
    TL_END(6)
}

typedef CUresult (*EncodeFn)(CUtensorMap*, CUtensorMapDataType, cuuint32_t, void*, const cuuint64_t*, const cuuint64_t*,
                             const cuuint32_t*, const cuuint32_t*, CUtensorMapInterleave, CUtensorMapSwizzle,
                             CUtensorMapL2promotion, CUtensorMapFloatOOBfill);

static CUtensorMap make_map(EncodeFn fn, const void* ptr, int rows, int cols, int box_cols, int box_rows,
                            CUtensorMapSwizzle swz) {
    CUtensorMap m;
    cuuint64_t dims[2] = {(cuuint64_t)cols, (cuuint64_t)rows};
    cuuint64_t strides[1] = {(cuuint64_t)cols * 2};
    cuuint32_t box[2] = {(cuuint32_t)box_cols, (cuuint32_t)box_rows};
    cuuint32_t es[2] = {1, 1};
    fn(&m, CU_TENSOR_MAP_DATA_TYPE_BFLOAT16, 2, const_cast<void*>(ptr), dims, strides, box, es,
       CU_TENSOR_MAP_INTERLEAVE_NONE, swz, CU_TENSOR_MAP_L2_PROMOTION_L2_256B, CU_TENSOR_MAP_FLOAT_OOB_FILL_NONE);
    return m;
}

template <typename... KArgs, typename... Args>
static void launch_ex(void (*kern)(KArgs...), int grid, int block, int smem, cudaStream_t st, int cluster, int pdl, Args... args) {
    cudaLaunchConfig_t cfg = {};
    cfg.gridDim = dim3(grid);
    cfg.blockDim = dim3(block);
    cfg.dynamicSmemBytes = smem;
    cfg.stream = st;
    cudaLaunchAttribute at[2];
    at[0].id = cudaLaunchAttributeProgrammaticStreamSerialization;
    at[0].val.programmaticStreamSerializationAllowed = pdl;
    at[1].id = cudaLaunchAttributeClusterDimension;
    at[1].val.clusterDim.x = cluster;
    at[1].val.clusterDim.y = 1;
    at[1].val.clusterDim.z = 1;
    cfg.attrs = at;
    cfg.numAttrs = cluster > 1 ? 2 : 1;
    cudaLaunchKernelEx(&cfg, kern, KArgs(args)...);
}

extern "C" void kernel_launch(void* const* d_in, const int* in_sizes, int n_in, void* d_out, int out_size) {
    const bf16* x = (const bf16*)d_in[0];
    const bf16* wqkv = (const bf16*)d_in[1];
    const bf16* wo = (const bf16*)d_in[2];
    const bf16* w1 = (const bf16*)d_in[4];
    const bf16* w2 = (const bf16*)d_in[5];
    const bf16* w3 = (const bf16*)d_in[6];
    const bf16* w4 = (const bf16*)d_in[7];
    const bf16* gate_w = (const bf16*)d_in[8];

    static EncodeFn enc = nullptr;
    static void *p_qkv, *p_h, *p_x1, *p_a5, *p_cs1, *p_cs3;
    static cudaStream_t s2;
    static cudaEvent_t ev_fork, ev_join;
    using G1 = GemmSmem<256, 4>;
    using G2 = GemmSmem<128, 5>;
#define G3BN 256
    using G3 = GemmSmem<G3BN, 4>;
    if (!enc) {
        void* fn = nullptr;
        cudaDriverEntryPointQueryResult qres;
        cudaGetDriverEntryPoint("cuTensorMapEncodeTiled", &fn, cudaEnableDefault, &qres);
        enc = (EncodeFn)fn;
        cudaGetSymbolAddress(&p_qkv, g_qkv);
        cudaGetSymbolAddress(&p_h, g_h);
        cudaGetSymbolAddress(&p_x1, g_x1);
        cudaGetSymbolAddress(&p_a5, g_a5);
        cudaGetSymbolAddress(&p_cs1, g_cs1);
        cudaGetSymbolAddress(&p_cs3, g_cs3);
        cudaFuncSetAttribute(gemm_kernel<1, 256, 4>, cudaFuncAttributeMaxDynamicSharedMemorySize, G1::TOTAL);
        cudaFuncSetAttribute(gemm_kernel<2, 128, 5>, cudaFuncAttributeMaxDynamicSharedMemorySize, G2::TOTAL);
        cudaFuncSetAttribute(gemm_kernel<3, G3BN, 4>, cudaFuncAttributeMaxDynamicSharedMemorySize, G3::TOTAL);
        cudaFuncSetAttribute(gemm_kernel<5, 128, 5>, cudaFuncAttributeMaxDynamicSharedMemorySize, G2::TOTAL);
        cudaStreamCreateWithFlags(&s2, cudaStreamNonBlocking);
        cudaEventCreateWithFlags(&ev_fork, cudaEventDisableTiming);
        cudaEventCreateWithFlags(&ev_join, cudaEventDisableTiming);
        cudaFuncSetAttribute(attn_kernel, cudaFuncAttributeMaxDynamicSharedMemorySize, ATT_SMEM);
        cudaFuncSetAttribute(attn_exact_kernel, cudaFuncAttributeMaxDynamicSharedMemorySize, ATT_SMEM);
    }
    const CUtensorMapSwizzle SW128 = CU_TENSOR_MAP_SWIZZLE_128B, SW64 = CU_TENSOR_MAP_SWIZZLE_64B;
    CUtensorMap mX = make_map(enc, x, S_LEN, DM, 64, 128, SW128);
    CUtensorMap mXres = make_map(enc, x, S_LEN, DM, 64, 64, SW128);
    CUtensorMap mWqkv = make_map(enc, wqkv, DM, 3 * DM, 64, 64, SW128);
    CUtensorMap mW1 = make_map(enc, w1, DM, DM, 64, 64, SW128);
    CUtensorMap mW2 = make_map(enc, w2, DM, DM, 64, 64, SW128);
    CUtensorMap mW3 = make_map(enc, w3, DM, FF, 64, 64, SW128);
    CUtensorMap mW4 = make_map(enc, w4, FF, DM, 64, 64, SW128);
    CUtensorMap mWo = make_map(enc, wo, DM, DM, 64, 64, SW128);
    CUtensorMap mQKVst = make_map(enc, p_qkv, S_LEN, 3 * DM, 64, 64, SW128);
    CUtensorMap mKV = make_map(enc, p_qkv, S_LEN, 3 * DM, 32, 128, SW64);
    CUtensorMap mHst = make_map(enc, p_h, S_LEN, DM, 64, 64, SW128);
    CUtensorMap mHld = make_map(enc, p_h, S_LEN, DM, 64, 128, SW128);
    CUtensorMap mX1st = make_map(enc, p_x1, S_LEN, DM, 64, 64, SW128);
    CUtensorMap mX1ld = make_map(enc, p_x1, S_LEN, DM, 64, 128, SW128);
    CUtensorMap mA5st = make_map(enc, p_a5, S_LEN, A5W, 64, 64, SW128);
    CUtensorMap mA5st32 = make_map(enc, p_a5, S_LEN, A5W, 32, 64, SW64);
    CUtensorMap mA5ld = make_map(enc, p_a5, S_LEN, A5W, 64, 128, SW128);
    CUtensorMap mOut = make_map(enc, d_out, S_LEN, DM, 64, 64, SW128);

    cudaStream_t st = cudaStreamPerThread;
    prep_kernel<<<256 + 64, 256, 0, st>>>(x, gate_w, w1, w3);
    launch_ex(gemm_kernel<1, 256, 4>, 132, 384, G1::TOTAL, st, 1, 1, mX, mWqkv, mW1, mQKVst, mHst, x, 16, 16);
    launch_ex(gemm_kernel<2, 128, 5>, 128, 384, G2::TOTAL, st, 1, 1, mHld, mW2, mW2, mX1st, mXres, w3, 8, 16);
    cudaEventRecord(ev_fork, st);
    launch_ex(attn_kernel, ATT_GRID, ATT_THREADS, ATT_SMEM, st, 1, 1, mKV);
    launch_ex(attn_exact_kernel, 32, 256, ATT_SMEM, st, 1, 1, mKV);
    cudaStreamWaitEvent(s2, ev_fork, 0);
    launch_ex(gemm_kernel<3, G3BN, 4>, 132, 384, G3::TOTAL, s2, 1, 0, mX1ld, mW3, mW3, mA5st, mA5st32, x, FF / G3BN, 16);
    cudaEventRecord(ev_join, s2);
    cudaStreamWaitEvent(st, ev_join, 0);
    launch_ex(gemm_kernel<5, 128, 5>, 128, 384, G2::TOTAL, st, 1, 0, mA5ld, mWo, mW4, mOut, mX1st, (const bf16*)p_x1, 8, 72);
}
```
